```python
import torch

def _softmax(x, axis=-1):
    return torch.softmax(x, dim=axis)

def _gelu(x):
    return torch.nn.functional.gelu(x, approximate='tanh')

def _silu(x):
    return torch.nn.functional.silu(x)

def _sigmoid(x):
    return torch.sigmoid(x)

def _layernorm(x, axis=-1, eps=1e-05):
    m = x.mean(dim=axis, keepdim=True)
    v = x.var(dim=axis, keepdim=True, unbiased=False)
    return (x - m) / torch.sqrt(v + eps)

def _scatter_add(tgt, idx, src, axis=0):
    return tgt.clone().index_add_(axis, idx, src)

def _segment_sum(src, seg, n):
    out = torch.zeros((n,) + src.shape[1:], dtype=src.dtype)
    return out.index_add_(0, seg, src)

def _pad(x, pw):
    flat = tuple((v for pair in reversed(pw) for v in pair))
    return torch.nn.functional.pad(x, flat)
kernel_name = 'gather_scatter__tensor_product_equiv_mace__graph'

def setup_inputs():

    _w = lambda a: (lambda t: t.to(torch.bfloat16) if t.is_floating_point() else t)(torch.as_tensor(a))
    N, deg = (10000, 32)
    Lmax, C, De = (1, 128, 16)
    M = (Lmax + 1) ** 2
    E = N * deg
    src = (lambda lo, hi, *s: torch.randint(lo, hi, s))(0, N, E).to(torch.int64)
    dst = (lambda lo, hi, *s: torch.randint(lo, hi, s))(0, N, E).to(torch.int64)
    r = (lambda *s: torch.randn(*s, dtype=torch.bfloat16) * 0.05)(E, 3).to(float)
    r = r / (torch.linalg.norm(r, dim=-1, keepdim=True).to(float) + 1e-06)
    rx, ry, rz = (r[:, 0].clone(), r[:, 1].clone(), r[:, 2].clone())
    x2, y2, z2 = (rx * rx, ry * ry, rz * rz)
    sh_list = [torch.ones_like(rx), rx, ry, rz, rx * ry, ry * rz, 2.0 * z2 - x2 - y2, rx * rz, x2 - y2, ry * (3.0 * x2 - y2), rx * ry * rz, ry * (4.0 * z2 - x2 - y2), rz * (2.0 * z2 - 3.0 * x2 - 3.0 * y2), rx * (4.0 * z2 - x2 - y2), rz * (x2 - y2), rx * (x2 - 3.0 * y2)]
    sh16 = torch.stack(sh_list, dim=-1).to(float)
    pad = max(0, M - 16)
    sh_full = torch.cat([sh16, torch.zeros((E, pad), dtype=float)], dim=-1)[:, :M]
    cg = ((lambda *s: torch.randn(*s, dtype=torch.bfloat16) * 0.05)(M, M, M) * (1.0 / float(M))).to(float)
    return {'x': _w(((lambda *s: torch.randn(*s, dtype=torch.bfloat16) * 0.05)(N, M, C) * 0.3).to(float)), 'src': _w(src), 'dst': _w(dst), 'sh': _w(sh_full.to(float)), 'edge_attr': _w(((lambda *s: torch.randn(*s, dtype=torch.bfloat16) * 0.05)(E, De) * 0.3).to(float)), 'cg': _w(cg), 'w_r': _w(((lambda *s: torch.randn(*s, dtype=torch.bfloat16) * 0.05)(De, C) * (1.0 / float(De) ** 0.5)).to(float)), 'w_out': _w(((lambda *s: torch.randn(*s, dtype=torch.bfloat16) * 0.05)(C, C) * (1.0 / float(C) ** 0.5)).to(float))}

def reference(x, src, dst, sh, edge_attr, cg, w_r, w_out):
    N = x.shape[0]
    M = x.shape[1]
    C = x.shape[2]
    h = x[src]
    tp = torch.einsum('uvw,euc,ev->ewc', cg, h, sh)
    rw = edge_attr @ w_r
    msg = tp * rw[:, None, :]
    msg2 = msg.reshape(-1, M * C)
    agg = _segment_sum(msg2, dst, N).reshape(N, M, C)
    out = torch.einsum('nmc,cd->nmd', agg, w_out)
    return out
```

```cpp
#include <cuda_runtime.h>
#include <cuda.h>
#include <cuda_bf16.h>
#include <stdint.h>
#include <stdlib.h>

#define MAXBINS 256
#define NW 16
#define NT (NW * 32)
#define HPB 38
#define BINCAP 3072
#define LCAP 1472
#define NBK 160
#define CE 3
#define GSZ 6
#define NS 10
#define RING_BYTES 40960
static_assert(RING_BYTES == NS * 4096, "ring");
#define CREG 224
#define PREG 24
#define HREG 40
#define TS 8
#define SM_EVEN 0
#define SM_MISC (2 * RING_BYTES)
#define SM_ODD (SM_MISC + 128)
#define SM_BT (SM_ODD + 2 * RING_BYTES)
#define SM_EA (SM_BT + TS * 4096)
#define SM_SIDE (SM_EA + 8192)
#define SM_EID (SM_SIDE + 2048)
#define SM_SRC (SM_EID + 2 * LCAP * 4)
#define SEQCAP (LCAP / 8 + 40)
#define SM_SEQ (SM_SRC + 2 * LCAP * 2)
#define SM_BAR (SM_SEQ + 2 * SEQCAP * 2)
#define SM_TOTAL (SM_BAR + 2 * NS * 16)
#define MI_WBAR 32
#define MI_INT 0
#define EPS ((2464 + NT - 1) / NT)
#define KS (BINCAP / NT)
#define SC_ENT 0
#define SC_BIN (SC_ENT + NT * EPS * 8)
#define SC_HIST (SC_BIN + NT * EPS)
#define SC_CNT (SC_HIST + 3 * MAXBINS * 4)
static_assert(SC_HIST % 16 == 0 && SC_CNT + 2 * (NBK + 1) * 16 <= SM_MISC, "scratch");
static_assert(SM_TOTAL <= 232448 && SM_BAR % 16 == 0 && SM_SEQ % 16 == 0 && SM_SRC % 16 == 0, "smem");
#define PACE 23.75
#define TOFF 8000
#define PSLEEP 20

__device__ int2 g_bin[MAXBINS * BINCAP];
__device__ int g_bincnt[MAXBINS * 32];
#define TLSTAMP(i)
#define TLMAX(i)

__device__ __forceinline__ uint32_t pack_bf16(float lo, float hi) {
    uint32_t r;
    asm("cvt.rn.bf16x2.f32 %0, %1, %2;" : "=r"(r) : "f"(hi), "f"(lo));
    return r;
}
__device__ __forceinline__ void mma1688_z(float (&d)[4], uint32_t a0, uint32_t a1, uint32_t b0) {
    asm("mma.sync.aligned.m16n8k8.row.col.f32.bf16.bf16.f32 {%0,%1,%2,%3}, {%4,%5}, {%6}, {%7,%7,%7,%7};"
        : "=f"(d[0]), "=f"(d[1]), "=f"(d[2]), "=f"(d[3])
        : "r"(a0), "r"(a1), "r"(b0), "f"(0.f));
}
__device__ __forceinline__ uint32_t s2u(const void* p) { return (uint32_t)__cvta_generic_to_shared(p); }
__device__ __forceinline__ void mbar_init(uint32_t a, int c) {
    asm volatile("mbarrier.init.shared.b64 [%0], %1;" ::"r"(a), "r"(c));
}
__device__ __forceinline__ void mbar_expect_tx(uint32_t a, int bytes) {
    asm volatile("mbarrier.arrive.expect_tx.shared.b64 _, [%0], %1;" ::"r"(a), "r"(bytes) : "memory");
}
__device__ __forceinline__ void mbar_arrive(uint32_t a) {
    asm volatile("mbarrier.arrive.shared.b64 _, [%0];" ::"r"(a) : "memory");
}
__device__ __forceinline__ void mbar_arrive_cnt(uint32_t a, int c) {
    asm volatile("mbarrier.arrive.shared.b64 _, [%0], %1;" ::"r"(a), "r"(c) : "memory");
}
__device__ __forceinline__ void mbar_wait(uint32_t a, int parity) {
    asm volatile(
        "{\n.reg .pred p;\n.reg .u32 c;\n"
        "mov.u32 c, 0;\n"
        "LAB_WAIT:\n"
        "mbarrier.try_wait.parity.shared.b64 p, [%0], %1, 2000;\n"
        "@p bra DONE;\n"
        "add.u32 c, c, 1;\n"
        "setp.lt.u32 p, c, 2000000;\n"
        "@p bra LAB_WAIT;\n"
        "trap;\n"
        "DONE:\n}" ::"r"(a),
        "r"(parity)
        : "memory");
}
__device__ __forceinline__ void mbar_wait_u(uint32_t a, int parity) {
    asm volatile(
        "{\n.reg .pred p;\n.reg .u32 c;\n"
        "mov.u32 c, 0;\n"
        "LAB_WAIT:\n"
        "mbarrier.try_wait.parity.shared.b64 p, [%0], %1, 2000;\n"
        "@p bra.uni DONE;\n"
        "add.u32 c, c, 1;\n"
        "setp.lt.u32 p, c, 2000000;\n"
        "@p bra.uni LAB_WAIT;\n"
        "trap;\n"
        "DONE:\n}" ::"r"(a),
        "r"(parity)
        : "memory");
}
__device__ __forceinline__ void mbar_spin_u(uint32_t a, int parity) {
    asm volatile(
        "{\n.reg .pred p;\n.reg .u32 c;\n"
        "mov.u32 c, 0;\n"
        "LAB_WAIT:\n"
        "mbarrier.test_wait.parity.shared.b64 p, [%0], %1;\n"
        "@p bra.uni DONE;\n"
        "add.u32 c, c, 1;\n"
        "setp.lt.u32 p, c, 20000000;\n"
        "@p bra.uni LAB_WAIT;\n"
        "trap;\n"
        "DONE:\n}" ::"r"(a),
        "r"(parity)
        : "memory");
}
__device__ __forceinline__ void mbar_lean(uint32_t a, int parity) {
    asm volatile(
        "{\n.reg .pred p;\n.reg .u32 c;\n"
        "mov.u32 c, 0;\n"
        "LAB_WAIT:\n"
        "mbarrier.try_wait.parity.shared.b64 p, [%0], %1;\n"
        "@p bra DONE;\n"
        "add.u32 c, c, 1;\n"
        "setp.lt.u32 p, c, 4000000;\n"
        "@p bra LAB_WAIT;\n"
        "trap;\n"
        "DONE:\n}" ::"r"(a),
        "r"(parity)
        : "memory");
}
__device__ __forceinline__ void mbar_lean_u(uint32_t a, int parity) {
    asm volatile(
        "{\n.reg .pred p;\n.reg .u32 c;\n"
        "mov.u32 c, 0;\n"
        "LAB_WAIT:\n"
        "mbarrier.try_wait.parity.shared.b64 p, [%0], %1;\n"
        "@p bra.uni DONE;\n"
        "add.u32 c, c, 1;\n"
        "setp.lt.u32 p, c, 4000000;\n"
        "@p bra.uni LAB_WAIT;\n"
        "trap;\n"
        "DONE:\n}" ::"r"(a),
        "r"(parity)
        : "memory");
}
__device__ __forceinline__ bool elect() {
    uint32_t p;
    asm volatile("{\n.reg .pred P;\nelect.sync _|P, 0xffffffff;\nselp.u32 %0, 1, 0, P;\n}" : "=r"(p));
    return p;
}
__device__ __forceinline__ void tma_2d(uint32_t dst, const CUtensorMap* tm, uint32_t bar, int c0, int c1) {
    asm volatile(
        "cp.async.bulk.tensor.2d.shared::cluster.global.mbarrier::complete_tx::bytes [%0], [%1, {%3, %4}], [%2];" ::"r"(dst),
        "l"(tm), "r"(bar), "r"(c0), "r"(c1)
        : "memory");
}
__device__ __forceinline__ void tma_row(uint32_t dst, const CUtensorMap* tm, uint32_t bar, int row8) {
    tma_2d(dst, tm, bar, 0, row8);
}
__device__ __forceinline__ void tma_store(const CUtensorMap* tm, uint32_t src, int c0, int c1) {
    asm volatile("cp.async.bulk.tensor.2d.global.shared::cta.bulk_group [%0, {%2, %3}], [%1];" ::"l"(tm), "r"(src),
                 "r"(c0), "r"(c1)
                 : "memory");
}
__device__ __forceinline__ uint2 lds_v2(uint32_t a) {
    uint2 v;
    asm volatile("ld.shared.v2.u32 {%0,%1}, [%2];" : "=r"(v.x), "=r"(v.y) : "r"(a));
    return v;
}
__device__ __forceinline__ uint4 lds_v4(uint32_t a) {
    uint4 v;
    asm volatile("ld.shared.v4.u32 {%0,%1,%2,%3}, [%4];" : "=r"(v.x), "=r"(v.y), "=r"(v.z), "=r"(v.w) : "r"(a));
    return v;
}
__device__ __forceinline__ uint32_t lds_u32(uint32_t a) {
    uint32_t v;
    asm volatile("ld.shared.u32 %0, [%1];" : "=r"(v) : "r"(a));
    return v;
}
__device__ __forceinline__ uint32_t lds_u16(uint32_t a) {
    uint32_t v;
    asm volatile("ld.shared.u16 %0, [%1];" : "=r"(v) : "r"(a));
    return v;
}
__device__ __forceinline__ void sts_v2(uint32_t a, uint32_t x, uint32_t y) {
    asm volatile("st.shared.v2.u32 [%0], {%1,%2};" ::"r"(a), "r"(x), "r"(y) : "memory");
}
__device__ __forceinline__ void sts_v4(uint32_t a, uint4 v) {
    asm volatile("st.shared.v4.u32 [%0], {%1,%2,%3,%4};" ::"r"(a), "r"(v.x), "r"(v.y), "r"(v.z), "r"(v.w) : "memory");
}
__device__ __forceinline__ void stsm4(uint32_t a, uint32_t r0, uint32_t r1, uint32_t r2, uint32_t r3) {
    asm volatile("stmatrix.sync.aligned.m8n8.x4.shared.b16 [%0], {%1,%2,%3,%4};" ::"r"(a), "r"(r0), "r"(r1), "r"(r2), "r"(r3)
                 : "memory");
}
__device__ __forceinline__ void stsm2(uint32_t a, uint32_t r0, uint32_t r1) {
    asm volatile("stmatrix.sync.aligned.m8n8.x2.shared.b16 [%0], {%1,%2};" ::"r"(a), "r"(r0), "r"(r1) : "memory");
}
__device__ __forceinline__ void stsm4t(uint32_t a, uint32_t r0, uint32_t r1, uint32_t r2, uint32_t r3) {
    asm volatile("stmatrix.sync.aligned.m8n8.x4.trans.shared.b16 [%0], {%1,%2,%3,%4};" ::"r"(a), "r"(r0), "r"(r1), "r"(r2),
                 "r"(r3)
                 : "memory");
}
__device__ __forceinline__ void stsm2t(uint32_t a, uint32_t r0, uint32_t r1) {
    asm volatile("stmatrix.sync.aligned.m8n8.x2.trans.shared.b16 [%0], {%1,%2};" ::"r"(a), "r"(r0), "r"(r1) : "memory");
}
__device__ __forceinline__ void cp_async16(uint32_t d, const void* s, int n) {
    asm volatile("cp.async.cg.shared.global [%0], [%1], 16, %2;" ::"r"(d), "l"(s), "r"(n) : "memory");
}
__device__ __forceinline__ void cp_async4(uint32_t d, const void* s, int n) {
    asm volatile("cp.async.ca.shared.global [%0], [%1], 4, %2;" ::"r"(d), "l"(s), "r"(n) : "memory");
}
__device__ __forceinline__ void sts_u32(uint32_t a, uint32_t x) {
    asm volatile("st.shared.u32 [%0], %1;" ::"r"(a), "r"(x) : "memory");
}
#define FENCE_ASYNC() asm volatile("fence.proxy.async.shared::cta;" ::: "memory")
__device__ __forceinline__ int warp_incl_scan(int v, int lane) {
#pragma unroll
    for (int o = 1; o < 32; o <<= 1) {
        const int y = __shfl_up_sync(0xffffffffu, v, o);
        if (lane >= o) v += y;
    }
    return v;
}

#define STR2(x) #x
#define STR(x) STR2(x)
#define NJ 19
__device__ __forceinline__ void consume(float (&acc)[2][NJ][4], uint32_t xa0, uint32_t xa1, uint32_t so0, uint32_t bar0,
                                        uint32_t ea0, uint32_t d0, uint32_t pl0, int lz, const uint32_t (&w)[8]) {
    asm volatile(
        "{\n"
        ".reg .pred p, pv, pf, plead, pok, t0, t1, t2;\n"
        ".reg .b32 cnt, so, par, q, qe, bar, rbar, pl, ctl, ga, dl, dh, v0, v1, v2, v3, pp;\n"
        ".reg .b16 sl, sh;\n"
        ".reg .b32 la0, la1, la2, la3, la4, la5, la6, la7, lb0, lb1, lb2, lb3, lb4, lb5, lb6, lb7, ha0, ha1, ha2, ha3, ha4, ha5, ha6, ha7, hb0, hb1, hb2, hb3, hb4, hb5, hb6, hb7;\n"
        ".reg .b32 p0, p1, p2, p3;\n"
        ".reg .f32 r0, r1, r2, r3, r4, r5, r6, r7;\n"
        ".reg .b64 da, db, de;\n"
        "mov.f32 %0, 0f00000000;\n"
        "mov.f32 %1, 0f00000000;\n"
        "mov.f32 %2, 0f00000000;\n"
        "mov.f32 %3, 0f00000000;\n"
        "mov.f32 %4, 0f00000000;\n"
        "mov.f32 %5, 0f00000000;\n"
        "mov.f32 %6, 0f00000000;\n"
        "mov.f32 %7, 0f00000000;\n"
        "mov.f32 %8, 0f00000000;\n"
        "mov.f32 %9, 0f00000000;\n"
        "mov.f32 %10, 0f00000000;\n"
        "mov.f32 %11, 0f00000000;\n"
        "mov.f32 %12, 0f00000000;\n"
        "mov.f32 %13, 0f00000000;\n"
        "mov.f32 %14, 0f00000000;\n"
        "mov.f32 %15, 0f00000000;\n"
        "mov.f32 %16, 0f00000000;\n"
        "mov.f32 %17, 0f00000000;\n"
        "mov.f32 %18, 0f00000000;\n"
        "mov.f32 %19, 0f00000000;\n"
        "mov.f32 %20, 0f00000000;\n"
        "mov.f32 %21, 0f00000000;\n"
        "mov.f32 %22, 0f00000000;\n"
        "mov.f32 %23, 0f00000000;\n"
        "mov.f32 %24, 0f00000000;\n"
        "mov.f32 %25, 0f00000000;\n"
        "mov.f32 %26, 0f00000000;\n"
        "mov.f32 %27, 0f00000000;\n"
        "mov.f32 %28, 0f00000000;\n"
        "mov.f32 %29, 0f00000000;\n"
        "mov.f32 %30, 0f00000000;\n"
        "mov.f32 %31, 0f00000000;\n"
        "mov.f32 %32, 0f00000000;\n"
        "mov.f32 %33, 0f00000000;\n"
        "mov.f32 %34, 0f00000000;\n"
        "mov.f32 %35, 0f00000000;\n"
        "mov.f32 %36, 0f00000000;\n"
        "mov.f32 %37, 0f00000000;\n"
        "mov.f32 %38, 0f00000000;\n"
        "mov.f32 %39, 0f00000000;\n"
        "mov.f32 %40, 0f00000000;\n"
        "mov.f32 %41, 0f00000000;\n"
        "mov.f32 %42, 0f00000000;\n"
        "mov.f32 %43, 0f00000000;\n"
        "mov.f32 %44, 0f00000000;\n"
        "mov.f32 %45, 0f00000000;\n"
        "mov.f32 %46, 0f00000000;\n"
        "mov.f32 %47, 0f00000000;\n"
        "mov.f32 %48, 0f00000000;\n"
        "mov.f32 %49, 0f00000000;\n"
        "mov.f32 %50, 0f00000000;\n"
        "mov.f32 %51, 0f00000000;\n"
        "mov.f32 %52, 0f00000000;\n"
        "mov.f32 %53, 0f00000000;\n"
        "mov.f32 %54, 0f00000000;\n"
        "mov.f32 %55, 0f00000000;\n"
        "mov.f32 %56, 0f00000000;\n"
        "mov.f32 %57, 0f00000000;\n"
        "mov.f32 %58, 0f00000000;\n"
        "mov.f32 %59, 0f00000000;\n"
        "mov.f32 %60, 0f00000000;\n"
        "mov.f32 %61, 0f00000000;\n"
        "mov.f32 %62, 0f00000000;\n"
        "mov.f32 %63, 0f00000000;\n"
        "mov.f32 %64, 0f00000000;\n"
        "mov.f32 %65, 0f00000000;\n"
        "mov.f32 %66, 0f00000000;\n"
        "mov.f32 %67, 0f00000000;\n"
        "mov.f32 %68, 0f00000000;\n"
        "mov.f32 %69, 0f00000000;\n"
        "mov.f32 %70, 0f00000000;\n"
        "mov.f32 %71, 0f00000000;\n"
        "mov.f32 %72, 0f00000000;\n"
        "mov.f32 %73, 0f00000000;\n"
        "mov.f32 %74, 0f00000000;\n"
        "mov.f32 %75, 0f00000000;\n"
        "mov.f32 %76, 0f00000000;\n"
        "mov.f32 %77, 0f00000000;\n"
        "mov.f32 %78, 0f00000000;\n"
        "mov.f32 %79, 0f00000000;\n"
        "mov.f32 %80, 0f00000000;\n"
        "mov.f32 %81, 0f00000000;\n"
        "mov.f32 %82, 0f00000000;\n"
        "mov.f32 %83, 0f00000000;\n"
        "mov.f32 %84, 0f00000000;\n"
        "mov.f32 %85, 0f00000000;\n"
        "mov.f32 %86, 0f00000000;\n"
        "mov.f32 %87, 0f00000000;\n"
        "mov.f32 %88, 0f00000000;\n"
        "mov.f32 %89, 0f00000000;\n"
        "mov.f32 %90, 0f00000000;\n"
        "mov.f32 %91, 0f00000000;\n"
        "mov.f32 %92, 0f00000000;\n"
        "mov.f32 %93, 0f00000000;\n"
        "mov.f32 %94, 0f00000000;\n"
        "mov.f32 %95, 0f00000000;\n"
        "mov.f32 %96, 0f00000000;\n"
        "mov.f32 %97, 0f00000000;\n"
        "mov.f32 %98, 0f00000000;\n"
        "mov.f32 %99, 0f00000000;\n"
        "mov.f32 %100, 0f00000000;\n"
        "mov.f32 %101, 0f00000000;\n"
        "mov.f32 %102, 0f00000000;\n"
        "mov.f32 %103, 0f00000000;\n"
        "mov.f32 %104, 0f00000000;\n"
        "mov.f32 %105, 0f00000000;\n"
        "mov.f32 %106, 0f00000000;\n"
        "mov.f32 %107, 0f00000000;\n"
        "mov.f32 %108, 0f00000000;\n"
        "mov.f32 %109, 0f00000000;\n"
        "mov.f32 %110, 0f00000000;\n"
        "mov.f32 %111, 0f00000000;\n"
        "mov.f32 %112, 0f00000000;\n"
        "mov.f32 %113, 0f00000000;\n"
        "mov.f32 %114, 0f00000000;\n"
        "mov.f32 %115, 0f00000000;\n"
        "mov.f32 %116, 0f00000000;\n"
        "mov.f32 %117, 0f00000000;\n"
        "mov.f32 %118, 0f00000000;\n"
        "mov.f32 %119, 0f00000000;\n"
        "mov.f32 %120, 0f00000000;\n"
        "mov.f32 %121, 0f00000000;\n"
        "mov.f32 %122, 0f00000000;\n"
        "mov.f32 %123, 0f00000000;\n"
        "mov.f32 %124, 0f00000000;\n"
        "mov.f32 %125, 0f00000000;\n"
        "mov.f32 %126, 0f00000000;\n"
        "mov.f32 %127, 0f00000000;\n"
        "mov.f32 %128, 0f00000000;\n"
        "mov.f32 %129, 0f00000000;\n"
        "mov.f32 %130, 0f00000000;\n"
        "mov.f32 %131, 0f00000000;\n"
        "mov.f32 %132, 0f00000000;\n"
        "mov.f32 %133, 0f00000000;\n"
        "mov.f32 %134, 0f00000000;\n"
        "mov.f32 %135, 0f00000000;\n"
        "mov.f32 %136, 0f00000000;\n"
        "mov.f32 %137, 0f00000000;\n"
        "mov.f32 %138, 0f00000000;\n"
        "mov.f32 %139, 0f00000000;\n"
        "mov.f32 %140, 0f00000000;\n"
        "mov.f32 %141, 0f00000000;\n"
        "mov.f32 %142, 0f00000000;\n"
        "mov.f32 %143, 0f00000000;\n"
        "mov.f32 %144, 0f00000000;\n"
        "mov.f32 %145, 0f00000000;\n"
        "mov.f32 %146, 0f00000000;\n"
        "mov.f32 %147, 0f00000000;\n"
        "mov.f32 %148, 0f00000000;\n"
        "mov.f32 %149, 0f00000000;\n"
        "mov.f32 %150, 0f00000000;\n"
        "mov.f32 %151, 0f00000000;\n"
        "setp.ne.u32 pf, 0, 0;\n"
        "mov.u32 dh, 16;\n"
        "add.u32 v0, %154, %159;\n"
        "shfl.sync.idx.b32 so, v0, 0, 31, 0xffffffff;\n"
        "mov.u32 par, 0;\n"
        "mov.u32 q, 0;\n"
        "mov.u32 pl, %158;\n"
        "shr.u32 bar, so, 8;\n"
        "add.u32 bar, bar, %155;\n"
        "elect.sync _|plead, 0xffffffff;\n"
        "mov.u32 cnt, 0;\n"
        "W1:\n"
        "mbarrier.try_wait.parity.shared.b64 p, [bar], par;\n"
        "@p bra.uni D0;\n"
        "add.u32 cnt, cnt, 1;\n"
        "setp.lt.u32 p, cnt, 4000000;\n"
        "@p bra.uni W1;\n"
        "trap;\n"
        "D0:\n"
        "add.u32 v0, %152, so;\n"
        "add.u32 v1, %153, so;\n"
        "ldmatrix.sync.aligned.m8n8.x4.trans.shared.b16 {la0,la1,la2,la3}, [v0+0];\n"
        "ldmatrix.sync.aligned.m8n8.x4.trans.shared.b16 {la4,la5,la6,la7}, [v1+0];\n"
        "ldmatrix.sync.aligned.m8n8.x4.trans.shared.b16 {lb0,lb1,lb2,lb3}, [v0+2048];\n"
        "ldmatrix.sync.aligned.m8n8.x4.trans.shared.b16 {lb4,lb5,lb6,lb7}, [v1+2048];\n"
        "mov.b64 de, {%156, dh};\n"
        "wgmma.fence.sync.aligned;\n"
        "wgmma.mma_async.sync.aligned.m64n8k16.f32.bf16.bf16 {r0,r1,r2,r3}, {%160,%161,%162,%163}, de, pf, 1, 1, 0;\n"
        "wgmma.mma_async.sync.aligned.m64n8k16.f32.bf16.bf16 {r4,r5,r6,r7}, {%164,%165,%166,%167}, de, pf, 1, 1, 0;\n"
        "wgmma.commit_group.sync.aligned;\n"
        "wgmma.wait_group.sync.aligned 0;\n"
        "cvt.rn.bf16x2.f32 p0, r1, r0;\n"
        "cvt.rn.bf16x2.f32 p1, r3, r2;\n"
        "cvt.rn.bf16x2.f32 p2, r5, r4;\n"
        "cvt.rn.bf16x2.f32 p3, r7, r6;\n"
        "add.u32 qe, %156, 16;\n"
        "mov.b64 de, {qe, dh};\n"
        "wgmma.fence.sync.aligned;\n"
        "wgmma.mma_async.sync.aligned.m64n8k16.f32.bf16.bf16 {r0,r1,r2,r3}, {%160,%161,%162,%163}, de, pf, 1, 1, 0;\n"
        "wgmma.mma_async.sync.aligned.m64n8k16.f32.bf16.bf16 {r4,r5,r6,r7}, {%164,%165,%166,%167}, de, pf, 1, 1, 0;\n"
        "wgmma.commit_group.sync.aligned;\n"
        "C:\n"
        "ld.shared.u16 ctl, [pl];\n"
        "add.u32 pl, pl, 2;\n"
        "mov.u32 rbar, bar;\n"
        "add.u32 so, so, 4096;\n"
        "setp.eq.u32 p, so, " STR(RING_BYTES) ";\n"
        "selp.b32 so, 0, so, p;\n"
        "selp.b32 v3, 1, 0, p;\n"
        "xor.b32 par, par, v3;\n"
        "shr.u32 bar, so, 8;\n"
        "add.u32 bar, bar, %155;\n"
        "mbarrier.try_wait.parity.shared.b64 pok, [bar], par;\n"
        "wgmma.wait_group.sync.aligned 2;\n"
        "mov.b32 {sl, sh}, p0;\n"
        "mov.b32 pp, {sl, sl};\n"
        "mul.rn.bf16x2 ha0, la0, pp;\n"
        "mul.rn.bf16x2 ha2, la2, pp;\n"
        "mov.b32 {sl, sh}, p1;\n"
        "mov.b32 pp, {sl, sl};\n"
        "mul.rn.bf16x2 ha1, la1, pp;\n"
        "mul.rn.bf16x2 ha3, la3, pp;\n"
        "mov.b32 {sl, sh}, p2;\n"
        "mov.b32 pp, {sl, sl};\n"
        "mul.rn.bf16x2 ha4, la4, pp;\n"
        "mul.rn.bf16x2 ha6, la6, pp;\n"
        "mov.b32 {sl, sh}, p3;\n"
        "mov.b32 pp, {sl, sl};\n"
        "mul.rn.bf16x2 ha5, la5, pp;\n"
        "mul.rn.bf16x2 ha7, la7, pp;\n"
        "lop3.b32 v2, la3, la7, %159, 0x80;\n"
        "@!pok bra.uni S2;\n"
        "R2:\n"
        "add.u32 v0, %152, so;\n"
        "add.u32 v1, %153, so;\n"
        "ldmatrix.sync.aligned.m8n8.x4.trans.shared.b16 {la0,la1,la2,la3}, [v0+0];\n"
        "ldmatrix.sync.aligned.m8n8.x4.trans.shared.b16 {la4,la5,la6,la7}, [v1+0];\n"
        "wgmma.wait_group.sync.aligned 1;\n"
        "and.b32 dl, q, 0x380;\n"
        "add.u32 dl, dl, %157;\n"
        "mov.b64 da, {dl, dh};\n"
        "add.u32 dl, dl, 64;\n"
        "mov.b64 db, {dl, dh};\n"
        "add.u32 q, q, 128;\n"
        "add.u32 qe, q, 128;\n"
        "and.b32 qe, qe, 0x780;\n"
        "shr.u32 qe, qe, 3;\n"
        "add.u32 qe, qe, %156;\n"
        "mov.b64 de, {qe, dh};\n"
        "mov.b32 {sl, sh}, p0;\n"
        "mov.b32 pp, {sh, sh};\n"
        "mul.rn.bf16x2 hb0, lb0, pp;\n"
        "mul.rn.bf16x2 hb2, lb2, pp;\n"
        "mov.b32 {sl, sh}, p1;\n"
        "mov.b32 pp, {sh, sh};\n"
        "mul.rn.bf16x2 hb1, lb1, pp;\n"
        "mul.rn.bf16x2 hb3, lb3, pp;\n"
        "mov.b32 {sl, sh}, p2;\n"
        "mov.b32 pp, {sh, sh};\n"
        "mul.rn.bf16x2 hb4, lb4, pp;\n"
        "mul.rn.bf16x2 hb6, lb6, pp;\n"
        "mov.b32 {sl, sh}, p3;\n"
        "mov.b32 pp, {sh, sh};\n"
        "mul.rn.bf16x2 hb5, lb5, pp;\n"
        "mul.rn.bf16x2 hb7, lb7, pp;\n"
        "lop3.b32 v2, lb3, lb7, v2, 0x80;\n"
        "setp.eq.and.u32 pv, v2, 0, plead;\n"
        "@pv mbarrier.arrive.shared.b64 _, [rbar+8];\n"
        "ldmatrix.sync.aligned.m8n8.x4.trans.shared.b16 {lb0,lb1,lb2,lb3}, [v0+2048];\n"
        "ldmatrix.sync.aligned.m8n8.x4.trans.shared.b16 {lb4,lb5,lb6,lb7}, [v1+2048];\n"
        "wgmma.wait_group.sync.aligned 0;\n"
        "cvt.rn.bf16x2.f32 p0, r1, r0;\n"
        "cvt.rn.bf16x2.f32 p1, r3, r2;\n"
        "cvt.rn.bf16x2.f32 p2, r5, r4;\n"
        "cvt.rn.bf16x2.f32 p3, r7, r6;\n"
        "and.b32 v3, ctl, 4096;\n"
        "setp.ne.u32 t0, v3, 0;\n"
        "and.b32 v3, ctl, 8192;\n"
        "setp.ne.u32 t1, v3, 0;\n"
        "and.b32 v3, ctl, 16384;\n"
        "setp.ne.u32 t2, v3, 0;\n"
        "@t2 bra.uni T4;\n"
        "@t1 bra.uni T2;\n"
        "@t0 bra.uni L1;\n"
        "L0:\n"
        "wgmma.fence.sync.aligned;\n"
        "wgmma.mma_async.sync.aligned.m64n24k16.f32.bf16.bf16 {%0,%1,%2,%3,%4,%5,%6,%7,%8,%9,%10,%11}, {ha0,ha1,ha2,ha3}, da, 1, 1, 1, 1;\n"
        "wgmma.mma_async.sync.aligned.m64n24k16.f32.bf16.bf16 {%76,%77,%78,%79,%80,%81,%82,%83,%84,%85,%86,%87}, {ha4,ha5,ha6,ha7}, da, 1, 1, 1, 1;\n"
        "wgmma.commit_group.sync.aligned;\n"
        "wgmma.mma_async.sync.aligned.m64n24k16.f32.bf16.bf16 {%0,%1,%2,%3,%4,%5,%6,%7,%8,%9,%10,%11}, {hb0,hb1,hb2,hb3}, db, 1, 1, 1, 1;\n"
        "wgmma.mma_async.sync.aligned.m64n24k16.f32.bf16.bf16 {%76,%77,%78,%79,%80,%81,%82,%83,%84,%85,%86,%87}, {hb4,hb5,hb6,hb7}, db, 1, 1, 1, 1;\n"
        "wgmma.commit_group.sync.aligned;\n"
        "wgmma.mma_async.sync.aligned.m64n8k16.f32.bf16.bf16 {r0,r1,r2,r3}, {%160,%161,%162,%163}, de, pf, 1, 1, 0;\n"
        "wgmma.mma_async.sync.aligned.m64n8k16.f32.bf16.bf16 {r4,r5,r6,r7}, {%164,%165,%166,%167}, de, pf, 1, 1, 0;\n"
        "wgmma.commit_group.sync.aligned;\n"
        "bra.uni C;\n"
        "L1:\n"
        "wgmma.fence.sync.aligned;\n"
        "wgmma.mma_async.sync.aligned.m64n24k16.f32.bf16.bf16 {%12,%13,%14,%15,%16,%17,%18,%19,%20,%21,%22,%23}, {ha0,ha1,ha2,ha3}, da, 1, 1, 1, 1;\n"
        "wgmma.mma_async.sync.aligned.m64n24k16.f32.bf16.bf16 {%88,%89,%90,%91,%92,%93,%94,%95,%96,%97,%98,%99}, {ha4,ha5,ha6,ha7}, da, 1, 1, 1, 1;\n"
        "wgmma.commit_group.sync.aligned;\n"
        "wgmma.mma_async.sync.aligned.m64n24k16.f32.bf16.bf16 {%12,%13,%14,%15,%16,%17,%18,%19,%20,%21,%22,%23}, {hb0,hb1,hb2,hb3}, db, 1, 1, 1, 1;\n"
        "wgmma.mma_async.sync.aligned.m64n24k16.f32.bf16.bf16 {%88,%89,%90,%91,%92,%93,%94,%95,%96,%97,%98,%99}, {hb4,hb5,hb6,hb7}, db, 1, 1, 1, 1;\n"
        "wgmma.commit_group.sync.aligned;\n"
        "wgmma.mma_async.sync.aligned.m64n8k16.f32.bf16.bf16 {r0,r1,r2,r3}, {%160,%161,%162,%163}, de, pf, 1, 1, 0;\n"
        "wgmma.mma_async.sync.aligned.m64n8k16.f32.bf16.bf16 {r4,r5,r6,r7}, {%164,%165,%166,%167}, de, pf, 1, 1, 0;\n"
        "wgmma.commit_group.sync.aligned;\n"
        "bra.uni C;\n"
        "T2:\n"
        "@t0 bra.uni L3;\n"
        "L2:\n"
        "wgmma.fence.sync.aligned;\n"
        "wgmma.mma_async.sync.aligned.m64n24k16.f32.bf16.bf16 {%24,%25,%26,%27,%28,%29,%30,%31,%32,%33,%34,%35}, {ha0,ha1,ha2,ha3}, da, 1, 1, 1, 1;\n"
        "wgmma.mma_async.sync.aligned.m64n24k16.f32.bf16.bf16 {%100,%101,%102,%103,%104,%105,%106,%107,%108,%109,%110,%111}, {ha4,ha5,ha6,ha7}, da, 1, 1, 1, 1;\n"
        "wgmma.commit_group.sync.aligned;\n"
        "wgmma.mma_async.sync.aligned.m64n24k16.f32.bf16.bf16 {%24,%25,%26,%27,%28,%29,%30,%31,%32,%33,%34,%35}, {hb0,hb1,hb2,hb3}, db, 1, 1, 1, 1;\n"
        "wgmma.mma_async.sync.aligned.m64n24k16.f32.bf16.bf16 {%100,%101,%102,%103,%104,%105,%106,%107,%108,%109,%110,%111}, {hb4,hb5,hb6,hb7}, db, 1, 1, 1, 1;\n"
        "wgmma.commit_group.sync.aligned;\n"
        "wgmma.mma_async.sync.aligned.m64n8k16.f32.bf16.bf16 {r0,r1,r2,r3}, {%160,%161,%162,%163}, de, pf, 1, 1, 0;\n"
        "wgmma.mma_async.sync.aligned.m64n8k16.f32.bf16.bf16 {r4,r5,r6,r7}, {%164,%165,%166,%167}, de, pf, 1, 1, 0;\n"
        "wgmma.commit_group.sync.aligned;\n"
        "bra.uni C;\n"
        "L3:\n"
        "wgmma.fence.sync.aligned;\n"
        "wgmma.mma_async.sync.aligned.m64n24k16.f32.bf16.bf16 {%36,%37,%38,%39,%40,%41,%42,%43,%44,%45,%46,%47}, {ha0,ha1,ha2,ha3}, da, 1, 1, 1, 1;\n"
        "wgmma.mma_async.sync.aligned.m64n24k16.f32.bf16.bf16 {%112,%113,%114,%115,%116,%117,%118,%119,%120,%121,%122,%123}, {ha4,ha5,ha6,ha7}, da, 1, 1, 1, 1;\n"
        "wgmma.commit_group.sync.aligned;\n"
        "wgmma.mma_async.sync.aligned.m64n24k16.f32.bf16.bf16 {%36,%37,%38,%39,%40,%41,%42,%43,%44,%45,%46,%47}, {hb0,hb1,hb2,hb3}, db, 1, 1, 1, 1;\n"
        "wgmma.mma_async.sync.aligned.m64n24k16.f32.bf16.bf16 {%112,%113,%114,%115,%116,%117,%118,%119,%120,%121,%122,%123}, {hb4,hb5,hb6,hb7}, db, 1, 1, 1, 1;\n"
        "wgmma.commit_group.sync.aligned;\n"
        "wgmma.mma_async.sync.aligned.m64n8k16.f32.bf16.bf16 {r0,r1,r2,r3}, {%160,%161,%162,%163}, de, pf, 1, 1, 0;\n"
        "wgmma.mma_async.sync.aligned.m64n8k16.f32.bf16.bf16 {r4,r5,r6,r7}, {%164,%165,%166,%167}, de, pf, 1, 1, 0;\n"
        "wgmma.commit_group.sync.aligned;\n"
        "bra.uni C;\n"
        "T4:\n"
        "@t1 bra.uni LEXIT;\n"
        "@t0 bra.uni L5;\n"
        "L4:\n"
        "wgmma.fence.sync.aligned;\n"
        "wgmma.mma_async.sync.aligned.m64n24k16.f32.bf16.bf16 {%48,%49,%50,%51,%52,%53,%54,%55,%56,%57,%58,%59}, {ha0,ha1,ha2,ha3}, da, 1, 1, 1, 1;\n"
        "wgmma.mma_async.sync.aligned.m64n24k16.f32.bf16.bf16 {%124,%125,%126,%127,%128,%129,%130,%131,%132,%133,%134,%135}, {ha4,ha5,ha6,ha7}, da, 1, 1, 1, 1;\n"
        "wgmma.commit_group.sync.aligned;\n"
        "wgmma.mma_async.sync.aligned.m64n24k16.f32.bf16.bf16 {%48,%49,%50,%51,%52,%53,%54,%55,%56,%57,%58,%59}, {hb0,hb1,hb2,hb3}, db, 1, 1, 1, 1;\n"
        "wgmma.mma_async.sync.aligned.m64n24k16.f32.bf16.bf16 {%124,%125,%126,%127,%128,%129,%130,%131,%132,%133,%134,%135}, {hb4,hb5,hb6,hb7}, db, 1, 1, 1, 1;\n"
        "wgmma.commit_group.sync.aligned;\n"
        "wgmma.mma_async.sync.aligned.m64n8k16.f32.bf16.bf16 {r0,r1,r2,r3}, {%160,%161,%162,%163}, de, pf, 1, 1, 0;\n"
        "wgmma.mma_async.sync.aligned.m64n8k16.f32.bf16.bf16 {r4,r5,r6,r7}, {%164,%165,%166,%167}, de, pf, 1, 1, 0;\n"
        "wgmma.commit_group.sync.aligned;\n"
        "bra.uni C;\n"
        "L5:\n"
        "wgmma.fence.sync.aligned;\n"
        "wgmma.mma_async.sync.aligned.m64n32k16.f32.bf16.bf16 {%60,%61,%62,%63,%64,%65,%66,%67,%68,%69,%70,%71,%72,%73,%74,%75}, {ha0,ha1,ha2,ha3}, da, 1, 1, 1, 1;\n"
        "wgmma.mma_async.sync.aligned.m64n32k16.f32.bf16.bf16 {%136,%137,%138,%139,%140,%141,%142,%143,%144,%145,%146,%147,%148,%149,%150,%151}, {ha4,ha5,ha6,ha7}, da, 1, 1, 1, 1;\n"
        "wgmma.commit_group.sync.aligned;\n"
        "wgmma.mma_async.sync.aligned.m64n32k16.f32.bf16.bf16 {%60,%61,%62,%63,%64,%65,%66,%67,%68,%69,%70,%71,%72,%73,%74,%75}, {hb0,hb1,hb2,hb3}, db, 1, 1, 1, 1;\n"
        "wgmma.mma_async.sync.aligned.m64n32k16.f32.bf16.bf16 {%136,%137,%138,%139,%140,%141,%142,%143,%144,%145,%146,%147,%148,%149,%150,%151}, {hb4,hb5,hb6,hb7}, db, 1, 1, 1, 1;\n"
        "wgmma.commit_group.sync.aligned;\n"
        "wgmma.mma_async.sync.aligned.m64n8k16.f32.bf16.bf16 {r0,r1,r2,r3}, {%160,%161,%162,%163}, de, pf, 1, 1, 0;\n"
        "wgmma.mma_async.sync.aligned.m64n8k16.f32.bf16.bf16 {r4,r5,r6,r7}, {%164,%165,%166,%167}, de, pf, 1, 1, 0;\n"
        "wgmma.commit_group.sync.aligned;\n"
        "bra.uni C;\n"
        "S2:\n"
        "mov.u32 cnt, 0;\n"
        "W3:\n"
        "mbarrier.try_wait.parity.shared.b64 p, [bar], par;\n"
        "@p bra.uni R2;\n"
        "add.u32 cnt, cnt, 1;\n"
        "setp.lt.u32 p, cnt, 4000000;\n"
        "@p bra.uni W3;\n"
        "trap;\n"
        "LEXIT:\n"
        "wgmma.wait_group.sync.aligned 0;\n"
        "}\n"
        : "=f"(acc[0][0][0]), "=f"(acc[0][0][1]), "=f"(acc[0][0][2]), "=f"(acc[0][0][3]),
          "=f"(acc[0][1][0]), "=f"(acc[0][1][1]), "=f"(acc[0][1][2]), "=f"(acc[0][1][3]),
          "=f"(acc[0][2][0]), "=f"(acc[0][2][1]), "=f"(acc[0][2][2]), "=f"(acc[0][2][3]),
          "=f"(acc[0][3][0]), "=f"(acc[0][3][1]), "=f"(acc[0][3][2]), "=f"(acc[0][3][3]),
          "=f"(acc[0][4][0]), "=f"(acc[0][4][1]), "=f"(acc[0][4][2]), "=f"(acc[0][4][3]),
          "=f"(acc[0][5][0]), "=f"(acc[0][5][1]), "=f"(acc[0][5][2]), "=f"(acc[0][5][3]),
          "=f"(acc[0][6][0]), "=f"(acc[0][6][1]), "=f"(acc[0][6][2]), "=f"(acc[0][6][3]),
          "=f"(acc[0][7][0]), "=f"(acc[0][7][1]), "=f"(acc[0][7][2]), "=f"(acc[0][7][3]),
          "=f"(acc[0][8][0]), "=f"(acc[0][8][1]), "=f"(acc[0][8][2]), "=f"(acc[0][8][3]),
          "=f"(acc[0][9][0]), "=f"(acc[0][9][1]), "=f"(acc[0][9][2]), "=f"(acc[0][9][3]),
          "=f"(acc[0][10][0]), "=f"(acc[0][10][1]), "=f"(acc[0][10][2]), "=f"(acc[0][10][3]),
          "=f"(acc[0][11][0]), "=f"(acc[0][11][1]), "=f"(acc[0][11][2]), "=f"(acc[0][11][3]),
          "=f"(acc[0][12][0]), "=f"(acc[0][12][1]), "=f"(acc[0][12][2]), "=f"(acc[0][12][3]),
          "=f"(acc[0][13][0]), "=f"(acc[0][13][1]), "=f"(acc[0][13][2]), "=f"(acc[0][13][3]),
          "=f"(acc[0][14][0]), "=f"(acc[0][14][1]), "=f"(acc[0][14][2]), "=f"(acc[0][14][3]),
          "=f"(acc[0][15][0]), "=f"(acc[0][15][1]), "=f"(acc[0][15][2]), "=f"(acc[0][15][3]),
          "=f"(acc[0][16][0]), "=f"(acc[0][16][1]), "=f"(acc[0][16][2]), "=f"(acc[0][16][3]),
          "=f"(acc[0][17][0]), "=f"(acc[0][17][1]), "=f"(acc[0][17][2]), "=f"(acc[0][17][3]),
          "=f"(acc[0][18][0]), "=f"(acc[0][18][1]), "=f"(acc[0][18][2]), "=f"(acc[0][18][3]),
          "=f"(acc[1][0][0]), "=f"(acc[1][0][1]), "=f"(acc[1][0][2]), "=f"(acc[1][0][3]),
          "=f"(acc[1][1][0]), "=f"(acc[1][1][1]), "=f"(acc[1][1][2]), "=f"(acc[1][1][3]),
          "=f"(acc[1][2][0]), "=f"(acc[1][2][1]), "=f"(acc[1][2][2]), "=f"(acc[1][2][3]),
          "=f"(acc[1][3][0]), "=f"(acc[1][3][1]), "=f"(acc[1][3][2]), "=f"(acc[1][3][3]),
          "=f"(acc[1][4][0]), "=f"(acc[1][4][1]), "=f"(acc[1][4][2]), "=f"(acc[1][4][3]),
          "=f"(acc[1][5][0]), "=f"(acc[1][5][1]), "=f"(acc[1][5][2]), "=f"(acc[1][5][3]),
          "=f"(acc[1][6][0]), "=f"(acc[1][6][1]), "=f"(acc[1][6][2]), "=f"(acc[1][6][3]),
          "=f"(acc[1][7][0]), "=f"(acc[1][7][1]), "=f"(acc[1][7][2]), "=f"(acc[1][7][3]),
          "=f"(acc[1][8][0]), "=f"(acc[1][8][1]), "=f"(acc[1][8][2]), "=f"(acc[1][8][3]),
          "=f"(acc[1][9][0]), "=f"(acc[1][9][1]), "=f"(acc[1][9][2]), "=f"(acc[1][9][3]),
          "=f"(acc[1][10][0]), "=f"(acc[1][10][1]), "=f"(acc[1][10][2]), "=f"(acc[1][10][3]),
          "=f"(acc[1][11][0]), "=f"(acc[1][11][1]), "=f"(acc[1][11][2]), "=f"(acc[1][11][3]),
          "=f"(acc[1][12][0]), "=f"(acc[1][12][1]), "=f"(acc[1][12][2]), "=f"(acc[1][12][3]),
          "=f"(acc[1][13][0]), "=f"(acc[1][13][1]), "=f"(acc[1][13][2]), "=f"(acc[1][13][3]),
          "=f"(acc[1][14][0]), "=f"(acc[1][14][1]), "=f"(acc[1][14][2]), "=f"(acc[1][14][3]),
          "=f"(acc[1][15][0]), "=f"(acc[1][15][1]), "=f"(acc[1][15][2]), "=f"(acc[1][15][3]),
          "=f"(acc[1][16][0]), "=f"(acc[1][16][1]), "=f"(acc[1][16][2]), "=f"(acc[1][16][3]),
          "=f"(acc[1][17][0]), "=f"(acc[1][17][1]), "=f"(acc[1][17][2]), "=f"(acc[1][17][3]),
          "=f"(acc[1][18][0]), "=f"(acc[1][18][1]), "=f"(acc[1][18][2]), "=f"(acc[1][18][3])
        : "r"(xa0), "r"(xa1), "r"(so0), "r"(bar0), "r"(ea0), "r"(d0), "r"(pl0), "r"(lz),
          "r"(w[0]), "r"(w[1]), "r"(w[2]), "r"(w[3]), "r"(w[4]), "r"(w[5]), "r"(w[6]), "r"(w[7])
        : "memory");
}
__device__ __forceinline__ void wgmma_out(float (&o)[NJ][4], uint64_t da, uint64_t db, int acc) {
    asm volatile(
        "{\n.reg .pred p;\nsetp.ne.b32 p, %78, 0;\n"
        "wgmma.mma_async.sync.aligned.m64n152k16.f32.bf16.bf16 {%0,%1,%2,%3,%4,%5,%6,%7,%8,%9,%10,%11,%12,%13,%14,%15,%16,%17,%18,%19,%20,%21,%22,%23,%24,%25,%26,%27,%28,%29,%30,%31,%32,%33,%34,%35,%36,%37,%38,%39,%40,%41,%42,%43,%44,%45,%46,%47,%48,%49,%50,%51,%52,%53,%54,%55,%56,%57,%58,%59,%60,%61,%62,%63,%64,%65,%66,%67,%68,%69,%70,%71,%72,%73,%74,%75}, %76, %77, p, 1, 1, 1, 1;\n}"
        : "+f"(o[0][0]), "+f"(o[0][1]), "+f"(o[0][2]), "+f"(o[0][3]),
          "+f"(o[1][0]), "+f"(o[1][1]), "+f"(o[1][2]), "+f"(o[1][3]),
          "+f"(o[2][0]), "+f"(o[2][1]), "+f"(o[2][2]), "+f"(o[2][3]),
          "+f"(o[3][0]), "+f"(o[3][1]), "+f"(o[3][2]), "+f"(o[3][3]),
          "+f"(o[4][0]), "+f"(o[4][1]), "+f"(o[4][2]), "+f"(o[4][3]),
          "+f"(o[5][0]), "+f"(o[5][1]), "+f"(o[5][2]), "+f"(o[5][3]),
          "+f"(o[6][0]), "+f"(o[6][1]), "+f"(o[6][2]), "+f"(o[6][3]),
          "+f"(o[7][0]), "+f"(o[7][1]), "+f"(o[7][2]), "+f"(o[7][3]),
          "+f"(o[8][0]), "+f"(o[8][1]), "+f"(o[8][2]), "+f"(o[8][3]),
          "+f"(o[9][0]), "+f"(o[9][1]), "+f"(o[9][2]), "+f"(o[9][3]),
          "+f"(o[10][0]), "+f"(o[10][1]), "+f"(o[10][2]), "+f"(o[10][3]),
          "+f"(o[11][0]), "+f"(o[11][1]), "+f"(o[11][2]), "+f"(o[11][3]),
          "+f"(o[12][0]), "+f"(o[12][1]), "+f"(o[12][2]), "+f"(o[12][3]),
          "+f"(o[13][0]), "+f"(o[13][1]), "+f"(o[13][2]), "+f"(o[13][3]),
          "+f"(o[14][0]), "+f"(o[14][1]), "+f"(o[14][2]), "+f"(o[14][3]),
          "+f"(o[15][0]), "+f"(o[15][1]), "+f"(o[15][2]), "+f"(o[15][3]),
          "+f"(o[16][0]), "+f"(o[16][1]), "+f"(o[16][2]), "+f"(o[16][3]),
          "+f"(o[17][0]), "+f"(o[17][1]), "+f"(o[17][2]), "+f"(o[17][3]),
          "+f"(o[18][0]), "+f"(o[18][1]), "+f"(o[18][2]), "+f"(o[18][3])
        : "l"(da), "l"(db), "r"(acc));
}

__device__ __forceinline__ void slow_edge(int ee, int s, float* accn, const __nv_bfloat16* __restrict__ x,
                                          const __nv_bfloat16* __restrict__ sh, const __nv_bfloat16* __restrict__ ea,
                                          const __nv_bfloat16* __restrict__ cg, const __nv_bfloat16* __restrict__ wr,
                                          int lane) {
    float rwv[4] = {0.f, 0.f, 0.f, 0.f};
#pragma unroll 4
    for (int d = 0; d < 16; d++) {
        const float a = __bfloat162float(ea[(size_t)ee * 16 + d]);
        const uint2 wv = *(const uint2*)(wr + d * 128 + lane * 4);
        rwv[0] += a * __uint_as_float(wv.x << 16);
        rwv[1] += a * __uint_as_float(wv.x & 0xffff0000u);
        rwv[2] += a * __uint_as_float(wv.y << 16);
        rwv[3] += a * __uint_as_float(wv.y & 0xffff0000u);
    }
    float A = 0.f;
#pragma unroll
    for (int v = 0; v < 4; v++)
        A += __bfloat162float(cg[((lane >> 2) & 3) * 16 + v * 4 + (lane & 3)]) * __bfloat162float(sh[(size_t)ee * 4 + v]);
    float m[4][4];
#pragma unroll
    for (int w = 0; w < 4; w++)
#pragma unroll
        for (int j = 0; j < 4; j++) m[w][j] = 0.f;
#pragma unroll
    for (int u = 0; u < 4; u++) {
        const uint2 xv = *(const uint2*)(x + (size_t)s * 512 + u * 128 + lane * 4);
        const float x0 = __uint_as_float(xv.x << 16), x1 = __uint_as_float(xv.x & 0xffff0000u);
        const float x2 = __uint_as_float(xv.y << 16), x3 = __uint_as_float(xv.y & 0xffff0000u);
#pragma unroll
        for (int w = 0; w < 4; w++) {
            const float a = __shfl_sync(0xffffffffu, A, u * 4 + w);
            m[w][0] += a * x0;
            m[w][1] += a * x1;
            m[w][2] += a * x2;
            m[w][3] += a * x3;
        }
    }
#pragma unroll
    for (int w = 0; w < 4; w++)
#pragma unroll
        for (int j = 0; j < 4; j++) atomicAdd(accn + w * 128 + lane * 4 + j, m[w][j] * rwv[j]);
}

__device__ __forceinline__ void slow_out(const float* accn, const __nv_bfloat16* __restrict__ wout,
                                         __nv_bfloat16* __restrict__ outn, int lane) {
    float o[4][4];
#pragma unroll
    for (int w = 0; w < 4; w++)
#pragma unroll
        for (int j = 0; j < 4; j++) o[w][j] = 0.f;
#pragma unroll 2
    for (int c = 0; c < 128; c++) {
        const uint2 wv = *(const uint2*)(wout + c * 128 + lane * 4);
        const float w0 = __uint_as_float(wv.x << 16), w1 = __uint_as_float(wv.x & 0xffff0000u);
        const float w2 = __uint_as_float(wv.y << 16), w3 = __uint_as_float(wv.y & 0xffff0000u);
#pragma unroll
        for (int w = 0; w < 4; w++) {
            const float a = __bfloat162float(__float2bfloat16(accn[w * 128 + c]));
            o[w][0] += a * w0;
            o[w][1] += a * w1;
            o[w][2] += a * w2;
            o[w][3] += a * w3;
        }
    }
#pragma unroll
    for (int w = 0; w < 4; w++)
        *(uint2*)(outn + w * 128 + lane * 4) = make_uint2(pack_bf16(o[w][0], o[w][1]), pack_bf16(o[w][2], o[w][3]));
}

static_assert(3 * NW >= 4 * NS, "barriers");
#define TWAIT mbar_lean_u
#define PWAIT mbar_lean
#define WG_SYNC(w) asm volatile("bar.sync %0, 128;" ::"r"((w) + 1) : "memory")
__global__ void __launch_bounds__(NT, 1)
main_kernel(const __grid_constant__ CUtensorMap tmx, const __grid_constant__ CUtensorMap tmw,
            const __grid_constant__ CUtensorMap tmo, const __nv_bfloat16* __restrict__ x, const int* __restrict__ src,
            const int* __restrict__ dst, const __nv_bfloat16* __restrict__ sh, const __nv_bfloat16* __restrict__ ea,
            const __nv_bfloat16* __restrict__ cg, const __nv_bfloat16* __restrict__ wr,
            const __nv_bfloat16* __restrict__ wout, __nv_bfloat16* __restrict__ out, int N, int E, int npb,
            unsigned npb_magic, int chunk, int fast_ok, int bsh, int tau16, int toff) {
    extern __shared__ __align__(1024) unsigned char smem[];
    const uint32_t sb = s2u(smem);
    int* s_int = (int*)(smem + SM_MISC + MI_INT);
    int* s_hist = (int*)(smem + SC_HIST);
    const int tid = threadIdx.x;
    const int warp = __shfl_sync(0xffffffffu, tid >> 5, 0), lane = tid & 31;
    const int g = lane >> 2, t = lane & 3;

    TLSTAMP(0);
    const int nbins = gridDim.x;
    const int bin = blockIdx.x;
    const int node0 = bin * npb, hpb = npb >> 1;
    const int ebeg = min(E, bin * chunk), eend = min(E, ebeg + chunk);
    int pd[EPS], ps[EPS];
#pragma unroll
    for (int k = 0; k < EPS; k++) {
        const int e = ebeg + tid + k * NT;
        pd[k] = e < eend ? __ldg(dst + e) : -1;
        ps[k] = e < eend ? __ldg(src + e) : 0;
    }
    int2* st_ent = (int2*)(smem + SC_ENT);
    unsigned char* st_bin = smem + SC_BIN;
    int* s_loc = s_hist + MAXBINS;
    int* s_del = s_loc + MAXBINS;
    if (lane < 3 && warp * 3 + lane < 4 * NS) mbar_init(sb + SM_BAR + (warp * 3 + lane) * 8, (warp + lane) & 1 ? 4 : 2);
    if (tid < MAXBINS) s_hist[tid] = 0;
    if (tid == 0) {
        s_int[3] = -1;
        mbar_init(sb + SM_MISC + MI_WBAR, 4);
        asm volatile("prefetch.tensormap [%0];" ::"l"(&tmx) : "memory");
    }
    if (tid < 2 * (NBK + 1)) ((uint4*)(smem + SC_CNT))[tid] = make_uint4(0, 0, 0, 0);
#pragma unroll
    for (int k = 0; k < TS / 2; k++) ((uint4*)(smem + SM_BT))[tid + k * NT] = make_uint4(0, 0, 0, 0);
    __syncthreads();
    TLSTAMP(1);
    for (int rb = ebeg;; rb += NT * EPS) {
        const bool last = rb + NT * EPS >= eend;
        int pb[EPS], pr[EPS];
#pragma unroll
        for (int k = 0; k < EPS; k++) {
            pb[k] = pd[k] >= 0 ? (int)__umulhi((unsigned)pd[k], npb_magic) : -1;
            if (pb[k] >= 0) pr[k] = atomicAdd(&s_hist[pb[k]], 1);
        }
        __syncthreads();
        TLSTAMP(6);
        int gbase = 0;
        if (warp == NW - 1) {
            int v[MAXBINS / 32], sum = 0;
#pragma unroll
            for (int c = 0; c < MAXBINS / 32; c++) {
                v[c] = s_hist[lane * (MAXBINS / 32) + c];
                sum += v[c];
            }
            int run = warp_incl_scan(sum, lane) - sum;
#pragma unroll
            for (int c = 0; c < MAXBINS / 32; c++) {
                s_loc[lane * (MAXBINS / 32) + c] = run;
                run += v[c];
            }
        } else if (tid < nbins) {
            gbase = atomicAdd(&g_bincnt[tid * 32], s_hist[tid] + (last ? 1 << 22 : 0));
        }
        __syncthreads();
#pragma unroll
        for (int k = 0; k < EPS; k++) {
            if (pb[k] >= 0) {
                const int pos = s_loc[pb[k]] + pr[k];
                st_ent[pos] = make_int2(ps[k], (rb + tid + k * NT) | ((pd[k] - pb[k] * npb) << 24) | 0x80000000);
                st_bin[pos] = pb[k];
            }
        }
        if (tid < nbins) s_del[tid] = (gbase & 0x3fffff) - s_loc[tid];
        __syncthreads();
        TLSTAMP(8);
        const int n = min(eend - rb, NT * EPS);
#pragma unroll
        for (int k = 0; k < EPS; k++) {
            const int i = tid + k * NT;
            if (i < n) {
                const int b = st_bin[i];
                const int gpos = i + s_del[b];
                if (gpos < BINCAP) __stcg(&g_bin[b * BINCAP + gpos], st_ent[i]);
            }
        }
        if (last) break;
        if (tid < MAXBINS) s_hist[tid] = 0;
#pragma unroll
        for (int k = 0; k < EPS; k++) {
            const int e = rb + NT * EPS + tid + k * NT;
            pd[k] = e < eend ? dst[e] : -1;
            ps[k] = e < eend ? src[e] : 0;
        }
        __syncthreads();
    }
    TLSTAMP(5);
    int2 ent[KS];
    int rank[KS];
    {
        int cnt = 0;
        if (lane == 0) {
            for (int spin = 0;; spin++) {
                asm volatile("ld.relaxed.gpu.global.s32 %0, [%1];" : "=r"(cnt) : "l"(&g_bincnt[bin * 32]) : "memory");
                if ((cnt >> 22) >= nbins) break;
                if (spin > 10000000) __trap();
            }
            atomicMin((unsigned*)s_int + 3, (unsigned)clock());
        }
        cnt = __shfl_sync(0xffffffffu, cnt, 0) & 0x3fffff;
        if (tid == 0) s_int[0] = cnt;
        const int n = min(cnt, BINCAP);
        unsigned pend = 0;
#pragma unroll
        for (int k = 0; k < KS; k++) {
            ent[k] = make_int2(0, 0);
            if (tid + k * NT < n) pend |= 1u << k;
        }
        int2* gp = &g_bin[bin * BINCAP + tid];
        for (int spin = 0; __any_sync(0xffffffffu, pend); spin++) {
#pragma unroll
            for (int k = 0; k < KS; k++)
                if ((pend >> k) & 1)
                    asm volatile("ld.relaxed.gpu.global.v2.s32 {%0,%1}, [%2];"
                                 : "=r"(ent[k].x), "=r"(ent[k].y)
                                 : "l"(gp + k * NT)
                                 : "memory");
#pragma unroll
            for (int k = 0; k < KS; k++)
                if (ent[k].y < 0) pend &= ~(1u << k);
            if (spin > 10000000) __trap();
        }
        TLSTAMP(2);
#pragma unroll
        for (int k = 0; k < KS; k++) {
            if (ent[k].y < 0) {
                if (fast_ok) {
                    const int dl = (ent[k].y >> 24) & 127, w = dl >= hpb;
                    const int loc = dl - (w ? hpb : 0), gr = GSZ == 6 ? min(loc * 43 >> 8, 5) : loc >> 3, sft = (gr & 1) * 16;
                    const int cw = (w * (NBK + 1) + (ent[k].x >> bsh)) * 4 + (gr >> 1);
                    const unsigned old = atomicAdd((unsigned*)(smem + SC_CNT) + cw, 1u << sft);
                    rank[k] = ((old >> sft) & 0xffff) | (gr << 12);
                    ent[k].x |= cw << 16;
                    ent[k].y = (ent[k].y & 0x80ffffff) | ((loc - gr * GSZ) << 24);
                }
                __stcg(gp + k * NT, make_int2(0, 0));
            }
        }
    }
    __syncthreads();
    if (tid == 0) g_bincnt[bin * 32] = 0;
    TLSTAMP(9);
    if (warp < 2) {
        uint4* cp = (uint4*)(smem + SC_CNT) + warp * (NBK + 1) + lane * (NBK / 32);
        uint4 v[NBK / 32];
        uint32_t s[3] = {0, 0, 0}, r[3], tot[3], base[3];
#pragma unroll
        for (int c = 0; c < NBK / 32; c++) {
            v[c] = cp[c];
            s[0] += v[c].x;
            s[1] += v[c].y;
            s[2] += v[c].z;
        }
        uint32_t sum = 0;
#pragma unroll
        for (int i = 0; i < 3; i++) {
            r[i] = warp_incl_scan(s[i], lane);
            tot[i] = __shfl_sync(0xffffffffu, r[i], 31);
            r[i] -= s[i];
            const uint32_t p = (tot[i] + 0x00070007u) & 0xfff8fff8u;
            base[i] = sum * 0x10001u + (p << 16);
            sum += (p & 0xffff) + (p >> 16);
        }
        auto blocks = [](const uint32_t(&a)[3]) {
            constexpr uint32_t c = (7 - CE) * 0x10001u;
            const uint32_t q = (((a[0] + c) >> 3) & 0x1fff1fffu) + (((a[1] + c) >> 3) & 0x1fff1fffu) + (((a[2] + c) >> 3) & 0x1fff1fffu);
            return (q & 0xffff) + (q >> 16);
        };
#pragma unroll
        for (int c = 0; c < NBK / 32; c++) {
            cp[c] = make_uint4(r[0] + base[0], r[1] + base[1], r[2] + base[2], blocks(r));
            r[0] += v[c].x;
            r[1] += v[c].y;
            r[2] += v[c].z;
        }
        const bool ok = sum + 8 <= LCAP;
        const int nst = sum >> 3;
        const uint32_t tw = g < 2 ? tot[0] : g < 4 ? tot[1] : tot[2], bw = g < 2 ? base[0] : g < 4 ? base[1] : base[2];
        const int le = g < 6 ? ((tw + bw) >> ((g & 1) * 16)) & 0xffff : sum;
        const bool tailb = t == 0 && (le & 7) >= 1 && (le & 7) <= CE;
        const unsigned tm = __ballot_sync(0xffffffffu, tailb);
        if (ok) {
#pragma unroll
            for (int k = 0; k < 2; k++) {
                const int i = (le & ~7) + 2 * t + k;
                if (i >= le) {
                    ((unsigned short*)(smem + SM_SRC))[warp * LCAP + i] = min(node0, N - 1);
                    ((uint32_t*)(smem + SM_EID))[warp * LCAP + i] = 0x80000000u;
                }
            }
            if (tailb) ((unsigned short*)(smem + SM_SEQ))[warp * SEQCAP + blocks(tot) + __popc(tm & ((1u << lane) - 1))] = (le >> 3) | g << 12;
            ((unsigned short*)(smem + SM_SEQ))[warp * SEQCAP + nst + lane] = nst | 6 << 12;
        }
        if (lane < (NS - (nst + 2) % NS) % NS) {
            mbar_arrive_cnt(sb + SM_BAR + (warp * NS + lane) * 16, 2);
            mbar_arrive_cnt(sb + SM_BAR + (warp * NS + lane) * 16 + 8, 4);
        }
        if (lane == 0) s_int[1 + warp] = ok ? nst : -1;
    }
    __syncthreads();
    TLSTAMP(10);
    const bool fast = s_int[0] <= BINCAP && fast_ok && (s_int[1] | s_int[2]) >= 0;
    if (fast) {
        int pos[KS];
#pragma unroll
        for (int k = 0; k < KS; k++)
            if (ent[k].y < 0) pos[k] = ((uint32_t*)(smem + SC_CNT))[ent[k].x >> 16];
#pragma unroll
        for (int k = 0; k < KS; k++) {
            if (ent[k].y < 0) {
                const int w = (ent[k].x >> 16) >= (NBK + 1) * 4;
                const int p = (((uint32_t)pos[k] >> ((rank[k] >> 8) & 16)) & 0xffff) + (rank[k] & 0xfff);
                ((unsigned short*)(smem + SM_SRC))[w * LCAP + p] = ent[k].x;
                ((uint32_t*)(smem + SM_EID))[w * LCAP + p] = ent[k].y & 0x7fffffff;
                if ((p & 7) == CE) {
                    const int i = atomicAdd((int*)(smem + SC_CNT) + ((ent[k].x >> 16) | 3), 1);
                    ((unsigned short*)(smem + SM_SEQ))[w * SEQCAP + i] = (p >> 3) | (rank[k] & 0x7000);
                }
            }
        }
    }
    FENCE_ASYNC();
    TLSTAMP(15);
    __syncthreads();
    TLSTAMP(3);

    if (fast && warp >= 12) {
        asm volatile("setmaxnreg.dec.sync.aligned.u32 %0;" ::"n"(HREG));
        const int w = warp & 1, j = (warp >> 1) & 1;
        const int nst = __shfl_sync(0xffffffffu, s_int[1 + w], 0);
        const uint32_t bar0 = sb + SM_BAR + w * NS * 16;
        uint32_t fseq = sb + SM_SEQ + w * SEQCAP * 2 + j * 4 + (lane >> 4) * 2;
        const uint32_t feid = sb + SM_EID + w * LCAP * 4 + ((lane >> 1) & 7) * 4;
        const uint32_t lea = ((lane >> 1) & 3) * 32 + ((lane >> 3) & 1) * 16 + (lane & 1) * 128, bea = sb + SM_EA + w * 4096;
        uint32_t oea[2] = {lea + (2 * j + 1 + (lane >> 4)) * 256, lea + (2 * j + 5 + (lane >> 4)) * 256};
        const uint32_t fsd = sb + SM_SIDE + (warp - 12) * 512 + lane * 8;
        const char* gea = (const char*)ea + (lane & 1) * 16;
        const char* gsh = (const char*)sh + (lane & 1) * 4;
        uint32_t es, ee;
        auto ids = [&]() {
            es = lds_u32(feid + (lds_u16(fseq) & 0xfff) * 32);
            ee = lds_u32(feid + (lds_u16(fseq + 2) & 0xfff) * 32);
            fseq += 8;
        };
        auto fetch = [&](int i) {
            cp_async16(bea + oea[i], gea + (size_t)(ee & 0xffffff) * 32, (int)ee >= 0 ? 16 : 0);
            cp_async4(fsd + i * 256, gsh + (size_t)(es & 0xffffff) * 8, (int)es >= 0 ? 4 : 0);
            sts_u32(fsd + i * 256 + 4, ((es >> 17) & 0x300) | ((es >> 21) & 8));
            asm volatile("cp.async.commit_group;" ::: "memory");
            oea[i] ^= 0x800;
        };
        ids();
        if (j == 0 && lane < 16) cp_async16(bea + lea, gea + (size_t)(es & 0xffffff) * 32, (int)es >= 0 ? 16 : 0);
        fetch(0);
        ids();
        fetch(1);
        uint32_t wf[2];
        {
            const unsigned short* cp = (const unsigned short*)cg + (g >> 1) * 16 + (t & 1) * 8 + (g & 1);
#pragma unroll
            for (int k = 0; k < 2; k++) wf[k] = t < 2 ? __ldg(cp + 2 * k) | ((uint32_t)__ldg(cp + 2 * k + 4) << 16) : 0u;
        }
        const uint32_t psd = sb + SM_SIDE + (warp - 12) * 512 + g * 16 + (t & 1) * 8;
        const uint32_t pt = sb + SM_BT + w * (TS * 2048) + j * 4096 + (g >> 2) * 1024 +
                            (2 * (g & 3) + (t & 1) + 8 * ((t >> 1) ^ ((g >> 1) & 1))) * 16;
        uint32_t old[4] = {pt, pt, pt, pt};
        const int v0 = (NS - (nst + 2) % NS) % NS + 2 * j;
        uint32_t af = bar0 + (v0 + (lane & 1)) % NS * 16;
        int ve = (v0 + 2 - TS + NS) * 16, pe = 1;
        if (ve >= NS * 16) ve -= NS * 16, pe = 0;
        const int lim = lane < 2 ? nst - lane : 0;
#pragma unroll 1
        for (int m = 2 * j; m < nst;) {
#pragma unroll
            for (int i = 0; i < 2; i++) {
                asm volatile("cp.async.wait_group 1;" ::: "memory");
                __syncwarp();
                const uint2 s0 = lds_v2(psd + i * 256), s1 = lds_v2(psd + i * 256 + 128);
                ids();
                float d0[4], d1[4];
                mma1688_z(d0, s0.x, s1.x, wf[0]);
                mma1688_z(d1, s0.x, s1.x, wf[1]);
                TWAIT(bar0 + ve + 8, pe);
                sts_v2(old[2 * i] + i * 8192, 0, 0);
                sts_v2(old[2 * i + 1] + i * 8192 + 2048, 0, 0);
                old[2 * i] = pt + s0.y;
                old[2 * i + 1] = pt + s1.y;
                sts_v2(old[2 * i] + i * 8192, pack_bf16(d0[0], d0[1]), pack_bf16(d1[0], d1[1]));
                sts_v2(old[2 * i + 1] + i * 8192 + 2048, pack_bf16(d0[2], d0[3]), pack_bf16(d1[2], d1[3]));
                FENCE_ASYNC();
                __syncwarp();
                if (m < lim) mbar_arrive(af);
                fetch(i);
                af += 64;
                if (af >= bar0 + NS * 16) af -= NS * 16;
                ve += 64;
                if (ve >= NS * 16) ve -= NS * 16, pe ^= 1;
                m += 4;
                if (m >= nst) break;
            }
        }
        asm volatile("cp.async.wait_group 0;" ::: "memory");
        TLMAX(13);
    } else if (fast && warp >= 8) {
        asm volatile("setmaxnreg.dec.sync.aligned.u32 %0;" ::"n"(PREG));
        if (elect()) {
            const int w = warp & 1, j = (warp >> 1) & 1;
            const int nst = s_int[1 + w];
            const uint32_t bar0 = sb + SM_BAR + w * NS * 16, ring = sb + w * RING_BYTES;
            const uint32_t pseq = sb + SM_SEQ + w * SEQCAP * 2, psrc = sb + SM_SRC + w * LCAP * 2;
            const unsigned tbase = (unsigned)s_int[3] + (unsigned)toff;
            const int tslack = N * tau16 >> 8, taug = (N * tau16 >> 4) / max(nst, 1);
            int v = (NS - (nst + 2) % NS) % NS + j, par = 1;
            if (v >= NS) v -= NS, par = 0;
            uint32_t sq = lds_u16(pseq + j * 2);
            int n = j;
#pragma unroll 1
            for (; n < nst; n += 2) {
                const uint4 a = lds_v4(psrc + (sq & 0xfff) * 16);
                sq = lds_u16(pseq + n * 2 + 4);
                const uint32_t fb = bar0 + v * 16, d = ring + v * 4096;
                PWAIT(fb + 8, par);
                const unsigned tgt = (unsigned)min((int)((CE == 2 ? a.y & 0xffff : CE == 3 ? a.y >> 16 : a.z & 0xffff) * tau16 >> 4), n * taug + tslack) + tbase;
                while ((int)((unsigned)clock() - tgt) < 0) __nanosleep(PSLEEP);
                mbar_expect_tx(fb, 8192);
                tma_row(d + SM_EVEN, &tmx, fb, (a.x & 0xffff) * 8);
                tma_row(d + SM_ODD, &tmx, fb, (a.x >> 16) * 8);
                tma_row(d + SM_EVEN + 1024, &tmx, fb, (a.y & 0xffff) * 8);
                tma_row(d + SM_ODD + 1024, &tmx, fb, (a.y >> 16) * 8);
                tma_row(d + SM_EVEN + 2048, &tmx, fb, (a.z & 0xffff) * 8);
                tma_row(d + SM_ODD + 2048, &tmx, fb, (a.z >> 16) * 8);
                tma_row(d + SM_EVEN + 3072, &tmx, fb, (a.w & 0xffff) * 8);
                tma_row(d + SM_ODD + 3072, &tmx, fb, (a.w >> 16) * 8);
                v += 2;
                if (v >= NS) v -= NS, par ^= 1;
            }
            const uint32_t fb = bar0 + v * 16, d = ring + v * 4096;
            mbar_wait(fb + 8, par);
            mbar_arrive_cnt(fb, 2);
            mbar_expect_tx(sb + SM_MISC + MI_WBAR, 8192);
            tma_2d(d + SM_EVEN, &tmw, sb + SM_MISC + MI_WBAR, w * 64, (n - nst) * 32);
            tma_2d(d + SM_ODD, &tmw, sb + SM_MISC + MI_WBAR, w * 64, (n - nst) * 32 + 64);
        }
        TLMAX(12);
    } else if (fast) {
        asm volatile("setmaxnreg.inc.sync.aligned.u32 %0;" ::"n"(CREG));
        const int w = warp >> 2, wq = warp & 3;
        const int nst = __shfl_sync(0xffffffffu, s_int[1 + w], 0);
        const uint32_t ring = sb + w * RING_BYTES;
        float acc[2][NJ][4];
        {
            uint32_t wf[8];
            const unsigned short* wp = (const unsigned short*)wr + t * 256 + wq * 16 + g;
#pragma unroll
            for (int k = 0; k < 8; k++) {
                const int o = (k >> 2) * 64 + (k & 1) * 8 + (k & 2) * 512;
                wf[k] = __ldg(wp + o) | ((uint32_t)__ldg(wp + o + 128) << 16);
            }
            const int e = (lane >> 1) & 3, m = lane >> 3;
            const int line = 2 * ((lane & 1) + 2 * ((m >> 1) ^ (e >> 1))), ch = 2 * wq + (m & 1);
            const uint32_t xb = ring + (e & 1 ? SM_ODD : SM_EVEN) + (e >> 1) * 1024 + line * 128;
            consume(acc, xb + ((ch ^ ((line + (e & 1)) & 7)) * 16), xb + 128 + ((ch ^ ((line + 1 + (e & 1)) & 7)) * 16),
                    (NS - (nst + 2) % NS) % NS * 4096, sb + SM_BAR + w * NS * 16, (((sb + SM_EA + w * 4096) & 0x3ffff) >> 4) | (8 << 16),
                    (((sb + SM_BT + w * (TS * 2048)) & 0x3ffff) >> 4) | (8 << 16), sb + SM_SEQ + w * SEQCAP * 2, lane & (E >> 31), wf);
        }
        TLMAX(11);
#pragma unroll
        for (int h = 0; h < 2; h++) {
            const uint32_t tb = ring + (h ? SM_ODD : SM_EVEN) + wq * (NJ * 256) + lane * 16;
#pragma unroll
            for (int j = 0; j + 1 < NJ; j += 2)
                stsm4(tb + j * 256, pack_bf16(acc[h][j][0], acc[h][j][1]), pack_bf16(acc[h][j][2], acc[h][j][3]),
                      pack_bf16(acc[h][j + 1][0], acc[h][j + 1][1]), pack_bf16(acc[h][j + 1][2], acc[h][j + 1][3]));
            if (NJ & 1)
                stsm2(tb + (NJ - 1) * 256, pack_bf16(acc[h][NJ - 1][0], acc[h][NJ - 1][1]),
                      pack_bf16(acc[h][NJ - 1][2], acc[h][NJ - 1][3]));
        }
        FENCE_ASYNC();
        WG_SYNC(w);
        mbar_wait_u(sb + SM_MISC + MI_WBAR, 0);
        float o[2][NJ][4];
        asm volatile("wgmma.fence.sync.aligned;" ::: "memory");
#pragma unroll
        for (int hh = 0; hh < 2; hh++) {
#pragma unroll
            for (int ks = 0; ks < 8; ks++) {
                const uint32_t rg = ks >> 2 ? SM_ODD : SM_EVEN;
                const uint64_t da = (uint64_t)(((sb + rg + hh * RING_BYTES + (NS - 2) * 4096 + (ks & 3) * 2048) & 0x3ffff) >> 4) |
                                    (64ull << 32) | (1ull << 62);
                const uint64_t db = (uint64_t)(((ring + rg + (ks & 3) * (NJ * 256)) & 0x3ffff) >> 4) | (8ull << 16) | (16ull << 32);
                wgmma_out(o[hh], da, db, ks);
            }
            asm volatile("wgmma.commit_group.sync.aligned;" ::: "memory");
        }
        const int nb = 2 * hpb;
#pragma unroll
        for (int hh = 0; hh < 2; hh++) {
            if (hh == 0) {
                asm volatile("wgmma.wait_group.sync.aligned 1;" ::: "memory");
            } else {
                asm volatile("wgmma.wait_group.sync.aligned 0;" ::: "memory");
                WG_SYNC(w);
            }
#pragma unroll
            for (int j = 0; j < NJ; j++)
#pragma unroll
                for (int k = 0; k < 4; k++) asm volatile("" : "+f"(o[hh][j][k])::"memory");
            const uint32_t b0 = ring + SM_EVEN + (hh ? 0 : 20480);
            const uint32_t b1 = hh ? b0 : ring + SM_ODD + 20480 + 896 - (nb * 128 & ~1023);
            const int r = (lane & 7) + (lane >> 4) * 8;
            const uint32_t co = r * 128 + (((2 * wq + ((lane >> 3) & 1)) ^ (lane & 7)) * 16);
#pragma unroll
            for (int j = 0; j + 1 < NJ; j += 2)
                stsm4t((8 * j + r < nb ? b0 : b1) + co + j * 1024, pack_bf16(o[hh][j][0], o[hh][j][1]),
                       pack_bf16(o[hh][j][2], o[hh][j][3]), pack_bf16(o[hh][j + 1][0], o[hh][j + 1][1]),
                       pack_bf16(o[hh][j + 1][2], o[hh][j + 1][3]));
            if (NJ & 1)
                stsm2t(b1 + co + (NJ - 1) * 1024, pack_bf16(o[hh][NJ - 1][0], o[hh][NJ - 1][1]),
                       pack_bf16(o[hh][NJ - 1][2], o[hh][NJ - 1][3]));
            FENCE_ASYNC();
            WG_SYNC(w);
            if (wq < 2 && elect()) {
                const int row = (node0 + w * hpb) * 4 + wq * nb;
                if (row < N * 4) tma_store(&tmo, wq ? b1 + nb * 128 : b0, hh * 64, row);
                asm volatile("cp.async.bulk.commit_group;" ::: "memory");
                if (hh) asm volatile("cp.async.bulk.wait_group.read 0;" ::: "memory");
            }
        }
    } else {
        float* accs = (float*)smem;
        constexpr int NACC = SM_EID / 2048;
        const int nnodes = max(0, min(npb, N - node0));
#pragma unroll 1
        for (int nb = 0; nb < nnodes; nb += NACC) {
            __syncthreads();
            for (int i = tid; i < NACC * 512; i += NT) accs[i] = 0.f;
            __syncthreads();
#pragma unroll 1
            for (int base = warp * 32; base < E; base += NT) {
                const int e = base + lane;
                int dl = e < E ? dst[e] - node0 - nb : -1;
                if (dl + nb >= nnodes) dl = -1;
                unsigned mask = __ballot_sync(0xffffffffu, dl >= 0 && dl < NACC);
#pragma unroll 1
                while (mask) {
                    const int l = __ffs(mask) - 1;
                    mask &= mask - 1;
                    const int ee = __shfl_sync(0xffffffffu, e, l);
                    const int dd = __shfl_sync(0xffffffffu, dl, l);
                    slow_edge(ee, src[ee], accs + dd * 512, x, sh, ea, cg, wr, lane);
                }
            }
            __syncthreads();
#pragma unroll 1
            for (int nl = warp; nl < NACC && nb + nl < nnodes; nl += NW)
                slow_out(accs + nl * 512, wout, out + (size_t)(node0 + nb + nl) * 512, lane);
        }
        __syncthreads();
    }

    TLMAX(4);
}

typedef CUresult (*EncodeTiledFn)(CUtensorMap*, CUtensorMapDataType, cuuint32_t, void*, const cuuint64_t*,
                                  const cuuint64_t*, const cuuint32_t*, const cuuint32_t*, CUtensorMapInterleave,
                                  CUtensorMapSwizzle, CUtensorMapL2promotion, CUtensorMapFloatOOBfill);

extern "C" void kernel_launch(void* const* d_in, const int* in_sizes, int n_in, void* d_out, int out_size) {
    const __nv_bfloat16* x = (const __nv_bfloat16*)d_in[0];
    const int* src = (const int*)d_in[1];
    const int* dst = (const int*)d_in[2];
    const __nv_bfloat16* sh = (const __nv_bfloat16*)d_in[3];
    const __nv_bfloat16* ea = (const __nv_bfloat16*)d_in[4];
    const __nv_bfloat16* cg = (const __nv_bfloat16*)d_in[5];
    const __nv_bfloat16* wr = (const __nv_bfloat16*)d_in[6];
    const __nv_bfloat16* wout = (const __nv_bfloat16*)d_in[7];
    __nv_bfloat16* out = (__nv_bfloat16*)d_out;
    const int N = in_sizes[0] / 512;
    const int E = in_sizes[1];

    static int num_sms = 0;
    static EncodeTiledFn encode = nullptr;
    if (num_sms == 0) {
        int dev = 0;
        cudaGetDevice(&dev);
        cudaDeviceGetAttribute(&num_sms, cudaDevAttrMultiProcessorCount, dev);
        cudaFuncSetAttribute(main_kernel, cudaFuncAttributeMaxDynamicSharedMemorySize, SM_TOTAL);
        void* fn = nullptr;
        cudaDriverEntryPointQueryResult qr;
        cudaGetDriverEntryPoint("cuTensorMapEncodeTiled", &fn, cudaEnableDefault, &qr);
        encode = (EncodeTiledFn)fn;
    }
    const int nbins = num_sms < MAXBINS ? num_sms : MAXBINS;
    int npb = ((N + nbins - 1) / nbins + 1) & ~1;
    if (npb < 32) npb = 32;
    const int fast_ok = npb <= 2 * HPB;
    auto map2d = [&](CUtensorMap* tm, const void* p, int d0, int d1, int b1) {
        const cuuint64_t gd[2] = {(cuuint64_t)d0, (cuuint64_t)d1};
        const cuuint64_t gs[1] = {(cuuint64_t)d0 * 2};
        const cuuint32_t bx[2] = {64, (cuuint32_t)b1};
        const cuuint32_t es[2] = {1, 1};
        encode(tm, CU_TENSOR_MAP_DATA_TYPE_BFLOAT16, 2, (void*)p, gd, gs, bx, es, CU_TENSOR_MAP_INTERLEAVE_NONE,
               CU_TENSOR_MAP_SWIZZLE_128B, CU_TENSOR_MAP_L2_PROMOTION_NONE, CU_TENSOR_MAP_FLOAT_OOB_FILL_NONE);
    };
    CUtensorMap tmx, tmw, tmo;
    map2d(&tmx, x, 64, N * 8, 8);
    map2d(&tmw, wout, 128, 128, 32);
    map2d(&tmo, out, 128, N * 4, fast_ok ? npb : 2);
    const unsigned npb_magic = (unsigned)((0x100000000ull + npb - 1) / npb);
    const int chunk = (E + nbins - 1) / nbins;
    int bsh = 0;
    while (((N - 1) >> bsh) >= NBK) bsh++;
    int tau16 = (int)((double)PACE * 16.0 * chunk / N), toff = TOFF;
    main_kernel<<<nbins, NT, SM_TOTAL, cudaStreamPerThread>>>(tmx, tmw, tmo, x, src, dst, sh, ea, cg, wr, wout, out, N, E,
                                                              npb, npb_magic, chunk, fast_ok, bsh, tau16, toff);
}
```

```cpp
#include <cuda_runtime.h>
#include <cuda.h>
#include <cuda_bf16.h>
#include <stdint.h>
#include <stdlib.h>

#define MAXBINS 256
#define NW 16
#define NT (NW * 32)
#define HPB 38
#define BINCAP 3072
#define LCAP 1472
#define NBK 160
#define CE 3
#define GSZ 6
#define NS 10
#define RING_BYTES 40960
static_assert(RING_BYTES == NS * 4096, "ring");
#define NP (NS / 2)
#define CREG 224
#define PREG 24
#define HREG 40
#define TS 8
#define SM_EVEN 0
#define SM_MISC (2 * RING_BYTES)
#define SM_ODD (SM_MISC + 128)
#define SM_BT (SM_ODD + 2 * RING_BYTES)
#define SM_EA (SM_BT + TS * 4096)
#define SM_WR (SM_EA + 8192)
#define SM_SIDE (SM_WR + 4096)
#define SM_EID (SM_SIDE + 2048)
#define SM_SRC (SM_EID + 2 * LCAP * 4)
#define SEQCAP (LCAP / 8 + 40)
#define SM_SEQ (SM_SRC + 2 * LCAP * 2)
#define SM_BAR (SM_SEQ + 2 * SEQCAP * 2)
#define SM_TOTAL (SM_BAR + 2 * NP * 16)
#define MI_WBAR 32
#define MI_INT 0
#define EPS ((2464 + NT - 1) / NT)
#define KS (BINCAP / NT)
#define SC_ENT 0
#define SC_BIN (SC_ENT + NT * EPS * 8)
#define SC_HIST (SC_BIN + NT * EPS)
#define SC_CNT (SC_HIST + 3 * MAXBINS * 4)
static_assert(SC_HIST % 16 == 0 && SC_CNT + 2 * (NBK + 1) * 16 <= SM_MISC, "scratch");
static_assert(SM_TOTAL <= 232448 && SM_BAR % 16 == 0 && SM_SEQ % 16 == 0 && SM_SRC % 16 == 0, "smem");
#define PACE 23.0
#define TOFF 7000
#define PSLEEP 20

__device__ int2 g_bin[MAXBINS * BINCAP];
__device__ int g_bincnt[MAXBINS * 32];
#define TLSTAMP(i)
#define TLMAX(i)

__device__ __forceinline__ uint32_t pack_bf16(float lo, float hi) {
    uint32_t r;
    asm("cvt.rn.bf16x2.f32 %0, %1, %2;" : "=r"(r) : "f"(hi), "f"(lo));
    return r;
}
__device__ __forceinline__ void mma1688_z(float (&d)[4], uint32_t a0, uint32_t a1, uint32_t b0) {
    asm("mma.sync.aligned.m16n8k8.row.col.f32.bf16.bf16.f32 {%0,%1,%2,%3}, {%4,%5}, {%6}, {%7,%7,%7,%7};"
        : "=f"(d[0]), "=f"(d[1]), "=f"(d[2]), "=f"(d[3])
        : "r"(a0), "r"(a1), "r"(b0), "f"(0.f));
}
__device__ __forceinline__ uint32_t s2u(const void* p) { return (uint32_t)__cvta_generic_to_shared(p); }
__device__ __forceinline__ void mbar_init(uint32_t a, int c) {
    asm volatile("mbarrier.init.shared.b64 [%0], %1;" ::"r"(a), "r"(c));
}
__device__ __forceinline__ void mbar_expect_tx(uint32_t a, int bytes) {
    asm volatile("mbarrier.arrive.expect_tx.shared.b64 _, [%0], %1;" ::"r"(a), "r"(bytes) : "memory");
}
__device__ __forceinline__ void mbar_arrive(uint32_t a) {
    asm volatile("mbarrier.arrive.shared.b64 _, [%0];" ::"r"(a) : "memory");
}
__device__ __forceinline__ void mbar_arrive_cnt(uint32_t a, int c) {
    asm volatile("mbarrier.arrive.shared.b64 _, [%0], %1;" ::"r"(a), "r"(c) : "memory");
}
__device__ __forceinline__ void mbar_wait(uint32_t a, int parity) {
    asm volatile(
        "{\n.reg .pred p;\n.reg .u32 c;\n"
        "mov.u32 c, 0;\n"
        "LAB_WAIT:\n"
        "mbarrier.try_wait.parity.shared.b64 p, [%0], %1, 2000;\n"
        "@p bra DONE;\n"
        "add.u32 c, c, 1;\n"
        "setp.lt.u32 p, c, 2000000;\n"
        "@p bra LAB_WAIT;\n"
        "trap;\n"
        "DONE:\n}" ::"r"(a),
        "r"(parity)
        : "memory");
}
__device__ __forceinline__ void mbar_wait_u(uint32_t a, int parity) {
    asm volatile(
        "{\n.reg .pred p;\n.reg .u32 c;\n"
        "mov.u32 c, 0;\n"
        "LAB_WAIT:\n"
        "mbarrier.try_wait.parity.shared.b64 p, [%0], %1, 2000;\n"
        "@p bra.uni DONE;\n"
        "add.u32 c, c, 1;\n"
        "setp.lt.u32 p, c, 2000000;\n"
        "@p bra.uni LAB_WAIT;\n"
        "trap;\n"
        "DONE:\n}" ::"r"(a),
        "r"(parity)
        : "memory");
}
__device__ __forceinline__ void mbar_spin_u(uint32_t a, int parity) {
    asm volatile(
        "{\n.reg .pred p;\n.reg .u32 c;\n"
        "mov.u32 c, 0;\n"
        "LAB_WAIT:\n"
        "mbarrier.test_wait.parity.shared.b64 p, [%0], %1;\n"
        "@p bra.uni DONE;\n"
        "add.u32 c, c, 1;\n"
        "setp.lt.u32 p, c, 20000000;\n"
        "@p bra.uni LAB_WAIT;\n"
        "trap;\n"
        "DONE:\n}" ::"r"(a),
        "r"(parity)
        : "memory");
}
__device__ __forceinline__ void mbar_lean(uint32_t a, int parity) {
    asm volatile(
        "{\n.reg .pred p;\n.reg .u32 c;\n"
        "mov.u32 c, 0;\n"
        "LAB_WAIT:\n"
        "mbarrier.try_wait.parity.shared.b64 p, [%0], %1;\n"
        "@p bra DONE;\n"
        "add.u32 c, c, 1;\n"
        "setp.lt.u32 p, c, 4000000;\n"
        "@p bra LAB_WAIT;\n"
        "trap;\n"
        "DONE:\n}" ::"r"(a),
        "r"(parity)
        : "memory");
}
__device__ __forceinline__ void mbar_lean_u(uint32_t a, int parity) {
    asm volatile(
        "{\n.reg .pred p;\n.reg .u32 c;\n"
        "mov.u32 c, 0;\n"
        "LAB_WAIT:\n"
        "mbarrier.try_wait.parity.shared.b64 p, [%0], %1;\n"
        "@p bra.uni DONE;\n"
        "add.u32 c, c, 1;\n"
        "setp.lt.u32 p, c, 4000000;\n"
        "@p bra.uni LAB_WAIT;\n"
        "trap;\n"
        "DONE:\n}" ::"r"(a),
        "r"(parity)
        : "memory");
}
__device__ __forceinline__ bool mbar_test(uint32_t a, int parity) {
    uint32_t p;
    asm volatile("{\n.reg .pred P;\nmbarrier.test_wait.parity.shared.b64 P, [%1], %2;\nselp.u32 %0, 1, 0, P;\n}"
                 : "=r"(p)
                 : "r"(a), "r"(parity)
                 : "memory");
    return p;
}
__device__ __forceinline__ bool elect() {
    uint32_t p;
    asm volatile("{\n.reg .pred P;\nelect.sync _|P, 0xffffffff;\nselp.u32 %0, 1, 0, P;\n}" : "=r"(p));
    return p;
}
__device__ __forceinline__ void tma_2d(uint32_t dst, const CUtensorMap* tm, uint32_t bar, int c0, int c1) {
    asm volatile(
        "cp.async.bulk.tensor.2d.shared::cluster.global.mbarrier::complete_tx::bytes [%0], [%1, {%3, %4}], [%2];" ::"r"(dst),
        "l"(tm), "r"(bar), "r"(c0), "r"(c1)
        : "memory");
}
__device__ __forceinline__ void tma_row(uint32_t dst, const CUtensorMap* tm, uint32_t bar, int row8) {
    tma_2d(dst, tm, bar, 0, row8);
}
__device__ __forceinline__ void tma_store(const CUtensorMap* tm, uint32_t src, int c0, int c1) {
    asm volatile("cp.async.bulk.tensor.2d.global.shared::cta.bulk_group [%0, {%2, %3}], [%1];" ::"l"(tm), "r"(src),
                 "r"(c0), "r"(c1)
                 : "memory");
}
__device__ __forceinline__ uint2 lds_v2(uint32_t a) {
    uint2 v;
    asm volatile("ld.shared.v2.u32 {%0,%1}, [%2];" : "=r"(v.x), "=r"(v.y) : "r"(a));
    return v;
}
__device__ __forceinline__ uint4 lds_v4(uint32_t a) {
    uint4 v;
    asm volatile("ld.shared.v4.u32 {%0,%1,%2,%3}, [%4];" : "=r"(v.x), "=r"(v.y), "=r"(v.z), "=r"(v.w) : "r"(a));
    return v;
}
__device__ __forceinline__ uint32_t lds_u32(uint32_t a) {
    uint32_t v;
    asm volatile("ld.shared.u32 %0, [%1];" : "=r"(v) : "r"(a));
    return v;
}
__device__ __forceinline__ uint32_t lds_u16(uint32_t a) {
    uint32_t v;
    asm volatile("ld.shared.u16 %0, [%1];" : "=r"(v) : "r"(a));
    return v;
}
__device__ __forceinline__ void sts_v2(uint32_t a, uint32_t x, uint32_t y) {
    asm volatile("st.shared.v2.u32 [%0], {%1,%2};" ::"r"(a), "r"(x), "r"(y) : "memory");
}
__device__ __forceinline__ void sts_v4(uint32_t a, uint4 v) {
    asm volatile("st.shared.v4.u32 [%0], {%1,%2,%3,%4};" ::"r"(a), "r"(v.x), "r"(v.y), "r"(v.z), "r"(v.w) : "memory");
}
__device__ __forceinline__ void stsm4(uint32_t a, uint32_t r0, uint32_t r1, uint32_t r2, uint32_t r3) {
    asm volatile("stmatrix.sync.aligned.m8n8.x4.shared.b16 [%0], {%1,%2,%3,%4};" ::"r"(a), "r"(r0), "r"(r1), "r"(r2), "r"(r3)
                 : "memory");
}
__device__ __forceinline__ void stsm2(uint32_t a, uint32_t r0, uint32_t r1) {
    asm volatile("stmatrix.sync.aligned.m8n8.x2.shared.b16 [%0], {%1,%2};" ::"r"(a), "r"(r0), "r"(r1) : "memory");
}
__device__ __forceinline__ void stsm4t(uint32_t a, uint32_t r0, uint32_t r1, uint32_t r2, uint32_t r3) {
    asm volatile("stmatrix.sync.aligned.m8n8.x4.trans.shared.b16 [%0], {%1,%2,%3,%4};" ::"r"(a), "r"(r0), "r"(r1), "r"(r2),
                 "r"(r3)
                 : "memory");
}
__device__ __forceinline__ void stsm2t(uint32_t a, uint32_t r0, uint32_t r1) {
    asm volatile("stmatrix.sync.aligned.m8n8.x2.trans.shared.b16 [%0], {%1,%2};" ::"r"(a), "r"(r0), "r"(r1) : "memory");
}
__device__ __forceinline__ void cp_async16(uint32_t d, const void* s, int n) {
    asm volatile("cp.async.cg.shared.global [%0], [%1], 16, %2;" ::"r"(d), "l"(s), "r"(n) : "memory");
}
__device__ __forceinline__ void cp_async4(uint32_t d, const void* s, int n) {
    asm volatile("cp.async.ca.shared.global [%0], [%1], 4, %2;" ::"r"(d), "l"(s), "r"(n) : "memory");
}
__device__ __forceinline__ void sts_u32(uint32_t a, uint32_t x) {
    asm volatile("st.shared.u32 [%0], %1;" ::"r"(a), "r"(x) : "memory");
}
#define FENCE_ASYNC() asm volatile("fence.proxy.async.shared::cta;" ::: "memory")
__device__ __forceinline__ int warp_incl_scan(int v, int lane) {
#pragma unroll
    for (int o = 1; o < 32; o <<= 1) {
        const int y = __shfl_up_sync(0xffffffffu, v, o);
        if (lane >= o) v += y;
    }
    return v;
}

#define STR2(x) #x
#define STR(x) STR2(x)
#define NJ 19
__device__ __forceinline__ void consume(float (&acc)[2][NJ][4], uint32_t xa0, uint32_t xa1, uint32_t so0, uint32_t bar0,
                                        uint32_t ea0, uint32_t d0, uint32_t pl0, int lz, uint32_t wd) {
    asm volatile(
        "{\n"
        ".reg .pred p, pf, plead, pok, t0, t1, t2, t3;\n"
        ".reg .b32 ca, cb;\n"
        "mov.b32 ca, 0x30002000;\n"
        "mov.b32 cb, 0xbfff0000;\n"
        ".reg .b32 cnt, so, q, qe, bar, rbar, pl, ctl, dl, dh, v0, v1, v2, v3, pp;\n"
        ".reg .b16 sl, sh;\n"
        ".reg .b32 hXa0, hXa1, hXa2, hXa3, hXa4, hXa5, hXa6, hXa7, hXb0, hXb1, hXb2, hXb3, hXb4, hXb5, hXb6, hXb7, hYa0, hYa1, hYa2, hYa3, hYa4, hYa5, hYa6, hYa7, hYb0, hYb1, hYb2, hYb3, hYb4, hYb5, hYb6, hYb7, hLa0, hLa1, hLa2, hLa3, hLa4, hLa5, hLa6, hLa7, hLb0, hLb1, hLb2, hLb3, hLb4, hLb5, hLb6, hLb7;\n"
        ".reg .b32 pX0, pX1, pX2, pX3, pY0, pY1, pY2, pY3;\n"
        ".reg .f32 r0, r1, r2, r3, r4, r5, r6, r7, r8, r9, r10, r11, r12, r13, r14, r15;\n"
        ".reg .b64 daX, dbX, daY, dbY, de0, de1, dw0, dw1;\n"
        ".reg .b32 dh<6>, eb0, par, px;\n"
        "mov.f32 %0, 0f00000000;\n"
        "mov.f32 %1, 0f00000000;\n"
        "mov.f32 %2, 0f00000000;\n"
        "mov.f32 %3, 0f00000000;\n"
        "mov.f32 %4, 0f00000000;\n"
        "mov.f32 %5, 0f00000000;\n"
        "mov.f32 %6, 0f00000000;\n"
        "mov.f32 %7, 0f00000000;\n"
        "mov.f32 %8, 0f00000000;\n"
        "mov.f32 %9, 0f00000000;\n"
        "mov.f32 %10, 0f00000000;\n"
        "mov.f32 %11, 0f00000000;\n"
        "mov.f32 %12, 0f00000000;\n"
        "mov.f32 %13, 0f00000000;\n"
        "mov.f32 %14, 0f00000000;\n"
        "mov.f32 %15, 0f00000000;\n"
        "mov.f32 %16, 0f00000000;\n"
        "mov.f32 %17, 0f00000000;\n"
        "mov.f32 %18, 0f00000000;\n"
        "mov.f32 %19, 0f00000000;\n"
        "mov.f32 %20, 0f00000000;\n"
        "mov.f32 %21, 0f00000000;\n"
        "mov.f32 %22, 0f00000000;\n"
        "mov.f32 %23, 0f00000000;\n"
        "mov.f32 %24, 0f00000000;\n"
        "mov.f32 %25, 0f00000000;\n"
        "mov.f32 %26, 0f00000000;\n"
        "mov.f32 %27, 0f00000000;\n"
        "mov.f32 %28, 0f00000000;\n"
        "mov.f32 %29, 0f00000000;\n"
        "mov.f32 %30, 0f00000000;\n"
        "mov.f32 %31, 0f00000000;\n"
        "mov.f32 %32, 0f00000000;\n"
        "mov.f32 %33, 0f00000000;\n"
        "mov.f32 %34, 0f00000000;\n"
        "mov.f32 %35, 0f00000000;\n"
        "mov.f32 %36, 0f00000000;\n"
        "mov.f32 %37, 0f00000000;\n"
        "mov.f32 %38, 0f00000000;\n"
        "mov.f32 %39, 0f00000000;\n"
        "mov.f32 %40, 0f00000000;\n"
        "mov.f32 %41, 0f00000000;\n"
        "mov.f32 %42, 0f00000000;\n"
        "mov.f32 %43, 0f00000000;\n"
        "mov.f32 %44, 0f00000000;\n"
        "mov.f32 %45, 0f00000000;\n"
        "mov.f32 %46, 0f00000000;\n"
        "mov.f32 %47, 0f00000000;\n"
        "mov.f32 %48, 0f00000000;\n"
        "mov.f32 %49, 0f00000000;\n"
        "mov.f32 %50, 0f00000000;\n"
        "mov.f32 %51, 0f00000000;\n"
        "mov.f32 %52, 0f00000000;\n"
        "mov.f32 %53, 0f00000000;\n"
        "mov.f32 %54, 0f00000000;\n"
        "mov.f32 %55, 0f00000000;\n"
        "mov.f32 %56, 0f00000000;\n"
        "mov.f32 %57, 0f00000000;\n"
        "mov.f32 %58, 0f00000000;\n"
        "mov.f32 %59, 0f00000000;\n"
        "mov.f32 %60, 0f00000000;\n"
        "mov.f32 %61, 0f00000000;\n"
        "mov.f32 %62, 0f00000000;\n"
        "mov.f32 %63, 0f00000000;\n"
        "mov.f32 %64, 0f00000000;\n"
        "mov.f32 %65, 0f00000000;\n"
        "mov.f32 %66, 0f00000000;\n"
        "mov.f32 %67, 0f00000000;\n"
        "mov.f32 %68, 0f00000000;\n"
        "mov.f32 %69, 0f00000000;\n"
        "mov.f32 %70, 0f00000000;\n"
        "mov.f32 %71, 0f00000000;\n"
        "mov.f32 %72, 0f00000000;\n"
        "mov.f32 %73, 0f00000000;\n"
        "mov.f32 %74, 0f00000000;\n"
        "mov.f32 %75, 0f00000000;\n"
        "mov.f32 %76, 0f00000000;\n"
        "mov.f32 %77, 0f00000000;\n"
        "mov.f32 %78, 0f00000000;\n"
        "mov.f32 %79, 0f00000000;\n"
        "mov.f32 %80, 0f00000000;\n"
        "mov.f32 %81, 0f00000000;\n"
        "mov.f32 %82, 0f00000000;\n"
        "mov.f32 %83, 0f00000000;\n"
        "mov.f32 %84, 0f00000000;\n"
        "mov.f32 %85, 0f00000000;\n"
        "mov.f32 %86, 0f00000000;\n"
        "mov.f32 %87, 0f00000000;\n"
        "mov.f32 %88, 0f00000000;\n"
        "mov.f32 %89, 0f00000000;\n"
        "mov.f32 %90, 0f00000000;\n"
        "mov.f32 %91, 0f00000000;\n"
        "mov.f32 %92, 0f00000000;\n"
        "mov.f32 %93, 0f00000000;\n"
        "mov.f32 %94, 0f00000000;\n"
        "mov.f32 %95, 0f00000000;\n"
        "mov.f32 %96, 0f00000000;\n"
        "mov.f32 %97, 0f00000000;\n"
        "mov.f32 %98, 0f00000000;\n"
        "mov.f32 %99, 0f00000000;\n"
        "mov.f32 %100, 0f00000000;\n"
        "mov.f32 %101, 0f00000000;\n"
        "mov.f32 %102, 0f00000000;\n"
        "mov.f32 %103, 0f00000000;\n"
        "mov.f32 %104, 0f00000000;\n"
        "mov.f32 %105, 0f00000000;\n"
        "mov.f32 %106, 0f00000000;\n"
        "mov.f32 %107, 0f00000000;\n"
        "mov.f32 %108, 0f00000000;\n"
        "mov.f32 %109, 0f00000000;\n"
        "mov.f32 %110, 0f00000000;\n"
        "mov.f32 %111, 0f00000000;\n"
        "mov.f32 %112, 0f00000000;\n"
        "mov.f32 %113, 0f00000000;\n"
        "mov.f32 %114, 0f00000000;\n"
        "mov.f32 %115, 0f00000000;\n"
        "mov.f32 %116, 0f00000000;\n"
        "mov.f32 %117, 0f00000000;\n"
        "mov.f32 %118, 0f00000000;\n"
        "mov.f32 %119, 0f00000000;\n"
        "mov.f32 %120, 0f00000000;\n"
        "mov.f32 %121, 0f00000000;\n"
        "mov.f32 %122, 0f00000000;\n"
        "mov.f32 %123, 0f00000000;\n"
        "mov.f32 %124, 0f00000000;\n"
        "mov.f32 %125, 0f00000000;\n"
        "mov.f32 %126, 0f00000000;\n"
        "mov.f32 %127, 0f00000000;\n"
        "mov.f32 %128, 0f00000000;\n"
        "mov.f32 %129, 0f00000000;\n"
        "mov.f32 %130, 0f00000000;\n"
        "mov.f32 %131, 0f00000000;\n"
        "mov.f32 %132, 0f00000000;\n"
        "mov.f32 %133, 0f00000000;\n"
        "mov.f32 %134, 0f00000000;\n"
        "mov.f32 %135, 0f00000000;\n"
        "mov.f32 %136, 0f00000000;\n"
        "mov.f32 %137, 0f00000000;\n"
        "mov.f32 %138, 0f00000000;\n"
        "mov.f32 %139, 0f00000000;\n"
        "mov.f32 %140, 0f00000000;\n"
        "mov.f32 %141, 0f00000000;\n"
        "mov.f32 %142, 0f00000000;\n"
        "mov.f32 %143, 0f00000000;\n"
        "mov.f32 %144, 0f00000000;\n"
        "mov.f32 %145, 0f00000000;\n"
        "mov.f32 %146, 0f00000000;\n"
        "mov.f32 %147, 0f00000000;\n"
        "mov.f32 %148, 0f00000000;\n"
        "mov.f32 %149, 0f00000000;\n"
        "mov.f32 %150, 0f00000000;\n"
        "mov.f32 %151, 0f00000000;\n"
        "setp.ne.u32 pf, 0, 0;\n"
        "mov.u32 dh, 16;\n"
        "add.u32 v0, %154, %159;\n"
        "shfl.sync.idx.b32 so, v0, 0, 31, 0xffffffff;\n"
        "mov.b64 dw0, {%160, dh};\n"
        "add.u64 dw1, dw0, 128;\n"
        "mov.u32 par, 0;\n"
        "shr.u32 px, so, 13;\n"
        "mul.lo.u32 px, px, 429496730;\n"
        "add.u32 v0, %159, 16;\n"
        "shfl.sync.idx.b32 dh0, v0, 0, 31, 0xffffffff;\n"
        "shfl.sync.idx.b32 dh1, v0, 1, 31, 0xffffffff;\n"
        "shfl.sync.idx.b32 dh2, v0, 2, 31, 0xffffffff;\n"
        "shfl.sync.idx.b32 dh3, v0, 3, 31, 0xffffffff;\n"
        "shfl.sync.idx.b32 dh4, v0, 4, 31, 0xffffffff;\n"
        "shfl.sync.idx.b32 dh5, v0, 5, 31, 0xffffffff;\n"
        "add.u32 v0, %159, %156;\n"
        "shfl.sync.idx.b32 eb0, v0, 0, 31, 0xffffffff;\n"
        "mov.u32 q, 0;\n"
        "mov.u32 pl, %158;\n"
        "shr.u32 bar, so, 9;\n"
        "add.u32 bar, bar, %155;\n"
        "mov.u32 v0, %%laneid;\n"
        "setp.eq.u32 plead, v0, 0;\n"
        "mov.b64 de0, {%156, dh4};\n"
        "mov.b64 de1, {eb0, dh5};\n"
        "mov.b32 hYa0, 0;\n"
        "mov.b32 hYa1, 0;\n"
        "mov.b32 hYa2, 0;\n"
        "mov.b32 hYa3, 0;\n"
        "mov.b32 hYa4, 0;\n"
        "mov.b32 hYa5, 0;\n"
        "mov.b32 hYa6, 0;\n"
        "mov.b32 hYa7, 0;\n"
        "mov.b32 hYb0, 0;\n"
        "mov.b32 hYb1, 0;\n"
        "mov.b32 hYb2, 0;\n"
        "mov.b32 hYb3, 0;\n"
        "mov.b32 hYb4, 0;\n"
        "mov.b32 hYb5, 0;\n"
        "mov.b32 hYb6, 0;\n"
        "mov.b32 hYb7, 0;\n"
        "setp.ne.u32 t0, 0, 0;\n"
        "setp.ne.u32 t1, 0, 0;\n"
        "setp.ne.u32 t2, 0, 0;\n"
        "mov.b64 daX, {%157, dh0};\n"
        "mov.b64 dbX, {%157, dh1};\n"
        "mov.b64 daY, {%157, dh2};\n"
        "mov.b64 dbY, {%157, dh3};\n"
        "mov.u32 cnt, 0;\n"
        "W1:\n"
        "mbarrier.try_wait.parity.shared.b64 p, [bar], 0;\n"
        "@p bra.uni RES;\n"
        "add.u32 cnt, cnt, 1;\n"
        "setp.lt.u32 p, cnt, 4000000;\n"
        "@p bra.uni W1;\n"
        "trap;\n"
        "CX:\n"
        "mov.u32 rbar, bar;\n"
        "add.u32 so, so, 8192;\n"
        "setp.eq.u32 p, so, " STR(RING_BYTES) ";\n"
        "selp.b32 so, 0, so, p;\n"
        "@p xor.b32 par, par, 1;\n"
        "shr.u32 bar, so, 9;\n"
        "add.u32 bar, bar, %155;\n"
        "mbarrier.test_wait.parity.shared.b64 pok, [bar], par;\n"
        "and.b32 dl, q, 0x300;\n"
        "add.u32 dl, dl, %157;\n"
        "add.u32 v3, dl, 0;\n"
        "mov.b64 {v2, dh0}, daX;\n"
        "mov.b64 daX, {v3, dh0};\n"
        "add.u32 v3, dl, 64;\n"
        "mov.b64 {v2, dh1}, dbX;\n"
        "mov.b64 dbX, {v3, dh1};\n"
        "add.u32 v3, dl, 128;\n"
        "mov.b64 {v2, dh2}, daY;\n"
        "mov.b64 daY, {v3, dh2};\n"
        "add.u32 v3, dl, 192;\n"
        "mov.b64 {v2, dh3}, dbY;\n"
        "mov.b64 dbY, {v3, dh3};\n"
        "add.u32 q, q, 256;\n"
        "and.b32 qe, q, 0x700;\n"
        "shr.u32 qe, qe, 3;\n"
        "add.u32 v3, qe, %156;\n"
        "mov.b64 {v2, dh4}, de0;\n"
        "mov.b64 de0, {v3, dh4};\n"
        "mov.b64 {v2, dh5}, de1;\n"
        "mov.b64 de1, {v3, dh5};\n"
        "mov.b32 {sl, sh}, ctl;\n"
        "mov.b32 v3, {sl, sl};\n"
        "setp.lt.f16x2 t0|t3, v3, cb;\n"
        "abs.f16x2 v3, v3;\n"
        "setp.ge.f16x2 t1|t2, v3, ca;\n"
        "wgmma.wait_group.sync.aligned 1;\n"
        "cvt.rn.bf16x2.f32 pX0, r1, r0;\n"
        "cvt.rn.bf16x2.f32 pX1, r3, r2;\n"
        "cvt.rn.bf16x2.f32 pX2, r9, r8;\n"
        "cvt.rn.bf16x2.f32 pX3, r11, r10;\n"
        "cvt.rn.bf16x2.f32 pY0, r5, r4;\n"
        "cvt.rn.bf16x2.f32 pY1, r7, r6;\n"
        "cvt.rn.bf16x2.f32 pY2, r13, r12;\n"
        "cvt.rn.bf16x2.f32 pY3, r15, r14;\n"
        "mov.b32 {sl, sh}, pX0;\n"
        "mov.b32 pp, {sl, sl};\n"
        "mul.rn.bf16x2 hXa0, hLa0, pp;\n"
        "mul.rn.bf16x2 hXa2, hLa2, pp;\n"
        "mov.b32 {sl, sh}, pX1;\n"
        "mov.b32 pp, {sl, sl};\n"
        "mul.rn.bf16x2 hXa1, hLa1, pp;\n"
        "mul.rn.bf16x2 hXa3, hLa3, pp;\n"
        "mov.b32 {sl, sh}, pX2;\n"
        "mov.b32 pp, {sl, sl};\n"
        "mul.rn.bf16x2 hXa4, hLa4, pp;\n"
        "mul.rn.bf16x2 hXa6, hLa6, pp;\n"
        "mov.b32 {sl, sh}, pX3;\n"
        "mov.b32 pp, {sl, sl};\n"
        "mul.rn.bf16x2 hXa5, hLa5, pp;\n"
        "mul.rn.bf16x2 hXa7, hLa7, pp;\n"
        "mov.b32 {sl, sh}, pX0;\n"
        "mov.b32 pp, {sh, sh};\n"
        "mul.rn.bf16x2 hXb0, hLb0, pp;\n"
        "mul.rn.bf16x2 hXb2, hLb2, pp;\n"
        "mov.b32 {sl, sh}, pX1;\n"
        "mov.b32 pp, {sh, sh};\n"
        "mul.rn.bf16x2 hXb1, hLb1, pp;\n"
        "mul.rn.bf16x2 hXb3, hLb3, pp;\n"
        "mov.b32 {sl, sh}, pX2;\n"
        "mov.b32 pp, {sh, sh};\n"
        "mul.rn.bf16x2 hXb4, hLb4, pp;\n"
        "mul.rn.bf16x2 hXb6, hLb6, pp;\n"
        "mov.b32 {sl, sh}, pX3;\n"
        "mov.b32 pp, {sh, sh};\n"
        "mul.rn.bf16x2 hXb5, hLb5, pp;\n"
        "mul.rn.bf16x2 hXb7, hLb7, pp;\n"
        "ldmatrix.sync.aligned.m8n8.x4.trans.shared.b16 {hLa0,hLa1,hLa2,hLa3}, [v0+4096];\n"
        "ldmatrix.sync.aligned.m8n8.x4.trans.shared.b16 {hLa4,hLa5,hLa6,hLa7}, [v1+4096];\n"
        "ldmatrix.sync.aligned.m8n8.x4.trans.shared.b16 {hLb0,hLb1,hLb2,hLb3}, [v0+6144];\n"
        "ldmatrix.sync.aligned.m8n8.x4.trans.shared.b16 {hLb4,hLb5,hLb6,hLb7}, [v1+6144];\n"
        "@t2 bra.uni T4X;\n"
        "@t1 bra.uni T2X;\n"
        "@t0 bra.uni L1X;\n"
        "L0X:\n"
        "wgmma.fence.sync.aligned;\n"
        "wgmma.mma_async.sync.aligned.m64n24k16.f32.bf16.bf16 {%0,%1,%2,%3,%4,%5,%6,%7,%8,%9,%10,%11}, {hXa0,hXa1,hXa2,hXa3}, daX, 1, 1, 1, 1;\n"
        "wgmma.mma_async.sync.aligned.m64n24k16.f32.bf16.bf16 {%76,%77,%78,%79,%80,%81,%82,%83,%84,%85,%86,%87}, {hXa4,hXa5,hXa6,hXa7}, daX, 1, 1, 1, 1;\n"
        "wgmma.mma_async.sync.aligned.m64n24k16.f32.bf16.bf16 {%0,%1,%2,%3,%4,%5,%6,%7,%8,%9,%10,%11}, {hXb0,hXb1,hXb2,hXb3}, dbX, 1, 1, 1, 1;\n"
        "wgmma.mma_async.sync.aligned.m64n24k16.f32.bf16.bf16 {%76,%77,%78,%79,%80,%81,%82,%83,%84,%85,%86,%87}, {hXb4,hXb5,hXb6,hXb7}, dbX, 1, 1, 1, 1;\n"
        "wgmma.commit_group.sync.aligned;\n"
        "bra.uni CY;\n"
        "L1X:\n"
        "wgmma.fence.sync.aligned;\n"
        "wgmma.mma_async.sync.aligned.m64n24k16.f32.bf16.bf16 {%12,%13,%14,%15,%16,%17,%18,%19,%20,%21,%22,%23}, {hXa0,hXa1,hXa2,hXa3}, daX, 1, 1, 1, 1;\n"
        "wgmma.mma_async.sync.aligned.m64n24k16.f32.bf16.bf16 {%88,%89,%90,%91,%92,%93,%94,%95,%96,%97,%98,%99}, {hXa4,hXa5,hXa6,hXa7}, daX, 1, 1, 1, 1;\n"
        "wgmma.mma_async.sync.aligned.m64n24k16.f32.bf16.bf16 {%12,%13,%14,%15,%16,%17,%18,%19,%20,%21,%22,%23}, {hXb0,hXb1,hXb2,hXb3}, dbX, 1, 1, 1, 1;\n"
        "wgmma.mma_async.sync.aligned.m64n24k16.f32.bf16.bf16 {%88,%89,%90,%91,%92,%93,%94,%95,%96,%97,%98,%99}, {hXb4,hXb5,hXb6,hXb7}, dbX, 1, 1, 1, 1;\n"
        "wgmma.commit_group.sync.aligned;\n"
        "bra.uni CY;\n"
        "T2X:\n"
        "@t0 bra.uni L3X;\n"
        "L2X:\n"
        "wgmma.fence.sync.aligned;\n"
        "wgmma.mma_async.sync.aligned.m64n24k16.f32.bf16.bf16 {%24,%25,%26,%27,%28,%29,%30,%31,%32,%33,%34,%35}, {hXa0,hXa1,hXa2,hXa3}, daX, 1, 1, 1, 1;\n"
        "wgmma.mma_async.sync.aligned.m64n24k16.f32.bf16.bf16 {%100,%101,%102,%103,%104,%105,%106,%107,%108,%109,%110,%111}, {hXa4,hXa5,hXa6,hXa7}, daX, 1, 1, 1, 1;\n"
        "wgmma.mma_async.sync.aligned.m64n24k16.f32.bf16.bf16 {%24,%25,%26,%27,%28,%29,%30,%31,%32,%33,%34,%35}, {hXb0,hXb1,hXb2,hXb3}, dbX, 1, 1, 1, 1;\n"
        "wgmma.mma_async.sync.aligned.m64n24k16.f32.bf16.bf16 {%100,%101,%102,%103,%104,%105,%106,%107,%108,%109,%110,%111}, {hXb4,hXb5,hXb6,hXb7}, dbX, 1, 1, 1, 1;\n"
        "wgmma.commit_group.sync.aligned;\n"
        "bra.uni CY;\n"
        "L3X:\n"
        "wgmma.fence.sync.aligned;\n"
        "wgmma.mma_async.sync.aligned.m64n24k16.f32.bf16.bf16 {%36,%37,%38,%39,%40,%41,%42,%43,%44,%45,%46,%47}, {hXa0,hXa1,hXa2,hXa3}, daX, 1, 1, 1, 1;\n"
        "wgmma.mma_async.sync.aligned.m64n24k16.f32.bf16.bf16 {%112,%113,%114,%115,%116,%117,%118,%119,%120,%121,%122,%123}, {hXa4,hXa5,hXa6,hXa7}, daX, 1, 1, 1, 1;\n"
        "wgmma.mma_async.sync.aligned.m64n24k16.f32.bf16.bf16 {%36,%37,%38,%39,%40,%41,%42,%43,%44,%45,%46,%47}, {hXb0,hXb1,hXb2,hXb3}, dbX, 1, 1, 1, 1;\n"
        "wgmma.mma_async.sync.aligned.m64n24k16.f32.bf16.bf16 {%112,%113,%114,%115,%116,%117,%118,%119,%120,%121,%122,%123}, {hXb4,hXb5,hXb6,hXb7}, dbX, 1, 1, 1, 1;\n"
        "wgmma.commit_group.sync.aligned;\n"
        "bra.uni CY;\n"
        "T4X:\n"
        "@t3 bra.uni LEXIT;\n"
        "@t0 bra.uni L5X;\n"
        "L4X:\n"
        "wgmma.fence.sync.aligned;\n"
        "wgmma.mma_async.sync.aligned.m64n24k16.f32.bf16.bf16 {%48,%49,%50,%51,%52,%53,%54,%55,%56,%57,%58,%59}, {hXa0,hXa1,hXa2,hXa3}, daX, 1, 1, 1, 1;\n"
        "wgmma.mma_async.sync.aligned.m64n24k16.f32.bf16.bf16 {%124,%125,%126,%127,%128,%129,%130,%131,%132,%133,%134,%135}, {hXa4,hXa5,hXa6,hXa7}, daX, 1, 1, 1, 1;\n"
        "wgmma.mma_async.sync.aligned.m64n24k16.f32.bf16.bf16 {%48,%49,%50,%51,%52,%53,%54,%55,%56,%57,%58,%59}, {hXb0,hXb1,hXb2,hXb3}, dbX, 1, 1, 1, 1;\n"
        "wgmma.mma_async.sync.aligned.m64n24k16.f32.bf16.bf16 {%124,%125,%126,%127,%128,%129,%130,%131,%132,%133,%134,%135}, {hXb4,hXb5,hXb6,hXb7}, dbX, 1, 1, 1, 1;\n"
        "wgmma.commit_group.sync.aligned;\n"
        "bra.uni CY;\n"
        "L5X:\n"
        "wgmma.fence.sync.aligned;\n"
        "wgmma.mma_async.sync.aligned.m64n32k16.f32.bf16.bf16 {%60,%61,%62,%63,%64,%65,%66,%67,%68,%69,%70,%71,%72,%73,%74,%75}, {hXa0,hXa1,hXa2,hXa3}, daX, 1, 1, 1, 1;\n"
        "wgmma.mma_async.sync.aligned.m64n32k16.f32.bf16.bf16 {%136,%137,%138,%139,%140,%141,%142,%143,%144,%145,%146,%147,%148,%149,%150,%151}, {hXa4,hXa5,hXa6,hXa7}, daX, 1, 1, 1, 1;\n"
        "wgmma.mma_async.sync.aligned.m64n32k16.f32.bf16.bf16 {%60,%61,%62,%63,%64,%65,%66,%67,%68,%69,%70,%71,%72,%73,%74,%75}, {hXb0,hXb1,hXb2,hXb3}, dbX, 1, 1, 1, 1;\n"
        "wgmma.mma_async.sync.aligned.m64n32k16.f32.bf16.bf16 {%136,%137,%138,%139,%140,%141,%142,%143,%144,%145,%146,%147,%148,%149,%150,%151}, {hXb4,hXb5,hXb6,hXb7}, dbX, 1, 1, 1, 1;\n"
        "wgmma.commit_group.sync.aligned;\n"
        "bra.uni CY;\n"
        "CY:\n"
        "wgmma.wait_group.sync.aligned 1;\n"
        "lop3.b32 v2, hLa3, hLa7, hLb3, 0x80;\n"
        "lop3.b32 v2, v2, hLb7, %159, 0x80;\n"
        "add.u32 v2, v2, rbar;\n"
        "@plead mbarrier.arrive.shared.b64 _, [v2+8];\n"
        "mov.b32 {sl, sh}, ctl;\n"
        "mov.b32 v3, {sh, sh};\n"
        "setp.lt.f16x2 t0|_, v3, cb;\n"
        "abs.f16x2 v3, v3;\n"
        "setp.ge.f16x2 t1|t2, v3, ca;\n"
        "mov.b32 {sl, sh}, pY0;\n"
        "mov.b32 pp, {sl, sl};\n"
        "mul.rn.bf16x2 hYa0, hLa0, pp;\n"
        "mul.rn.bf16x2 hYa2, hLa2, pp;\n"
        "mov.b32 {sl, sh}, pY1;\n"
        "mov.b32 pp, {sl, sl};\n"
        "mul.rn.bf16x2 hYa1, hLa1, pp;\n"
        "mul.rn.bf16x2 hYa3, hLa3, pp;\n"
        "mov.b32 {sl, sh}, pY2;\n"
        "mov.b32 pp, {sl, sl};\n"
        "mul.rn.bf16x2 hYa4, hLa4, pp;\n"
        "mul.rn.bf16x2 hYa6, hLa6, pp;\n"
        "mov.b32 {sl, sh}, pY3;\n"
        "mov.b32 pp, {sl, sl};\n"
        "mul.rn.bf16x2 hYa5, hLa5, pp;\n"
        "mul.rn.bf16x2 hYa7, hLa7, pp;\n"
        "mov.b32 {sl, sh}, pY0;\n"
        "mov.b32 pp, {sh, sh};\n"
        "mul.rn.bf16x2 hYb0, hLb0, pp;\n"
        "mul.rn.bf16x2 hYb2, hLb2, pp;\n"
        "mov.b32 {sl, sh}, pY1;\n"
        "mov.b32 pp, {sh, sh};\n"
        "mul.rn.bf16x2 hYb1, hLb1, pp;\n"
        "mul.rn.bf16x2 hYb3, hLb3, pp;\n"
        "mov.b32 {sl, sh}, pY2;\n"
        "mov.b32 pp, {sh, sh};\n"
        "mul.rn.bf16x2 hYb4, hLb4, pp;\n"
        "mul.rn.bf16x2 hYb6, hLb6, pp;\n"
        "mov.b32 {sl, sh}, pY3;\n"
        "mov.b32 pp, {sh, sh};\n"
        "mul.rn.bf16x2 hYb5, hLb5, pp;\n"
        "mul.rn.bf16x2 hYb7, hLb7, pp;\n"
        "@!pok bra.uni SLOW;\n"
        "RES:\n"
        "add.u32 v0, %152, so;\n"
        "add.u32 v1, %153, so;\n"
        "ldmatrix.sync.aligned.m8n8.x4.trans.shared.b16 {hLa0,hLa1,hLa2,hLa3}, [v0+0];\n"
        "ldmatrix.sync.aligned.m8n8.x4.trans.shared.b16 {hLa4,hLa5,hLa6,hLa7}, [v1+0];\n"
        "ldmatrix.sync.aligned.m8n8.x4.trans.shared.b16 {hLb0,hLb1,hLb2,hLb3}, [v0+2048];\n"
        "ldmatrix.sync.aligned.m8n8.x4.trans.shared.b16 {hLb4,hLb5,hLb6,hLb7}, [v1+2048];\n"
        "ld.shared.u32 ctl, [pl];\n"
        "add.u32 pl, pl, 4;\n"
        "wgmma.wait_group.sync.aligned 0;\n"
        "@t2 bra.uni T4Y;\n"
        "@t1 bra.uni T2Y;\n"
        "@t0 bra.uni L1Y;\n"
        "L0Y:\n"
        "wgmma.fence.sync.aligned;\n"
        "wgmma.mma_async.sync.aligned.m64n16k16.f32.bf16.bf16 {r0,r1,r2,r3,r4,r5,r6,r7}, dw0, de0, pf, 1, 1, 1, 0;\n"
        "wgmma.mma_async.sync.aligned.m64n16k16.f32.bf16.bf16 {r8,r9,r10,r11,r12,r13,r14,r15}, dw1, de1, pf, 1, 1, 1, 0;\n"
        "wgmma.commit_group.sync.aligned;\n"
        "wgmma.mma_async.sync.aligned.m64n24k16.f32.bf16.bf16 {%0,%1,%2,%3,%4,%5,%6,%7,%8,%9,%10,%11}, {hYa0,hYa1,hYa2,hYa3}, daY, 1, 1, 1, 1;\n"
        "wgmma.mma_async.sync.aligned.m64n24k16.f32.bf16.bf16 {%76,%77,%78,%79,%80,%81,%82,%83,%84,%85,%86,%87}, {hYa4,hYa5,hYa6,hYa7}, daY, 1, 1, 1, 1;\n"
        "wgmma.mma_async.sync.aligned.m64n24k16.f32.bf16.bf16 {%0,%1,%2,%3,%4,%5,%6,%7,%8,%9,%10,%11}, {hYb0,hYb1,hYb2,hYb3}, dbY, 1, 1, 1, 1;\n"
        "wgmma.mma_async.sync.aligned.m64n24k16.f32.bf16.bf16 {%76,%77,%78,%79,%80,%81,%82,%83,%84,%85,%86,%87}, {hYb4,hYb5,hYb6,hYb7}, dbY, 1, 1, 1, 1;\n"
        "wgmma.commit_group.sync.aligned;\n"
        "bra.uni CX;\n"
        "L1Y:\n"
        "wgmma.fence.sync.aligned;\n"
        "wgmma.mma_async.sync.aligned.m64n16k16.f32.bf16.bf16 {r0,r1,r2,r3,r4,r5,r6,r7}, dw0, de0, pf, 1, 1, 1, 0;\n"
        "wgmma.mma_async.sync.aligned.m64n16k16.f32.bf16.bf16 {r8,r9,r10,r11,r12,r13,r14,r15}, dw1, de1, pf, 1, 1, 1, 0;\n"
        "wgmma.commit_group.sync.aligned;\n"
        "wgmma.mma_async.sync.aligned.m64n24k16.f32.bf16.bf16 {%12,%13,%14,%15,%16,%17,%18,%19,%20,%21,%22,%23}, {hYa0,hYa1,hYa2,hYa3}, daY, 1, 1, 1, 1;\n"
        "wgmma.mma_async.sync.aligned.m64n24k16.f32.bf16.bf16 {%88,%89,%90,%91,%92,%93,%94,%95,%96,%97,%98,%99}, {hYa4,hYa5,hYa6,hYa7}, daY, 1, 1, 1, 1;\n"
        "wgmma.mma_async.sync.aligned.m64n24k16.f32.bf16.bf16 {%12,%13,%14,%15,%16,%17,%18,%19,%20,%21,%22,%23}, {hYb0,hYb1,hYb2,hYb3}, dbY, 1, 1, 1, 1;\n"
        "wgmma.mma_async.sync.aligned.m64n24k16.f32.bf16.bf16 {%88,%89,%90,%91,%92,%93,%94,%95,%96,%97,%98,%99}, {hYb4,hYb5,hYb6,hYb7}, dbY, 1, 1, 1, 1;\n"
        "wgmma.commit_group.sync.aligned;\n"
        "bra.uni CX;\n"
        "T2Y:\n"
        "@t0 bra.uni L3Y;\n"
        "L2Y:\n"
        "wgmma.fence.sync.aligned;\n"
        "wgmma.mma_async.sync.aligned.m64n16k16.f32.bf16.bf16 {r0,r1,r2,r3,r4,r5,r6,r7}, dw0, de0, pf, 1, 1, 1, 0;\n"
        "wgmma.mma_async.sync.aligned.m64n16k16.f32.bf16.bf16 {r8,r9,r10,r11,r12,r13,r14,r15}, dw1, de1, pf, 1, 1, 1, 0;\n"
        "wgmma.commit_group.sync.aligned;\n"
        "wgmma.mma_async.sync.aligned.m64n24k16.f32.bf16.bf16 {%24,%25,%26,%27,%28,%29,%30,%31,%32,%33,%34,%35}, {hYa0,hYa1,hYa2,hYa3}, daY, 1, 1, 1, 1;\n"
        "wgmma.mma_async.sync.aligned.m64n24k16.f32.bf16.bf16 {%100,%101,%102,%103,%104,%105,%106,%107,%108,%109,%110,%111}, {hYa4,hYa5,hYa6,hYa7}, daY, 1, 1, 1, 1;\n"
        "wgmma.mma_async.sync.aligned.m64n24k16.f32.bf16.bf16 {%24,%25,%26,%27,%28,%29,%30,%31,%32,%33,%34,%35}, {hYb0,hYb1,hYb2,hYb3}, dbY, 1, 1, 1, 1;\n"
        "wgmma.mma_async.sync.aligned.m64n24k16.f32.bf16.bf16 {%100,%101,%102,%103,%104,%105,%106,%107,%108,%109,%110,%111}, {hYb4,hYb5,hYb6,hYb7}, dbY, 1, 1, 1, 1;\n"
        "wgmma.commit_group.sync.aligned;\n"
        "bra.uni CX;\n"
        "L3Y:\n"
        "wgmma.fence.sync.aligned;\n"
        "wgmma.mma_async.sync.aligned.m64n16k16.f32.bf16.bf16 {r0,r1,r2,r3,r4,r5,r6,r7}, dw0, de0, pf, 1, 1, 1, 0;\n"
        "wgmma.mma_async.sync.aligned.m64n16k16.f32.bf16.bf16 {r8,r9,r10,r11,r12,r13,r14,r15}, dw1, de1, pf, 1, 1, 1, 0;\n"
        "wgmma.commit_group.sync.aligned;\n"
        "wgmma.mma_async.sync.aligned.m64n24k16.f32.bf16.bf16 {%36,%37,%38,%39,%40,%41,%42,%43,%44,%45,%46,%47}, {hYa0,hYa1,hYa2,hYa3}, daY, 1, 1, 1, 1;\n"
        "wgmma.mma_async.sync.aligned.m64n24k16.f32.bf16.bf16 {%112,%113,%114,%115,%116,%117,%118,%119,%120,%121,%122,%123}, {hYa4,hYa5,hYa6,hYa7}, daY, 1, 1, 1, 1;\n"
        "wgmma.mma_async.sync.aligned.m64n24k16.f32.bf16.bf16 {%36,%37,%38,%39,%40,%41,%42,%43,%44,%45,%46,%47}, {hYb0,hYb1,hYb2,hYb3}, dbY, 1, 1, 1, 1;\n"
        "wgmma.mma_async.sync.aligned.m64n24k16.f32.bf16.bf16 {%112,%113,%114,%115,%116,%117,%118,%119,%120,%121,%122,%123}, {hYb4,hYb5,hYb6,hYb7}, dbY, 1, 1, 1, 1;\n"
        "wgmma.commit_group.sync.aligned;\n"
        "bra.uni CX;\n"
        "T4Y:\n"
        "@t0 bra.uni L5Y;\n"
        "L4Y:\n"
        "wgmma.fence.sync.aligned;\n"
        "wgmma.mma_async.sync.aligned.m64n16k16.f32.bf16.bf16 {r0,r1,r2,r3,r4,r5,r6,r7}, dw0, de0, pf, 1, 1, 1, 0;\n"
        "wgmma.mma_async.sync.aligned.m64n16k16.f32.bf16.bf16 {r8,r9,r10,r11,r12,r13,r14,r15}, dw1, de1, pf, 1, 1, 1, 0;\n"
        "wgmma.commit_group.sync.aligned;\n"
        "wgmma.mma_async.sync.aligned.m64n24k16.f32.bf16.bf16 {%48,%49,%50,%51,%52,%53,%54,%55,%56,%57,%58,%59}, {hYa0,hYa1,hYa2,hYa3}, daY, 1, 1, 1, 1;\n"
        "wgmma.mma_async.sync.aligned.m64n24k16.f32.bf16.bf16 {%124,%125,%126,%127,%128,%129,%130,%131,%132,%133,%134,%135}, {hYa4,hYa5,hYa6,hYa7}, daY, 1, 1, 1, 1;\n"
        "wgmma.mma_async.sync.aligned.m64n24k16.f32.bf16.bf16 {%48,%49,%50,%51,%52,%53,%54,%55,%56,%57,%58,%59}, {hYb0,hYb1,hYb2,hYb3}, dbY, 1, 1, 1, 1;\n"
        "wgmma.mma_async.sync.aligned.m64n24k16.f32.bf16.bf16 {%124,%125,%126,%127,%128,%129,%130,%131,%132,%133,%134,%135}, {hYb4,hYb5,hYb6,hYb7}, dbY, 1, 1, 1, 1;\n"
        "wgmma.commit_group.sync.aligned;\n"
        "bra.uni CX;\n"
        "L5Y:\n"
        "wgmma.fence.sync.aligned;\n"
        "wgmma.mma_async.sync.aligned.m64n16k16.f32.bf16.bf16 {r0,r1,r2,r3,r4,r5,r6,r7}, dw0, de0, pf, 1, 1, 1, 0;\n"
        "wgmma.mma_async.sync.aligned.m64n16k16.f32.bf16.bf16 {r8,r9,r10,r11,r12,r13,r14,r15}, dw1, de1, pf, 1, 1, 1, 0;\n"
        "wgmma.commit_group.sync.aligned;\n"
        "wgmma.mma_async.sync.aligned.m64n32k16.f32.bf16.bf16 {%60,%61,%62,%63,%64,%65,%66,%67,%68,%69,%70,%71,%72,%73,%74,%75}, {hYa0,hYa1,hYa2,hYa3}, daY, 1, 1, 1, 1;\n"
        "wgmma.mma_async.sync.aligned.m64n32k16.f32.bf16.bf16 {%136,%137,%138,%139,%140,%141,%142,%143,%144,%145,%146,%147,%148,%149,%150,%151}, {hYa4,hYa5,hYa6,hYa7}, daY, 1, 1, 1, 1;\n"
        "wgmma.mma_async.sync.aligned.m64n32k16.f32.bf16.bf16 {%60,%61,%62,%63,%64,%65,%66,%67,%68,%69,%70,%71,%72,%73,%74,%75}, {hYb0,hYb1,hYb2,hYb3}, dbY, 1, 1, 1, 1;\n"
        "wgmma.mma_async.sync.aligned.m64n32k16.f32.bf16.bf16 {%136,%137,%138,%139,%140,%141,%142,%143,%144,%145,%146,%147,%148,%149,%150,%151}, {hYb4,hYb5,hYb6,hYb7}, dbY, 1, 1, 1, 1;\n"
        "wgmma.commit_group.sync.aligned;\n"
        "bra.uni CX;\n"
        "SLOW:\n"
        "mov.u32 cnt, 0;\n"
        "W2:\n"
        "mbarrier.try_wait.parity.shared.b64 p, [bar], par;\n"
        "@p bra.uni RES;\n"
        "add.u32 cnt, cnt, 1;\n"
        "setp.lt.u32 p, cnt, 4000000;\n"
        "@p bra.uni W2;\n"
        "trap;\n"
        "LEXIT:\n"
        "wgmma.wait_group.sync.aligned 0;\n"
        "}\n"
        : "=f"(acc[0][0][0]), "=f"(acc[0][0][1]), "=f"(acc[0][0][2]), "=f"(acc[0][0][3]),
          "=f"(acc[0][1][0]), "=f"(acc[0][1][1]), "=f"(acc[0][1][2]), "=f"(acc[0][1][3]),
          "=f"(acc[0][2][0]), "=f"(acc[0][2][1]), "=f"(acc[0][2][2]), "=f"(acc[0][2][3]),
          "=f"(acc[0][3][0]), "=f"(acc[0][3][1]), "=f"(acc[0][3][2]), "=f"(acc[0][3][3]),
          "=f"(acc[0][4][0]), "=f"(acc[0][4][1]), "=f"(acc[0][4][2]), "=f"(acc[0][4][3]),
          "=f"(acc[0][5][0]), "=f"(acc[0][5][1]), "=f"(acc[0][5][2]), "=f"(acc[0][5][3]),
          "=f"(acc[0][6][0]), "=f"(acc[0][6][1]), "=f"(acc[0][6][2]), "=f"(acc[0][6][3]),
          "=f"(acc[0][7][0]), "=f"(acc[0][7][1]), "=f"(acc[0][7][2]), "=f"(acc[0][7][3]),
          "=f"(acc[0][8][0]), "=f"(acc[0][8][1]), "=f"(acc[0][8][2]), "=f"(acc[0][8][3]),
          "=f"(acc[0][9][0]), "=f"(acc[0][9][1]), "=f"(acc[0][9][2]), "=f"(acc[0][9][3]),
          "=f"(acc[0][10][0]), "=f"(acc[0][10][1]), "=f"(acc[0][10][2]), "=f"(acc[0][10][3]),
          "=f"(acc[0][11][0]), "=f"(acc[0][11][1]), "=f"(acc[0][11][2]), "=f"(acc[0][11][3]),
          "=f"(acc[0][12][0]), "=f"(acc[0][12][1]), "=f"(acc[0][12][2]), "=f"(acc[0][12][3]),
          "=f"(acc[0][13][0]), "=f"(acc[0][13][1]), "=f"(acc[0][13][2]), "=f"(acc[0][13][3]),
          "=f"(acc[0][14][0]), "=f"(acc[0][14][1]), "=f"(acc[0][14][2]), "=f"(acc[0][14][3]),
          "=f"(acc[0][15][0]), "=f"(acc[0][15][1]), "=f"(acc[0][15][2]), "=f"(acc[0][15][3]),
          "=f"(acc[0][16][0]), "=f"(acc[0][16][1]), "=f"(acc[0][16][2]), "=f"(acc[0][16][3]),
          "=f"(acc[0][17][0]), "=f"(acc[0][17][1]), "=f"(acc[0][17][2]), "=f"(acc[0][17][3]),
          "=f"(acc[0][18][0]), "=f"(acc[0][18][1]), "=f"(acc[0][18][2]), "=f"(acc[0][18][3]),
          "=f"(acc[1][0][0]), "=f"(acc[1][0][1]), "=f"(acc[1][0][2]), "=f"(acc[1][0][3]),
          "=f"(acc[1][1][0]), "=f"(acc[1][1][1]), "=f"(acc[1][1][2]), "=f"(acc[1][1][3]),
          "=f"(acc[1][2][0]), "=f"(acc[1][2][1]), "=f"(acc[1][2][2]), "=f"(acc[1][2][3]),
          "=f"(acc[1][3][0]), "=f"(acc[1][3][1]), "=f"(acc[1][3][2]), "=f"(acc[1][3][3]),
          "=f"(acc[1][4][0]), "=f"(acc[1][4][1]), "=f"(acc[1][4][2]), "=f"(acc[1][4][3]),
          "=f"(acc[1][5][0]), "=f"(acc[1][5][1]), "=f"(acc[1][5][2]), "=f"(acc[1][5][3]),
          "=f"(acc[1][6][0]), "=f"(acc[1][6][1]), "=f"(acc[1][6][2]), "=f"(acc[1][6][3]),
          "=f"(acc[1][7][0]), "=f"(acc[1][7][1]), "=f"(acc[1][7][2]), "=f"(acc[1][7][3]),
          "=f"(acc[1][8][0]), "=f"(acc[1][8][1]), "=f"(acc[1][8][2]), "=f"(acc[1][8][3]),
          "=f"(acc[1][9][0]), "=f"(acc[1][9][1]), "=f"(acc[1][9][2]), "=f"(acc[1][9][3]),
          "=f"(acc[1][10][0]), "=f"(acc[1][10][1]), "=f"(acc[1][10][2]), "=f"(acc[1][10][3]),
          "=f"(acc[1][11][0]), "=f"(acc[1][11][1]), "=f"(acc[1][11][2]), "=f"(acc[1][11][3]),
          "=f"(acc[1][12][0]), "=f"(acc[1][12][1]), "=f"(acc[1][12][2]), "=f"(acc[1][12][3]),
          "=f"(acc[1][13][0]), "=f"(acc[1][13][1]), "=f"(acc[1][13][2]), "=f"(acc[1][13][3]),
          "=f"(acc[1][14][0]), "=f"(acc[1][14][1]), "=f"(acc[1][14][2]), "=f"(acc[1][14][3]),
          "=f"(acc[1][15][0]), "=f"(acc[1][15][1]), "=f"(acc[1][15][2]), "=f"(acc[1][15][3]),
          "=f"(acc[1][16][0]), "=f"(acc[1][16][1]), "=f"(acc[1][16][2]), "=f"(acc[1][16][3]),
          "=f"(acc[1][17][0]), "=f"(acc[1][17][1]), "=f"(acc[1][17][2]), "=f"(acc[1][17][3]),
          "=f"(acc[1][18][0]), "=f"(acc[1][18][1]), "=f"(acc[1][18][2]), "=f"(acc[1][18][3])
        : "r"(xa0), "r"(xa1), "r"(so0), "r"(bar0), "r"(ea0), "r"(d0), "r"(pl0), "r"(lz), "r"(wd)
        : "memory");
}
__device__ __forceinline__ void wgmma_out(float (&o)[NJ][4], uint64_t da, uint64_t db, int acc) {
    asm volatile(
        "{\n.reg .pred p;\nsetp.ne.b32 p, %78, 0;\n"
        "wgmma.mma_async.sync.aligned.m64n152k16.f32.bf16.bf16 {%0,%1,%2,%3,%4,%5,%6,%7,%8,%9,%10,%11,%12,%13,%14,%15,%16,%17,%18,%19,%20,%21,%22,%23,%24,%25,%26,%27,%28,%29,%30,%31,%32,%33,%34,%35,%36,%37,%38,%39,%40,%41,%42,%43,%44,%45,%46,%47,%48,%49,%50,%51,%52,%53,%54,%55,%56,%57,%58,%59,%60,%61,%62,%63,%64,%65,%66,%67,%68,%69,%70,%71,%72,%73,%74,%75}, %76, %77, p, 1, 1, 1, 1;\n}"
        : "+f"(o[0][0]), "+f"(o[0][1]), "+f"(o[0][2]), "+f"(o[0][3]),
          "+f"(o[1][0]), "+f"(o[1][1]), "+f"(o[1][2]), "+f"(o[1][3]),
          "+f"(o[2][0]), "+f"(o[2][1]), "+f"(o[2][2]), "+f"(o[2][3]),
          "+f"(o[3][0]), "+f"(o[3][1]), "+f"(o[3][2]), "+f"(o[3][3]),
          "+f"(o[4][0]), "+f"(o[4][1]), "+f"(o[4][2]), "+f"(o[4][3]),
          "+f"(o[5][0]), "+f"(o[5][1]), "+f"(o[5][2]), "+f"(o[5][3]),
          "+f"(o[6][0]), "+f"(o[6][1]), "+f"(o[6][2]), "+f"(o[6][3]),
          "+f"(o[7][0]), "+f"(o[7][1]), "+f"(o[7][2]), "+f"(o[7][3]),
          "+f"(o[8][0]), "+f"(o[8][1]), "+f"(o[8][2]), "+f"(o[8][3]),
          "+f"(o[9][0]), "+f"(o[9][1]), "+f"(o[9][2]), "+f"(o[9][3]),
          "+f"(o[10][0]), "+f"(o[10][1]), "+f"(o[10][2]), "+f"(o[10][3]),
          "+f"(o[11][0]), "+f"(o[11][1]), "+f"(o[11][2]), "+f"(o[11][3]),
          "+f"(o[12][0]), "+f"(o[12][1]), "+f"(o[12][2]), "+f"(o[12][3]),
          "+f"(o[13][0]), "+f"(o[13][1]), "+f"(o[13][2]), "+f"(o[13][3]),
          "+f"(o[14][0]), "+f"(o[14][1]), "+f"(o[14][2]), "+f"(o[14][3]),
          "+f"(o[15][0]), "+f"(o[15][1]), "+f"(o[15][2]), "+f"(o[15][3]),
          "+f"(o[16][0]), "+f"(o[16][1]), "+f"(o[16][2]), "+f"(o[16][3]),
          "+f"(o[17][0]), "+f"(o[17][1]), "+f"(o[17][2]), "+f"(o[17][3]),
          "+f"(o[18][0]), "+f"(o[18][1]), "+f"(o[18][2]), "+f"(o[18][3])
        : "l"(da), "l"(db), "r"(acc));
}

__device__ __forceinline__ void slow_edge(int ee, int s, float* accn, const __nv_bfloat16* __restrict__ x,
                                          const __nv_bfloat16* __restrict__ sh, const __nv_bfloat16* __restrict__ ea,
                                          const __nv_bfloat16* __restrict__ cg, const __nv_bfloat16* __restrict__ wr,
                                          int lane) {
    float rwv[4] = {0.f, 0.f, 0.f, 0.f};
#pragma unroll 4
    for (int d = 0; d < 16; d++) {
        const float a = __bfloat162float(ea[(size_t)ee * 16 + d]);
        const uint2 wv = *(const uint2*)(wr + d * 128 + lane * 4);
        rwv[0] += a * __uint_as_float(wv.x << 16);
        rwv[1] += a * __uint_as_float(wv.x & 0xffff0000u);
        rwv[2] += a * __uint_as_float(wv.y << 16);
        rwv[3] += a * __uint_as_float(wv.y & 0xffff0000u);
    }
    float A = 0.f;
#pragma unroll
    for (int v = 0; v < 4; v++)
        A += __bfloat162float(cg[((lane >> 2) & 3) * 16 + v * 4 + (lane & 3)]) * __bfloat162float(sh[(size_t)ee * 4 + v]);
    float m[4][4];
#pragma unroll
    for (int w = 0; w < 4; w++)
#pragma unroll
        for (int j = 0; j < 4; j++) m[w][j] = 0.f;
#pragma unroll
    for (int u = 0; u < 4; u++) {
        const uint2 xv = *(const uint2*)(x + (size_t)s * 512 + u * 128 + lane * 4);
        const float x0 = __uint_as_float(xv.x << 16), x1 = __uint_as_float(xv.x & 0xffff0000u);
        const float x2 = __uint_as_float(xv.y << 16), x3 = __uint_as_float(xv.y & 0xffff0000u);
#pragma unroll
        for (int w = 0; w < 4; w++) {
            const float a = __shfl_sync(0xffffffffu, A, u * 4 + w);
            m[w][0] += a * x0;
            m[w][1] += a * x1;
            m[w][2] += a * x2;
            m[w][3] += a * x3;
        }
    }
#pragma unroll
    for (int w = 0; w < 4; w++)
#pragma unroll
        for (int j = 0; j < 4; j++) atomicAdd(accn + w * 128 + lane * 4 + j, m[w][j] * rwv[j]);
}

__device__ __forceinline__ void slow_out(const float* accn, const __nv_bfloat16* __restrict__ wout,
                                         __nv_bfloat16* __restrict__ outn, int lane) {
    float o[4][4];
#pragma unroll
    for (int w = 0; w < 4; w++)
#pragma unroll
        for (int j = 0; j < 4; j++) o[w][j] = 0.f;
#pragma unroll 2
    for (int c = 0; c < 128; c++) {
        const uint2 wv = *(const uint2*)(wout + c * 128 + lane * 4);
        const float w0 = __uint_as_float(wv.x << 16), w1 = __uint_as_float(wv.x & 0xffff0000u);
        const float w2 = __uint_as_float(wv.y << 16), w3 = __uint_as_float(wv.y & 0xffff0000u);
#pragma unroll
        for (int w = 0; w < 4; w++) {
            const float a = __bfloat162float(__float2bfloat16(accn[w * 128 + c]));
            o[w][0] += a * w0;
            o[w][1] += a * w1;
            o[w][2] += a * w2;
            o[w][3] += a * w3;
        }
    }
#pragma unroll
    for (int w = 0; w < 4; w++)
        *(uint2*)(outn + w * 128 + lane * 4) = make_uint2(pack_bf16(o[w][0], o[w][1]), pack_bf16(o[w][2], o[w][3]));
}

static_assert(2 * NW >= 4 * NP && CE == 3, "barriers");
#define PW 0
#define TWAIT mbar_lean_u
#define PWAIT mbar_lean
#define TMA_ROW(k) "@pl cp.async.bulk.tensor.2d.shared::cluster.global.mbarrier::complete_tx::bytes [d" #k "], [tm, {z" #k ", r" #k "}], [b" #k "];\n"
#define TMA_INIT(k, o) "shfl.sync.idx.b32 z" #k ", %12, " #k ", 31, 0xffffffff;\nadd.u32 d" #k ", %4, " STR(o) ";\n"
#define TMA_PREP(k) "add.u32 d" #k ", d" #k ", dd;\nadd.u32 b" #k ", %0, z" #k ";\n"
__device__ __forceinline__ void produce(const CUtensorMap* tm, uint32_t& fb, uint32_t& par, uint32_t bend, uint32_t d0, uint32_t ps,
                                        uint32_t pe, uint32_t psrc, uint32_t tbase, uint32_t lim, uint32_t taug, uint32_t taus, int lz
) {
    asm volatile(
        "{\n.reg .pred p, pl, ok;\n.reg .b32 a<4>, r<8>, d<8>, b<8>, z<8>, sq, ps, lim, tgt, c, dd, t0;\n"
        ".reg .b64 st, tm;\n"
        "elect.sync _|pl, 0xffffffff;\n"
        TMA_INIT(0, 0) TMA_INIT(1, SM_ODD) TMA_INIT(2, 1024) TMA_INIT(3, SM_ODD + 1024)
        TMA_INIT(4, 2048) TMA_INIT(5, SM_ODD + 2048) TMA_INIT(6, 3072) TMA_INIT(7, SM_ODD + 3072)
        "mov.b64 {a0, a1}, %2;\n"
        "add.u32 a0, a0, %12;\n"
        "add.u32 a1, a1, %12;\n"
        "shfl.sync.idx.b32 a0, a0, 0, 31, 0xffffffff;\n"
        "shfl.sync.idx.b32 a1, a1, 0, 31, 0xffffffff;\n"
        "mov.b64 tm, {a0, a1};\n"
        "mov.u32 ps, %5;\n"
        "mov.u32 lim, %9;\n"
        "mov.u32 dd, 0;\n"
        "ld.shared.u16 sq, [ps];\n"
        "and.b32 sq, sq, 0xffe;\n"
        "mad.lo.u32 sq, sq, 8, %7;\n"
        "ld.shared.v4.u32 {a0, a1, a2, a3}, [sq];\n"
        "ld.shared.u16 sq, [ps+4];\n"
        "mbarrier.test_wait.parity.shared.b64 ok, [%0+8], %1;\n"
        "setp.ge.u32 p, ps, %6;\n"
        "@p bra.uni PEND;\n"
        "PLOOP:\n"
        "mov.u32 t0, %%clock;\n"
        "mad.hi.u32 tgt, a1, %11, %8;\n"
        "min.u32 tgt, tgt, lim;\n"
        "add.u32 lim, lim, %10;\n"
        "and.b32 sq, sq, 0xffe;\n"
        "mad.lo.u32 sq, sq, 8, %7;\n"
        "shl.b32 r0, a0, 3;\nand.b32 r0, r0, 0x7fff8;\nshr.u32 r1, a0, 13;\nand.b32 r1, r1, 0x7fff8;\n"
        "shl.b32 r2, a1, 3;\nand.b32 r2, r2, 0x7fff8;\nshr.u32 r3, a1, 13;\nand.b32 r3, r3, 0x7fff8;\n"
        "shl.b32 r4, a2, 3;\nand.b32 r4, r4, 0x7fff8;\nshr.u32 r5, a2, 13;\nand.b32 r5, r5, 0x7fff8;\n"
        "shl.b32 r6, a3, 3;\nand.b32 r6, r6, 0x7fff8;\nshr.u32 r7, a3, 13;\nand.b32 r7, r7, 0x7fff8;\n"
        "ld.shared.v4.u32 {a0, a1, a2, a3}, [sq];\n"
        "ld.shared.u16 sq, [ps+8];\n"
        "add.u32 ps, ps, 4;\n"
        TMA_PREP(0) TMA_PREP(1) TMA_PREP(2) TMA_PREP(3) TMA_PREP(4) TMA_PREP(5) TMA_PREP(6) TMA_PREP(7)
        "sub.s32 c, t0, tgt;\n"
        "setp.ge.and.s32 p, c, 0, ok;\n"
        "@!p bra.uni PSLP;\n"
        "PRES:\n"
        "@pl mbarrier.arrive.expect_tx.shared.b64 _, [%0], 8192;\n"
        TMA_ROW(0) TMA_ROW(1) TMA_ROW(2) TMA_ROW(3) TMA_ROW(4) TMA_ROW(5) TMA_ROW(6) TMA_ROW(7)
        "setp.eq.u32 p, %0, %3;\n"
        "selp.b32 c, " STR(16 - NP * 16) ", 16, p;\n"
        "add.u32 %0, %0, c;\n"
        "shl.b32 dd, c, 9;\n"
        "selp.b32 c, 1, 0, p;\n"
        "xor.b32 %1, %1, c;\n"
        "mbarrier.test_wait.parity.shared.b64 ok, [%0+8], %1;\n"
        "setp.lt.u32 p, ps, %6;\n"
        "@p bra.uni PLOOP;\n"
        "bra.uni PEND;\n"
        "PSLP:\n"
        "mov.u32 c, %%clock;\n"
        "sub.s32 c, c, tgt;\n"
        "setp.lt.s32 p, c, 0;\n"
        "@p nanosleep.u32 " STR(PSLEEP) ";\n"
        "@p bra.uni PSLP;\n"
        "@ok bra.uni PRES;\n"
        "mov.u32 c, 0;\n"
        "PW:\n"
        "mbarrier.try_wait.parity.shared.b64 p, [%0+8], %1;\n"
        "@p bra.uni PRES;\n"
        "add.u32 c, c, 1;\n"
        "setp.lt.u32 p, c, 4000000;\n"
        "@p bra.uni PW;\n"
        "trap;\n"
        "PEND:\n}"
        : "+r"(fb), "+r"(par)
        : "l"(tm), "r"(bend), "r"(d0), "r"(ps), "r"(pe), "r"(psrc), "r"(tbase), "r"(lim), "r"(taug), "r"(taus), "r"(lz)
        : "memory");
}
#define GCODE(g) ((((g) >> 1) + 1) << 12 | ((g) & 1) << 15)
#define WG_SYNC(w) asm volatile("bar.sync %0, 128;" ::"r"((w) + 1) : "memory")
__global__ void __launch_bounds__(NT, 1)
main_kernel(const __grid_constant__ CUtensorMap tmx, const __grid_constant__ CUtensorMap tmw,
            const __grid_constant__ CUtensorMap tmo, const __nv_bfloat16* __restrict__ x, const int* __restrict__ src,
            const int* __restrict__ dst, const __nv_bfloat16* __restrict__ sh, const __nv_bfloat16* __restrict__ ea,
            const __nv_bfloat16* __restrict__ cg, const __nv_bfloat16* __restrict__ wr,
            const __nv_bfloat16* __restrict__ wout, __nv_bfloat16* __restrict__ out, int N, int E, int npb,
            unsigned npb_magic, int chunk, int fast_ok, int bsh, int tau16, int toff) {
    extern __shared__ __align__(1024) unsigned char smem[];
    const uint32_t sb = s2u(smem);
    int* s_int = (int*)(smem + SM_MISC + MI_INT);
    int* s_hist = (int*)(smem + SC_HIST);
    const int tid = threadIdx.x;
    const int warp = __shfl_sync(0xffffffffu, tid >> 5, 0), lane = tid & 31;
    const int g = lane >> 2, t = lane & 3;

    TLSTAMP(0);
    const int nbins = gridDim.x;
    const int bin = blockIdx.x;
    const int node0 = bin * npb, hpb = npb >> 1;
    const int ebeg = min(E, bin * chunk), eend = min(E, ebeg + chunk);
    int pd[EPS], ps[EPS];
#pragma unroll
    for (int k = 0; k < EPS; k++) {
        const int e = ebeg + tid + k * NT;
        pd[k] = e < eend ? __ldg(dst + e) : -1;
        ps[k] = e < eend ? __ldg(src + e) : 0;
    }
    int2* st_ent = (int2*)(smem + SC_ENT);
    unsigned char* st_bin = smem + SC_BIN;
    int* s_loc = s_hist + MAXBINS;
    int* s_del = s_loc + MAXBINS;
    if (lane < 2 && warp < 2 * NP) mbar_init(sb + SM_BAR + (warp * 2 + lane) * 8, 3 + lane);
    if (tid < MAXBINS) s_hist[tid] = 0;
    if (tid == 0) {
        s_int[3] = -1;
        mbar_init(sb + SM_MISC + MI_WBAR, 4);
        asm volatile("prefetch.tensormap [%0];" ::"l"(&tmx) : "memory");
    }
    if (tid < 2 * (NBK + 1)) ((uint4*)(smem + SC_CNT))[tid] = make_uint4(0, 0, 0, 0);
#pragma unroll
    for (int k = 0; k < TS / 2; k++) ((uint4*)(smem + SM_BT))[tid + k * NT] = make_uint4(0, 0, 0, 0);
    __syncthreads();
    TLSTAMP(1);
    for (int rb = ebeg;; rb += NT * EPS) {
        const bool last = rb + NT * EPS >= eend;
        int pb[EPS], pr[EPS];
#pragma unroll
        for (int k = 0; k < EPS; k++) {
            pb[k] = pd[k] >= 0 ? (int)__umulhi((unsigned)pd[k], npb_magic) : -1;
            if (pb[k] >= 0) pr[k] = atomicAdd(&s_hist[pb[k]], 1);
        }
        __syncthreads();
        TLSTAMP(6);
        int gbase = 0;
        if (warp == NW - 1) {
            int v[MAXBINS / 32], sum = 0;
#pragma unroll
            for (int c = 0; c < MAXBINS / 32; c++) {
                v[c] = s_hist[lane * (MAXBINS / 32) + c];
                sum += v[c];
            }
            int run = warp_incl_scan(sum, lane) - sum;
#pragma unroll
            for (int c = 0; c < MAXBINS / 32; c++) {
                s_loc[lane * (MAXBINS / 32) + c] = run;
                run += v[c];
            }
        } else if (tid < nbins) {
            gbase = atomicAdd(&g_bincnt[tid * 32], s_hist[tid] + (last ? 1 << 22 : 0));
        }
        __syncthreads();
#pragma unroll
        for (int k = 0; k < EPS; k++) {
            if (pb[k] >= 0) {
                const int pos = s_loc[pb[k]] + pr[k];
                st_ent[pos] = make_int2(ps[k], (rb + tid + k * NT) | ((pd[k] - pb[k] * npb) << 24) | 0x80000000);
                st_bin[pos] = pb[k];
            }
        }
        if (tid < nbins) s_del[tid] = (gbase & 0x3fffff) - s_loc[tid];
        __syncthreads();
        TLSTAMP(8);
        const int n = min(eend - rb, NT * EPS);
#pragma unroll
        for (int k = 0; k < EPS; k++) {
            const int i = tid + k * NT;
            if (i < n) {
                const int b = st_bin[i];
                const int gpos = i + s_del[b];
                if (gpos < BINCAP) __stcg(&g_bin[b * BINCAP + gpos], st_ent[i]);
            }
        }
        if (last) break;
        if (tid < MAXBINS) s_hist[tid] = 0;
#pragma unroll
        for (int k = 0; k < EPS; k++) {
            const int e = rb + NT * EPS + tid + k * NT;
            pd[k] = e < eend ? dst[e] : -1;
            ps[k] = e < eend ? src[e] : 0;
        }
        __syncthreads();
    }
    TLSTAMP(5);
    int2 ent[KS];
    uint2 wv;
    int rank[KS];
    {
        int cnt = 0;
        if (lane == 0) {
            for (int spin = 0;; spin++) {
                asm volatile("ld.relaxed.gpu.global.s32 %0, [%1];" : "=r"(cnt) : "l"(&g_bincnt[bin * 32]) : "memory");
                if ((cnt >> 22) >= nbins) break;
                if (spin > 10000000) __trap();
            }
            atomicMin((unsigned*)s_int + 3, (unsigned)clock());
        }
        cnt = __shfl_sync(0xffffffffu, cnt, 0) & 0x3fffff;
        if (tid == 0) s_int[0] = cnt;
        const int n = min(cnt, BINCAP);
        unsigned pend = 0;
#pragma unroll
        for (int k = 0; k < KS; k++) {
            ent[k] = make_int2(0, 0);
            if (tid + k * NT < n) pend |= 1u << k;
        }
        int2* gp = &g_bin[bin * BINCAP + tid];
        for (int spin = 0; __any_sync(0xffffffffu, pend); spin++) {
#pragma unroll
            for (int k = 0; k < KS; k++)
                if ((pend >> k) & 1)
                    asm volatile("ld.relaxed.gpu.global.v2.s32 {%0,%1}, [%2];"
                                 : "=r"(ent[k].x), "=r"(ent[k].y)
                                 : "l"(gp + k * NT)
                                 : "memory");
#pragma unroll
            for (int k = 0; k < KS; k++)
                if (ent[k].y < 0) pend &= ~(1u << k);
            if (spin > 10000000) __trap();
        }
        TLSTAMP(2);
        asm volatile("ld.global.nc.v2.u32 {%0,%1}, [%2];" : "=r"(wv.x), "=r"(wv.y) : "l"((const uint2*)wr + tid));
#pragma unroll
        for (int k = 0; k < KS; k++) {
            if (ent[k].y < 0) {
                if (fast_ok) {
                    const int dl = (ent[k].y >> 24) & 127, w = dl >= hpb;
                    const int loc = dl - (w ? hpb : 0), gr = GSZ == 6 ? min(loc * 43 >> 8, 5) : loc >> 3, sft = (gr & 1) * 16;
                    const int cw = (w * (NBK + 1) + (ent[k].x >> bsh)) * 4 + (gr >> 1);
                    const unsigned old = atomicAdd((unsigned*)(smem + SC_CNT) + cw, 1u << sft);
                    rank[k] = ((old >> sft) & 0xffff) | GCODE(gr);
                    ent[k].x |= cw << 16;
                    ent[k].y = (ent[k].y & 0x80ffffff) | ((loc - gr * GSZ) << 24);
                }
                __stcg(gp + k * NT, make_int2(0, 0));
            }
        }
    }
    __syncthreads();
    if (tid == 0) g_bincnt[bin * 32] = 0;
    TLSTAMP(9);
    if (warp < 2) {
        uint4* cp = (uint4*)(smem + SC_CNT) + warp * (NBK + 1) + lane * (NBK / 32);
        uint4 v[NBK / 32];
        uint32_t s[3] = {0, 0, 0}, r[3], tot[3], base[3];
#pragma unroll
        for (int c = 0; c < NBK / 32; c++) {
            v[c] = cp[c];
            s[0] += v[c].x;
            s[1] += v[c].y;
            s[2] += v[c].z;
        }
        uint32_t sum = 0;
#pragma unroll
        for (int i = 0; i < 3; i++) {
            r[i] = warp_incl_scan(s[i], lane);
            tot[i] = __shfl_sync(0xffffffffu, r[i], 31);
            r[i] -= s[i];
            const uint32_t p = (tot[i] + 0x00070007u) & 0xfff8fff8u;
            base[i] = sum * 0x10001u + (p << 16);
            sum += (p & 0xffff) + (p >> 16);
        }
        auto blocks = [](const uint32_t(&a)[3]) {
            constexpr uint32_t c = (7 - CE) * 0x10001u;
            const uint32_t q = (((a[0] + c) >> 3) & 0x1fff1fffu) + (((a[1] + c) >> 3) & 0x1fff1fffu) + (((a[2] + c) >> 3) & 0x1fff1fffu);
            return (q & 0xffff) + (q >> 16);
        };
#pragma unroll
        for (int c = 0; c < NBK / 32; c++) {
            cp[c] = make_uint4(r[0] + base[0], r[1] + base[1], r[2] + base[2], blocks(r));
            r[0] += v[c].x;
            r[1] += v[c].y;
            r[2] += v[c].z;
        }
        const bool ok = sum + 8 <= LCAP;
        const int nst = sum >> 3;
        const int npr = (nst + 1) >> 1;
        const uint32_t tw = g < 2 ? tot[0] : g < 4 ? tot[1] : tot[2], bw = g < 2 ? base[0] : g < 4 ? base[1] : base[2];
        const int le = g < 6 ? ((tw + bw) >> ((g & 1) * 16)) & 0xffff : sum;
        const bool tailb = t == 0 && (le & 7) >= 1 && (le & 7) <= CE;
        const unsigned tm = __ballot_sync(0xffffffffu, tailb);
        if (ok) {
#pragma unroll
            for (int k = 0; k < 2; k++) {
                const int i = (le & ~7) + 2 * t + k;
                if (i >= le) {
                    ((unsigned short*)(smem + SM_SRC))[warp * LCAP + i] = min(node0, N - 1);
                    ((uint32_t*)(smem + SM_EID))[warp * LCAP + i] = 0x80000000u;
                }
            }
            if (tailb) {
                const int i = blocks(tot) + __popc(tm & ((1u << lane) - 1));
                ((unsigned short*)(smem + SM_SEQ))[warp * SEQCAP + i] = (le >> 3) * 2 | GCODE(g);
            }
            ((unsigned short*)(smem + SM_SEQ))[warp * SEQCAP + nst + lane] = nst * 2 | (lane < (nst & 1) ? GCODE(0) : GCODE(7));
        }
        if (lane < NP - 1 - npr % NP) {
            mbar_arrive_cnt(sb + SM_BAR + (warp * NP + lane) * 16, 3);
            mbar_arrive_cnt(sb + SM_BAR + (warp * NP + lane) * 16 + 8, 4);
        }
        if (lane == 0) s_int[1 + warp] = ok ? npr : -1;
    }
    __syncthreads();
    TLSTAMP(10);
    const bool fast = s_int[0] <= BINCAP && fast_ok && (s_int[1] | s_int[2]) >= 0;
    if (fast) {
        int pos[KS];
#pragma unroll
        for (int k = 0; k < KS; k++)
            if (ent[k].y < 0) pos[k] = ((uint32_t*)(smem + SC_CNT))[ent[k].x >> 16];
#pragma unroll
        for (int k = 0; k < KS; k++) {
            if (ent[k].y < 0) {
                const int w = (ent[k].x >> 16) >= (NBK + 1) * 4;
                const int p = (((uint32_t)pos[k] >> ((rank[k] >> 11) & 16)) & 0xffff) + (rank[k] & 0xfff);
                ((unsigned short*)(smem + SM_SRC))[w * LCAP + p] = ent[k].x;
                ((uint32_t*)(smem + SM_EID))[w * LCAP + p] = ent[k].y & 0x7fffffff;
                if ((p & 7) == CE) {
                    const int i = atomicAdd((int*)(smem + SC_CNT) + ((ent[k].x >> 16) | 3), 1);
                    ((unsigned short*)(smem + SM_SEQ))[w * SEQCAP + i] = (p >> 3) * 2 | (rank[k] & 0xf000);
                }
            }
        }
    }
    sts_v2(sb + SM_WR + ((tid >> 1) & 15) * 256 + (tid >> 5) * 16 + (tid & 1) * 8, wv.x, wv.y);
    FENCE_ASYNC();
    TLSTAMP(15);
    __syncthreads();
    TLSTAMP(3);

    if (fast && warp >= 12) {
        asm volatile("setmaxnreg.dec.sync.aligned.u32 %0;" ::"n"(HREG));
        const int w = warp & 1, j = (warp >> 1) & 1;
        const int npr = __shfl_sync(0xffffffffu, s_int[1 + w], 0);
        const uint32_t bar0 = sb + SM_BAR + w * NP * 16;
        uint32_t fseq = sb + SM_SEQ + w * SEQCAP * 2 + j * 4 + (lane >> 4) * 2;
        const uint32_t feid = sb + SM_EID + w * LCAP * 4 + ((lane >> 1) & 7) * 4;
        const uint32_t bea = sb + SM_EA + w * 4096;
        uint32_t oea = ((lane >> 1) & 3) * 32 + ((lane >> 3) & 1) * 16 + (lane & 1) * 128 + (2 * j + (lane >> 4)) * 256;
        const uint32_t fsd = sb + SM_SIDE + (warp - 12) * 512 + lane * 8;
        const char* gea = (const char*)ea + (lane & 1) * 16;
        const char* gsh = (const char*)sh + (lane & 1) * 4;
        uint32_t es;
        auto ids = [&]() {
            es = lds_u32(feid + (lds_u16(fseq) & 0xffe) * 16);
            fseq += 8;
        };
        auto fetch = [&](int i) {
            cp_async16(bea + oea + i * 1024, gea + (size_t)(es & 0xffffff) * 32, (int)es >= 0 ? 16 : 0);
            cp_async4(fsd + i * 256, gsh + (size_t)(es & 0xffffff) * 8, (int)es >= 0 ? 4 : 0);
            sts_u32(fsd + i * 256 + 4, ((es >> 17) & 0x300) | ((es >> 21) & 8));
            asm volatile("cp.async.commit_group;" ::: "memory");
            if (i) oea ^= 0x800;
        };
        ids();
        fetch(0);
        ids();
        fetch(1);
        uint32_t wf[2];
        {
            const unsigned short* cp = (const unsigned short*)cg + (g >> 1) * 16 + (t & 1) * 8 + (g & 1);
#pragma unroll
            for (int k = 0; k < 2; k++) wf[k] = t < 2 ? __ldg(cp + 2 * k) | ((uint32_t)__ldg(cp + 2 * k + 4) << 16) : 0u;
        }
        const uint32_t psd = sb + SM_SIDE + (warp - 12) * 512 + g * 16 + (t & 1) * 8;
        const uint32_t pt = sb + SM_BT + w * (TS * 2048) + j * 4096 + (g >> 2) * 1024 +
                            (2 * (g & 3) + (t & 1) + 8 * ((t >> 1) ^ ((g >> 1) & 1))) * 16;
        uint32_t old[4] = {pt, pt, pt, pt};
        int vf = (NP - 1 - npr % NP + j) % NP * 16;
        int ve = (NP - 1 - npr % NP + j + 1 - TS / 2 + NP) * 16, pe = 1;
        if (ve >= NP * 16) ve -= NP * 16, pe = 0;
#pragma unroll 1
        for (int m = j; m < npr;) {
#pragma unroll
            for (int i = 0; i < 2; i++) {
                asm volatile("cp.async.wait_group 1;" ::: "memory");
                __syncwarp();
                const uint2 s0 = lds_v2(psd + i * 256), s1 = lds_v2(psd + i * 256 + 128);
                ids();
                float d0[4], d1[4];
                mma1688_z(d0, s0.x, s1.x, wf[0]);
                mma1688_z(d1, s0.x, s1.x, wf[1]);
                TWAIT(bar0 + ve + 8, pe);
                sts_v2(old[2 * i] + i * 8192, 0, 0);
                sts_v2(old[2 * i + 1] + i * 8192 + 2048, 0, 0);
                old[2 * i] = pt + s0.y;
                old[2 * i + 1] = pt + s1.y;
                sts_v2(old[2 * i] + i * 8192, pack_bf16(d0[0], d0[1]), pack_bf16(d1[0], d1[1]));
                sts_v2(old[2 * i + 1] + i * 8192 + 2048, pack_bf16(d0[2], d0[3]), pack_bf16(d1[2], d1[3]));
                FENCE_ASYNC();
                __syncwarp();
                if (lane == 0) mbar_arrive(bar0 + vf);
                fetch(i);
                vf += 32;
                if (vf >= NP * 16) vf -= NP * 16;
                ve += 32;
                if (ve >= NP * 16) ve -= NP * 16, pe ^= 1;
                m += 2;
                if (m >= npr) break;
            }
        }
        asm volatile("cp.async.wait_group 0;" ::: "memory");
        TLMAX(13);
    } else if (fast && warp >= 8) {
        asm volatile("setmaxnreg.dec.sync.aligned.u32 %0;" ::"n"(PREG));
        const int w = warp & 1, j = (warp >> 1) & 1;
        const int nst = 2 * __shfl_sync(0xffffffffu, s_int[1 + w], 0);
        const uint32_t bar0 = sb + SM_BAR + w * NP * 16, ring = sb + w * RING_BYTES + j * 4096;
        const uint32_t pseq = sb + SM_SEQ + w * SEQCAP * 2 + j * 2;
        const unsigned tbase = __shfl_sync(0xffffffffu, (unsigned)s_int[3], 0) + (unsigned)toff;
        const unsigned taug = __shfl_sync(0xffffffffu, (N * tau16 >> 4) / max(nst, 1), 0);
        uint32_t fb = bar0 + (NP - 1 - (nst >> 1) % NP) * 16, par = 1;
        produce(&tmx, fb, par, bar0 + NP * 16 - 16, ring + (fb - bar0) * 512, pseq, pseq + nst * 2, sb + SM_SRC + w * LCAP * 2, tbase,
                tbase + (N * tau16 >> 8) + j * taug, 2 * taug, tau16 << 12, lane & (E >> 31)
        );
        if (elect()) {
            const uint32_t d = ring + (NP - 1) * 8192;
            mbar_wait(fb + 8, par);
            mbar_arrive_cnt(fb, 1 + j);
            mbar_expect_tx(sb + SM_MISC + MI_WBAR, 8192);
            tma_2d(d + SM_EVEN, &tmw, sb + SM_MISC + MI_WBAR, w * 64, j * 32);
            tma_2d(d + SM_ODD, &tmw, sb + SM_MISC + MI_WBAR, w * 64, j * 32 + 64);
        }
        TLMAX(12);
    } else if (fast) {
        asm volatile("setmaxnreg.inc.sync.aligned.u32 %0;" ::"n"(CREG));
        const int w = warp >> 2, wq = warp & 3;
        const int nst = __shfl_sync(0xffffffffu, s_int[1 + w], 0);
        const uint32_t ring = sb + w * RING_BYTES;
        float acc[2][NJ][4];
        {
            const int e = (lane >> 1) & 3, m = lane >> 3;
            const int line = 2 * ((lane & 1) + 2 * ((m >> 1) ^ (e >> 1))), ch = 2 * wq + (m & 1);
            const uint32_t xb = ring + (e & 1 ? SM_ODD : SM_EVEN) + (e >> 1) * 1024 + line * 128;
            consume(acc, xb + ((ch ^ ((line + (e & 1)) & 7)) * 16), xb + 128 + ((ch ^ ((line + 1 + (e & 1)) & 7)) * 16),
                    (NP - 1 - nst % NP) * 8192, sb + SM_BAR + w * NP * 16, (((sb + SM_EA + w * 4096) & 0x3ffff) >> 4) | (8 << 16),
                    (((sb + SM_BT + w * (TS * 2048)) & 0x3ffff) >> 4) | (8 << 16), sb + SM_SEQ + w * SEQCAP * 2, lane & (E >> 31),
                    (((sb + SM_WR) & 0x3ffff) >> 4) | (8 << 16));
        }
        TLMAX(11);
#pragma unroll
        for (int h = 0; h < 2; h++) {
            const uint32_t tb = ring + (h ? SM_ODD : SM_EVEN) + wq * (NJ * 256) + lane * 16;
#pragma unroll
            for (int j = 0; j + 1 < NJ; j += 2)
                stsm4(tb + j * 256, pack_bf16(acc[h][j][0], acc[h][j][1]), pack_bf16(acc[h][j][2], acc[h][j][3]),
                      pack_bf16(acc[h][j + 1][0], acc[h][j + 1][1]), pack_bf16(acc[h][j + 1][2], acc[h][j + 1][3]));
            if (NJ & 1)
                stsm2(tb + (NJ - 1) * 256, pack_bf16(acc[h][NJ - 1][0], acc[h][NJ - 1][1]),
                      pack_bf16(acc[h][NJ - 1][2], acc[h][NJ - 1][3]));
        }
        FENCE_ASYNC();
        WG_SYNC(w);
        mbar_wait_u(sb + SM_MISC + MI_WBAR, 0);
        float o[2][NJ][4];
        asm volatile("wgmma.fence.sync.aligned;" ::: "memory");
#pragma unroll
        for (int hh = 0; hh < 2; hh++) {
#pragma unroll
            for (int ks = 0; ks < 8; ks++) {
                const uint32_t rg = ks >> 2 ? SM_ODD : SM_EVEN;
                const uint64_t da = (uint64_t)(((sb + rg + hh * RING_BYTES + (NS - 2) * 4096 + (ks & 3) * 2048) & 0x3ffff) >> 4) |
                                    (64ull << 32) | (1ull << 62);
                const uint64_t db = (uint64_t)(((ring + rg + (ks & 3) * (NJ * 256)) & 0x3ffff) >> 4) | (8ull << 16) | (16ull << 32);
                wgmma_out(o[hh], da, db, ks);
            }
            asm volatile("wgmma.commit_group.sync.aligned;" ::: "memory");
        }
        const int nb = 2 * hpb;
#pragma unroll
        for (int hh = 0; hh < 2; hh++) {
            if (hh == 0) {
                asm volatile("wgmma.wait_group.sync.aligned 1;" ::: "memory");
            } else {
                asm volatile("wgmma.wait_group.sync.aligned 0;" ::: "memory");
                WG_SYNC(w);
            }
#pragma unroll
            for (int j = 0; j < NJ; j++)
#pragma unroll
                for (int k = 0; k < 4; k++) asm volatile("" : "+f"(o[hh][j][k])::"memory");
            const uint32_t b0 = ring + SM_EVEN + (hh ? 0 : 20480);
            const uint32_t b1 = hh ? b0 : ring + SM_ODD + 20480 + 896 - (nb * 128 & ~1023);
            const int r = (lane & 7) + (lane >> 4) * 8;
            const uint32_t co = r * 128 + (((2 * wq + ((lane >> 3) & 1)) ^ (lane & 7)) * 16);
#pragma unroll
            for (int j = 0; j + 1 < NJ; j += 2)
                stsm4t((8 * j + r < nb ? b0 : b1) + co + j * 1024, pack_bf16(o[hh][j][0], o[hh][j][1]),
                       pack_bf16(o[hh][j][2], o[hh][j][3]), pack_bf16(o[hh][j + 1][0], o[hh][j + 1][1]),
                       pack_bf16(o[hh][j + 1][2], o[hh][j + 1][3]));
            if (NJ & 1)
                stsm2t(b1 + co + (NJ - 1) * 1024, pack_bf16(o[hh][NJ - 1][0], o[hh][NJ - 1][1]),
                       pack_bf16(o[hh][NJ - 1][2], o[hh][NJ - 1][3]));
            FENCE_ASYNC();
            WG_SYNC(w);
            if (wq < 2 && elect()) {
                const int row = (node0 + w * hpb) * 4 + wq * nb;
                if (row < N * 4) tma_store(&tmo, wq ? b1 + nb * 128 : b0, hh * 64, row);
                asm volatile("cp.async.bulk.commit_group;" ::: "memory");
                if (hh) asm volatile("cp.async.bulk.wait_group.read 0;" ::: "memory");
            }
        }
    } else {
        float* accs = (float*)smem;
        constexpr int NACC = SM_EID / 2048;
        const int nnodes = max(0, min(npb, N - node0));
#pragma unroll 1
        for (int nb = 0; nb < nnodes; nb += NACC) {
            __syncthreads();
            for (int i = tid; i < NACC * 512; i += NT) accs[i] = 0.f;
            __syncthreads();
#pragma unroll 1
            for (int base = warp * 32; base < E; base += NT) {
                const int e = base + lane;
                int dl = e < E ? dst[e] - node0 - nb : -1;
                if (dl + nb >= nnodes) dl = -1;
                unsigned mask = __ballot_sync(0xffffffffu, dl >= 0 && dl < NACC);
#pragma unroll 1
                while (mask) {
                    const int l = __ffs(mask) - 1;
                    mask &= mask - 1;
                    const int ee = __shfl_sync(0xffffffffu, e, l);
                    const int dd = __shfl_sync(0xffffffffu, dl, l);
                    slow_edge(ee, src[ee], accs + dd * 512, x, sh, ea, cg, wr, lane);
                }
            }
            __syncthreads();
#pragma unroll 1
            for (int nl = warp; nl < NACC && nb + nl < nnodes; nl += NW)
                slow_out(accs + nl * 512, wout, out + (size_t)(node0 + nb + nl) * 512, lane);
        }
        __syncthreads();
    }

    TLMAX(4);
}

typedef CUresult (*EncodeTiledFn)(CUtensorMap*, CUtensorMapDataType, cuuint32_t, void*, const cuuint64_t*,
                                  const cuuint64_t*, const cuuint32_t*, const cuuint32_t*, CUtensorMapInterleave,
                                  CUtensorMapSwizzle, CUtensorMapL2promotion, CUtensorMapFloatOOBfill);

extern "C" void kernel_launch(void* const* d_in, const int* in_sizes, int n_in, void* d_out, int out_size) {
    const __nv_bfloat16* x = (const __nv_bfloat16*)d_in[0];
    const int* src = (const int*)d_in[1];
    const int* dst = (const int*)d_in[2];
    const __nv_bfloat16* sh = (const __nv_bfloat16*)d_in[3];
    const __nv_bfloat16* ea = (const __nv_bfloat16*)d_in[4];
    const __nv_bfloat16* cg = (const __nv_bfloat16*)d_in[5];
    const __nv_bfloat16* wr = (const __nv_bfloat16*)d_in[6];
    const __nv_bfloat16* wout = (const __nv_bfloat16*)d_in[7];
    __nv_bfloat16* out = (__nv_bfloat16*)d_out;
    const int N = in_sizes[0] / 512;
    const int E = in_sizes[1];

    static int num_sms = 0;
    static EncodeTiledFn encode = nullptr;
    if (num_sms == 0) {
        int dev = 0;
        cudaGetDevice(&dev);
        cudaDeviceGetAttribute(&num_sms, cudaDevAttrMultiProcessorCount, dev);
        cudaFuncSetAttribute(main_kernel, cudaFuncAttributeMaxDynamicSharedMemorySize, SM_TOTAL);
        void* fn = nullptr;
        cudaDriverEntryPointQueryResult qr;
        cudaGetDriverEntryPoint("cuTensorMapEncodeTiled", &fn, cudaEnableDefault, &qr);
        encode = (EncodeTiledFn)fn;
    }
    const int nbins = num_sms < MAXBINS ? num_sms : MAXBINS;
    int npb = ((N + nbins - 1) / nbins + 1) & ~1;
    if (npb < 32) npb = 32;
    const int fast_ok = npb <= 2 * HPB;
    auto map2d = [&](CUtensorMap* tm, const void* p, int d0, int d1, int b1) {
        const cuuint64_t gd[2] = {(cuuint64_t)d0, (cuuint64_t)d1};
        const cuuint64_t gs[1] = {(cuuint64_t)d0 * 2};
        const cuuint32_t bx[2] = {64, (cuuint32_t)b1};
        const cuuint32_t es[2] = {1, 1};
        encode(tm, CU_TENSOR_MAP_DATA_TYPE_BFLOAT16, 2, (void*)p, gd, gs, bx, es, CU_TENSOR_MAP_INTERLEAVE_NONE,
               CU_TENSOR_MAP_SWIZZLE_128B, CU_TENSOR_MAP_L2_PROMOTION_NONE, CU_TENSOR_MAP_FLOAT_OOB_FILL_NONE);
    };
    CUtensorMap tmx, tmw, tmo;
    map2d(&tmx, x, 64, N * 8, 8);
    map2d(&tmw, wout, 128, 128, 32);
    map2d(&tmo, out, 128, N * 4, fast_ok ? npb : 2);
    const unsigned npb_magic = (unsigned)((0x100000000ull + npb - 1) / npb);
    const int chunk = (E + nbins - 1) / nbins;
    int bsh = 0;
    while (((N - 1) >> bsh) >= NBK) bsh++;
    int tau16 = (int)fmin((double)PACE * 16.0 * chunk / N, 100000.0), toff = TOFF;
    main_kernel<<<nbins, NT, SM_TOTAL, cudaStreamPerThread>>>(tmx, tmw, tmo, x, src, dst, sh, ea, cg, wr, wout, out, N, E,
                                                              npb, npb_magic, chunk, fast_ok, bsh, tau16, toff);
}
```

```cpp
#include <cuda_runtime.h>
#include <cuda.h>
#include <cuda_bf16.h>
#include <stdint.h>
#include <stdlib.h>

#define MAXBINS 256
#define NW 16
#define NT (NW * 32)
#define HPB 38
#define BINCAP 3072
#define LCAP 1472
#define NBK 160
#define CE 2
#define GSZ 6
#define NS 10
#define RING_BYTES 40960
static_assert(RING_BYTES == NS * 4096, "ring");
#define NP (NS / 2)
#define CREG 224
#define PREG 24
#define HREG 40
#define TS 8
#define SM_EVEN 0
#define SM_MISC (2 * RING_BYTES)
#define SM_ODD (SM_MISC + 128)
#define SM_BT (SM_ODD + 2 * RING_BYTES)
#define SM_EA (SM_BT + TS * 4096)
#define SM_WR (SM_EA + 8192)
#define SM_SIDE (SM_WR + 4096)
#define SM_EID (SM_SIDE + 2048)
#define SM_SRC (SM_EID + 2 * LCAP * 4)
#define SEQCAP (LCAP / 4 + 40)
#define SM_SEQ (SM_SRC + 2 * LCAP * 2)
#define SM_BAR (SM_SEQ + 2 * SEQCAP * 2)
#define SM_TOTAL (SM_BAR + 2 * NP * 16)
#define MI_WBAR 32
#define MI_INT 0
#define EPS ((2464 + NT - 1) / NT)
#define KS (BINCAP / NT)
#define SC_ENT 0
#define SC_BIN (SC_ENT + NT * EPS * 8)
#define SC_HIST (SC_BIN + NT * EPS)
#define SC_CNT (SC_HIST + 3 * MAXBINS * 4)
static_assert(SC_HIST % 16 == 0 && SC_CNT + 2 * (NBK + 1) * 16 <= SM_MISC, "scratch");
static_assert(SM_TOTAL <= 232448 && SM_BAR % 16 == 0 && SM_SEQ % 16 == 0 && SM_SRC % 16 == 0, "smem");
#define PACE 20.7
#define TOFF 10400
#define PSLEEP 20

__device__ int2 g_bin[MAXBINS * BINCAP];
__device__ __align__(128) int g_bincnt[MAXBINS * 32];
#define TLSTAMP(i)
#define TLMAX(i)

__device__ __forceinline__ uint32_t pack_bf16(float lo, float hi) {
    uint32_t r;
    asm("cvt.rn.bf16x2.f32 %0, %1, %2;" : "=r"(r) : "f"(hi), "f"(lo));
    return r;
}
__device__ __forceinline__ void mma1688_z(float (&d)[4], uint32_t a0, uint32_t a1, uint32_t b0) {
    asm("mma.sync.aligned.m16n8k8.row.col.f32.bf16.bf16.f32 {%0,%1,%2,%3}, {%4,%5}, {%6}, {%7,%7,%7,%7};"
        : "=f"(d[0]), "=f"(d[1]), "=f"(d[2]), "=f"(d[3])
        : "r"(a0), "r"(a1), "r"(b0), "f"(0.f));
}
__device__ __forceinline__ uint32_t s2u(const void* p) { return (uint32_t)__cvta_generic_to_shared(p); }
__device__ __forceinline__ void mbar_init(uint32_t a, int c) {
    asm volatile("mbarrier.init.shared.b64 [%0], %1;" ::"r"(a), "r"(c));
}
__device__ __forceinline__ void mbar_expect_tx(uint32_t a, int bytes) {
    asm volatile("mbarrier.arrive.expect_tx.shared.b64 _, [%0], %1;" ::"r"(a), "r"(bytes) : "memory");
}
__device__ __forceinline__ void mbar_arrive(uint32_t a) {
    asm volatile("mbarrier.arrive.shared.b64 _, [%0];" ::"r"(a) : "memory");
}
__device__ __forceinline__ void mbar_arrive_cnt(uint32_t a, int c) {
    asm volatile("mbarrier.arrive.shared.b64 _, [%0], %1;" ::"r"(a), "r"(c) : "memory");
}
__device__ __forceinline__ void mbar_wait(uint32_t a, int parity) {
    asm volatile(
        "{\n.reg .pred p;\n.reg .u32 c;\n"
        "mov.u32 c, 0;\n"
        "LAB_WAIT:\n"
        "mbarrier.try_wait.parity.shared.b64 p, [%0], %1, 2000;\n"
        "@p bra DONE;\n"
        "add.u32 c, c, 1;\n"
        "setp.lt.u32 p, c, 2000000;\n"
        "@p bra LAB_WAIT;\n"
        "trap;\n"
        "DONE:\n}" ::"r"(a),
        "r"(parity)
        : "memory");
}
__device__ __forceinline__ void mbar_wait_u(uint32_t a, int parity) {
    asm volatile(
        "{\n.reg .pred p;\n.reg .u32 c;\n"
        "mov.u32 c, 0;\n"
        "LAB_WAIT:\n"
        "mbarrier.try_wait.parity.shared.b64 p, [%0], %1, 2000;\n"
        "@p bra.uni DONE;\n"
        "add.u32 c, c, 1;\n"
        "setp.lt.u32 p, c, 2000000;\n"
        "@p bra.uni LAB_WAIT;\n"
        "trap;\n"
        "DONE:\n}" ::"r"(a),
        "r"(parity)
        : "memory");
}
__device__ __forceinline__ void mbar_spin_u(uint32_t a, int parity) {
    asm volatile(
        "{\n.reg .pred p;\n.reg .u32 c;\n"
        "mov.u32 c, 0;\n"
        "LAB_WAIT:\n"
        "mbarrier.test_wait.parity.shared.b64 p, [%0], %1;\n"
        "@p bra.uni DONE;\n"
        "add.u32 c, c, 1;\n"
        "setp.lt.u32 p, c, 20000000;\n"
        "@p bra.uni LAB_WAIT;\n"
        "trap;\n"
        "DONE:\n}" ::"r"(a),
        "r"(parity)
        : "memory");
}
__device__ __forceinline__ void mbar_lean(uint32_t a, int parity) {
    asm volatile(
        "{\n.reg .pred p;\n.reg .u32 c;\n"
        "mov.u32 c, 0;\n"
        "LAB_WAIT:\n"
        "mbarrier.try_wait.parity.shared.b64 p, [%0], %1;\n"
        "@p bra DONE;\n"
        "add.u32 c, c, 1;\n"
        "setp.lt.u32 p, c, 4000000;\n"
        "@p bra LAB_WAIT;\n"
        "trap;\n"
        "DONE:\n}" ::"r"(a),
        "r"(parity)
        : "memory");
}
__device__ __forceinline__ void mbar_lean_u(uint32_t a, int parity) {
    asm volatile(
        "{\n.reg .pred p;\n.reg .u32 c;\n"
        "mov.u32 c, 0;\n"
        "LAB_WAIT:\n"
        "mbarrier.try_wait.parity.shared.b64 p, [%0], %1;\n"
        "@p bra.uni DONE;\n"
        "add.u32 c, c, 1;\n"
        "setp.lt.u32 p, c, 4000000;\n"
        "@p bra.uni LAB_WAIT;\n"
        "trap;\n"
        "DONE:\n}" ::"r"(a),
        "r"(parity)
        : "memory");
}
__device__ __forceinline__ bool mbar_test(uint32_t a, int parity) {
    uint32_t p;
    asm volatile("{\n.reg .pred P;\nmbarrier.test_wait.parity.shared.b64 P, [%1], %2;\nselp.u32 %0, 1, 0, P;\n}"
                 : "=r"(p)
                 : "r"(a), "r"(parity)
                 : "memory");
    return p;
}
__device__ __forceinline__ bool elect() {
    uint32_t p;
    asm volatile("{\n.reg .pred P;\nelect.sync _|P, 0xffffffff;\nselp.u32 %0, 1, 0, P;\n}" : "=r"(p));
    return p;
}
__device__ __forceinline__ void tma_2d(uint32_t dst, const CUtensorMap* tm, uint32_t bar, int c0, int c1) {
    asm volatile(
        "cp.async.bulk.tensor.2d.shared::cluster.global.mbarrier::complete_tx::bytes [%0], [%1, {%3, %4}], [%2];" ::"r"(dst),
        "l"(tm), "r"(bar), "r"(c0), "r"(c1)
        : "memory");
}
__device__ __forceinline__ void tma_row(uint32_t dst, const CUtensorMap* tm, uint32_t bar, int row8) {
    tma_2d(dst, tm, bar, 0, row8);
}
__device__ __forceinline__ void tma_store(const CUtensorMap* tm, uint32_t src, int c0, int c1) {
    asm volatile("cp.async.bulk.tensor.2d.global.shared::cta.bulk_group [%0, {%2, %3}], [%1];" ::"l"(tm), "r"(src),
                 "r"(c0), "r"(c1)
                 : "memory");
}
__device__ __forceinline__ uint2 lds_v2(uint32_t a) {
    uint2 v;
    asm volatile("ld.shared.v2.u32 {%0,%1}, [%2];" : "=r"(v.x), "=r"(v.y) : "r"(a));
    return v;
}
__device__ __forceinline__ uint4 lds_v4(uint32_t a) {
    uint4 v;
    asm volatile("ld.shared.v4.u32 {%0,%1,%2,%3}, [%4];" : "=r"(v.x), "=r"(v.y), "=r"(v.z), "=r"(v.w) : "r"(a));
    return v;
}
__device__ __forceinline__ uint32_t lds_u32(uint32_t a) {
    uint32_t v;
    asm volatile("ld.shared.u32 %0, [%1];" : "=r"(v) : "r"(a));
    return v;
}
__device__ __forceinline__ uint32_t lds_u16(uint32_t a) {
    uint32_t v;
    asm volatile("ld.shared.u16 %0, [%1];" : "=r"(v) : "r"(a));
    return v;
}
__device__ __forceinline__ void sts_v2(uint32_t a, uint32_t x, uint32_t y) {
    asm volatile("st.shared.v2.u32 [%0], {%1,%2};" ::"r"(a), "r"(x), "r"(y) : "memory");
}
__device__ __forceinline__ void sts_v4(uint32_t a, uint4 v) {
    asm volatile("st.shared.v4.u32 [%0], {%1,%2,%3,%4};" ::"r"(a), "r"(v.x), "r"(v.y), "r"(v.z), "r"(v.w) : "memory");
}
__device__ __forceinline__ void stsm4(uint32_t a, uint32_t r0, uint32_t r1, uint32_t r2, uint32_t r3) {
    asm volatile("stmatrix.sync.aligned.m8n8.x4.shared.b16 [%0], {%1,%2,%3,%4};" ::"r"(a), "r"(r0), "r"(r1), "r"(r2), "r"(r3)
                 : "memory");
}
__device__ __forceinline__ void stsm2(uint32_t a, uint32_t r0, uint32_t r1) {
    asm volatile("stmatrix.sync.aligned.m8n8.x2.shared.b16 [%0], {%1,%2};" ::"r"(a), "r"(r0), "r"(r1) : "memory");
}
__device__ __forceinline__ void stsm4t(uint32_t a, uint32_t r0, uint32_t r1, uint32_t r2, uint32_t r3) {
    asm volatile("stmatrix.sync.aligned.m8n8.x4.trans.shared.b16 [%0], {%1,%2,%3,%4};" ::"r"(a), "r"(r0), "r"(r1), "r"(r2),
                 "r"(r3)
                 : "memory");
}
__device__ __forceinline__ void stsm2t(uint32_t a, uint32_t r0, uint32_t r1) {
    asm volatile("stmatrix.sync.aligned.m8n8.x2.trans.shared.b16 [%0], {%1,%2};" ::"r"(a), "r"(r0), "r"(r1) : "memory");
}
__device__ __forceinline__ void cp_async16(uint32_t d, const void* s, int n) {
    asm volatile("cp.async.ca.shared.global [%0], [%1], 16, %2;" ::"r"(d), "l"(s), "r"(n) : "memory");
}
__device__ __forceinline__ void cp_async4(uint32_t d, const void* s, int n) {
    asm volatile("cp.async.ca.shared.global [%0], [%1], 4, %2;" ::"r"(d), "l"(s), "r"(n) : "memory");
}
__device__ __forceinline__ void sts_u32(uint32_t a, uint32_t x) {
    asm volatile("st.shared.u32 [%0], %1;" ::"r"(a), "r"(x) : "memory");
}
#define FENCE_ASYNC() asm volatile("fence.proxy.async.shared::cta;" ::: "memory")
__device__ __forceinline__ int warp_incl_scan(int v, int lane) {
#pragma unroll
    for (int o = 1; o < 32; o <<= 1) {
        const int y = __shfl_up_sync(0xffffffffu, v, o);
        if (lane >= o) v += y;
    }
    return v;
}

#define STR2(x) #x
#define STR(x) STR2(x)
#define WRS 1
#define NJ 19
__device__ __forceinline__ void consume(float (&acc)[2][NJ][4], uint32_t xa0, uint32_t xa1, uint32_t so0, uint32_t bar0,
                                        uint32_t ea0, uint32_t d0, uint32_t pl0, int lz, uint32_t wd) {
    asm volatile(
        "{\n"
        ".reg .pred p, pf, plead, pok, t0, t1, t2, u0, u1, u2;\n"
        ".reg .b32 ca, cb, cz, ctm;\n"
        "mov.b32 cz, 0;\n"
        "mov.b32 ca, 0x20002000;\n"
        "mov.b32 cb, 0x30003000;\n"
        ".reg .b32 cnt, so, q, qe, bar, rbar, pl, ctl, dl, dh, v0, v1, v2, v3, pp;\n"
        ".reg .b16 sl, sh;\n"
        ".reg .b32 hXa0, hXa1, hXa2, hXa3, hXa4, hXa5, hXa6, hXa7, hXb0, hXb1, hXb2, hXb3, hXb4, hXb5, hXb6, hXb7, hYa0, hYa1, hYa2, hYa3, hYa4, hYa5, hYa6, hYa7, hYb0, hYb1, hYb2, hYb3, hYb4, hYb5, hYb6, hYb7, hLa0, hLa1, hLa2, hLa3, hLa4, hLa5, hLa6, hLa7, hLb0, hLb1, hLb2, hLb3, hLb4, hLb5, hLb6, hLb7;\n"
        ".reg .b32 pX0, pX1, pX2, pX3, pY0, pY1, pY2, pY3;\n"
        ".reg .f32 r0, r1, r2, r3, r4, r5, r6, r7, r8, r9, r10, r11, r12, r13, r14, r15;\n"
        ".reg .b64 daX, dbX, daY, dbY, de0, de1, dw0, dw1;\n"
        ".reg .b32 dh<6>, eb0, par, px;\n"
        "mov.f32 %0, 0f00000000;\n"
        "mov.f32 %1, 0f00000000;\n"
        "mov.f32 %2, 0f00000000;\n"
        "mov.f32 %3, 0f00000000;\n"
        "mov.f32 %4, 0f00000000;\n"
        "mov.f32 %5, 0f00000000;\n"
        "mov.f32 %6, 0f00000000;\n"
        "mov.f32 %7, 0f00000000;\n"
        "mov.f32 %8, 0f00000000;\n"
        "mov.f32 %9, 0f00000000;\n"
        "mov.f32 %10, 0f00000000;\n"
        "mov.f32 %11, 0f00000000;\n"
        "mov.f32 %12, 0f00000000;\n"
        "mov.f32 %13, 0f00000000;\n"
        "mov.f32 %14, 0f00000000;\n"
        "mov.f32 %15, 0f00000000;\n"
        "mov.f32 %16, 0f00000000;\n"
        "mov.f32 %17, 0f00000000;\n"
        "mov.f32 %18, 0f00000000;\n"
        "mov.f32 %19, 0f00000000;\n"
        "mov.f32 %20, 0f00000000;\n"
        "mov.f32 %21, 0f00000000;\n"
        "mov.f32 %22, 0f00000000;\n"
        "mov.f32 %23, 0f00000000;\n"
        "mov.f32 %24, 0f00000000;\n"
        "mov.f32 %25, 0f00000000;\n"
        "mov.f32 %26, 0f00000000;\n"
        "mov.f32 %27, 0f00000000;\n"
        "mov.f32 %28, 0f00000000;\n"
        "mov.f32 %29, 0f00000000;\n"
        "mov.f32 %30, 0f00000000;\n"
        "mov.f32 %31, 0f00000000;\n"
        "mov.f32 %32, 0f00000000;\n"
        "mov.f32 %33, 0f00000000;\n"
        "mov.f32 %34, 0f00000000;\n"
        "mov.f32 %35, 0f00000000;\n"
        "mov.f32 %36, 0f00000000;\n"
        "mov.f32 %37, 0f00000000;\n"
        "mov.f32 %38, 0f00000000;\n"
        "mov.f32 %39, 0f00000000;\n"
        "mov.f32 %40, 0f00000000;\n"
        "mov.f32 %41, 0f00000000;\n"
        "mov.f32 %42, 0f00000000;\n"
        "mov.f32 %43, 0f00000000;\n"
        "mov.f32 %44, 0f00000000;\n"
        "mov.f32 %45, 0f00000000;\n"
        "mov.f32 %46, 0f00000000;\n"
        "mov.f32 %47, 0f00000000;\n"
        "mov.f32 %48, 0f00000000;\n"
        "mov.f32 %49, 0f00000000;\n"
        "mov.f32 %50, 0f00000000;\n"
        "mov.f32 %51, 0f00000000;\n"
        "mov.f32 %52, 0f00000000;\n"
        "mov.f32 %53, 0f00000000;\n"
        "mov.f32 %54, 0f00000000;\n"
        "mov.f32 %55, 0f00000000;\n"
        "mov.f32 %56, 0f00000000;\n"
        "mov.f32 %57, 0f00000000;\n"
        "mov.f32 %58, 0f00000000;\n"
        "mov.f32 %59, 0f00000000;\n"
        "mov.f32 %60, 0f00000000;\n"
        "mov.f32 %61, 0f00000000;\n"
        "mov.f32 %62, 0f00000000;\n"
        "mov.f32 %63, 0f00000000;\n"
        "mov.f32 %64, 0f00000000;\n"
        "mov.f32 %65, 0f00000000;\n"
        "mov.f32 %66, 0f00000000;\n"
        "mov.f32 %67, 0f00000000;\n"
        "mov.f32 %68, 0f00000000;\n"
        "mov.f32 %69, 0f00000000;\n"
        "mov.f32 %70, 0f00000000;\n"
        "mov.f32 %71, 0f00000000;\n"
        "mov.f32 %72, 0f00000000;\n"
        "mov.f32 %73, 0f00000000;\n"
        "mov.f32 %74, 0f00000000;\n"
        "mov.f32 %75, 0f00000000;\n"
        "mov.f32 %76, 0f00000000;\n"
        "mov.f32 %77, 0f00000000;\n"
        "mov.f32 %78, 0f00000000;\n"
        "mov.f32 %79, 0f00000000;\n"
        "mov.f32 %80, 0f00000000;\n"
        "mov.f32 %81, 0f00000000;\n"
        "mov.f32 %82, 0f00000000;\n"
        "mov.f32 %83, 0f00000000;\n"
        "mov.f32 %84, 0f00000000;\n"
        "mov.f32 %85, 0f00000000;\n"
        "mov.f32 %86, 0f00000000;\n"
        "mov.f32 %87, 0f00000000;\n"
        "mov.f32 %88, 0f00000000;\n"
        "mov.f32 %89, 0f00000000;\n"
        "mov.f32 %90, 0f00000000;\n"
        "mov.f32 %91, 0f00000000;\n"
        "mov.f32 %92, 0f00000000;\n"
        "mov.f32 %93, 0f00000000;\n"
        "mov.f32 %94, 0f00000000;\n"
        "mov.f32 %95, 0f00000000;\n"
        "mov.f32 %96, 0f00000000;\n"
        "mov.f32 %97, 0f00000000;\n"
        "mov.f32 %98, 0f00000000;\n"
        "mov.f32 %99, 0f00000000;\n"
        "mov.f32 %100, 0f00000000;\n"
        "mov.f32 %101, 0f00000000;\n"
        "mov.f32 %102, 0f00000000;\n"
        "mov.f32 %103, 0f00000000;\n"
        "mov.f32 %104, 0f00000000;\n"
        "mov.f32 %105, 0f00000000;\n"
        "mov.f32 %106, 0f00000000;\n"
        "mov.f32 %107, 0f00000000;\n"
        "mov.f32 %108, 0f00000000;\n"
        "mov.f32 %109, 0f00000000;\n"
        "mov.f32 %110, 0f00000000;\n"
        "mov.f32 %111, 0f00000000;\n"
        "mov.f32 %112, 0f00000000;\n"
        "mov.f32 %113, 0f00000000;\n"
        "mov.f32 %114, 0f00000000;\n"
        "mov.f32 %115, 0f00000000;\n"
        "mov.f32 %116, 0f00000000;\n"
        "mov.f32 %117, 0f00000000;\n"
        "mov.f32 %118, 0f00000000;\n"
        "mov.f32 %119, 0f00000000;\n"
        "mov.f32 %120, 0f00000000;\n"
        "mov.f32 %121, 0f00000000;\n"
        "mov.f32 %122, 0f00000000;\n"
        "mov.f32 %123, 0f00000000;\n"
        "mov.f32 %124, 0f00000000;\n"
        "mov.f32 %125, 0f00000000;\n"
        "mov.f32 %126, 0f00000000;\n"
        "mov.f32 %127, 0f00000000;\n"
        "mov.f32 %128, 0f00000000;\n"
        "mov.f32 %129, 0f00000000;\n"
        "mov.f32 %130, 0f00000000;\n"
        "mov.f32 %131, 0f00000000;\n"
        "mov.f32 %132, 0f00000000;\n"
        "mov.f32 %133, 0f00000000;\n"
        "mov.f32 %134, 0f00000000;\n"
        "mov.f32 %135, 0f00000000;\n"
        "mov.f32 %136, 0f00000000;\n"
        "mov.f32 %137, 0f00000000;\n"
        "mov.f32 %138, 0f00000000;\n"
        "mov.f32 %139, 0f00000000;\n"
        "mov.f32 %140, 0f00000000;\n"
        "mov.f32 %141, 0f00000000;\n"
        "mov.f32 %142, 0f00000000;\n"
        "mov.f32 %143, 0f00000000;\n"
        "mov.f32 %144, 0f00000000;\n"
        "mov.f32 %145, 0f00000000;\n"
        "mov.f32 %146, 0f00000000;\n"
        "mov.f32 %147, 0f00000000;\n"
        "mov.f32 %148, 0f00000000;\n"
        "mov.f32 %149, 0f00000000;\n"
        "mov.f32 %150, 0f00000000;\n"
        "mov.f32 %151, 0f00000000;\n"
        "setp.ne.u32 pf, 0, 0;\n"
        "mov.u32 dh, 16;\n"
        "add.u32 v0, %154, %159;\n"
        "shfl.sync.idx.b32 so, v0, 0, 31, 0xffffffff;\n"
        ".reg .b32 wa<8>;\n"
        "ldmatrix.sync.aligned.m8n8.x4.trans.shared.b16 {wa0,wa1,wa2,wa3}, [%160+0];\n"
        "ldmatrix.sync.aligned.m8n8.x4.trans.shared.b16 {wa4,wa5,wa6,wa7}, [%160+2048];\n"
        "mov.u32 par, 0;\n"
        ".reg .b32 uz, bend;\n"
        "shfl.sync.idx.b32 uz, %159, 7, 31, 0xffffffff;\n"
        "add.u32 bend, %155, " STR(NP * 16) ";\n"
        "shr.u32 px, so, 13;\n"
        "mul.lo.u32 px, px, 429496730;\n"
        "add.u32 v0, %159, 16;\n"
        "shfl.sync.idx.b32 dh0, v0, 0, 31, 0xffffffff;\n"
        "shfl.sync.idx.b32 dh1, v0, 1, 31, 0xffffffff;\n"
        "shfl.sync.idx.b32 dh2, v0, 2, 31, 0xffffffff;\n"
        "shfl.sync.idx.b32 dh3, v0, 3, 31, 0xffffffff;\n"
        "shfl.sync.idx.b32 dh4, v0, 4, 31, 0xffffffff;\n"
        "shfl.sync.idx.b32 dh5, v0, 5, 31, 0xffffffff;\n"
        "add.u32 v0, %159, %156;\n"
        "shfl.sync.idx.b32 eb0, v0, 0, 31, 0xffffffff;\n"
        "mov.u32 q, 0;\n"
        "mov.u32 pl, %158;\n"
        "shr.u32 bar, so, 9;\n"
        "add.u32 bar, bar, %155;\n"
        "elect.sync _|plead, 0xffffffff;\n"
        "mov.b64 de0, {%156, dh4};\n"
        "mov.b64 de1, {eb0, dh5};\n"
        "mov.b32 hYa0, 0;\n"
        "mov.b32 hYa1, 0;\n"
        "mov.b32 hYa2, 0;\n"
        "mov.b32 hYa3, 0;\n"
        "mov.b32 hYa4, 0;\n"
        "mov.b32 hYa5, 0;\n"
        "mov.b32 hYa6, 0;\n"
        "mov.b32 hYa7, 0;\n"
        "mov.b32 hYb0, 0;\n"
        "mov.b32 hYb1, 0;\n"
        "mov.b32 hYb2, 0;\n"
        "mov.b32 hYb3, 0;\n"
        "mov.b32 hYb4, 0;\n"
        "mov.b32 hYb5, 0;\n"
        "mov.b32 hYb6, 0;\n"
        "mov.b32 hYb7, 0;\n"
        "setp.ne.u32 t0, 0, 0;\n"
        "setp.ne.u32 u0, 0, 0;\n"
        "setp.ne.u32 t1, 0, 0;\n"
        "setp.ne.u32 u1, 0, 0;\n"
        "setp.ne.u32 t2, 0, 0;\n"
        "setp.ne.u32 u2, 0, 0;\n"
        "mov.b64 daX, {%157, dh0};\n"
        "mov.b64 dbX, {%157, dh1};\n"
        "mov.b64 daY, {%157, dh2};\n"
        "mov.b64 dbY, {%157, dh3};\n"
        "mov.u32 cnt, 0;\n"
        "W1:\n"
        "mbarrier.try_wait.parity.shared.b64 p, [bar], 0;\n"
        "@p bra.uni RES;\n"
        "add.u32 cnt, cnt, 1;\n"
        "setp.lt.u32 p, cnt, 4000000;\n"
        "@p bra.uni W1;\n"
        "trap;\n"
        "CX:\n"
        "mov.u32 rbar, bar;\n"
        "add.u32 bar, bar, 16;\n"
        "setp.eq.u32 p, bar, bend;\n"
        "selp.b32 bar, %155, bar, p;\n"
        "@p xor.b32 par, par, 1;\n"
        "mbarrier.test_wait.parity.shared.b64 pok, [bar], par;\n"
        "and.b32 dl, q, 0x300;\n"
        "add.u32 dl, dl, %157;\n"
        "add.u32 v3, dl, 0;\n"
        "mov.b64 {v2, dh0}, daX;\n"
        "mov.b64 daX, {v3, dh0};\n"
        "add.u32 v3, dl, 64;\n"
        "mov.b64 {v2, dh1}, dbX;\n"
        "mov.b64 dbX, {v3, dh1};\n"
        "add.u32 v3, dl, 128;\n"
        "mov.b64 {v2, dh2}, daY;\n"
        "mov.b64 daY, {v3, dh2};\n"
        "add.u32 v3, dl, 192;\n"
        "mov.b64 {v2, dh3}, dbY;\n"
        "mov.b64 dbY, {v3, dh3};\n"
        "add.u32 q, q, 256;\n"
        "and.b32 qe, q, 0x700;\n"
        "shr.u32 qe, qe, 3;\n"
        "add.u32 v3, qe, %156;\n"
        "mov.b64 {v2, dh4}, de0;\n"
        "mov.b64 de0, {v3, dh4};\n"
        "mov.b64 {v2, dh5}, de1;\n"
        "mov.b64 de1, {v3, dh5};\n"
        "setp.lt.f16x2 t0|u0, ctl, cz;\n"
        "abs.f16x2 v3, ctl;\n"
        "setp.ge.f16x2 t1|u1, v3, ca;\n"
        "setp.geu.f16x2 t2|u2, v3, cb;\n"
        "wgmma.wait_group.sync.aligned 2;\n"
        "cvt.rn.bf16x2.f32 pX0, r1, r0;\n"
        "cvt.rn.bf16x2.f32 pX1, r3, r2;\n"
        "cvt.rn.bf16x2.f32 pX2, r9, r8;\n"
        "cvt.rn.bf16x2.f32 pX3, r11, r10;\n"
        "cvt.rn.bf16x2.f32 pY0, r5, r4;\n"
        "cvt.rn.bf16x2.f32 pY1, r7, r6;\n"
        "cvt.rn.bf16x2.f32 pY2, r13, r12;\n"
        "cvt.rn.bf16x2.f32 pY3, r15, r14;\n"
        "mov.b32 {sl, sh}, pX0;\n"
        "mov.b32 pp, {sl, sl};\n"
        "mul.rn.bf16x2 hXa0, hLa0, pp;\n"
        "mul.rn.bf16x2 hXa2, hLa2, pp;\n"
        "mov.b32 {sl, sh}, pX1;\n"
        "mov.b32 pp, {sl, sl};\n"
        "mul.rn.bf16x2 hXa1, hLa1, pp;\n"
        "mul.rn.bf16x2 hXa3, hLa3, pp;\n"
        "mov.b32 {sl, sh}, pX2;\n"
        "mov.b32 pp, {sl, sl};\n"
        "mul.rn.bf16x2 hXa4, hLa4, pp;\n"
        "mul.rn.bf16x2 hXa6, hLa6, pp;\n"
        "mov.b32 {sl, sh}, pX3;\n"
        "mov.b32 pp, {sl, sl};\n"
        "mul.rn.bf16x2 hXa5, hLa5, pp;\n"
        "mul.rn.bf16x2 hXa7, hLa7, pp;\n"
        "mov.b32 {sl, sh}, pX0;\n"
        "mov.b32 pp, {sh, sh};\n"
        "mul.rn.bf16x2 hXb0, hLb0, pp;\n"
        "mul.rn.bf16x2 hXb2, hLb2, pp;\n"
        "mov.b32 {sl, sh}, pX1;\n"
        "mov.b32 pp, {sh, sh};\n"
        "mul.rn.bf16x2 hXb1, hLb1, pp;\n"
        "mul.rn.bf16x2 hXb3, hLb3, pp;\n"
        "mov.b32 {sl, sh}, pX2;\n"
        "mov.b32 pp, {sh, sh};\n"
        "mul.rn.bf16x2 hXb4, hLb4, pp;\n"
        "mul.rn.bf16x2 hXb6, hLb6, pp;\n"
        "mov.b32 {sl, sh}, pX3;\n"
        "mov.b32 pp, {sh, sh};\n"
        "mul.rn.bf16x2 hXb5, hLb5, pp;\n"
        "mul.rn.bf16x2 hXb7, hLb7, pp;\n"
        "ldmatrix.sync.aligned.m8n8.x4.trans.shared.b16 {hLa0,hLa1,hLa2,hLa3}, [v0+4096];\n"
        "ldmatrix.sync.aligned.m8n8.x4.trans.shared.b16 {hLa4,hLa5,hLa6,hLa7}, [v1+4096];\n"
        "ldmatrix.sync.aligned.m8n8.x4.trans.shared.b16 {hLb0,hLb1,hLb2,hLb3}, [v0+6144];\n"
        "ldmatrix.sync.aligned.m8n8.x4.trans.shared.b16 {hLb4,hLb5,hLb6,hLb7}, [v1+6144];\n"
        "@t2 bra.uni T4X;\n"
        "@t1 bra.uni T2X;\n"
        "@t0 bra.uni L1X;\n"
        "L0X:\n"
        "wgmma.fence.sync.aligned;\n"
        "wgmma.mma_async.sync.aligned.m64n24k16.f32.bf16.bf16 {%0,%1,%2,%3,%4,%5,%6,%7,%8,%9,%10,%11}, {hXa0,hXa1,hXa2,hXa3}, daX, 1, 1, 1, 1;\n"
        "wgmma.mma_async.sync.aligned.m64n24k16.f32.bf16.bf16 {%76,%77,%78,%79,%80,%81,%82,%83,%84,%85,%86,%87}, {hXa4,hXa5,hXa6,hXa7}, daX, 1, 1, 1, 1;\n"
        "wgmma.commit_group.sync.aligned;\n"
        "@u2 bra.uni T4Xb;\n"
        "@u1 bra.uni T2Xb;\n"
        "@u0 bra.uni L1Xb;\n"
        "bra.uni L0Xb;\n"
        "L1X:\n"
        "wgmma.fence.sync.aligned;\n"
        "wgmma.mma_async.sync.aligned.m64n24k16.f32.bf16.bf16 {%12,%13,%14,%15,%16,%17,%18,%19,%20,%21,%22,%23}, {hXa0,hXa1,hXa2,hXa3}, daX, 1, 1, 1, 1;\n"
        "wgmma.mma_async.sync.aligned.m64n24k16.f32.bf16.bf16 {%88,%89,%90,%91,%92,%93,%94,%95,%96,%97,%98,%99}, {hXa4,hXa5,hXa6,hXa7}, daX, 1, 1, 1, 1;\n"
        "wgmma.commit_group.sync.aligned;\n"
        "@u2 bra.uni T4Xb;\n"
        "@u1 bra.uni T2Xb;\n"
        "@u0 bra.uni L1Xb;\n"
        "bra.uni L0Xb;\n"
        "T2X:\n"
        "@t0 bra.uni L3X;\n"
        "L2X:\n"
        "wgmma.fence.sync.aligned;\n"
        "wgmma.mma_async.sync.aligned.m64n24k16.f32.bf16.bf16 {%24,%25,%26,%27,%28,%29,%30,%31,%32,%33,%34,%35}, {hXa0,hXa1,hXa2,hXa3}, daX, 1, 1, 1, 1;\n"
        "wgmma.mma_async.sync.aligned.m64n24k16.f32.bf16.bf16 {%100,%101,%102,%103,%104,%105,%106,%107,%108,%109,%110,%111}, {hXa4,hXa5,hXa6,hXa7}, daX, 1, 1, 1, 1;\n"
        "wgmma.commit_group.sync.aligned;\n"
        "@u2 bra.uni T4Xb;\n"
        "@u1 bra.uni T2Xb;\n"
        "@u0 bra.uni L1Xb;\n"
        "bra.uni L0Xb;\n"
        "L3X:\n"
        "wgmma.fence.sync.aligned;\n"
        "wgmma.mma_async.sync.aligned.m64n24k16.f32.bf16.bf16 {%36,%37,%38,%39,%40,%41,%42,%43,%44,%45,%46,%47}, {hXa0,hXa1,hXa2,hXa3}, daX, 1, 1, 1, 1;\n"
        "wgmma.mma_async.sync.aligned.m64n24k16.f32.bf16.bf16 {%112,%113,%114,%115,%116,%117,%118,%119,%120,%121,%122,%123}, {hXa4,hXa5,hXa6,hXa7}, daX, 1, 1, 1, 1;\n"
        "wgmma.commit_group.sync.aligned;\n"
        "@u2 bra.uni T4Xb;\n"
        "@u1 bra.uni T2Xb;\n"
        "@u0 bra.uni L1Xb;\n"
        "bra.uni L0Xb;\n"
        "T4X:\n"
        "@!t1 bra.uni LEXIT;\n"
        "@t0 bra.uni L5X;\n"
        "L4X:\n"
        "wgmma.fence.sync.aligned;\n"
        "wgmma.mma_async.sync.aligned.m64n24k16.f32.bf16.bf16 {%48,%49,%50,%51,%52,%53,%54,%55,%56,%57,%58,%59}, {hXa0,hXa1,hXa2,hXa3}, daX, 1, 1, 1, 1;\n"
        "wgmma.mma_async.sync.aligned.m64n24k16.f32.bf16.bf16 {%124,%125,%126,%127,%128,%129,%130,%131,%132,%133,%134,%135}, {hXa4,hXa5,hXa6,hXa7}, daX, 1, 1, 1, 1;\n"
        "wgmma.commit_group.sync.aligned;\n"
        "@u2 bra.uni T4Xb;\n"
        "@u1 bra.uni T2Xb;\n"
        "@u0 bra.uni L1Xb;\n"
        "bra.uni L0Xb;\n"
        "L5X:\n"
        "wgmma.fence.sync.aligned;\n"
        "wgmma.mma_async.sync.aligned.m64n32k16.f32.bf16.bf16 {%60,%61,%62,%63,%64,%65,%66,%67,%68,%69,%70,%71,%72,%73,%74,%75}, {hXa0,hXa1,hXa2,hXa3}, daX, 1, 1, 1, 1;\n"
        "wgmma.mma_async.sync.aligned.m64n32k16.f32.bf16.bf16 {%136,%137,%138,%139,%140,%141,%142,%143,%144,%145,%146,%147,%148,%149,%150,%151}, {hXa4,hXa5,hXa6,hXa7}, daX, 1, 1, 1, 1;\n"
        "wgmma.commit_group.sync.aligned;\n"
        "@u2 bra.uni T4Xb;\n"
        "@u1 bra.uni T2Xb;\n"
        "@u0 bra.uni L1Xb;\n"
        "L0Xb:\n"
        "wgmma.fence.sync.aligned;\n"
        "wgmma.mma_async.sync.aligned.m64n24k16.f32.bf16.bf16 {%0,%1,%2,%3,%4,%5,%6,%7,%8,%9,%10,%11}, {hXb0,hXb1,hXb2,hXb3}, dbX, 1, 1, 1, 1;\n"
        "wgmma.mma_async.sync.aligned.m64n24k16.f32.bf16.bf16 {%76,%77,%78,%79,%80,%81,%82,%83,%84,%85,%86,%87}, {hXb4,hXb5,hXb6,hXb7}, dbX, 1, 1, 1, 1;\n"
        "wgmma.commit_group.sync.aligned;\n"
        "bra.uni CY;\n"
        "L1Xb:\n"
        "wgmma.fence.sync.aligned;\n"
        "wgmma.mma_async.sync.aligned.m64n24k16.f32.bf16.bf16 {%12,%13,%14,%15,%16,%17,%18,%19,%20,%21,%22,%23}, {hXb0,hXb1,hXb2,hXb3}, dbX, 1, 1, 1, 1;\n"
        "wgmma.mma_async.sync.aligned.m64n24k16.f32.bf16.bf16 {%88,%89,%90,%91,%92,%93,%94,%95,%96,%97,%98,%99}, {hXb4,hXb5,hXb6,hXb7}, dbX, 1, 1, 1, 1;\n"
        "wgmma.commit_group.sync.aligned;\n"
        "bra.uni CY;\n"
        "T2Xb:\n"
        "@u0 bra.uni L3Xb;\n"
        "L2Xb:\n"
        "wgmma.fence.sync.aligned;\n"
        "wgmma.mma_async.sync.aligned.m64n24k16.f32.bf16.bf16 {%24,%25,%26,%27,%28,%29,%30,%31,%32,%33,%34,%35}, {hXb0,hXb1,hXb2,hXb3}, dbX, 1, 1, 1, 1;\n"
        "wgmma.mma_async.sync.aligned.m64n24k16.f32.bf16.bf16 {%100,%101,%102,%103,%104,%105,%106,%107,%108,%109,%110,%111}, {hXb4,hXb5,hXb6,hXb7}, dbX, 1, 1, 1, 1;\n"
        "wgmma.commit_group.sync.aligned;\n"
        "bra.uni CY;\n"
        "L3Xb:\n"
        "wgmma.fence.sync.aligned;\n"
        "wgmma.mma_async.sync.aligned.m64n24k16.f32.bf16.bf16 {%36,%37,%38,%39,%40,%41,%42,%43,%44,%45,%46,%47}, {hXb0,hXb1,hXb2,hXb3}, dbX, 1, 1, 1, 1;\n"
        "wgmma.mma_async.sync.aligned.m64n24k16.f32.bf16.bf16 {%112,%113,%114,%115,%116,%117,%118,%119,%120,%121,%122,%123}, {hXb4,hXb5,hXb6,hXb7}, dbX, 1, 1, 1, 1;\n"
        "wgmma.commit_group.sync.aligned;\n"
        "bra.uni CY;\n"
        "T4Xb:\n"
        "@u0 bra.uni L5Xb;\n"
        "L4Xb:\n"
        "wgmma.fence.sync.aligned;\n"
        "wgmma.mma_async.sync.aligned.m64n24k16.f32.bf16.bf16 {%48,%49,%50,%51,%52,%53,%54,%55,%56,%57,%58,%59}, {hXb0,hXb1,hXb2,hXb3}, dbX, 1, 1, 1, 1;\n"
        "wgmma.mma_async.sync.aligned.m64n24k16.f32.bf16.bf16 {%124,%125,%126,%127,%128,%129,%130,%131,%132,%133,%134,%135}, {hXb4,hXb5,hXb6,hXb7}, dbX, 1, 1, 1, 1;\n"
        "wgmma.commit_group.sync.aligned;\n"
        "bra.uni CY;\n"
        "L5Xb:\n"
        "wgmma.fence.sync.aligned;\n"
        "wgmma.mma_async.sync.aligned.m64n32k16.f32.bf16.bf16 {%60,%61,%62,%63,%64,%65,%66,%67,%68,%69,%70,%71,%72,%73,%74,%75}, {hXb0,hXb1,hXb2,hXb3}, dbX, 1, 1, 1, 1;\n"
        "wgmma.mma_async.sync.aligned.m64n32k16.f32.bf16.bf16 {%136,%137,%138,%139,%140,%141,%142,%143,%144,%145,%146,%147,%148,%149,%150,%151}, {hXb4,hXb5,hXb6,hXb7}, dbX, 1, 1, 1, 1;\n"
        "wgmma.commit_group.sync.aligned;\n"
        "bra.uni CY;\n"
        "CY:\n"
        "wgmma.wait_group.sync.aligned 2;\n"
        "lop3.b32 v2, hLa3, hLa7, hLb3, 0x80;\n"
        "lop3.b32 v2, v2, hLb7, uz, 0x80;\n"
        "add.u32 v2, v2, rbar;\n"
        "@plead mbarrier.arrive.shared.b64 _, [v2+8];\n"
        "setp.lt.f16x2 t0|u0, ctm, cz;\n"
        "abs.f16x2 v3, ctm;\n"
        "setp.ge.f16x2 t1|u1, v3, ca;\n"
        "setp.geu.f16x2 t2|u2, v3, cb;\n"
        "mov.b32 {sl, sh}, pY0;\n"
        "mov.b32 pp, {sl, sl};\n"
        "mul.rn.bf16x2 hYa0, hLa0, pp;\n"
        "mul.rn.bf16x2 hYa2, hLa2, pp;\n"
        "mov.b32 {sl, sh}, pY1;\n"
        "mov.b32 pp, {sl, sl};\n"
        "mul.rn.bf16x2 hYa1, hLa1, pp;\n"
        "mul.rn.bf16x2 hYa3, hLa3, pp;\n"
        "mov.b32 {sl, sh}, pY2;\n"
        "mov.b32 pp, {sl, sl};\n"
        "mul.rn.bf16x2 hYa4, hLa4, pp;\n"
        "mul.rn.bf16x2 hYa6, hLa6, pp;\n"
        "mov.b32 {sl, sh}, pY3;\n"
        "mov.b32 pp, {sl, sl};\n"
        "mul.rn.bf16x2 hYa5, hLa5, pp;\n"
        "mul.rn.bf16x2 hYa7, hLa7, pp;\n"
        "mov.b32 {sl, sh}, pY0;\n"
        "mov.b32 pp, {sh, sh};\n"
        "mul.rn.bf16x2 hYb0, hLb0, pp;\n"
        "mul.rn.bf16x2 hYb2, hLb2, pp;\n"
        "mov.b32 {sl, sh}, pY1;\n"
        "mov.b32 pp, {sh, sh};\n"
        "mul.rn.bf16x2 hYb1, hLb1, pp;\n"
        "mul.rn.bf16x2 hYb3, hLb3, pp;\n"
        "mov.b32 {sl, sh}, pY2;\n"
        "mov.b32 pp, {sh, sh};\n"
        "mul.rn.bf16x2 hYb4, hLb4, pp;\n"
        "mul.rn.bf16x2 hYb6, hLb6, pp;\n"
        "mov.b32 {sl, sh}, pY3;\n"
        "mov.b32 pp, {sh, sh};\n"
        "mul.rn.bf16x2 hYb5, hLb5, pp;\n"
        "mul.rn.bf16x2 hYb7, hLb7, pp;\n"
        "@!pok bra.uni SLOW;\n"
        "RES:\n"
        "sub.u32 so, bar, %155;\n"
        "shl.b32 so, so, 9;\n"
        "add.u32 v0, %152, so;\n"
        "add.u32 v1, %153, so;\n"
        "ldmatrix.sync.aligned.m8n8.x4.trans.shared.b16 {hLa0,hLa1,hLa2,hLa3}, [v0+0];\n"
        "ldmatrix.sync.aligned.m8n8.x4.trans.shared.b16 {hLa4,hLa5,hLa6,hLa7}, [v1+0];\n"
        "ldmatrix.sync.aligned.m8n8.x4.trans.shared.b16 {hLb0,hLb1,hLb2,hLb3}, [v0+2048];\n"
        "ldmatrix.sync.aligned.m8n8.x4.trans.shared.b16 {hLb4,hLb5,hLb6,hLb7}, [v1+2048];\n"
        "ld.shared.v2.u32 {ctl, ctm}, [pl];\n"
        "add.u32 pl, pl, 8;\n"
        "wgmma.wait_group.sync.aligned 0;\n"
        "@t2 bra.uni T4Y;\n"
        "@t1 bra.uni T2Y;\n"
        "@t0 bra.uni L1Y;\n"
        "L0Y:\n"
        "wgmma.fence.sync.aligned;\n"
        "wgmma.mma_async.sync.aligned.m64n16k16.f32.bf16.bf16 {r0,r1,r2,r3,r4,r5,r6,r7}, {wa0,wa1,wa2,wa3}, de0, pf, 1, 1, 0;\n"
        "wgmma.mma_async.sync.aligned.m64n16k16.f32.bf16.bf16 {r8,r9,r10,r11,r12,r13,r14,r15}, {wa4,wa5,wa6,wa7}, de1, pf, 1, 1, 0;\n"
        "wgmma.commit_group.sync.aligned;\n"
        "wgmma.mma_async.sync.aligned.m64n24k16.f32.bf16.bf16 {%0,%1,%2,%3,%4,%5,%6,%7,%8,%9,%10,%11}, {hYa0,hYa1,hYa2,hYa3}, daY, 1, 1, 1, 1;\n"
        "wgmma.mma_async.sync.aligned.m64n24k16.f32.bf16.bf16 {%76,%77,%78,%79,%80,%81,%82,%83,%84,%85,%86,%87}, {hYa4,hYa5,hYa6,hYa7}, daY, 1, 1, 1, 1;\n"
        "wgmma.commit_group.sync.aligned;\n"
        "@u2 bra.uni T4Yb;\n"
        "@u1 bra.uni T2Yb;\n"
        "@u0 bra.uni L1Yb;\n"
        "bra.uni L0Yb;\n"
        "L1Y:\n"
        "wgmma.fence.sync.aligned;\n"
        "wgmma.mma_async.sync.aligned.m64n16k16.f32.bf16.bf16 {r0,r1,r2,r3,r4,r5,r6,r7}, {wa0,wa1,wa2,wa3}, de0, pf, 1, 1, 0;\n"
        "wgmma.mma_async.sync.aligned.m64n16k16.f32.bf16.bf16 {r8,r9,r10,r11,r12,r13,r14,r15}, {wa4,wa5,wa6,wa7}, de1, pf, 1, 1, 0;\n"
        "wgmma.commit_group.sync.aligned;\n"
        "wgmma.mma_async.sync.aligned.m64n24k16.f32.bf16.bf16 {%12,%13,%14,%15,%16,%17,%18,%19,%20,%21,%22,%23}, {hYa0,hYa1,hYa2,hYa3}, daY, 1, 1, 1, 1;\n"
        "wgmma.mma_async.sync.aligned.m64n24k16.f32.bf16.bf16 {%88,%89,%90,%91,%92,%93,%94,%95,%96,%97,%98,%99}, {hYa4,hYa5,hYa6,hYa7}, daY, 1, 1, 1, 1;\n"
        "wgmma.commit_group.sync.aligned;\n"
        "@u2 bra.uni T4Yb;\n"
        "@u1 bra.uni T2Yb;\n"
        "@u0 bra.uni L1Yb;\n"
        "bra.uni L0Yb;\n"
        "T2Y:\n"
        "@t0 bra.uni L3Y;\n"
        "L2Y:\n"
        "wgmma.fence.sync.aligned;\n"
        "wgmma.mma_async.sync.aligned.m64n16k16.f32.bf16.bf16 {r0,r1,r2,r3,r4,r5,r6,r7}, {wa0,wa1,wa2,wa3}, de0, pf, 1, 1, 0;\n"
        "wgmma.mma_async.sync.aligned.m64n16k16.f32.bf16.bf16 {r8,r9,r10,r11,r12,r13,r14,r15}, {wa4,wa5,wa6,wa7}, de1, pf, 1, 1, 0;\n"
        "wgmma.commit_group.sync.aligned;\n"
        "wgmma.mma_async.sync.aligned.m64n24k16.f32.bf16.bf16 {%24,%25,%26,%27,%28,%29,%30,%31,%32,%33,%34,%35}, {hYa0,hYa1,hYa2,hYa3}, daY, 1, 1, 1, 1;\n"
        "wgmma.mma_async.sync.aligned.m64n24k16.f32.bf16.bf16 {%100,%101,%102,%103,%104,%105,%106,%107,%108,%109,%110,%111}, {hYa4,hYa5,hYa6,hYa7}, daY, 1, 1, 1, 1;\n"
        "wgmma.commit_group.sync.aligned;\n"
        "@u2 bra.uni T4Yb;\n"
        "@u1 bra.uni T2Yb;\n"
        "@u0 bra.uni L1Yb;\n"
        "bra.uni L0Yb;\n"
        "L3Y:\n"
        "wgmma.fence.sync.aligned;\n"
        "wgmma.mma_async.sync.aligned.m64n16k16.f32.bf16.bf16 {r0,r1,r2,r3,r4,r5,r6,r7}, {wa0,wa1,wa2,wa3}, de0, pf, 1, 1, 0;\n"
        "wgmma.mma_async.sync.aligned.m64n16k16.f32.bf16.bf16 {r8,r9,r10,r11,r12,r13,r14,r15}, {wa4,wa5,wa6,wa7}, de1, pf, 1, 1, 0;\n"
        "wgmma.commit_group.sync.aligned;\n"
        "wgmma.mma_async.sync.aligned.m64n24k16.f32.bf16.bf16 {%36,%37,%38,%39,%40,%41,%42,%43,%44,%45,%46,%47}, {hYa0,hYa1,hYa2,hYa3}, daY, 1, 1, 1, 1;\n"
        "wgmma.mma_async.sync.aligned.m64n24k16.f32.bf16.bf16 {%112,%113,%114,%115,%116,%117,%118,%119,%120,%121,%122,%123}, {hYa4,hYa5,hYa6,hYa7}, daY, 1, 1, 1, 1;\n"
        "wgmma.commit_group.sync.aligned;\n"
        "@u2 bra.uni T4Yb;\n"
        "@u1 bra.uni T2Yb;\n"
        "@u0 bra.uni L1Yb;\n"
        "bra.uni L0Yb;\n"
        "T4Y:\n"
        "@t0 bra.uni L5Y;\n"
        "L4Y:\n"
        "wgmma.fence.sync.aligned;\n"
        "wgmma.mma_async.sync.aligned.m64n16k16.f32.bf16.bf16 {r0,r1,r2,r3,r4,r5,r6,r7}, {wa0,wa1,wa2,wa3}, de0, pf, 1, 1, 0;\n"
        "wgmma.mma_async.sync.aligned.m64n16k16.f32.bf16.bf16 {r8,r9,r10,r11,r12,r13,r14,r15}, {wa4,wa5,wa6,wa7}, de1, pf, 1, 1, 0;\n"
        "wgmma.commit_group.sync.aligned;\n"
        "wgmma.mma_async.sync.aligned.m64n24k16.f32.bf16.bf16 {%48,%49,%50,%51,%52,%53,%54,%55,%56,%57,%58,%59}, {hYa0,hYa1,hYa2,hYa3}, daY, 1, 1, 1, 1;\n"
        "wgmma.mma_async.sync.aligned.m64n24k16.f32.bf16.bf16 {%124,%125,%126,%127,%128,%129,%130,%131,%132,%133,%134,%135}, {hYa4,hYa5,hYa6,hYa7}, daY, 1, 1, 1, 1;\n"
        "wgmma.commit_group.sync.aligned;\n"
        "@u2 bra.uni T4Yb;\n"
        "@u1 bra.uni T2Yb;\n"
        "@u0 bra.uni L1Yb;\n"
        "bra.uni L0Yb;\n"
        "L5Y:\n"
        "wgmma.fence.sync.aligned;\n"
        "wgmma.mma_async.sync.aligned.m64n16k16.f32.bf16.bf16 {r0,r1,r2,r3,r4,r5,r6,r7}, {wa0,wa1,wa2,wa3}, de0, pf, 1, 1, 0;\n"
        "wgmma.mma_async.sync.aligned.m64n16k16.f32.bf16.bf16 {r8,r9,r10,r11,r12,r13,r14,r15}, {wa4,wa5,wa6,wa7}, de1, pf, 1, 1, 0;\n"
        "wgmma.commit_group.sync.aligned;\n"
        "wgmma.mma_async.sync.aligned.m64n32k16.f32.bf16.bf16 {%60,%61,%62,%63,%64,%65,%66,%67,%68,%69,%70,%71,%72,%73,%74,%75}, {hYa0,hYa1,hYa2,hYa3}, daY, 1, 1, 1, 1;\n"
        "wgmma.mma_async.sync.aligned.m64n32k16.f32.bf16.bf16 {%136,%137,%138,%139,%140,%141,%142,%143,%144,%145,%146,%147,%148,%149,%150,%151}, {hYa4,hYa5,hYa6,hYa7}, daY, 1, 1, 1, 1;\n"
        "wgmma.commit_group.sync.aligned;\n"
        "@u2 bra.uni T4Yb;\n"
        "@u1 bra.uni T2Yb;\n"
        "@u0 bra.uni L1Yb;\n"
        "L0Yb:\n"
        "wgmma.fence.sync.aligned;\n"
        "wgmma.mma_async.sync.aligned.m64n24k16.f32.bf16.bf16 {%0,%1,%2,%3,%4,%5,%6,%7,%8,%9,%10,%11}, {hYb0,hYb1,hYb2,hYb3}, dbY, 1, 1, 1, 1;\n"
        "wgmma.mma_async.sync.aligned.m64n24k16.f32.bf16.bf16 {%76,%77,%78,%79,%80,%81,%82,%83,%84,%85,%86,%87}, {hYb4,hYb5,hYb6,hYb7}, dbY, 1, 1, 1, 1;\n"
        "wgmma.commit_group.sync.aligned;\n"
        "bra.uni CX;\n"
        "L1Yb:\n"
        "wgmma.fence.sync.aligned;\n"
        "wgmma.mma_async.sync.aligned.m64n24k16.f32.bf16.bf16 {%12,%13,%14,%15,%16,%17,%18,%19,%20,%21,%22,%23}, {hYb0,hYb1,hYb2,hYb3}, dbY, 1, 1, 1, 1;\n"
        "wgmma.mma_async.sync.aligned.m64n24k16.f32.bf16.bf16 {%88,%89,%90,%91,%92,%93,%94,%95,%96,%97,%98,%99}, {hYb4,hYb5,hYb6,hYb7}, dbY, 1, 1, 1, 1;\n"
        "wgmma.commit_group.sync.aligned;\n"
        "bra.uni CX;\n"
        "T2Yb:\n"
        "@u0 bra.uni L3Yb;\n"
        "L2Yb:\n"
        "wgmma.fence.sync.aligned;\n"
        "wgmma.mma_async.sync.aligned.m64n24k16.f32.bf16.bf16 {%24,%25,%26,%27,%28,%29,%30,%31,%32,%33,%34,%35}, {hYb0,hYb1,hYb2,hYb3}, dbY, 1, 1, 1, 1;\n"
        "wgmma.mma_async.sync.aligned.m64n24k16.f32.bf16.bf16 {%100,%101,%102,%103,%104,%105,%106,%107,%108,%109,%110,%111}, {hYb4,hYb5,hYb6,hYb7}, dbY, 1, 1, 1, 1;\n"
        "wgmma.commit_group.sync.aligned;\n"
        "bra.uni CX;\n"
        "L3Yb:\n"
        "wgmma.fence.sync.aligned;\n"
        "wgmma.mma_async.sync.aligned.m64n24k16.f32.bf16.bf16 {%36,%37,%38,%39,%40,%41,%42,%43,%44,%45,%46,%47}, {hYb0,hYb1,hYb2,hYb3}, dbY, 1, 1, 1, 1;\n"
        "wgmma.mma_async.sync.aligned.m64n24k16.f32.bf16.bf16 {%112,%113,%114,%115,%116,%117,%118,%119,%120,%121,%122,%123}, {hYb4,hYb5,hYb6,hYb7}, dbY, 1, 1, 1, 1;\n"
        "wgmma.commit_group.sync.aligned;\n"
        "bra.uni CX;\n"
        "T4Yb:\n"
        "@u0 bra.uni L5Yb;\n"
        "L4Yb:\n"
        "wgmma.fence.sync.aligned;\n"
        "wgmma.mma_async.sync.aligned.m64n24k16.f32.bf16.bf16 {%48,%49,%50,%51,%52,%53,%54,%55,%56,%57,%58,%59}, {hYb0,hYb1,hYb2,hYb3}, dbY, 1, 1, 1, 1;\n"
        "wgmma.mma_async.sync.aligned.m64n24k16.f32.bf16.bf16 {%124,%125,%126,%127,%128,%129,%130,%131,%132,%133,%134,%135}, {hYb4,hYb5,hYb6,hYb7}, dbY, 1, 1, 1, 1;\n"
        "wgmma.commit_group.sync.aligned;\n"
        "bra.uni CX;\n"
        "L5Yb:\n"
        "wgmma.fence.sync.aligned;\n"
        "wgmma.mma_async.sync.aligned.m64n32k16.f32.bf16.bf16 {%60,%61,%62,%63,%64,%65,%66,%67,%68,%69,%70,%71,%72,%73,%74,%75}, {hYb0,hYb1,hYb2,hYb3}, dbY, 1, 1, 1, 1;\n"
        "wgmma.mma_async.sync.aligned.m64n32k16.f32.bf16.bf16 {%136,%137,%138,%139,%140,%141,%142,%143,%144,%145,%146,%147,%148,%149,%150,%151}, {hYb4,hYb5,hYb6,hYb7}, dbY, 1, 1, 1, 1;\n"
        "wgmma.commit_group.sync.aligned;\n"
        "bra.uni CX;\n"
        "SLOW:\n"
        "mov.u32 cnt, 0;\n"
        "W2:\n"
        "mbarrier.try_wait.parity.shared.b64 p, [bar], par;\n"
        "@p bra.uni RES;\n"
        "add.u32 cnt, cnt, 1;\n"
        "setp.lt.u32 p, cnt, 4000000;\n"
        "@p bra.uni W2;\n"
        "trap;\n"
        "LEXIT:\n"
        "wgmma.wait_group.sync.aligned 0;\n"
        "}\n"
        : "=f"(acc[0][0][0]), "=f"(acc[0][0][1]), "=f"(acc[0][0][2]), "=f"(acc[0][0][3]),
          "=f"(acc[0][1][0]), "=f"(acc[0][1][1]), "=f"(acc[0][1][2]), "=f"(acc[0][1][3]),
          "=f"(acc[0][2][0]), "=f"(acc[0][2][1]), "=f"(acc[0][2][2]), "=f"(acc[0][2][3]),
          "=f"(acc[0][3][0]), "=f"(acc[0][3][1]), "=f"(acc[0][3][2]), "=f"(acc[0][3][3]),
          "=f"(acc[0][4][0]), "=f"(acc[0][4][1]), "=f"(acc[0][4][2]), "=f"(acc[0][4][3]),
          "=f"(acc[0][5][0]), "=f"(acc[0][5][1]), "=f"(acc[0][5][2]), "=f"(acc[0][5][3]),
          "=f"(acc[0][6][0]), "=f"(acc[0][6][1]), "=f"(acc[0][6][2]), "=f"(acc[0][6][3]),
          "=f"(acc[0][7][0]), "=f"(acc[0][7][1]), "=f"(acc[0][7][2]), "=f"(acc[0][7][3]),
          "=f"(acc[0][8][0]), "=f"(acc[0][8][1]), "=f"(acc[0][8][2]), "=f"(acc[0][8][3]),
          "=f"(acc[0][9][0]), "=f"(acc[0][9][1]), "=f"(acc[0][9][2]), "=f"(acc[0][9][3]),
          "=f"(acc[0][10][0]), "=f"(acc[0][10][1]), "=f"(acc[0][10][2]), "=f"(acc[0][10][3]),
          "=f"(acc[0][11][0]), "=f"(acc[0][11][1]), "=f"(acc[0][11][2]), "=f"(acc[0][11][3]),
          "=f"(acc[0][12][0]), "=f"(acc[0][12][1]), "=f"(acc[0][12][2]), "=f"(acc[0][12][3]),
          "=f"(acc[0][13][0]), "=f"(acc[0][13][1]), "=f"(acc[0][13][2]), "=f"(acc[0][13][3]),
          "=f"(acc[0][14][0]), "=f"(acc[0][14][1]), "=f"(acc[0][14][2]), "=f"(acc[0][14][3]),
          "=f"(acc[0][15][0]), "=f"(acc[0][15][1]), "=f"(acc[0][15][2]), "=f"(acc[0][15][3]),
          "=f"(acc[0][16][0]), "=f"(acc[0][16][1]), "=f"(acc[0][16][2]), "=f"(acc[0][16][3]),
          "=f"(acc[0][17][0]), "=f"(acc[0][17][1]), "=f"(acc[0][17][2]), "=f"(acc[0][17][3]),
          "=f"(acc[0][18][0]), "=f"(acc[0][18][1]), "=f"(acc[0][18][2]), "=f"(acc[0][18][3]),
          "=f"(acc[1][0][0]), "=f"(acc[1][0][1]), "=f"(acc[1][0][2]), "=f"(acc[1][0][3]),
          "=f"(acc[1][1][0]), "=f"(acc[1][1][1]), "=f"(acc[1][1][2]), "=f"(acc[1][1][3]),
          "=f"(acc[1][2][0]), "=f"(acc[1][2][1]), "=f"(acc[1][2][2]), "=f"(acc[1][2][3]),
          "=f"(acc[1][3][0]), "=f"(acc[1][3][1]), "=f"(acc[1][3][2]), "=f"(acc[1][3][3]),
          "=f"(acc[1][4][0]), "=f"(acc[1][4][1]), "=f"(acc[1][4][2]), "=f"(acc[1][4][3]),
          "=f"(acc[1][5][0]), "=f"(acc[1][5][1]), "=f"(acc[1][5][2]), "=f"(acc[1][5][3]),
          "=f"(acc[1][6][0]), "=f"(acc[1][6][1]), "=f"(acc[1][6][2]), "=f"(acc[1][6][3]),
          "=f"(acc[1][7][0]), "=f"(acc[1][7][1]), "=f"(acc[1][7][2]), "=f"(acc[1][7][3]),
          "=f"(acc[1][8][0]), "=f"(acc[1][8][1]), "=f"(acc[1][8][2]), "=f"(acc[1][8][3]),
          "=f"(acc[1][9][0]), "=f"(acc[1][9][1]), "=f"(acc[1][9][2]), "=f"(acc[1][9][3]),
          "=f"(acc[1][10][0]), "=f"(acc[1][10][1]), "=f"(acc[1][10][2]), "=f"(acc[1][10][3]),
          "=f"(acc[1][11][0]), "=f"(acc[1][11][1]), "=f"(acc[1][11][2]), "=f"(acc[1][11][3]),
          "=f"(acc[1][12][0]), "=f"(acc[1][12][1]), "=f"(acc[1][12][2]), "=f"(acc[1][12][3]),
          "=f"(acc[1][13][0]), "=f"(acc[1][13][1]), "=f"(acc[1][13][2]), "=f"(acc[1][13][3]),
          "=f"(acc[1][14][0]), "=f"(acc[1][14][1]), "=f"(acc[1][14][2]), "=f"(acc[1][14][3]),
          "=f"(acc[1][15][0]), "=f"(acc[1][15][1]), "=f"(acc[1][15][2]), "=f"(acc[1][15][3]),
          "=f"(acc[1][16][0]), "=f"(acc[1][16][1]), "=f"(acc[1][16][2]), "=f"(acc[1][16][3]),
          "=f"(acc[1][17][0]), "=f"(acc[1][17][1]), "=f"(acc[1][17][2]), "=f"(acc[1][17][3]),
          "=f"(acc[1][18][0]), "=f"(acc[1][18][1]), "=f"(acc[1][18][2]), "=f"(acc[1][18][3])
        : "r"(xa0), "r"(xa1), "r"(so0), "r"(bar0), "r"(ea0), "r"(d0), "r"(pl0), "r"(lz), "r"(wd)
        : "memory");
}
__device__ __forceinline__ void wgmma_out(float (&o)[NJ][4], uint64_t da, uint64_t db, int acc) {
    asm volatile(
        "{\n.reg .pred p;\nsetp.ne.b32 p, %78, 0;\n"
        "wgmma.mma_async.sync.aligned.m64n152k16.f32.bf16.bf16 {%0,%1,%2,%3,%4,%5,%6,%7,%8,%9,%10,%11,%12,%13,%14,%15,%16,%17,%18,%19,%20,%21,%22,%23,%24,%25,%26,%27,%28,%29,%30,%31,%32,%33,%34,%35,%36,%37,%38,%39,%40,%41,%42,%43,%44,%45,%46,%47,%48,%49,%50,%51,%52,%53,%54,%55,%56,%57,%58,%59,%60,%61,%62,%63,%64,%65,%66,%67,%68,%69,%70,%71,%72,%73,%74,%75}, %76, %77, p, 1, 1, 1, 1;\n}"
        : "+f"(o[0][0]), "+f"(o[0][1]), "+f"(o[0][2]), "+f"(o[0][3]),
          "+f"(o[1][0]), "+f"(o[1][1]), "+f"(o[1][2]), "+f"(o[1][3]),
          "+f"(o[2][0]), "+f"(o[2][1]), "+f"(o[2][2]), "+f"(o[2][3]),
          "+f"(o[3][0]), "+f"(o[3][1]), "+f"(o[3][2]), "+f"(o[3][3]),
          "+f"(o[4][0]), "+f"(o[4][1]), "+f"(o[4][2]), "+f"(o[4][3]),
          "+f"(o[5][0]), "+f"(o[5][1]), "+f"(o[5][2]), "+f"(o[5][3]),
          "+f"(o[6][0]), "+f"(o[6][1]), "+f"(o[6][2]), "+f"(o[6][3]),
          "+f"(o[7][0]), "+f"(o[7][1]), "+f"(o[7][2]), "+f"(o[7][3]),
          "+f"(o[8][0]), "+f"(o[8][1]), "+f"(o[8][2]), "+f"(o[8][3]),
          "+f"(o[9][0]), "+f"(o[9][1]), "+f"(o[9][2]), "+f"(o[9][3]),
          "+f"(o[10][0]), "+f"(o[10][1]), "+f"(o[10][2]), "+f"(o[10][3]),
          "+f"(o[11][0]), "+f"(o[11][1]), "+f"(o[11][2]), "+f"(o[11][3]),
          "+f"(o[12][0]), "+f"(o[12][1]), "+f"(o[12][2]), "+f"(o[12][3]),
          "+f"(o[13][0]), "+f"(o[13][1]), "+f"(o[13][2]), "+f"(o[13][3]),
          "+f"(o[14][0]), "+f"(o[14][1]), "+f"(o[14][2]), "+f"(o[14][3]),
          "+f"(o[15][0]), "+f"(o[15][1]), "+f"(o[15][2]), "+f"(o[15][3]),
          "+f"(o[16][0]), "+f"(o[16][1]), "+f"(o[16][2]), "+f"(o[16][3]),
          "+f"(o[17][0]), "+f"(o[17][1]), "+f"(o[17][2]), "+f"(o[17][3]),
          "+f"(o[18][0]), "+f"(o[18][1]), "+f"(o[18][2]), "+f"(o[18][3])
        : "l"(da), "l"(db), "r"(acc));
}

__device__ __forceinline__ void slow_edge(int ee, int s, float* accn, const __nv_bfloat16* __restrict__ x,
                                          const __nv_bfloat16* __restrict__ sh, const __nv_bfloat16* __restrict__ ea,
                                          const __nv_bfloat16* __restrict__ cg, const __nv_bfloat16* __restrict__ wr,
                                          int lane) {
    float rwv[4] = {0.f, 0.f, 0.f, 0.f};
#pragma unroll 4
    for (int d = 0; d < 16; d++) {
        const float a = __bfloat162float(ea[(size_t)ee * 16 + d]);
        const uint2 wv = *(const uint2*)(wr + d * 128 + lane * 4);
        rwv[0] += a * __uint_as_float(wv.x << 16);
        rwv[1] += a * __uint_as_float(wv.x & 0xffff0000u);
        rwv[2] += a * __uint_as_float(wv.y << 16);
        rwv[3] += a * __uint_as_float(wv.y & 0xffff0000u);
    }
    float A = 0.f;
#pragma unroll
    for (int v = 0; v < 4; v++)
        A += __bfloat162float(cg[((lane >> 2) & 3) * 16 + v * 4 + (lane & 3)]) * __bfloat162float(sh[(size_t)ee * 4 + v]);
    float m[4][4];
#pragma unroll
    for (int w = 0; w < 4; w++)
#pragma unroll
        for (int j = 0; j < 4; j++) m[w][j] = 0.f;
#pragma unroll
    for (int u = 0; u < 4; u++) {
        const uint2 xv = *(const uint2*)(x + (size_t)s * 512 + u * 128 + lane * 4);
        const float x0 = __uint_as_float(xv.x << 16), x1 = __uint_as_float(xv.x & 0xffff0000u);
        const float x2 = __uint_as_float(xv.y << 16), x3 = __uint_as_float(xv.y & 0xffff0000u);
#pragma unroll
        for (int w = 0; w < 4; w++) {
            const float a = __shfl_sync(0xffffffffu, A, u * 4 + w);
            m[w][0] += a * x0;
            m[w][1] += a * x1;
            m[w][2] += a * x2;
            m[w][3] += a * x3;
        }
    }
#pragma unroll
    for (int w = 0; w < 4; w++)
#pragma unroll
        for (int j = 0; j < 4; j++) atomicAdd(accn + w * 128 + lane * 4 + j, m[w][j] * rwv[j]);
}

__device__ __forceinline__ void slow_out(const float* accn, const __nv_bfloat16* __restrict__ wout,
                                         __nv_bfloat16* __restrict__ outn, int lane) {
    float o[4][4];
#pragma unroll
    for (int w = 0; w < 4; w++)
#pragma unroll
        for (int j = 0; j < 4; j++) o[w][j] = 0.f;
#pragma unroll 2
    for (int c = 0; c < 128; c++) {
        const uint2 wv = *(const uint2*)(wout + c * 128 + lane * 4);
        const float w0 = __uint_as_float(wv.x << 16), w1 = __uint_as_float(wv.x & 0xffff0000u);
        const float w2 = __uint_as_float(wv.y << 16), w3 = __uint_as_float(wv.y & 0xffff0000u);
#pragma unroll
        for (int w = 0; w < 4; w++) {
            const float a = __bfloat162float(__float2bfloat16(accn[w * 128 + c]));
            o[w][0] += a * w0;
            o[w][1] += a * w1;
            o[w][2] += a * w2;
            o[w][3] += a * w3;
        }
    }
#pragma unroll
    for (int w = 0; w < 4; w++)
        *(uint2*)(outn + w * 128 + lane * 4) = make_uint2(pack_bf16(o[w][0], o[w][1]), pack_bf16(o[w][2], o[w][3]));
}

static_assert(2 * NW >= 4 * NP, "barriers");
#define EMASK 0xffffff
#define TBIN 0
#define PW 0
#define TWAIT mbar_lean_u
#define PWAIT mbar_lean
#define TMA_ROW(k) "@pl cp.async.bulk.tensor.2d.shared::cluster.global.mbarrier::complete_tx::bytes [d" #k "], [tm, {z" #k ", r" #k "}], [b" #k "];\n"
#define TMA_INIT(k, o) "shfl.sync.idx.b32 z" #k ", %12, " #k ", 31, 0xffffffff;\nadd.u32 d" #k ", %4, " STR(o) ";\n"
#define TMA_PREP(k) "add.u32 d" #k ", d" #k ", dd;\nadd.u32 b" #k ", %0, z" #k ";\n"
#define PSRC "and.b32 sq, sq, 0x3fe;\nand.b32 sr, sr, 0x3fe;\nmad.lo.u32 sq, sq, 4, %7;\nmad.lo.u32 sr, sr, 4, %7;\n"
#define TA 1
#define TB 2
#define TC 5
#define TD 6
__device__ __forceinline__ void produce(const CUtensorMap* tm, uint32_t& fb, uint32_t& par, uint32_t bend, uint32_t d0, uint32_t ps,
                                        uint32_t pe, uint32_t psrc, uint32_t tbase, uint32_t lim, uint32_t taug, uint32_t taus, int lz
) {
    asm volatile(
        "{\n.reg .pred p, pl, ok;\n.reg .b32 a<4>, r<8>, d<8>, b<8>, z<8>, sq, sr, ps, lim, tgt, tgu, c, dd, t0;\n"
        ".reg .b64 st, tm;\n"
        "elect.sync _|pl, 0xffffffff;\n"
        TMA_INIT(0, 0) TMA_INIT(1, SM_ODD) TMA_INIT(2, 1024) TMA_INIT(3, SM_ODD + 1024)
        TMA_INIT(4, 4096) TMA_INIT(5, SM_ODD + 4096) TMA_INIT(6, 5120) TMA_INIT(7, SM_ODD + 5120)
        "mov.b64 {a0, a1}, %2;\n"
        "add.u32 a0, a0, %12;\n"
        "add.u32 a1, a1, %12;\n"
        "shfl.sync.idx.b32 a0, a0, 0, 31, 0xffffffff;\n"
        "shfl.sync.idx.b32 a1, a1, 0, 31, 0xffffffff;\n"
        "mov.b64 tm, {a0, a1};\n"
        "mov.u32 ps, %5;\n"
        "mov.u32 lim, %9;\n"
        "mov.u32 dd, 0;\n"
        "ld.shared.u16 sq, [ps];\n"
        "ld.shared.u16 sr, [ps+4];\n"
        PSRC
        "ld.shared.v2.u32 {a0, a1}, [sq];\n"
        "ld.shared.v2.u32 {a2, a3}, [sr];\n"
        "ld.shared.u16 sq, [ps+8];\n"
        "ld.shared.u16 sr, [ps+12];\n"
        "mbarrier.test_wait.parity.shared.b64 ok, [%0+8], %1;\n"
        "setp.ge.u32 p, ps, %6;\n"
        "@p bra.uni PEND;\n"
        "PLOOP:\n"
        "mov.u32 t0, %%clock;\n"
        PSRC
        "shl.b32 r0, a0, 3;\nand.b32 r0, r0, 0x7fff8;\nshr.u32 r1, a0, 13;\nand.b32 r1, r1, 0x7fff8;\n"
        "shl.b32 r2, a1, 3;\nand.b32 r2, r2, 0x7fff8;\nshr.u32 r3, a1, 13;\nand.b32 r3, r3, 0x7fff8;\n"
        "shl.b32 r4, a2, 3;\nand.b32 r4, r4, 0x7fff8;\nshr.u32 r5, a2, 13;\nand.b32 r5, r5, 0x7fff8;\n"
        "shl.b32 r6, a3, 3;\nand.b32 r6, r6, 0x7fff8;\nshr.u32 r7, a3, 13;\nand.b32 r7, r7, 0x7fff8;\n"
        "add.u32 tgt, r" STR(TA) ", r" STR(TB) ";\nmul.lo.u32 tgt, tgt, %11;\nshr.u32 tgt, tgt, 8;\nadd.u32 tgt, tgt, %8;\n"
        "add.u32 tgu, r" STR(TC) ", r" STR(TD) ";\nmul.lo.u32 tgu, tgu, %11;\nshr.u32 tgu, tgu, 8;\nadd.u32 tgu, tgu, %8;\n"
        "min.u32 tgt, tgt, lim;\n"
        "add.u32 lim, lim, %10;\n"
        "min.u32 tgu, tgu, lim;\n"
        "add.u32 lim, lim, %10;\n"
        "ld.shared.v2.u32 {a0, a1}, [sq];\n"
        "ld.shared.v2.u32 {a2, a3}, [sr];\n"
        "ld.shared.u16 sq, [ps+16];\n"
        "ld.shared.u16 sr, [ps+20];\n"
        "add.u32 ps, ps, 8;\n"
        TMA_PREP(0) TMA_PREP(1) TMA_PREP(2) TMA_PREP(3) TMA_PREP(4) TMA_PREP(5) TMA_PREP(6) TMA_PREP(7)
        "sub.s32 c, t0, tgt;\n"
        "setp.ge.and.s32 p, c, 0, ok;\n"
        "@!p bra.uni PSLP;\n"
        "PRES:\n"
        "@pl mbarrier.arrive.expect_tx.shared.b64 _, [%0], 8192;\n"
        TMA_ROW(0) TMA_ROW(1) TMA_ROW(2) TMA_ROW(3)
        "PSL2:\n"
        "mov.u32 c, %%clock;\n"
        "sub.s32 c, c, tgu;\n"
        "setp.lt.s32 p, c, 0;\n"
        "@p nanosleep.u32 " STR(PSLEEP) ";\n"
        "@p bra.uni PSL2;\n"
        TMA_ROW(4) TMA_ROW(5) TMA_ROW(6) TMA_ROW(7)
        "setp.eq.u32 p, %0, %3;\n"
        "selp.b32 c, " STR(16 - NP * 16) ", 16, p;\n"
        "add.u32 %0, %0, c;\n"
        "shl.b32 dd, c, 9;\n"
        "selp.b32 c, 1, 0, p;\n"
        "xor.b32 %1, %1, c;\n"
        "mbarrier.test_wait.parity.shared.b64 ok, [%0+8], %1;\n"
        "setp.lt.u32 p, ps, %6;\n"
        "@p bra.uni PLOOP;\n"
        "bra.uni PEND;\n"
        "PSLP:\n"
        "mov.u32 c, %%clock;\n"
        "sub.s32 c, c, tgt;\n"
        "setp.lt.s32 p, c, 0;\n"
        "@p nanosleep.u32 " STR(PSLEEP) ";\n"
        "@p bra.uni PSLP;\n"
        "@ok bra.uni PRES;\n"
        "mov.u32 c, 0;\n"
        "PW:\n"
        "mbarrier.try_wait.parity.shared.b64 p, [%0+8], %1;\n"
        "@p bra.uni PRES;\n"
        "add.u32 c, c, 1;\n"
        "setp.lt.u32 p, c, 4000000;\n"
        "@p bra.uni PW;\n"
        "trap;\n"
        "PEND:\n}"
        : "+r"(fb), "+r"(par)
        : "l"(tm), "r"(bend), "r"(d0), "r"(ps), "r"(pe), "r"(psrc), "r"(tbase), "r"(lim), "r"(taug), "r"(taus), "r"(lz)
        : "memory");
}
#define GCODE(g) ((((g) >> 1) + 1) << 12 | ((g) & 1) << 15)
#define WG_SYNC(w) asm volatile("bar.sync %0, 128;" ::"r"((w) + 1) : "memory")
__global__ void __launch_bounds__(NT, 1)
main_kernel(const __grid_constant__ CUtensorMap tmx, const __grid_constant__ CUtensorMap tmw,
            const __grid_constant__ CUtensorMap tmo, const __nv_bfloat16* __restrict__ x, const int* __restrict__ src,
            const int* __restrict__ dst, const __nv_bfloat16* __restrict__ sh, const __nv_bfloat16* __restrict__ ea,
            const __nv_bfloat16* __restrict__ cg, const __nv_bfloat16* __restrict__ wr,
            const __nv_bfloat16* __restrict__ wout, __nv_bfloat16* __restrict__ out, int N, int E, int npb,
            unsigned npb_magic, int chunk, int fast_ok, int bsh, int tau16, int toff) {
    extern __shared__ __align__(1024) unsigned char smem[];
    const uint32_t sb = s2u(smem);
    int* s_int = (int*)(smem + SM_MISC + MI_INT);
    int* s_hist = (int*)(smem + SC_HIST);
    const int tid = threadIdx.x;
    const int warp = __shfl_sync(0xffffffffu, tid >> 5, 0), lane = tid & 31;
    const int g = lane >> 2, t = lane & 3;

    TLSTAMP(0);
    const int nbins = gridDim.x;
    const int bin = blockIdx.x;
    const int node0 = bin * npb, hpb = npb >> 1;
    const int ebeg = min(E, bin * chunk), eend = min(E, ebeg + chunk);
    int pd[EPS], ps[EPS];
#pragma unroll
    for (int k = 0; k < EPS; k++) {
        const int e = ebeg + tid + k * NT;
        pd[k] = e < eend ? __ldg(dst + e) : -1;
        ps[k] = e < eend ? __ldg(src + e) : 0;
    }
    int2* st_ent = (int2*)(smem + SC_ENT);
    unsigned char* st_bin = smem + SC_BIN;
    int* s_loc = s_hist + MAXBINS;
    int* s_del = s_loc + MAXBINS;
    if (lane < 2 && warp < 2 * NP) mbar_init(sb + SM_BAR + (warp * 2 + lane) * 8, 3 + lane);
    if (tid < MAXBINS) s_hist[tid] = 0;
    if (tid == 0) {
        mbar_init(sb + SM_MISC + MI_WBAR, 4);
        asm volatile("prefetch.tensormap [%0];" ::"l"(&tmx) : "memory");
    }
    if (tid < 2 * (NBK + 1)) ((uint4*)(smem + SC_CNT))[tid] = make_uint4(0, 0, 0, 0);
#pragma unroll
    for (int k = 0; k < TS / 2; k++) ((uint4*)(smem + SM_BT))[tid + k * NT] = make_uint4(0, 0, 0, 0);
    __syncthreads();
    TLSTAMP(1);
    for (int rb = ebeg;; rb += NT * EPS) {
        const bool last = rb + NT * EPS >= eend;
        int pb[EPS], pr[EPS];
#pragma unroll
        for (int k = 0; k < EPS; k++) {
            pb[k] = pd[k] >= 0 ? (int)__umulhi((unsigned)pd[k], npb_magic) : -1;
            if (pb[k] >= 0) pr[k] = atomicAdd(&s_hist[pb[k]], 1);
        }
        if (tid == 0) asm volatile("mov.u32 %0, %%globaltimer_lo;" : "=r"(s_int[3]));
        __syncthreads();
        TLSTAMP(6);
        const int now = s_int[3];
        int gbase = 0;
        if (warp == NW - 1) {
            int v[MAXBINS / 32], sum = 0;
#pragma unroll
            for (int c = 0; c < MAXBINS / 32; c++) {
                v[c] = s_hist[lane * (MAXBINS / 32) + c];
                sum += v[c];
            }
            int run = warp_incl_scan(sum, lane) - sum;
#pragma unroll
            for (int c = 0; c < MAXBINS / 32; c++) {
                s_loc[lane * (MAXBINS / 32) + c] = run;
                run += v[c];
            }
        } else if (tid < nbins) {
            if (bin == TBIN && last) __stcg(&g_bincnt[tid * 32 + 1], now | 1);
            gbase = atomicAdd(&g_bincnt[tid * 32], s_hist[tid] + (last ? 1 << 22 : 0));
        }
        __syncthreads();
#pragma unroll
        for (int k = 0; k < EPS; k++) {
            if (pb[k] >= 0) {
                const int pos = s_loc[pb[k]] + pr[k];
                st_ent[pos] = make_int2(ps[k], (rb + tid + k * NT) | ((pd[k] - pb[k] * npb) << 24) | 0x80000000);
                st_bin[pos] = pb[k];
            }
        }
        if (tid < nbins) s_del[tid] = (gbase & 0x3fffff) - s_loc[tid];
        __syncthreads();
        TLSTAMP(8);
        const int n = min(eend - rb, NT * EPS);
#pragma unroll
        for (int k = 0; k < EPS; k++) {
            const int i = tid + k * NT;
            if (i < n) {
                const int b = st_bin[i];
                const int gpos = i + s_del[b];
                if (gpos < BINCAP) __stcg(&g_bin[b * BINCAP + gpos], st_ent[i]);
            }
        }
        if (last) break;
        if (tid < MAXBINS) s_hist[tid] = 0;
#pragma unroll
        for (int k = 0; k < EPS; k++) {
            const int e = rb + NT * EPS + tid + k * NT;
            pd[k] = e < eend ? dst[e] : -1;
            ps[k] = e < eend ? src[e] : 0;
        }
        __syncthreads();
    }
    TLSTAMP(5);
    int2 ent[KS];
    uint2 wv;
    int rank[KS];
    {
        int cnt = 0;
        if (lane == 0) {
            int tsum;
            for (int spin = 0;; spin++) {
                asm volatile("ld.relaxed.gpu.global.v2.s32 {%0,%1}, [%2];" : "=r"(cnt), "=r"(tsum) : "l"(&g_bincnt[bin * 32]) : "memory");
                if ((cnt >> 22) >= nbins && tsum) break;
                if (spin > 10000000) __trap();
            }
            if (tid == 0) s_int[3] = tsum;
        }
        cnt = __shfl_sync(0xffffffffu, cnt, 0) & 0x3fffff;
        if (tid == 0) s_int[0] = cnt;
        const int n = min(cnt, BINCAP);
        unsigned pend = 0;
#pragma unroll
        for (int k = 0; k < KS; k++) {
            ent[k] = make_int2(0, 0);
            if (tid + k * NT < n) pend |= 1u << k;
        }
        int2* gp = &g_bin[bin * BINCAP + tid];
        for (int spin = 0; __any_sync(0xffffffffu, pend); spin++) {
#pragma unroll
            for (int k = 0; k < KS; k++)
                if ((pend >> k) & 1)
                    asm volatile("ld.relaxed.gpu.global.v2.s32 {%0,%1}, [%2];"
                                 : "=r"(ent[k].x), "=r"(ent[k].y)
                                 : "l"(gp + k * NT)
                                 : "memory");
#pragma unroll
            for (int k = 0; k < KS; k++)
                if (ent[k].y < 0) pend &= ~(1u << k);
            if (spin > 10000000) __trap();
        }
        TLSTAMP(2);
        asm volatile("ld.global.nc.v2.u32 {%0,%1}, [%2];" : "=r"(wv.x), "=r"(wv.y) : "l"((const uint2*)wr + tid));
#pragma unroll
        for (int k = 0; k < KS; k++) {
            if (ent[k].y < 0) {
                if (fast_ok) {
                    const int dl = (ent[k].y >> 24) & 127, w = dl >= hpb;
                    const int loc = dl - (w ? hpb : 0), gr = GSZ == 6 ? min(loc * 43 >> 8, 5) : loc >> 3, sft = (gr & 1) * 16;
                    const int cw = (w * (NBK + 1) + (ent[k].x >> bsh)) * 4 + (gr >> 1);
                    const unsigned old = atomicAdd((unsigned*)(smem + SC_CNT) + cw, 1u << sft);
                    rank[k] = ((old >> sft) & 0xffff) | GCODE(gr);
                    ent[k].x |= cw << 16;
                    ent[k].y = (ent[k].y & 0x80ffffff) | ((loc - gr * GSZ) << 24);
                }
                __stcg(gp + k * NT, make_int2(0, 0));
            }
        }
    }
    __syncthreads();
    if (tid == 0) *(int2*)&g_bincnt[bin * 32] = make_int2(0, 0);
    TLSTAMP(9);
    if (warp < 2) {
        uint4* cp = (uint4*)(smem + SC_CNT) + warp * (NBK + 1) + lane * (NBK / 32);
        uint4 v[NBK / 32];
        uint32_t s[3] = {0, 0, 0}, r[3], tot[3], base[3];
#pragma unroll
        for (int c = 0; c < NBK / 32; c++) {
            v[c] = cp[c];
            s[0] += v[c].x;
            s[1] += v[c].y;
            s[2] += v[c].z;
        }
        uint32_t sum = 0;
#pragma unroll
        for (int i = 0; i < 3; i++) {
            r[i] = warp_incl_scan(s[i], lane);
            tot[i] = __shfl_sync(0xffffffffu, r[i], 31);
            r[i] -= s[i];
            const uint32_t p = (tot[i] + 0x00030003u) & 0xfffcfffcu;
            base[i] = sum * 0x10001u + (p << 16);
            sum += (p & 0xffff) + (p >> 16);
        }
        auto blocks = [](const uint32_t(&a)[3]) {
            constexpr uint32_t c = (3 - CE) * 0x10001u;
            const uint32_t q = (((a[0] + c) >> 2) & 0x3fff3fffu) + (((a[1] + c) >> 2) & 0x3fff3fffu) + (((a[2] + c) >> 2) & 0x3fff3fffu);
            return (q & 0xffff) + (q >> 16);
        };
#pragma unroll
        for (int c = 0; c < NBK / 32; c++) {
            cp[c] = make_uint4(r[0] + base[0], r[1] + base[1], r[2] + base[2], blocks(r));
            r[0] += v[c].x;
            r[1] += v[c].y;
            r[2] += v[c].z;
        }
        const bool ok = sum + 4 <= LCAP;
        const int nst = sum >> 2;
        const int npr = (nst + 3) >> 2;
        const uint32_t tw = g < 2 ? tot[0] : g < 4 ? tot[1] : tot[2], bw = g < 2 ? base[0] : g < 4 ? base[1] : base[2];
        const int le = g < 6 ? ((tw + bw) >> ((g & 1) * 16)) & 0xffff : sum;
        const bool tailb = t == 0 && (le & 3) >= 1 && (le & 3) <= CE;
        const unsigned tm = __ballot_sync(0xffffffffu, tailb);
        if (ok) {
            {
                const int i = (le & ~3) + t;
                if (i >= le) {
                    ((unsigned short*)(smem + SM_SRC))[warp * LCAP + i] = min(node0, N - 1);
                    ((uint32_t*)(smem + SM_EID))[warp * LCAP + i] = 0x80000000u;
                }
            }
            if (tailb) {
                const int i = blocks(tot) + __popc(tm & ((1u << lane) - 1));
                ((unsigned short*)(smem + SM_SEQ))[warp * SEQCAP + i] = (le >> 2) * 2 | GCODE(g);
            }
            ((unsigned short*)(smem + SM_SEQ))[warp * SEQCAP + nst + lane] = nst * 2 | (lane < (-nst & 3) ? GCODE(0) : 0x7c01);
        }
        if (lane < NP - 1 - npr % NP) {
            mbar_arrive_cnt(sb + SM_BAR + (warp * NP + lane) * 16, 3);
            mbar_arrive_cnt(sb + SM_BAR + (warp * NP + lane) * 16 + 8, 4);
        }
        if (lane == 0) s_int[1 + warp] = ok ? npr : -1;
    }
    __syncthreads();
    TLSTAMP(10);
    const bool fast = s_int[0] <= BINCAP && fast_ok && (s_int[1] | s_int[2]) >= 0;
    if (fast) {
        int pos[KS];
#pragma unroll
        for (int k = 0; k < KS; k++)
            if (ent[k].y < 0) pos[k] = ((uint32_t*)(smem + SC_CNT))[ent[k].x >> 16];
#pragma unroll
        for (int k = 0; k < KS; k++) {
            if (ent[k].y < 0) {
                const int w = (ent[k].x >> 16) >= (NBK + 1) * 4;
                const int p = (((uint32_t)pos[k] >> ((rank[k] >> 11) & 16)) & 0xffff) + (rank[k] & 0xfff);
                ((unsigned short*)(smem + SM_SRC))[w * LCAP + p] = ent[k].x;
                ((uint32_t*)(smem + SM_EID))[w * LCAP + p] = ent[k].y & 0x7fffffff;
                if ((p & 3) == CE) {
                    const int i = atomicAdd((int*)(smem + SC_CNT) + ((ent[k].x >> 16) | 3), 1);
                    ((unsigned short*)(smem + SM_SEQ))[w * SEQCAP + i] = (p >> 2) * 2 | (rank[k] & 0xf000);
                }
            }
        }
    }
    sts_v2(sb + SM_WR + ((tid >> 1) & 15) * 256 + (tid >> 5) * 16 + (tid & 1) * 8, wv.x, wv.y);
    FENCE_ASYNC();
    TLSTAMP(15);
    __syncthreads();
    TLSTAMP(3);

    if (fast && warp >= 12) {
        asm volatile("setmaxnreg.dec.sync.aligned.u32 %0;" ::"n"(HREG));
        const int w = warp & 1, j = (warp >> 1) & 1;
        const int npr = __shfl_sync(0xffffffffu, s_int[1 + w], 0);
        const uint32_t bar0 = sb + SM_BAR + w * NP * 16;
        uint32_t fseq = sb + SM_SEQ + w * SEQCAP * 2 + j * 8 + (lane >> 3) * 2;
        const uint32_t feid = sb + SM_EID + w * LCAP * 4 + ((lane >> 1) & 3) * 4;
        const uint32_t bea = sb + SM_EA + w * 4096;
        uint32_t oea = ((lane >> 1) & 3) * 32 + ((lane >> 3) & 1) * 16 + (lane & 1) * 128 + (2 * j + (lane >> 4)) * 256;
        const uint32_t fsd = sb + SM_SIDE + (warp - 12) * 512 + lane * 8;
        const char* gea = (const char*)ea + (lane & 1) * 16;
        const char* gsh = (const char*)sh + (lane & 1) * 4;
        uint32_t es;
        auto ids = [&]() {
            es = lds_u32(feid + (lds_u16(fseq) & 0x3fe) * 8);
            fseq += 16;
        };
        auto fetch = [&](int i) {
            cp_async16(bea + oea + i * 1024, gea + (size_t)(es & EMASK) * 32, (int)es >= 0 ? 16 : 0);
            cp_async4(fsd + i * 256, gsh + (size_t)(es & EMASK) * 8, (int)es >= 0 ? 4 : 0);
            sts_u32(fsd + i * 256 + 4, ((es >> 17) & 0x300) | ((es >> 21) & 8));
            asm volatile("cp.async.commit_group;" ::: "memory");
            if (i) oea ^= 0x800;
        };
        ids();
        fetch(0);
        ids();
        fetch(1);
        uint32_t wf[2];
        {
            const unsigned short* cp = (const unsigned short*)cg + (g >> 1) * 16 + (t & 1) * 8 + (g & 1);
#pragma unroll
            for (int k = 0; k < 2; k++) wf[k] = t < 2 ? __ldg(cp + 2 * k) | ((uint32_t)__ldg(cp + 2 * k + 4) << 16) : 0u;
        }
        const uint32_t psd = sb + SM_SIDE + (warp - 12) * 512 + g * 16 + (t & 1) * 8;
        const uint32_t pt = sb + SM_BT + w * (TS * 2048) + j * 4096 + (g >> 2) * 1024 +
                            (2 * (g & 3) + (t & 1) + 8 * ((t >> 1) ^ ((g >> 1) & 1))) * 16;
        uint32_t old[4] = {pt, pt, pt, pt};
        int vf = (NP - 1 - npr % NP + j) % NP * 16;
        int ve = (NP - 1 - npr % NP + j + 1 - TS / 2 + NP) * 16, pe = 1;
        if (ve >= NP * 16) ve -= NP * 16, pe = 0;
#pragma unroll 1
        for (int m = j; m < npr;) {
#pragma unroll
            for (int i = 0; i < 2; i++) {
                asm volatile("cp.async.wait_group 1;" ::: "memory");
                __syncwarp();
                const uint2 s0 = lds_v2(psd + i * 256), s1 = lds_v2(psd + i * 256 + 128);
                ids();
                float d0[4], d1[4];
                mma1688_z(d0, s0.x, s1.x, wf[0]);
                mma1688_z(d1, s0.x, s1.x, wf[1]);
                TWAIT(bar0 + ve + 8, pe);
                sts_v2(old[2 * i] + i * 8192, 0, 0);
                sts_v2(old[2 * i + 1] + i * 8192 + 2048, 0, 0);
                old[2 * i] = pt + s0.y;
                old[2 * i + 1] = pt + s1.y;
                sts_v2(old[2 * i] + i * 8192, pack_bf16(d0[0], d0[1]), pack_bf16(d1[0], d1[1]));
                sts_v2(old[2 * i + 1] + i * 8192 + 2048, pack_bf16(d0[2], d0[3]), pack_bf16(d1[2], d1[3]));
                FENCE_ASYNC();
                __syncwarp();
                if (lane == 0) mbar_arrive(bar0 + vf);
                fetch(i);
                vf += 32;
                if (vf >= NP * 16) vf -= NP * 16;
                ve += 32;
                if (ve >= NP * 16) ve -= NP * 16, pe ^= 1;
                m += 2;
                if (m >= npr) break;
            }
        }
        asm volatile("cp.async.wait_group 0;" ::: "memory");
        TLMAX(13);
    } else if (fast && warp >= 8) {
        asm volatile("setmaxnreg.dec.sync.aligned.u32 %0;" ::"n"(PREG));
        const int w = warp & 1, j = (warp >> 1) & 1;
        const int nst = 2 * __shfl_sync(0xffffffffu, s_int[1 + w], 0);
        const uint32_t bar0 = sb + SM_BAR + w * NP * 16, ring = sb + w * RING_BYTES + j * 4096;
        const uint32_t pseq = sb + SM_SEQ + w * SEQCAP * 2 + j * 2;
        unsigned now;
        asm volatile("mov.u32 %0, %%globaltimer_lo;" : "=r"(now));
        const int ago = min(max((int)(now - s_int[3]), 0), 1 << 16) * 7 >> 2;
        const unsigned tbase = __shfl_sync(0xffffffffu, (unsigned)clock() - ago, 0) + (unsigned)toff;
        const unsigned taug = __shfl_sync(0xffffffffu, (N * tau16 >> 4) / max(nst, 1), 0);
        uint32_t fb = bar0 + (NP - 1 - (nst >> 1) % NP) * 16, par = 1;
        produce(&tmx, fb, par, bar0 + NP * 16 - 16, ring - j * 2048 + (fb - bar0) * 512, pseq, pseq + nst * 4, sb + SM_SRC + w * LCAP * 2, tbase,
                tbase + (N * tau16 >> 8), taug, tau16, lane & (E >> 31)
        );
        if (elect()) {
            const uint32_t d = ring + (NP - 1) * 8192;
            mbar_wait(fb + 8, par);
            mbar_arrive_cnt(fb, 1 + j);
            mbar_expect_tx(sb + SM_MISC + MI_WBAR, 8192);
            tma_2d(d + SM_EVEN, &tmw, sb + SM_MISC + MI_WBAR, w * 64, j * 32);
            tma_2d(d + SM_ODD, &tmw, sb + SM_MISC + MI_WBAR, w * 64, j * 32 + 64);
        }
        TLMAX(12);
    } else if (fast) {
        asm volatile("setmaxnreg.inc.sync.aligned.u32 %0;" ::"n"(CREG));
        const int w = warp >> 2, wq = warp & 3;
        const int nst = __shfl_sync(0xffffffffu, s_int[1 + w], 0);
        const uint32_t ring = sb + w * RING_BYTES;
        float acc[2][NJ][4];
        {
            const int e = (lane >> 1) & 3, m = lane >> 3;
            const int line = 2 * ((lane & 1) + 2 * ((m >> 1) ^ (e >> 1))), ch = 2 * wq + (m & 1);
            const uint32_t xb = ring + (e & 1 ? SM_ODD : SM_EVEN) + (e >> 1) * 1024 + line * 128;
            consume(acc, xb + ((ch ^ ((line + (e & 1)) & 7)) * 16), xb + 128 + ((ch ^ ((line + 1 + (e & 1)) & 7)) * 16),
                    (NP - 1 - nst % NP) * 8192, sb + SM_BAR + w * NP * 16, (((sb + SM_EA + w * 4096) & 0x3ffff) >> 4) | (8 << 16),
                    (((sb + SM_BT + w * (TS * 2048)) & 0x3ffff) >> 4) | (8 << 16), sb + SM_SEQ + w * SEQCAP * 2, lane & (E >> 31),
                    sb + SM_WR + wq * 512 + ((lane >> 3) & 1) * 256 + (lane >> 4) * 128 + (lane & 7) * 16);
        }
        TLMAX(11);
#pragma unroll
        for (int h = 0; h < 2; h++) {
            const uint32_t tb = ring + (h ? SM_ODD : SM_EVEN) + wq * (NJ * 256) + lane * 16;
#pragma unroll
            for (int j = 0; j + 1 < NJ; j += 2)
                stsm4(tb + j * 256, pack_bf16(acc[h][j][0], acc[h][j][1]), pack_bf16(acc[h][j][2], acc[h][j][3]),
                      pack_bf16(acc[h][j + 1][0], acc[h][j + 1][1]), pack_bf16(acc[h][j + 1][2], acc[h][j + 1][3]));
            if (NJ & 1)
                stsm2(tb + (NJ - 1) * 256, pack_bf16(acc[h][NJ - 1][0], acc[h][NJ - 1][1]),
                      pack_bf16(acc[h][NJ - 1][2], acc[h][NJ - 1][3]));
        }
        FENCE_ASYNC();
        WG_SYNC(w);
        mbar_wait_u(sb + SM_MISC + MI_WBAR, 0);
        float o[2][NJ][4];
        asm volatile("wgmma.fence.sync.aligned;" ::: "memory");
#pragma unroll
        for (int hh = 0; hh < 2; hh++) {
#pragma unroll
            for (int ks = 0; ks < 8; ks++) {
                const uint32_t rg = ks >> 2 ? SM_ODD : SM_EVEN;
                const uint64_t da = (uint64_t)(((sb + rg + hh * RING_BYTES + (NS - 2) * 4096 + (ks & 3) * 2048) & 0x3ffff) >> 4) |
                                    (64ull << 32) | (1ull << 62);
                const uint64_t db = (uint64_t)(((ring + rg + (ks & 3) * (NJ * 256)) & 0x3ffff) >> 4) | (8ull << 16) | (16ull << 32);
                wgmma_out(o[hh], da, db, ks);
            }
            asm volatile("wgmma.commit_group.sync.aligned;" ::: "memory");
        }
        const int nb = 2 * hpb;
#pragma unroll
        for (int hh = 0; hh < 2; hh++) {
            if (hh == 0) {
                asm volatile("wgmma.wait_group.sync.aligned 1;" ::: "memory");
            } else {
                asm volatile("wgmma.wait_group.sync.aligned 0;" ::: "memory");
                WG_SYNC(w);
            }
#pragma unroll
            for (int j = 0; j < NJ; j++)
#pragma unroll
                for (int k = 0; k < 4; k++) asm volatile("" : "+f"(o[hh][j][k])::"memory");
            const uint32_t b0 = ring + SM_EVEN + (hh ? 0 : 20480);
            const uint32_t b1 = hh ? b0 : ring + SM_ODD + 20480 + 896 - (nb * 128 & ~1023);
            const int r = (lane & 7) + (lane >> 4) * 8;
            const uint32_t co = r * 128 + (((2 * wq + ((lane >> 3) & 1)) ^ (lane & 7)) * 16);
#pragma unroll
            for (int j = 0; j + 1 < NJ; j += 2)
                stsm4t((8 * j + r < nb ? b0 : b1) + co + j * 1024, pack_bf16(o[hh][j][0], o[hh][j][1]),
                       pack_bf16(o[hh][j][2], o[hh][j][3]), pack_bf16(o[hh][j + 1][0], o[hh][j + 1][1]),
                       pack_bf16(o[hh][j + 1][2], o[hh][j + 1][3]));
            if (NJ & 1)
                stsm2t(b1 + co + (NJ - 1) * 1024, pack_bf16(o[hh][NJ - 1][0], o[hh][NJ - 1][1]),
                       pack_bf16(o[hh][NJ - 1][2], o[hh][NJ - 1][3]));
            FENCE_ASYNC();
            WG_SYNC(w);
            if (wq < 2 && elect()) {
                const int row = (node0 + w * hpb) * 4 + wq * nb;
                if (row < N * 4) tma_store(&tmo, wq ? b1 + nb * 128 : b0, hh * 64, row);
                asm volatile("cp.async.bulk.commit_group;" ::: "memory");
                if (hh) asm volatile("cp.async.bulk.wait_group.read 0;" ::: "memory");
            }
        }
    } else {
        float* accs = (float*)smem;
        constexpr int NACC = SM_EID / 2048;
        const int nnodes = max(0, min(npb, N - node0));
#pragma unroll 1
        for (int nb = 0; nb < nnodes; nb += NACC) {
            __syncthreads();
            for (int i = tid; i < NACC * 512; i += NT) accs[i] = 0.f;
            __syncthreads();
#pragma unroll 1
            for (int base = warp * 32; base < E; base += NT) {
                const int e = base + lane;
                int dl = e < E ? dst[e] - node0 - nb : -1;
                if (dl + nb >= nnodes) dl = -1;
                unsigned mask = __ballot_sync(0xffffffffu, dl >= 0 && dl < NACC);
#pragma unroll 1
                while (mask) {
                    const int l = __ffs(mask) - 1;
                    mask &= mask - 1;
                    const int ee = __shfl_sync(0xffffffffu, e, l);
                    const int dd = __shfl_sync(0xffffffffu, dl, l);
                    slow_edge(ee, src[ee], accs + dd * 512, x, sh, ea, cg, wr, lane);
                }
            }
            __syncthreads();
#pragma unroll 1
            for (int nl = warp; nl < NACC && nb + nl < nnodes; nl += NW)
                slow_out(accs + nl * 512, wout, out + (size_t)(node0 + nb + nl) * 512, lane);
        }
        __syncthreads();
    }

    TLMAX(4);
}

typedef CUresult (*EncodeTiledFn)(CUtensorMap*, CUtensorMapDataType, cuuint32_t, void*, const cuuint64_t*,
                                  const cuuint64_t*, const cuuint32_t*, const cuuint32_t*, CUtensorMapInterleave,
                                  CUtensorMapSwizzle, CUtensorMapL2promotion, CUtensorMapFloatOOBfill);

extern "C" void kernel_launch(void* const* d_in, const int* in_sizes, int n_in, void* d_out, int out_size) {
    const __nv_bfloat16* x = (const __nv_bfloat16*)d_in[0];
    const int* src = (const int*)d_in[1];
    const int* dst = (const int*)d_in[2];
    const __nv_bfloat16* sh = (const __nv_bfloat16*)d_in[3];
    const __nv_bfloat16* ea = (const __nv_bfloat16*)d_in[4];
    const __nv_bfloat16* cg = (const __nv_bfloat16*)d_in[5];
    const __nv_bfloat16* wr = (const __nv_bfloat16*)d_in[6];
    const __nv_bfloat16* wout = (const __nv_bfloat16*)d_in[7];
    __nv_bfloat16* out = (__nv_bfloat16*)d_out;
    const int N = in_sizes[0] / 512;
    const int E = in_sizes[1];

    static int num_sms = 0;
    static EncodeTiledFn encode = nullptr;
    if (num_sms == 0) {
        int dev = 0;
        cudaGetDevice(&dev);
        cudaDeviceGetAttribute(&num_sms, cudaDevAttrMultiProcessorCount, dev);
        cudaFuncSetAttribute(main_kernel, cudaFuncAttributeMaxDynamicSharedMemorySize, SM_TOTAL);
        void* fn = nullptr;
        cudaDriverEntryPointQueryResult qr;
        cudaGetDriverEntryPoint("cuTensorMapEncodeTiled", &fn, cudaEnableDefault, &qr);
        encode = (EncodeTiledFn)fn;
    }
    const int nbins = num_sms < MAXBINS ? num_sms : MAXBINS;
    int npb = ((N + nbins - 1) / nbins + 1) & ~1;
    if (npb < 32) npb = 32;
    const int fast_ok = npb <= 2 * HPB;
    auto map2d = [&](CUtensorMap* tm, const void* p, int d0, int d1, int b1) {
        const cuuint64_t gd[2] = {(cuuint64_t)d0, (cuuint64_t)d1};
        const cuuint64_t gs[1] = {(cuuint64_t)d0 * 2};
        const cuuint32_t bx[2] = {64, (cuuint32_t)b1};
        const cuuint32_t es[2] = {1, 1};
        encode(tm, CU_TENSOR_MAP_DATA_TYPE_BFLOAT16, 2, (void*)p, gd, gs, bx, es, CU_TENSOR_MAP_INTERLEAVE_NONE,
               CU_TENSOR_MAP_SWIZZLE_128B, CU_TENSOR_MAP_L2_PROMOTION_NONE, CU_TENSOR_MAP_FLOAT_OOB_FILL_NONE);
    };
    CUtensorMap tmx, tmw, tmo;
    map2d(&tmx, x, 64, N * 8, 8);
    map2d(&tmw, wout, 128, 128, 32);
    map2d(&tmo, out, 128, N * 4, fast_ok ? npb : 2);
    const unsigned npb_magic = (unsigned)((0x100000000ull + npb - 1) / npb);
    const int chunk = (E + nbins - 1) / nbins;
    int bsh = 0;
    while (((N - 1) >> bsh) >= NBK) bsh++;
    int tau16 = (int)fmin((double)PACE * 16.0 * chunk / N, 100000.0), toff = TOFF;
    main_kernel<<<nbins, NT, SM_TOTAL, cudaStreamPerThread>>>(tmx, tmw, tmo, x, src, dst, sh, ea, cg, wr, wout, out, N, E,
                                                              npb, npb_magic, chunk, fast_ok, bsh, tau16, toff);
}
```

```cpp
#include <cuda_runtime.h>
#include <cuda.h>
#include <cuda_bf16.h>
#include <stdint.h>
#include <stdlib.h>
#include <type_traits>

#define MAXBINS 256
#define NW 16
#define NT (NW * 32)
#define HPB 38
#define BINCAP 3072
#define LCAP 1472
#define NBK 160
#define CE 2
#define GSZ 6
#define NS 10
#define RING_BYTES 40960
static_assert(RING_BYTES == NS * 4096, "ring");
#define NP (NS / 2)
#define CREG 224
#define PREG 24
#define HREG 40
#define TS 8
#define SM_EVEN 0
#define SM_MISC (2 * RING_BYTES)
#define SM_ODD (SM_MISC + 128)
#define SM_BT (SM_ODD + 2 * RING_BYTES)
#define BT_B (TS * 512 + 16)
#define BT_K (4 * BT_B)
#define SM_EA (SM_BT + TS * 4096 + 128)
#define SM_WR (SM_EA + 8192)
#define SM_SIDE (SM_WR + 4096)
#define SM_EID (SM_SIDE + 2048)
#define SM_SRC (SM_EID + 2 * LCAP * 4)
#define SEQCAP (LCAP / 4 + 40)
#define SM_SEQ (SM_SRC + 2 * LCAP * 2)
#define SM_BAR (SM_SEQ + 2 * SEQCAP * 2)
#define SM_TOTAL (SM_BAR + NW * 16)
#define DUMB (2 * NP * 16)
#define MI_WBAR 32
#define MI_INT 0
#define EPS ((2464 + NT - 1) / NT)
#define KS (BINCAP / NT)
#define SC_ENT 0
#define SC_BIN (SC_ENT + NT * EPS * 8)
#define SC_HIST (SC_BIN + NT * EPS)
#define SC_CNT (SC_HIST + 3 * MAXBINS * 4)
static_assert(SC_HIST % 16 == 0 && SC_CNT + 2 * (NBK + 1) * 16 <= SM_MISC, "scratch");
static_assert(SM_TOTAL <= 232448 && SM_BAR % 16 == 0 && SM_SEQ % 16 == 0 && SM_SRC % 16 == 0 && SM_EA % 256 == 0, "smem");
#define PACE 19.4
#define TOFF 10600
#define PSLEEP 20

__device__ int2 g_bin[MAXBINS * BINCAP];
__device__ __align__(128) int g_bincnt[MAXBINS * 32];
#define TLSTAMP(i)
#define TLMAX(i)

__device__ __forceinline__ uint32_t pack_bf16(float lo, float hi) {
    uint32_t r;
    asm("cvt.rn.bf16x2.f32 %0, %1, %2;" : "=r"(r) : "f"(hi), "f"(lo));
    return r;
}
__device__ __forceinline__ void mma1688_z(float (&d)[4], uint32_t a0, uint32_t a1, uint32_t b0) {
    asm("mma.sync.aligned.m16n8k8.row.col.f32.bf16.bf16.f32 {%0,%1,%2,%3}, {%4,%5}, {%6}, {%7,%7,%7,%7};"
        : "=f"(d[0]), "=f"(d[1]), "=f"(d[2]), "=f"(d[3])
        : "r"(a0), "r"(a1), "r"(b0), "f"(0.f));
}
__device__ __forceinline__ void mma_diag(float (&d)[4], uint32_t a, uint32_t b0, uint32_t b1) {
    asm("mma.sync.aligned.m16n8k16.row.col.f32.bf16.bf16.f32 {%0,%1,%2,%3}, {%4,%8,%8,%4}, {%5,%6}, {%7,%7,%7,%7};"
        : "=f"(d[0]), "=f"(d[1]), "=f"(d[2]), "=f"(d[3])
        : "r"(a), "r"(b0), "r"(b1), "f"(0.f), "r"(0));
}
__device__ __forceinline__ uint32_t s2u(const void* p) { return (uint32_t)__cvta_generic_to_shared(p); }
__device__ __forceinline__ void mbar_init(uint32_t a, int c) {
    asm volatile("mbarrier.init.shared.b64 [%0], %1;" ::"r"(a), "r"(c));
}
__device__ __forceinline__ void mbar_expect_tx(uint32_t a, int bytes) {
    asm volatile("mbarrier.arrive.expect_tx.shared.b64 _, [%0], %1;" ::"r"(a), "r"(bytes) : "memory");
}
__device__ __forceinline__ void mbar_arrive(uint32_t a) {
    asm volatile("mbarrier.arrive.shared.b64 _, [%0];" ::"r"(a) : "memory");
}
__device__ __forceinline__ void mbar_arrive_cnt(uint32_t a, int c) {
    asm volatile("mbarrier.arrive.shared.b64 _, [%0], %1;" ::"r"(a), "r"(c) : "memory");
}
__device__ __forceinline__ void mbar_wait(uint32_t a, int parity) {
    asm volatile(
        "{\n.reg .pred p;\n.reg .u32 c;\n"
        "mov.u32 c, 0;\n"
        "LAB_WAIT:\n"
        "mbarrier.try_wait.parity.shared.b64 p, [%0], %1, 2000;\n"
        "@p bra DONE;\n"
        "add.u32 c, c, 1;\n"
        "setp.lt.u32 p, c, 2000000;\n"
        "@p bra LAB_WAIT;\n"
        "trap;\n"
        "DONE:\n}" ::"r"(a),
        "r"(parity)
        : "memory");
}
__device__ __forceinline__ void mbar_wait_u(uint32_t a, int parity) {
    asm volatile(
        "{\n.reg .pred p;\n.reg .u32 c;\n"
        "mov.u32 c, 0;\n"
        "LAB_WAIT:\n"
        "mbarrier.try_wait.parity.shared.b64 p, [%0], %1, 2000;\n"
        "@p bra.uni DONE;\n"
        "add.u32 c, c, 1;\n"
        "setp.lt.u32 p, c, 2000000;\n"
        "@p bra.uni LAB_WAIT;\n"
        "trap;\n"
        "DONE:\n}" ::"r"(a),
        "r"(parity)
        : "memory");
}
__device__ __forceinline__ void mbar_spin_u(uint32_t a, int parity) {
    asm volatile(
        "{\n.reg .pred p;\n.reg .u32 c;\n"
        "mov.u32 c, 0;\n"
        "LAB_WAIT:\n"
        "mbarrier.test_wait.parity.shared.b64 p, [%0], %1;\n"
        "@p bra.uni DONE;\n"
        "add.u32 c, c, 1;\n"
        "setp.lt.u32 p, c, 20000000;\n"
        "@p bra.uni LAB_WAIT;\n"
        "trap;\n"
        "DONE:\n}" ::"r"(a),
        "r"(parity)
        : "memory");
}
__device__ __forceinline__ void mbar_lean(uint32_t a, int parity) {
    asm volatile(
        "{\n.reg .pred p;\n.reg .u32 c;\n"
        "mov.u32 c, 0;\n"
        "LAB_WAIT:\n"
        "mbarrier.try_wait.parity.shared.b64 p, [%0], %1;\n"
        "@p bra DONE;\n"
        "add.u32 c, c, 1;\n"
        "setp.lt.u32 p, c, 4000000;\n"
        "@p bra LAB_WAIT;\n"
        "trap;\n"
        "DONE:\n}" ::"r"(a),
        "r"(parity)
        : "memory");
}
__device__ __forceinline__ void mbar_lean_u(uint32_t a, int parity) {
    asm volatile(
        "{\n.reg .pred p;\n.reg .u32 c;\n"
        "mov.u32 c, 0;\n"
        "LAB_WAIT:\n"
        "mbarrier.try_wait.parity.shared.b64 p, [%0], %1;\n"
        "@p bra.uni DONE;\n"
        "add.u32 c, c, 1;\n"
        "setp.lt.u32 p, c, 4000000;\n"
        "@p bra.uni LAB_WAIT;\n"
        "trap;\n"
        "DONE:\n}" ::"r"(a),
        "r"(parity)
        : "memory");
}
__device__ __forceinline__ bool mbar_test(uint32_t a, int parity) {
    uint32_t p;
    asm volatile("{\n.reg .pred P;\nmbarrier.test_wait.parity.shared.b64 P, [%1], %2;\nselp.u32 %0, 1, 0, P;\n}"
                 : "=r"(p)
                 : "r"(a), "r"(parity)
                 : "memory");
    return p;
}
__device__ __forceinline__ bool elect() {
    uint32_t p;
    asm volatile("{\n.reg .pred P;\nelect.sync _|P, 0xffffffff;\nselp.u32 %0, 1, 0, P;\n}" : "=r"(p));
    return p;
}
__device__ __forceinline__ void tma_2d(uint32_t dst, const CUtensorMap* tm, uint32_t bar, int c0, int c1) {
    asm volatile(
        "cp.async.bulk.tensor.2d.shared::cluster.global.mbarrier::complete_tx::bytes [%0], [%1, {%3, %4}], [%2];" ::"r"(dst),
        "l"(tm), "r"(bar), "r"(c0), "r"(c1)
        : "memory");
}
__device__ __forceinline__ void tma_row(uint32_t dst, const CUtensorMap* tm, uint32_t bar, int row8) {
    tma_2d(dst, tm, bar, 0, row8);
}
__device__ __forceinline__ void tma_store(const CUtensorMap* tm, uint32_t src, int c0, int c1) {
    asm volatile("cp.async.bulk.tensor.2d.global.shared::cta.bulk_group [%0, {%2, %3}], [%1];" ::"l"(tm), "r"(src),
                 "r"(c0), "r"(c1)
                 : "memory");
}
__device__ __forceinline__ uint2 lds_v2(uint32_t a) {
    uint2 v;
    asm volatile("ld.shared.v2.u32 {%0,%1}, [%2];" : "=r"(v.x), "=r"(v.y) : "r"(a));
    return v;
}
__device__ __forceinline__ uint4 lds_v4(uint32_t a) {
    uint4 v;
    asm volatile("ld.shared.v4.u32 {%0,%1,%2,%3}, [%4];" : "=r"(v.x), "=r"(v.y), "=r"(v.z), "=r"(v.w) : "r"(a));
    return v;
}
__device__ __forceinline__ uint32_t lds_u32(uint32_t a) {
    uint32_t v;
    asm volatile("ld.shared.u32 %0, [%1];" : "=r"(v) : "r"(a));
    return v;
}
__device__ __forceinline__ uint32_t lds_u16(uint32_t a) {
    uint32_t v;
    asm volatile("ld.shared.u16 %0, [%1];" : "=r"(v) : "r"(a));
    return v;
}
__device__ __forceinline__ void sts_v2(uint32_t a, uint32_t x, uint32_t y) {
    asm volatile("st.shared.v2.u32 [%0], {%1,%2};" ::"r"(a), "r"(x), "r"(y) : "memory");
}
__device__ __forceinline__ void sts_v4(uint32_t a, uint4 v) {
    asm volatile("st.shared.v4.u32 [%0], {%1,%2,%3,%4};" ::"r"(a), "r"(v.x), "r"(v.y), "r"(v.z), "r"(v.w) : "memory");
}
__device__ __forceinline__ void stsm4(uint32_t a, uint32_t r0, uint32_t r1, uint32_t r2, uint32_t r3) {
    asm volatile("stmatrix.sync.aligned.m8n8.x4.shared.b16 [%0], {%1,%2,%3,%4};" ::"r"(a), "r"(r0), "r"(r1), "r"(r2), "r"(r3)
                 : "memory");
}
__device__ __forceinline__ void stsm2(uint32_t a, uint32_t r0, uint32_t r1) {
    asm volatile("stmatrix.sync.aligned.m8n8.x2.shared.b16 [%0], {%1,%2};" ::"r"(a), "r"(r0), "r"(r1) : "memory");
}
__device__ __forceinline__ void stsm4t(uint32_t a, uint32_t r0, uint32_t r1, uint32_t r2, uint32_t r3) {
    asm volatile("stmatrix.sync.aligned.m8n8.x4.trans.shared.b16 [%0], {%1,%2,%3,%4};" ::"r"(a), "r"(r0), "r"(r1), "r"(r2),
                 "r"(r3)
                 : "memory");
}
__device__ __forceinline__ void stsm2t(uint32_t a, uint32_t r0, uint32_t r1) {
    asm volatile("stmatrix.sync.aligned.m8n8.x2.trans.shared.b16 [%0], {%1,%2};" ::"r"(a), "r"(r0), "r"(r1) : "memory");
}
__device__ __forceinline__ void cp_async16(uint32_t d, const void* s, int n) {
    asm volatile("cp.async.cg.shared.global [%0], [%1], 16, %2;" ::"r"(d), "l"(s), "r"(n) : "memory");
}
__device__ __forceinline__ void cp_async4(uint32_t d, const void* s, int n) {
    asm volatile("cp.async.ca.shared.global [%0], [%1], 4, %2;" ::"r"(d), "l"(s), "r"(n) : "memory");
}
__device__ __forceinline__ void sts_u32(uint32_t a, uint32_t x) {
    asm volatile("st.shared.u32 [%0], %1;" ::"r"(a), "r"(x) : "memory");
}
#define FENCE_ASYNC() asm volatile("fence.proxy.async.shared::cta;" ::: "memory")
__device__ __forceinline__ int warp_incl_scan(int v, int lane) {
#pragma unroll
    for (int o = 1; o < 32; o <<= 1) {
        const int y = __shfl_up_sync(0xffffffffu, v, o);
        if (lane >= o) v += y;
    }
    return v;
}

#define STR2(x) #x
#define STR(x) STR2(x)
#define WRS 1
#define NJ 19
__device__ __forceinline__ void consume(float (&acc)[2][NJ][4], uint32_t xa0, uint32_t xa1, uint32_t so0, uint32_t bar0,
                                        uint32_t ea0, uint32_t d0, uint32_t pl0, int lz, uint32_t wd) {
    asm volatile(
        "{\n"
        ".reg .pred p, pf, plead, pok, t0, t1, t2, u0, u1, u2;\n"
        ".reg .b32 ca, cb, cz, rbar;\n"
        "mov.b32 cz, 0;\n"
        "mov.b32 ca, 0x20002000;\n"
        "mov.b32 cb, 0x30003000;\n"
        ".reg .b32 cnt, so, q, qe, bar, nbar, pl, ctl, ctm, ix, iy, dl, v0, v1, v2, v3, pp;\n"
        ".reg .b16 sl, sh;\n"
        ".reg .b32 hXa0, hXa1, hXa2, hXa3, hXa4, hXa5, hXa6, hXa7, hXb0, hXb1, hXb2, hXb3, hXb4, hXb5, hXb6, hXb7, hYa0, hYa1, hYa2, hYa3, hYa4, hYa5, hYa6, hYa7, hYb0, hYb1, hYb2, hYb3, hYb4, hYb5, hYb6, hYb7, hLa0, hLa1, hLa2, hLa3, hLa4, hLa5, hLa6, hLa7, hLb0, hLb1, hLb2, hLb3, hLb4, hLb5, hLb6, hLb7;\n"
        ".reg .b32 pX0, pX1, pX2, pX3, pY0, pY1, pY2, pY3;\n"
        ".reg .f32 r0, r1, r2, r3, r4, r5, r6, r7, r8, r9, r10, r11, r12, r13, r14, r15;\n"
        ".reg .b64 daX, dbX, daY, dbY, de0, de1;\n"
        ".reg .b32 dh<6>, eb0, par, npar, wa<8>, uz, bend;\n"
        "mov.f32 %0, 0f00000000;\n"
        "mov.f32 %1, 0f00000000;\n"
        "mov.f32 %2, 0f00000000;\n"
        "mov.f32 %3, 0f00000000;\n"
        "mov.f32 %4, 0f00000000;\n"
        "mov.f32 %5, 0f00000000;\n"
        "mov.f32 %6, 0f00000000;\n"
        "mov.f32 %7, 0f00000000;\n"
        "mov.f32 %8, 0f00000000;\n"
        "mov.f32 %9, 0f00000000;\n"
        "mov.f32 %10, 0f00000000;\n"
        "mov.f32 %11, 0f00000000;\n"
        "mov.f32 %12, 0f00000000;\n"
        "mov.f32 %13, 0f00000000;\n"
        "mov.f32 %14, 0f00000000;\n"
        "mov.f32 %15, 0f00000000;\n"
        "mov.f32 %16, 0f00000000;\n"
        "mov.f32 %17, 0f00000000;\n"
        "mov.f32 %18, 0f00000000;\n"
        "mov.f32 %19, 0f00000000;\n"
        "mov.f32 %20, 0f00000000;\n"
        "mov.f32 %21, 0f00000000;\n"
        "mov.f32 %22, 0f00000000;\n"
        "mov.f32 %23, 0f00000000;\n"
        "mov.f32 %24, 0f00000000;\n"
        "mov.f32 %25, 0f00000000;\n"
        "mov.f32 %26, 0f00000000;\n"
        "mov.f32 %27, 0f00000000;\n"
        "mov.f32 %28, 0f00000000;\n"
        "mov.f32 %29, 0f00000000;\n"
        "mov.f32 %30, 0f00000000;\n"
        "mov.f32 %31, 0f00000000;\n"
        "mov.f32 %32, 0f00000000;\n"
        "mov.f32 %33, 0f00000000;\n"
        "mov.f32 %34, 0f00000000;\n"
        "mov.f32 %35, 0f00000000;\n"
        "mov.f32 %36, 0f00000000;\n"
        "mov.f32 %37, 0f00000000;\n"
        "mov.f32 %38, 0f00000000;\n"
        "mov.f32 %39, 0f00000000;\n"
        "mov.f32 %40, 0f00000000;\n"
        "mov.f32 %41, 0f00000000;\n"
        "mov.f32 %42, 0f00000000;\n"
        "mov.f32 %43, 0f00000000;\n"
        "mov.f32 %44, 0f00000000;\n"
        "mov.f32 %45, 0f00000000;\n"
        "mov.f32 %46, 0f00000000;\n"
        "mov.f32 %47, 0f00000000;\n"
        "mov.f32 %48, 0f00000000;\n"
        "mov.f32 %49, 0f00000000;\n"
        "mov.f32 %50, 0f00000000;\n"
        "mov.f32 %51, 0f00000000;\n"
        "mov.f32 %52, 0f00000000;\n"
        "mov.f32 %53, 0f00000000;\n"
        "mov.f32 %54, 0f00000000;\n"
        "mov.f32 %55, 0f00000000;\n"
        "mov.f32 %56, 0f00000000;\n"
        "mov.f32 %57, 0f00000000;\n"
        "mov.f32 %58, 0f00000000;\n"
        "mov.f32 %59, 0f00000000;\n"
        "mov.f32 %60, 0f00000000;\n"
        "mov.f32 %61, 0f00000000;\n"
        "mov.f32 %62, 0f00000000;\n"
        "mov.f32 %63, 0f00000000;\n"
        "mov.f32 %64, 0f00000000;\n"
        "mov.f32 %65, 0f00000000;\n"
        "mov.f32 %66, 0f00000000;\n"
        "mov.f32 %67, 0f00000000;\n"
        "mov.f32 %68, 0f00000000;\n"
        "mov.f32 %69, 0f00000000;\n"
        "mov.f32 %70, 0f00000000;\n"
        "mov.f32 %71, 0f00000000;\n"
        "mov.f32 %72, 0f00000000;\n"
        "mov.f32 %73, 0f00000000;\n"
        "mov.f32 %74, 0f00000000;\n"
        "mov.f32 %75, 0f00000000;\n"
        "mov.f32 %76, 0f00000000;\n"
        "mov.f32 %77, 0f00000000;\n"
        "mov.f32 %78, 0f00000000;\n"
        "mov.f32 %79, 0f00000000;\n"
        "mov.f32 %80, 0f00000000;\n"
        "mov.f32 %81, 0f00000000;\n"
        "mov.f32 %82, 0f00000000;\n"
        "mov.f32 %83, 0f00000000;\n"
        "mov.f32 %84, 0f00000000;\n"
        "mov.f32 %85, 0f00000000;\n"
        "mov.f32 %86, 0f00000000;\n"
        "mov.f32 %87, 0f00000000;\n"
        "mov.f32 %88, 0f00000000;\n"
        "mov.f32 %89, 0f00000000;\n"
        "mov.f32 %90, 0f00000000;\n"
        "mov.f32 %91, 0f00000000;\n"
        "mov.f32 %92, 0f00000000;\n"
        "mov.f32 %93, 0f00000000;\n"
        "mov.f32 %94, 0f00000000;\n"
        "mov.f32 %95, 0f00000000;\n"
        "mov.f32 %96, 0f00000000;\n"
        "mov.f32 %97, 0f00000000;\n"
        "mov.f32 %98, 0f00000000;\n"
        "mov.f32 %99, 0f00000000;\n"
        "mov.f32 %100, 0f00000000;\n"
        "mov.f32 %101, 0f00000000;\n"
        "mov.f32 %102, 0f00000000;\n"
        "mov.f32 %103, 0f00000000;\n"
        "mov.f32 %104, 0f00000000;\n"
        "mov.f32 %105, 0f00000000;\n"
        "mov.f32 %106, 0f00000000;\n"
        "mov.f32 %107, 0f00000000;\n"
        "mov.f32 %108, 0f00000000;\n"
        "mov.f32 %109, 0f00000000;\n"
        "mov.f32 %110, 0f00000000;\n"
        "mov.f32 %111, 0f00000000;\n"
        "mov.f32 %112, 0f00000000;\n"
        "mov.f32 %113, 0f00000000;\n"
        "mov.f32 %114, 0f00000000;\n"
        "mov.f32 %115, 0f00000000;\n"
        "mov.f32 %116, 0f00000000;\n"
        "mov.f32 %117, 0f00000000;\n"
        "mov.f32 %118, 0f00000000;\n"
        "mov.f32 %119, 0f00000000;\n"
        "mov.f32 %120, 0f00000000;\n"
        "mov.f32 %121, 0f00000000;\n"
        "mov.f32 %122, 0f00000000;\n"
        "mov.f32 %123, 0f00000000;\n"
        "mov.f32 %124, 0f00000000;\n"
        "mov.f32 %125, 0f00000000;\n"
        "mov.f32 %126, 0f00000000;\n"
        "mov.f32 %127, 0f00000000;\n"
        "mov.f32 %128, 0f00000000;\n"
        "mov.f32 %129, 0f00000000;\n"
        "mov.f32 %130, 0f00000000;\n"
        "mov.f32 %131, 0f00000000;\n"
        "mov.f32 %132, 0f00000000;\n"
        "mov.f32 %133, 0f00000000;\n"
        "mov.f32 %134, 0f00000000;\n"
        "mov.f32 %135, 0f00000000;\n"
        "mov.f32 %136, 0f00000000;\n"
        "mov.f32 %137, 0f00000000;\n"
        "mov.f32 %138, 0f00000000;\n"
        "mov.f32 %139, 0f00000000;\n"
        "mov.f32 %140, 0f00000000;\n"
        "mov.f32 %141, 0f00000000;\n"
        "mov.f32 %142, 0f00000000;\n"
        "mov.f32 %143, 0f00000000;\n"
        "mov.f32 %144, 0f00000000;\n"
        "mov.f32 %145, 0f00000000;\n"
        "mov.f32 %146, 0f00000000;\n"
        "mov.f32 %147, 0f00000000;\n"
        "mov.f32 %148, 0f00000000;\n"
        "mov.f32 %149, 0f00000000;\n"
        "mov.f32 %150, 0f00000000;\n"
        "mov.f32 %151, 0f00000000;\n"
        "setp.ne.u32 pf, 0, 0;\n"
        "add.u32 v0, %154, %159;\n"
        "shfl.sync.idx.b32 so, v0, 0, 31, 0xffffffff;\n"
        "ldmatrix.sync.aligned.m8n8.x4.trans.shared.b16 {wa0,wa1,wa2,wa3}, [%160+0];\n"
        "ldmatrix.sync.aligned.m8n8.x4.trans.shared.b16 {wa4,wa5,wa6,wa7}, [%160+2048];\n"
        "mov.u32 npar, 0;\n"
        "shfl.sync.idx.b32 uz, %159, 7, 31, 0xffffffff;\n"
        "add.u32 bend, %155, " STR(NP * 16) ";\n"
        "add.u32 v0, %159, 8;\n"
        "shfl.sync.idx.b32 dh0, v0, 0, 31, 0xffffffff;\n"
        "shfl.sync.idx.b32 dh1, v0, 1, 31, 0xffffffff;\n"
        "shfl.sync.idx.b32 dh2, v0, 2, 31, 0xffffffff;\n"
        "shfl.sync.idx.b32 dh3, v0, 3, 31, 0xffffffff;\n"
        "add.u32 v0, %159, 0xc0000010;\n"
        "shfl.sync.idx.b32 dh4, v0, 4, 31, 0xffffffff;\n"
        "shfl.sync.idx.b32 dh5, v0, 5, 31, 0xffffffff;\n"
        "add.u32 v0, %159, %156;\n"
        "shfl.sync.idx.b32 eb0, v0, 0, 31, 0xffffffff;\n"
        "mov.u32 q, 0;\n"
        "mov.u32 pl, %158;\n"
        "shr.u32 nbar, so, 9;\n"
        "add.u32 nbar, nbar, %155;\n"
        "elect.sync _|plead, 0xffffffff;\n"
        "mov.b64 de0, {%156, dh4};\n"
        "mov.b64 de1, {eb0, dh5};\n"
        "mov.b32 hLa0, 0;\n"
        "mov.b32 hLa1, 0;\n"
        "mov.b32 hLa2, 0;\n"
        "mov.b32 hLa3, 0;\n"
        "mov.b32 hLa4, 0;\n"
        "mov.b32 hLa5, 0;\n"
        "mov.b32 hLa6, 0;\n"
        "mov.b32 hLa7, 0;\n"
        "mov.b32 hLb0, 0;\n"
        "mov.b32 hLb1, 0;\n"
        "mov.b32 hLb2, 0;\n"
        "mov.b32 hLb3, 0;\n"
        "mov.b32 hLb4, 0;\n"
        "mov.b32 hLb5, 0;\n"
        "mov.b32 hLb6, 0;\n"
        "mov.b32 hLb7, 0;\n"
        "mov.b32 pY0, 0;\n"
        "mov.b32 pY1, 0;\n"
        "mov.b32 pY2, 0;\n"
        "mov.b32 pY3, 0;\n"
        "mov.u32 ctm, 0x10001000;\n"
        "add.u32 rbar, %155, " STR(DUMB) ";\n"
        "mov.b64 daX, {%157, dh0};\n"
        "mov.b64 dbX, {%157, dh1};\n"
        "mov.b64 daY, {%157, dh2};\n"
        "mov.b64 dbY, {%157, dh3};\n"
        "mov.u32 bar, nbar;\n"
        "mov.u32 par, npar;\n"
        "sub.u32 so, bar, %155;\n"
        "shl.b32 so, so, 9;\n"
        "add.u32 v0, %152, so;\n"
        "add.u32 v1, %153, so;\n"
        "add.u32 nbar, nbar, 16;\n"
        "setp.eq.u32 p, nbar, bend;\n"
        "selp.b32 nbar, %155, nbar, p;\n"
        "@p xor.b32 npar, npar, 1;\n"
        "SLOW:\n"
        "mov.u32 cnt, 0;\n"
        "W1:\n"
        "mbarrier.try_wait.parity.shared.b64 p, [bar], par;\n"
        "@p bra.uni RES;\n"
        "add.u32 cnt, cnt, 1;\n"
        "setp.lt.u32 p, cnt, 4000000;\n"
        "@p bra.uni W1;\n"
        "trap;\n"
        "CX:\n"
        "mbarrier.test_wait.parity.shared.b64 pok, [nbar], npar;\n"
        "and.b32 dl, q, 0x60;\n"
        "add.u32 dl, dl, %157;\n"
        "add.u32 v3, dl, 0;\n"
        "mov.b64 {v2, dh0}, daX;\n"
        "mov.b64 daX, {v3, dh0};\n"
        "add.u32 v3, dl, 257;\n"
        "mov.b64 {v2, dh1}, dbX;\n"
        "mov.b64 dbX, {v3, dh1};\n"
        "add.u32 v3, dl, 514;\n"
        "mov.b64 {v2, dh2}, daY;\n"
        "mov.b64 daY, {v3, dh2};\n"
        "add.u32 v3, dl, 771;\n"
        "mov.b64 {v2, dh3}, dbY;\n"
        "mov.b64 dbY, {v3, dh3};\n"
        "add.u32 q, q, 32;\n"
        "and.b32 qe, q, 0xe0;\n"
        "add.u32 v3, qe, %156;\n"
        "mov.b64 {v2, dh4}, de0;\n"
        "mov.b64 de0, {v3, dh4};\n"
        "mov.b64 {v2, dh5}, de1;\n"
        "mov.b64 de1, {v3, dh5};\n"
        "setp.lt.f16x2 t0|u0, ctl, cz;\n"
        "abs.f16x2 v3, ctl;\n"
        "setp.ge.f16x2 t1|u1, v3, ca;\n"
        "setp.geu.f16x2 t2|u2, v3, cb;\n"
        "wgmma.wait_group.sync.aligned 2;\n"
        "cvt.rn.bf16x2.f32 pX0, r1, r0;\n"
        "cvt.rn.bf16x2.f32 pX1, r3, r2;\n"
        "cvt.rn.bf16x2.f32 pX2, r9, r8;\n"
        "cvt.rn.bf16x2.f32 pX3, r11, r10;\n"
        "cvt.rn.bf16x2.f32 pY0, r5, r4;\n"
        "cvt.rn.bf16x2.f32 pY1, r7, r6;\n"
        "cvt.rn.bf16x2.f32 pY2, r13, r12;\n"
        "cvt.rn.bf16x2.f32 pY3, r15, r14;\n"
        "mov.b32 {sl, sh}, pX0;\n"
        "mov.b32 pp, {sl, sl};\n"
        "mul.rn.bf16x2 hXa0, hLa0, pp;\n"
        "mul.rn.bf16x2 hXa2, hLa2, pp;\n"
        "mov.b32 {sl, sh}, pX1;\n"
        "mov.b32 pp, {sl, sl};\n"
        "mul.rn.bf16x2 hXa1, hLa1, pp;\n"
        "mul.rn.bf16x2 hXa3, hLa3, pp;\n"
        "mov.b32 {sl, sh}, pX2;\n"
        "mov.b32 pp, {sl, sl};\n"
        "mul.rn.bf16x2 hXa4, hLa4, pp;\n"
        "mul.rn.bf16x2 hXa6, hLa6, pp;\n"
        "mov.b32 {sl, sh}, pX3;\n"
        "mov.b32 pp, {sl, sl};\n"
        "mul.rn.bf16x2 hXa5, hLa5, pp;\n"
        "mul.rn.bf16x2 hXa7, hLa7, pp;\n"
        "mov.b32 {sl, sh}, pX0;\n"
        "mov.b32 pp, {sh, sh};\n"
        "mul.rn.bf16x2 hXb0, hLb0, pp;\n"
        "mul.rn.bf16x2 hXb2, hLb2, pp;\n"
        "mov.b32 {sl, sh}, pX1;\n"
        "mov.b32 pp, {sh, sh};\n"
        "mul.rn.bf16x2 hXb1, hLb1, pp;\n"
        "mul.rn.bf16x2 hXb3, hLb3, pp;\n"
        "mov.b32 {sl, sh}, pX2;\n"
        "mov.b32 pp, {sh, sh};\n"
        "mul.rn.bf16x2 hXb4, hLb4, pp;\n"
        "mul.rn.bf16x2 hXb6, hLb6, pp;\n"
        "mov.b32 {sl, sh}, pX3;\n"
        "mov.b32 pp, {sh, sh};\n"
        "mul.rn.bf16x2 hXb5, hLb5, pp;\n"
        "mul.rn.bf16x2 hXb7, hLb7, pp;\n"
        "ldmatrix.sync.aligned.m8n8.x4.trans.shared.b16 {hLa0,hLa1,hLa2,hLa3}, [v0+4096];\n"
        "ldmatrix.sync.aligned.m8n8.x4.trans.shared.b16 {hLa4,hLa5,hLa6,hLa7}, [v1+4096];\n"
        "ldmatrix.sync.aligned.m8n8.x4.trans.shared.b16 {hLb0,hLb1,hLb2,hLb3}, [v0+6144];\n"
        "ldmatrix.sync.aligned.m8n8.x4.trans.shared.b16 {hLb4,hLb5,hLb6,hLb7}, [v1+6144];\n"
        "@t2 bra.uni T4X;\n"
        "@t1 bra.uni T2X;\n"
        "@t0 bra.uni L1X;\n"
        "L0X:\n"
        "wgmma.fence.sync.aligned;\n"
        "wgmma.mma_async.sync.aligned.m64n24k16.f32.bf16.bf16 {%0,%1,%2,%3,%4,%5,%6,%7,%8,%9,%10,%11}, {hXa0,hXa1,hXa2,hXa3}, daX, 1, 1, 1, 0;\n"
        "wgmma.mma_async.sync.aligned.m64n24k16.f32.bf16.bf16 {%76,%77,%78,%79,%80,%81,%82,%83,%84,%85,%86,%87}, {hXa4,hXa5,hXa6,hXa7}, daX, 1, 1, 1, 0;\n"
        "wgmma.commit_group.sync.aligned;\n"
        "@u2 bra.uni T4Xb;\n"
        "@u1 bra.uni T2Xb;\n"
        "@u0 bra.uni L1Xb;\n"
        "bra.uni L0Xb;\n"
        "L1X:\n"
        "wgmma.fence.sync.aligned;\n"
        "wgmma.mma_async.sync.aligned.m64n24k16.f32.bf16.bf16 {%12,%13,%14,%15,%16,%17,%18,%19,%20,%21,%22,%23}, {hXa0,hXa1,hXa2,hXa3}, daX, 1, 1, 1, 0;\n"
        "wgmma.mma_async.sync.aligned.m64n24k16.f32.bf16.bf16 {%88,%89,%90,%91,%92,%93,%94,%95,%96,%97,%98,%99}, {hXa4,hXa5,hXa6,hXa7}, daX, 1, 1, 1, 0;\n"
        "wgmma.commit_group.sync.aligned;\n"
        "@u2 bra.uni T4Xb;\n"
        "@u1 bra.uni T2Xb;\n"
        "@u0 bra.uni L1Xb;\n"
        "bra.uni L0Xb;\n"
        "T2X:\n"
        "@t0 bra.uni L3X;\n"
        "L2X:\n"
        "wgmma.fence.sync.aligned;\n"
        "wgmma.mma_async.sync.aligned.m64n24k16.f32.bf16.bf16 {%24,%25,%26,%27,%28,%29,%30,%31,%32,%33,%34,%35}, {hXa0,hXa1,hXa2,hXa3}, daX, 1, 1, 1, 0;\n"
        "wgmma.mma_async.sync.aligned.m64n24k16.f32.bf16.bf16 {%100,%101,%102,%103,%104,%105,%106,%107,%108,%109,%110,%111}, {hXa4,hXa5,hXa6,hXa7}, daX, 1, 1, 1, 0;\n"
        "wgmma.commit_group.sync.aligned;\n"
        "@u2 bra.uni T4Xb;\n"
        "@u1 bra.uni T2Xb;\n"
        "@u0 bra.uni L1Xb;\n"
        "bra.uni L0Xb;\n"
        "L3X:\n"
        "wgmma.fence.sync.aligned;\n"
        "wgmma.mma_async.sync.aligned.m64n24k16.f32.bf16.bf16 {%36,%37,%38,%39,%40,%41,%42,%43,%44,%45,%46,%47}, {hXa0,hXa1,hXa2,hXa3}, daX, 1, 1, 1, 0;\n"
        "wgmma.mma_async.sync.aligned.m64n24k16.f32.bf16.bf16 {%112,%113,%114,%115,%116,%117,%118,%119,%120,%121,%122,%123}, {hXa4,hXa5,hXa6,hXa7}, daX, 1, 1, 1, 0;\n"
        "wgmma.commit_group.sync.aligned;\n"
        "@u2 bra.uni T4Xb;\n"
        "@u1 bra.uni T2Xb;\n"
        "@u0 bra.uni L1Xb;\n"
        "bra.uni L0Xb;\n"
        "T4X:\n"
        "@!t1 bra.uni LEXIT;\n"
        "@t0 bra.uni L5X;\n"
        "L4X:\n"
        "wgmma.fence.sync.aligned;\n"
        "wgmma.mma_async.sync.aligned.m64n24k16.f32.bf16.bf16 {%48,%49,%50,%51,%52,%53,%54,%55,%56,%57,%58,%59}, {hXa0,hXa1,hXa2,hXa3}, daX, 1, 1, 1, 0;\n"
        "wgmma.mma_async.sync.aligned.m64n24k16.f32.bf16.bf16 {%124,%125,%126,%127,%128,%129,%130,%131,%132,%133,%134,%135}, {hXa4,hXa5,hXa6,hXa7}, daX, 1, 1, 1, 0;\n"
        "wgmma.commit_group.sync.aligned;\n"
        "@u2 bra.uni T4Xb;\n"
        "@u1 bra.uni T2Xb;\n"
        "@u0 bra.uni L1Xb;\n"
        "bra.uni L0Xb;\n"
        "L5X:\n"
        "wgmma.fence.sync.aligned;\n"
        "wgmma.mma_async.sync.aligned.m64n32k16.f32.bf16.bf16 {%60,%61,%62,%63,%64,%65,%66,%67,%68,%69,%70,%71,%72,%73,%74,%75}, {hXa0,hXa1,hXa2,hXa3}, daX, 1, 1, 1, 0;\n"
        "wgmma.mma_async.sync.aligned.m64n32k16.f32.bf16.bf16 {%136,%137,%138,%139,%140,%141,%142,%143,%144,%145,%146,%147,%148,%149,%150,%151}, {hXa4,hXa5,hXa6,hXa7}, daX, 1, 1, 1, 0;\n"
        "wgmma.commit_group.sync.aligned;\n"
        "@u2 bra.uni T4Xb;\n"
        "@u1 bra.uni T2Xb;\n"
        "@u0 bra.uni L1Xb;\n"
        "L0Xb:\n"
        "wgmma.fence.sync.aligned;\n"
        "wgmma.mma_async.sync.aligned.m64n24k16.f32.bf16.bf16 {%0,%1,%2,%3,%4,%5,%6,%7,%8,%9,%10,%11}, {hXb0,hXb1,hXb2,hXb3}, dbX, 1, 1, 1, 0;\n"
        "wgmma.mma_async.sync.aligned.m64n24k16.f32.bf16.bf16 {%76,%77,%78,%79,%80,%81,%82,%83,%84,%85,%86,%87}, {hXb4,hXb5,hXb6,hXb7}, dbX, 1, 1, 1, 0;\n"
        "wgmma.commit_group.sync.aligned;\n"
        "bra.uni CY;\n"
        "L1Xb:\n"
        "wgmma.fence.sync.aligned;\n"
        "wgmma.mma_async.sync.aligned.m64n24k16.f32.bf16.bf16 {%12,%13,%14,%15,%16,%17,%18,%19,%20,%21,%22,%23}, {hXb0,hXb1,hXb2,hXb3}, dbX, 1, 1, 1, 0;\n"
        "wgmma.mma_async.sync.aligned.m64n24k16.f32.bf16.bf16 {%88,%89,%90,%91,%92,%93,%94,%95,%96,%97,%98,%99}, {hXb4,hXb5,hXb6,hXb7}, dbX, 1, 1, 1, 0;\n"
        "wgmma.commit_group.sync.aligned;\n"
        "bra.uni CY;\n"
        "T2Xb:\n"
        "@u0 bra.uni L3Xb;\n"
        "L2Xb:\n"
        "wgmma.fence.sync.aligned;\n"
        "wgmma.mma_async.sync.aligned.m64n24k16.f32.bf16.bf16 {%24,%25,%26,%27,%28,%29,%30,%31,%32,%33,%34,%35}, {hXb0,hXb1,hXb2,hXb3}, dbX, 1, 1, 1, 0;\n"
        "wgmma.mma_async.sync.aligned.m64n24k16.f32.bf16.bf16 {%100,%101,%102,%103,%104,%105,%106,%107,%108,%109,%110,%111}, {hXb4,hXb5,hXb6,hXb7}, dbX, 1, 1, 1, 0;\n"
        "wgmma.commit_group.sync.aligned;\n"
        "bra.uni CY;\n"
        "L3Xb:\n"
        "wgmma.fence.sync.aligned;\n"
        "wgmma.mma_async.sync.aligned.m64n24k16.f32.bf16.bf16 {%36,%37,%38,%39,%40,%41,%42,%43,%44,%45,%46,%47}, {hXb0,hXb1,hXb2,hXb3}, dbX, 1, 1, 1, 0;\n"
        "wgmma.mma_async.sync.aligned.m64n24k16.f32.bf16.bf16 {%112,%113,%114,%115,%116,%117,%118,%119,%120,%121,%122,%123}, {hXb4,hXb5,hXb6,hXb7}, dbX, 1, 1, 1, 0;\n"
        "wgmma.commit_group.sync.aligned;\n"
        "bra.uni CY;\n"
        "T4Xb:\n"
        "@u0 bra.uni L5Xb;\n"
        "L4Xb:\n"
        "wgmma.fence.sync.aligned;\n"
        "wgmma.mma_async.sync.aligned.m64n24k16.f32.bf16.bf16 {%48,%49,%50,%51,%52,%53,%54,%55,%56,%57,%58,%59}, {hXb0,hXb1,hXb2,hXb3}, dbX, 1, 1, 1, 0;\n"
        "wgmma.mma_async.sync.aligned.m64n24k16.f32.bf16.bf16 {%124,%125,%126,%127,%128,%129,%130,%131,%132,%133,%134,%135}, {hXb4,hXb5,hXb6,hXb7}, dbX, 1, 1, 1, 0;\n"
        "wgmma.commit_group.sync.aligned;\n"
        "bra.uni CY;\n"
        "L5Xb:\n"
        "wgmma.fence.sync.aligned;\n"
        "wgmma.mma_async.sync.aligned.m64n32k16.f32.bf16.bf16 {%60,%61,%62,%63,%64,%65,%66,%67,%68,%69,%70,%71,%72,%73,%74,%75}, {hXb0,hXb1,hXb2,hXb3}, dbX, 1, 1, 1, 0;\n"
        "wgmma.mma_async.sync.aligned.m64n32k16.f32.bf16.bf16 {%136,%137,%138,%139,%140,%141,%142,%143,%144,%145,%146,%147,%148,%149,%150,%151}, {hXb4,hXb5,hXb6,hXb7}, dbX, 1, 1, 1, 0;\n"
        "wgmma.commit_group.sync.aligned;\n"
        "bra.uni CY;\n"
        "CY:\n"
        "mov.u32 rbar, bar;\n"
        "mov.u32 bar, nbar;\n"
        "mov.u32 par, npar;\n"
        "sub.u32 so, bar, %155;\n"
        "shl.b32 so, so, 9;\n"
        "add.u32 v0, %152, so;\n"
        "add.u32 v1, %153, so;\n"
        "add.u32 nbar, nbar, 16;\n"
        "setp.eq.u32 p, nbar, bend;\n"
        "selp.b32 nbar, %155, nbar, p;\n"
        "@p xor.b32 npar, npar, 1;\n"
        "@!pok bra.uni SLOW;\n"
        "RES:\n"
        "wgmma.wait_group.sync.aligned 2;\n"
        "lop3.b32 v2, hLa3, hLa7, hLb3, 0x80;\n"
        "lop3.b32 v2, v2, hLb7, uz, 0x80;\n"
        "add.u32 v2, v2, rbar;\n"
        "@plead mbarrier.arrive.shared.b64 _, [v2+8];\n"
        "setp.lt.f16x2 t0|u0, ctm, cz;\n"
        "abs.f16x2 v3, ctm;\n"
        "setp.ge.f16x2 t1|u1, v3, ca;\n"
        "setp.geu.f16x2 t2|u2, v3, cb;\n"
        "ld.shared.v2.u32 {ctl, ctm}, [pl];\n"
        "add.u32 pl, pl, 8;\n"
        "mov.b32 {sl, sh}, pY0;\n"
        "mov.b32 pp, {sl, sl};\n"
        "mul.rn.bf16x2 hYa0, hLa0, pp;\n"
        "mul.rn.bf16x2 hYa2, hLa2, pp;\n"
        "mov.b32 {sl, sh}, pY1;\n"
        "mov.b32 pp, {sl, sl};\n"
        "mul.rn.bf16x2 hYa1, hLa1, pp;\n"
        "mul.rn.bf16x2 hYa3, hLa3, pp;\n"
        "mov.b32 {sl, sh}, pY2;\n"
        "mov.b32 pp, {sl, sl};\n"
        "mul.rn.bf16x2 hYa4, hLa4, pp;\n"
        "mul.rn.bf16x2 hYa6, hLa6, pp;\n"
        "mov.b32 {sl, sh}, pY3;\n"
        "mov.b32 pp, {sl, sl};\n"
        "mul.rn.bf16x2 hYa5, hLa5, pp;\n"
        "mul.rn.bf16x2 hYa7, hLa7, pp;\n"
        "mov.b32 {sl, sh}, pY0;\n"
        "mov.b32 pp, {sh, sh};\n"
        "mul.rn.bf16x2 hYb0, hLb0, pp;\n"
        "mul.rn.bf16x2 hYb2, hLb2, pp;\n"
        "mov.b32 {sl, sh}, pY1;\n"
        "mov.b32 pp, {sh, sh};\n"
        "mul.rn.bf16x2 hYb1, hLb1, pp;\n"
        "mul.rn.bf16x2 hYb3, hLb3, pp;\n"
        "mov.b32 {sl, sh}, pY2;\n"
        "mov.b32 pp, {sh, sh};\n"
        "mul.rn.bf16x2 hYb4, hLb4, pp;\n"
        "mul.rn.bf16x2 hYb6, hLb6, pp;\n"
        "mov.b32 {sl, sh}, pY3;\n"
        "mov.b32 pp, {sh, sh};\n"
        "mul.rn.bf16x2 hYb5, hLb5, pp;\n"
        "mul.rn.bf16x2 hYb7, hLb7, pp;\n"
        "ldmatrix.sync.aligned.m8n8.x4.trans.shared.b16 {hLa0,hLa1,hLa2,hLa3}, [v0+0];\n"
        "ldmatrix.sync.aligned.m8n8.x4.trans.shared.b16 {hLa4,hLa5,hLa6,hLa7}, [v1+0];\n"
        "ldmatrix.sync.aligned.m8n8.x4.trans.shared.b16 {hLb0,hLb1,hLb2,hLb3}, [v0+2048];\n"
        "ldmatrix.sync.aligned.m8n8.x4.trans.shared.b16 {hLb4,hLb5,hLb6,hLb7}, [v1+2048];\n"
        "wgmma.wait_group.sync.aligned 0;\n"
        "@t2 bra.uni T4Y;\n"
        "@t1 bra.uni T2Y;\n"
        "@t0 bra.uni L1Y;\n"
        "L0Y:\n"
        "wgmma.fence.sync.aligned;\n"
        "wgmma.mma_async.sync.aligned.m64n16k16.f32.bf16.bf16 {r0,r1,r2,r3,r4,r5,r6,r7}, {wa0,wa1,wa2,wa3}, de0, pf, 1, 1, 0;\n"
        "wgmma.mma_async.sync.aligned.m64n16k16.f32.bf16.bf16 {r8,r9,r10,r11,r12,r13,r14,r15}, {wa4,wa5,wa6,wa7}, de1, pf, 1, 1, 0;\n"
        "wgmma.commit_group.sync.aligned;\n"
        "wgmma.mma_async.sync.aligned.m64n24k16.f32.bf16.bf16 {%0,%1,%2,%3,%4,%5,%6,%7,%8,%9,%10,%11}, {hYa0,hYa1,hYa2,hYa3}, daY, 1, 1, 1, 0;\n"
        "wgmma.mma_async.sync.aligned.m64n24k16.f32.bf16.bf16 {%76,%77,%78,%79,%80,%81,%82,%83,%84,%85,%86,%87}, {hYa4,hYa5,hYa6,hYa7}, daY, 1, 1, 1, 0;\n"
        "wgmma.commit_group.sync.aligned;\n"
        "@u2 bra.uni T4Yb;\n"
        "@u1 bra.uni T2Yb;\n"
        "@u0 bra.uni L1Yb;\n"
        "bra.uni L0Yb;\n"
        "L1Y:\n"
        "wgmma.fence.sync.aligned;\n"
        "wgmma.mma_async.sync.aligned.m64n16k16.f32.bf16.bf16 {r0,r1,r2,r3,r4,r5,r6,r7}, {wa0,wa1,wa2,wa3}, de0, pf, 1, 1, 0;\n"
        "wgmma.mma_async.sync.aligned.m64n16k16.f32.bf16.bf16 {r8,r9,r10,r11,r12,r13,r14,r15}, {wa4,wa5,wa6,wa7}, de1, pf, 1, 1, 0;\n"
        "wgmma.commit_group.sync.aligned;\n"
        "wgmma.mma_async.sync.aligned.m64n24k16.f32.bf16.bf16 {%12,%13,%14,%15,%16,%17,%18,%19,%20,%21,%22,%23}, {hYa0,hYa1,hYa2,hYa3}, daY, 1, 1, 1, 0;\n"
        "wgmma.mma_async.sync.aligned.m64n24k16.f32.bf16.bf16 {%88,%89,%90,%91,%92,%93,%94,%95,%96,%97,%98,%99}, {hYa4,hYa5,hYa6,hYa7}, daY, 1, 1, 1, 0;\n"
        "wgmma.commit_group.sync.aligned;\n"
        "@u2 bra.uni T4Yb;\n"
        "@u1 bra.uni T2Yb;\n"
        "@u0 bra.uni L1Yb;\n"
        "bra.uni L0Yb;\n"
        "T2Y:\n"
        "@t0 bra.uni L3Y;\n"
        "L2Y:\n"
        "wgmma.fence.sync.aligned;\n"
        "wgmma.mma_async.sync.aligned.m64n16k16.f32.bf16.bf16 {r0,r1,r2,r3,r4,r5,r6,r7}, {wa0,wa1,wa2,wa3}, de0, pf, 1, 1, 0;\n"
        "wgmma.mma_async.sync.aligned.m64n16k16.f32.bf16.bf16 {r8,r9,r10,r11,r12,r13,r14,r15}, {wa4,wa5,wa6,wa7}, de1, pf, 1, 1, 0;\n"
        "wgmma.commit_group.sync.aligned;\n"
        "wgmma.mma_async.sync.aligned.m64n24k16.f32.bf16.bf16 {%24,%25,%26,%27,%28,%29,%30,%31,%32,%33,%34,%35}, {hYa0,hYa1,hYa2,hYa3}, daY, 1, 1, 1, 0;\n"
        "wgmma.mma_async.sync.aligned.m64n24k16.f32.bf16.bf16 {%100,%101,%102,%103,%104,%105,%106,%107,%108,%109,%110,%111}, {hYa4,hYa5,hYa6,hYa7}, daY, 1, 1, 1, 0;\n"
        "wgmma.commit_group.sync.aligned;\n"
        "@u2 bra.uni T4Yb;\n"
        "@u1 bra.uni T2Yb;\n"
        "@u0 bra.uni L1Yb;\n"
        "bra.uni L0Yb;\n"
        "L3Y:\n"
        "wgmma.fence.sync.aligned;\n"
        "wgmma.mma_async.sync.aligned.m64n16k16.f32.bf16.bf16 {r0,r1,r2,r3,r4,r5,r6,r7}, {wa0,wa1,wa2,wa3}, de0, pf, 1, 1, 0;\n"
        "wgmma.mma_async.sync.aligned.m64n16k16.f32.bf16.bf16 {r8,r9,r10,r11,r12,r13,r14,r15}, {wa4,wa5,wa6,wa7}, de1, pf, 1, 1, 0;\n"
        "wgmma.commit_group.sync.aligned;\n"
        "wgmma.mma_async.sync.aligned.m64n24k16.f32.bf16.bf16 {%36,%37,%38,%39,%40,%41,%42,%43,%44,%45,%46,%47}, {hYa0,hYa1,hYa2,hYa3}, daY, 1, 1, 1, 0;\n"
        "wgmma.mma_async.sync.aligned.m64n24k16.f32.bf16.bf16 {%112,%113,%114,%115,%116,%117,%118,%119,%120,%121,%122,%123}, {hYa4,hYa5,hYa6,hYa7}, daY, 1, 1, 1, 0;\n"
        "wgmma.commit_group.sync.aligned;\n"
        "@u2 bra.uni T4Yb;\n"
        "@u1 bra.uni T2Yb;\n"
        "@u0 bra.uni L1Yb;\n"
        "bra.uni L0Yb;\n"
        "T4Y:\n"
        "@t0 bra.uni L5Y;\n"
        "L4Y:\n"
        "wgmma.fence.sync.aligned;\n"
        "wgmma.mma_async.sync.aligned.m64n16k16.f32.bf16.bf16 {r0,r1,r2,r3,r4,r5,r6,r7}, {wa0,wa1,wa2,wa3}, de0, pf, 1, 1, 0;\n"
        "wgmma.mma_async.sync.aligned.m64n16k16.f32.bf16.bf16 {r8,r9,r10,r11,r12,r13,r14,r15}, {wa4,wa5,wa6,wa7}, de1, pf, 1, 1, 0;\n"
        "wgmma.commit_group.sync.aligned;\n"
        "wgmma.mma_async.sync.aligned.m64n24k16.f32.bf16.bf16 {%48,%49,%50,%51,%52,%53,%54,%55,%56,%57,%58,%59}, {hYa0,hYa1,hYa2,hYa3}, daY, 1, 1, 1, 0;\n"
        "wgmma.mma_async.sync.aligned.m64n24k16.f32.bf16.bf16 {%124,%125,%126,%127,%128,%129,%130,%131,%132,%133,%134,%135}, {hYa4,hYa5,hYa6,hYa7}, daY, 1, 1, 1, 0;\n"
        "wgmma.commit_group.sync.aligned;\n"
        "@u2 bra.uni T4Yb;\n"
        "@u1 bra.uni T2Yb;\n"
        "@u0 bra.uni L1Yb;\n"
        "bra.uni L0Yb;\n"
        "L5Y:\n"
        "wgmma.fence.sync.aligned;\n"
        "wgmma.mma_async.sync.aligned.m64n16k16.f32.bf16.bf16 {r0,r1,r2,r3,r4,r5,r6,r7}, {wa0,wa1,wa2,wa3}, de0, pf, 1, 1, 0;\n"
        "wgmma.mma_async.sync.aligned.m64n16k16.f32.bf16.bf16 {r8,r9,r10,r11,r12,r13,r14,r15}, {wa4,wa5,wa6,wa7}, de1, pf, 1, 1, 0;\n"
        "wgmma.commit_group.sync.aligned;\n"
        "wgmma.mma_async.sync.aligned.m64n32k16.f32.bf16.bf16 {%60,%61,%62,%63,%64,%65,%66,%67,%68,%69,%70,%71,%72,%73,%74,%75}, {hYa0,hYa1,hYa2,hYa3}, daY, 1, 1, 1, 0;\n"
        "wgmma.mma_async.sync.aligned.m64n32k16.f32.bf16.bf16 {%136,%137,%138,%139,%140,%141,%142,%143,%144,%145,%146,%147,%148,%149,%150,%151}, {hYa4,hYa5,hYa6,hYa7}, daY, 1, 1, 1, 0;\n"
        "wgmma.commit_group.sync.aligned;\n"
        "@u2 bra.uni T4Yb;\n"
        "@u1 bra.uni T2Yb;\n"
        "@u0 bra.uni L1Yb;\n"
        "L0Yb:\n"
        "wgmma.fence.sync.aligned;\n"
        "wgmma.mma_async.sync.aligned.m64n24k16.f32.bf16.bf16 {%0,%1,%2,%3,%4,%5,%6,%7,%8,%9,%10,%11}, {hYb0,hYb1,hYb2,hYb3}, dbY, 1, 1, 1, 0;\n"
        "wgmma.mma_async.sync.aligned.m64n24k16.f32.bf16.bf16 {%76,%77,%78,%79,%80,%81,%82,%83,%84,%85,%86,%87}, {hYb4,hYb5,hYb6,hYb7}, dbY, 1, 1, 1, 0;\n"
        "wgmma.commit_group.sync.aligned;\n"
        "bra.uni CX;\n"
        "L1Yb:\n"
        "wgmma.fence.sync.aligned;\n"
        "wgmma.mma_async.sync.aligned.m64n24k16.f32.bf16.bf16 {%12,%13,%14,%15,%16,%17,%18,%19,%20,%21,%22,%23}, {hYb0,hYb1,hYb2,hYb3}, dbY, 1, 1, 1, 0;\n"
        "wgmma.mma_async.sync.aligned.m64n24k16.f32.bf16.bf16 {%88,%89,%90,%91,%92,%93,%94,%95,%96,%97,%98,%99}, {hYb4,hYb5,hYb6,hYb7}, dbY, 1, 1, 1, 0;\n"
        "wgmma.commit_group.sync.aligned;\n"
        "bra.uni CX;\n"
        "T2Yb:\n"
        "@u0 bra.uni L3Yb;\n"
        "L2Yb:\n"
        "wgmma.fence.sync.aligned;\n"
        "wgmma.mma_async.sync.aligned.m64n24k16.f32.bf16.bf16 {%24,%25,%26,%27,%28,%29,%30,%31,%32,%33,%34,%35}, {hYb0,hYb1,hYb2,hYb3}, dbY, 1, 1, 1, 0;\n"
        "wgmma.mma_async.sync.aligned.m64n24k16.f32.bf16.bf16 {%100,%101,%102,%103,%104,%105,%106,%107,%108,%109,%110,%111}, {hYb4,hYb5,hYb6,hYb7}, dbY, 1, 1, 1, 0;\n"
        "wgmma.commit_group.sync.aligned;\n"
        "bra.uni CX;\n"
        "L3Yb:\n"
        "wgmma.fence.sync.aligned;\n"
        "wgmma.mma_async.sync.aligned.m64n24k16.f32.bf16.bf16 {%36,%37,%38,%39,%40,%41,%42,%43,%44,%45,%46,%47}, {hYb0,hYb1,hYb2,hYb3}, dbY, 1, 1, 1, 0;\n"
        "wgmma.mma_async.sync.aligned.m64n24k16.f32.bf16.bf16 {%112,%113,%114,%115,%116,%117,%118,%119,%120,%121,%122,%123}, {hYb4,hYb5,hYb6,hYb7}, dbY, 1, 1, 1, 0;\n"
        "wgmma.commit_group.sync.aligned;\n"
        "bra.uni CX;\n"
        "T4Yb:\n"
        "@u0 bra.uni L5Yb;\n"
        "L4Yb:\n"
        "wgmma.fence.sync.aligned;\n"
        "wgmma.mma_async.sync.aligned.m64n24k16.f32.bf16.bf16 {%48,%49,%50,%51,%52,%53,%54,%55,%56,%57,%58,%59}, {hYb0,hYb1,hYb2,hYb3}, dbY, 1, 1, 1, 0;\n"
        "wgmma.mma_async.sync.aligned.m64n24k16.f32.bf16.bf16 {%124,%125,%126,%127,%128,%129,%130,%131,%132,%133,%134,%135}, {hYb4,hYb5,hYb6,hYb7}, dbY, 1, 1, 1, 0;\n"
        "wgmma.commit_group.sync.aligned;\n"
        "bra.uni CX;\n"
        "L5Yb:\n"
        "wgmma.fence.sync.aligned;\n"
        "wgmma.mma_async.sync.aligned.m64n32k16.f32.bf16.bf16 {%60,%61,%62,%63,%64,%65,%66,%67,%68,%69,%70,%71,%72,%73,%74,%75}, {hYb0,hYb1,hYb2,hYb3}, dbY, 1, 1, 1, 0;\n"
        "wgmma.mma_async.sync.aligned.m64n32k16.f32.bf16.bf16 {%136,%137,%138,%139,%140,%141,%142,%143,%144,%145,%146,%147,%148,%149,%150,%151}, {hYb4,hYb5,hYb6,hYb7}, dbY, 1, 1, 1, 0;\n"
        "wgmma.commit_group.sync.aligned;\n"
        "bra.uni CX;\n"
        "LEXIT:\n"
        "wgmma.wait_group.sync.aligned 0;\n"
        "}\n"
        : "=f"(acc[0][0][0]), "=f"(acc[0][0][1]), "=f"(acc[0][0][2]), "=f"(acc[0][0][3]),
          "=f"(acc[0][1][0]), "=f"(acc[0][1][1]), "=f"(acc[0][1][2]), "=f"(acc[0][1][3]),
          "=f"(acc[0][2][0]), "=f"(acc[0][2][1]), "=f"(acc[0][2][2]), "=f"(acc[0][2][3]),
          "=f"(acc[0][3][0]), "=f"(acc[0][3][1]), "=f"(acc[0][3][2]), "=f"(acc[0][3][3]),
          "=f"(acc[0][4][0]), "=f"(acc[0][4][1]), "=f"(acc[0][4][2]), "=f"(acc[0][4][3]),
          "=f"(acc[0][5][0]), "=f"(acc[0][5][1]), "=f"(acc[0][5][2]), "=f"(acc[0][5][3]),
          "=f"(acc[0][6][0]), "=f"(acc[0][6][1]), "=f"(acc[0][6][2]), "=f"(acc[0][6][3]),
          "=f"(acc[0][7][0]), "=f"(acc[0][7][1]), "=f"(acc[0][7][2]), "=f"(acc[0][7][3]),
          "=f"(acc[0][8][0]), "=f"(acc[0][8][1]), "=f"(acc[0][8][2]), "=f"(acc[0][8][3]),
          "=f"(acc[0][9][0]), "=f"(acc[0][9][1]), "=f"(acc[0][9][2]), "=f"(acc[0][9][3]),
          "=f"(acc[0][10][0]), "=f"(acc[0][10][1]), "=f"(acc[0][10][2]), "=f"(acc[0][10][3]),
          "=f"(acc[0][11][0]), "=f"(acc[0][11][1]), "=f"(acc[0][11][2]), "=f"(acc[0][11][3]),
          "=f"(acc[0][12][0]), "=f"(acc[0][12][1]), "=f"(acc[0][12][2]), "=f"(acc[0][12][3]),
          "=f"(acc[0][13][0]), "=f"(acc[0][13][1]), "=f"(acc[0][13][2]), "=f"(acc[0][13][3]),
          "=f"(acc[0][14][0]), "=f"(acc[0][14][1]), "=f"(acc[0][14][2]), "=f"(acc[0][14][3]),
          "=f"(acc[0][15][0]), "=f"(acc[0][15][1]), "=f"(acc[0][15][2]), "=f"(acc[0][15][3]),
          "=f"(acc[0][16][0]), "=f"(acc[0][16][1]), "=f"(acc[0][16][2]), "=f"(acc[0][16][3]),
          "=f"(acc[0][17][0]), "=f"(acc[0][17][1]), "=f"(acc[0][17][2]), "=f"(acc[0][17][3]),
          "=f"(acc[0][18][0]), "=f"(acc[0][18][1]), "=f"(acc[0][18][2]), "=f"(acc[0][18][3]),
          "=f"(acc[1][0][0]), "=f"(acc[1][0][1]), "=f"(acc[1][0][2]), "=f"(acc[1][0][3]),
          "=f"(acc[1][1][0]), "=f"(acc[1][1][1]), "=f"(acc[1][1][2]), "=f"(acc[1][1][3]),
          "=f"(acc[1][2][0]), "=f"(acc[1][2][1]), "=f"(acc[1][2][2]), "=f"(acc[1][2][3]),
          "=f"(acc[1][3][0]), "=f"(acc[1][3][1]), "=f"(acc[1][3][2]), "=f"(acc[1][3][3]),
          "=f"(acc[1][4][0]), "=f"(acc[1][4][1]), "=f"(acc[1][4][2]), "=f"(acc[1][4][3]),
          "=f"(acc[1][5][0]), "=f"(acc[1][5][1]), "=f"(acc[1][5][2]), "=f"(acc[1][5][3]),
          "=f"(acc[1][6][0]), "=f"(acc[1][6][1]), "=f"(acc[1][6][2]), "=f"(acc[1][6][3]),
          "=f"(acc[1][7][0]), "=f"(acc[1][7][1]), "=f"(acc[1][7][2]), "=f"(acc[1][7][3]),
          "=f"(acc[1][8][0]), "=f"(acc[1][8][1]), "=f"(acc[1][8][2]), "=f"(acc[1][8][3]),
          "=f"(acc[1][9][0]), "=f"(acc[1][9][1]), "=f"(acc[1][9][2]), "=f"(acc[1][9][3]),
          "=f"(acc[1][10][0]), "=f"(acc[1][10][1]), "=f"(acc[1][10][2]), "=f"(acc[1][10][3]),
          "=f"(acc[1][11][0]), "=f"(acc[1][11][1]), "=f"(acc[1][11][2]), "=f"(acc[1][11][3]),
          "=f"(acc[1][12][0]), "=f"(acc[1][12][1]), "=f"(acc[1][12][2]), "=f"(acc[1][12][3]),
          "=f"(acc[1][13][0]), "=f"(acc[1][13][1]), "=f"(acc[1][13][2]), "=f"(acc[1][13][3]),
          "=f"(acc[1][14][0]), "=f"(acc[1][14][1]), "=f"(acc[1][14][2]), "=f"(acc[1][14][3]),
          "=f"(acc[1][15][0]), "=f"(acc[1][15][1]), "=f"(acc[1][15][2]), "=f"(acc[1][15][3]),
          "=f"(acc[1][16][0]), "=f"(acc[1][16][1]), "=f"(acc[1][16][2]), "=f"(acc[1][16][3]),
          "=f"(acc[1][17][0]), "=f"(acc[1][17][1]), "=f"(acc[1][17][2]), "=f"(acc[1][17][3]),
          "=f"(acc[1][18][0]), "=f"(acc[1][18][1]), "=f"(acc[1][18][2]), "=f"(acc[1][18][3])
        : "r"(xa0), "r"(xa1), "r"(so0), "r"(bar0), "r"(ea0), "r"(d0), "r"(pl0), "r"(lz), "r"(wd)
        : "memory");
}
__device__ __forceinline__ void wgmma_out(float (&o)[NJ][4], uint64_t da, uint64_t db, int acc) {
    asm volatile(
        "{\n.reg .pred p;\nsetp.ne.b32 p, %78, 0;\n"
        "wgmma.mma_async.sync.aligned.m64n152k16.f32.bf16.bf16 {%0,%1,%2,%3,%4,%5,%6,%7,%8,%9,%10,%11,%12,%13,%14,%15,%16,%17,%18,%19,%20,%21,%22,%23,%24,%25,%26,%27,%28,%29,%30,%31,%32,%33,%34,%35,%36,%37,%38,%39,%40,%41,%42,%43,%44,%45,%46,%47,%48,%49,%50,%51,%52,%53,%54,%55,%56,%57,%58,%59,%60,%61,%62,%63,%64,%65,%66,%67,%68,%69,%70,%71,%72,%73,%74,%75}, %76, %77, p, 1, 1, 1, 1;\n}"
        : "+f"(o[0][0]), "+f"(o[0][1]), "+f"(o[0][2]), "+f"(o[0][3]),
          "+f"(o[1][0]), "+f"(o[1][1]), "+f"(o[1][2]), "+f"(o[1][3]),
          "+f"(o[2][0]), "+f"(o[2][1]), "+f"(o[2][2]), "+f"(o[2][3]),
          "+f"(o[3][0]), "+f"(o[3][1]), "+f"(o[3][2]), "+f"(o[3][3]),
          "+f"(o[4][0]), "+f"(o[4][1]), "+f"(o[4][2]), "+f"(o[4][3]),
          "+f"(o[5][0]), "+f"(o[5][1]), "+f"(o[5][2]), "+f"(o[5][3]),
          "+f"(o[6][0]), "+f"(o[6][1]), "+f"(o[6][2]), "+f"(o[6][3]),
          "+f"(o[7][0]), "+f"(o[7][1]), "+f"(o[7][2]), "+f"(o[7][3]),
          "+f"(o[8][0]), "+f"(o[8][1]), "+f"(o[8][2]), "+f"(o[8][3]),
          "+f"(o[9][0]), "+f"(o[9][1]), "+f"(o[9][2]), "+f"(o[9][3]),
          "+f"(o[10][0]), "+f"(o[10][1]), "+f"(o[10][2]), "+f"(o[10][3]),
          "+f"(o[11][0]), "+f"(o[11][1]), "+f"(o[11][2]), "+f"(o[11][3]),
          "+f"(o[12][0]), "+f"(o[12][1]), "+f"(o[12][2]), "+f"(o[12][3]),
          "+f"(o[13][0]), "+f"(o[13][1]), "+f"(o[13][2]), "+f"(o[13][3]),
          "+f"(o[14][0]), "+f"(o[14][1]), "+f"(o[14][2]), "+f"(o[14][3]),
          "+f"(o[15][0]), "+f"(o[15][1]), "+f"(o[15][2]), "+f"(o[15][3]),
          "+f"(o[16][0]), "+f"(o[16][1]), "+f"(o[16][2]), "+f"(o[16][3]),
          "+f"(o[17][0]), "+f"(o[17][1]), "+f"(o[17][2]), "+f"(o[17][3]),
          "+f"(o[18][0]), "+f"(o[18][1]), "+f"(o[18][2]), "+f"(o[18][3])
        : "l"(da), "l"(db), "r"(acc));
}

__device__ __forceinline__ void slow_edge(int ee, int s, float* accn, const __nv_bfloat16* __restrict__ x,
                                          const __nv_bfloat16* __restrict__ sh, const __nv_bfloat16* __restrict__ ea,
                                          const __nv_bfloat16* __restrict__ cg, const __nv_bfloat16* __restrict__ wr,
                                          int lane) {
    float rwv[4] = {0.f, 0.f, 0.f, 0.f};
#pragma unroll 4
    for (int d = 0; d < 16; d++) {
        const float a = __bfloat162float(ea[(size_t)ee * 16 + d]);
        const uint2 wv = *(const uint2*)(wr + d * 128 + lane * 4);
        rwv[0] += a * __uint_as_float(wv.x << 16);
        rwv[1] += a * __uint_as_float(wv.x & 0xffff0000u);
        rwv[2] += a * __uint_as_float(wv.y << 16);
        rwv[3] += a * __uint_as_float(wv.y & 0xffff0000u);
    }
    float A = 0.f;
#pragma unroll
    for (int v = 0; v < 4; v++)
        A += __bfloat162float(cg[((lane >> 2) & 3) * 16 + v * 4 + (lane & 3)]) * __bfloat162float(sh[(size_t)ee * 4 + v]);
    float m[4][4];
#pragma unroll
    for (int w = 0; w < 4; w++)
#pragma unroll
        for (int j = 0; j < 4; j++) m[w][j] = 0.f;
#pragma unroll
    for (int u = 0; u < 4; u++) {
        const uint2 xv = *(const uint2*)(x + (size_t)s * 512 + u * 128 + lane * 4);
        const float x0 = __uint_as_float(xv.x << 16), x1 = __uint_as_float(xv.x & 0xffff0000u);
        const float x2 = __uint_as_float(xv.y << 16), x3 = __uint_as_float(xv.y & 0xffff0000u);
#pragma unroll
        for (int w = 0; w < 4; w++) {
            const float a = __shfl_sync(0xffffffffu, A, u * 4 + w);
            m[w][0] += a * x0;
            m[w][1] += a * x1;
            m[w][2] += a * x2;
            m[w][3] += a * x3;
        }
    }
#pragma unroll
    for (int w = 0; w < 4; w++)
#pragma unroll
        for (int j = 0; j < 4; j++) atomicAdd(accn + w * 128 + lane * 4 + j, m[w][j] * rwv[j]);
}

__device__ __forceinline__ void slow_out(const float* accn, const __nv_bfloat16* __restrict__ wout,
                                         __nv_bfloat16* __restrict__ outn, int lane) {
    float o[4][4];
#pragma unroll
    for (int w = 0; w < 4; w++)
#pragma unroll
        for (int j = 0; j < 4; j++) o[w][j] = 0.f;
#pragma unroll 2
    for (int c = 0; c < 128; c++) {
        const uint2 wv = *(const uint2*)(wout + c * 128 + lane * 4);
        const float w0 = __uint_as_float(wv.x << 16), w1 = __uint_as_float(wv.x & 0xffff0000u);
        const float w2 = __uint_as_float(wv.y << 16), w3 = __uint_as_float(wv.y & 0xffff0000u);
#pragma unroll
        for (int w = 0; w < 4; w++) {
            const float a = __bfloat162float(__float2bfloat16(accn[w * 128 + c]));
            o[w][0] += a * w0;
            o[w][1] += a * w1;
            o[w][2] += a * w2;
            o[w][3] += a * w3;
        }
    }
#pragma unroll
    for (int w = 0; w < 4; w++)
        *(uint2*)(outn + w * 128 + lane * 4) = make_uint2(pack_bf16(o[w][0], o[w][1]), pack_bf16(o[w][2], o[w][3]));
}

static_assert(NW > 3 * NP, "barriers");
#define FPOS 1
#define EMASK 0xffffff
#define TBIN 0
#define PW 0
#define TWAIT mbar_lean_u
#define PWAIT mbar_lean
#define TMA_ROW(k) "@pl cp.async.bulk.tensor.2d.shared::cluster.global.mbarrier::complete_tx::bytes [d" #k "], [tm, {z" #k ", r" #k "}], [b" #k "];\n"
#define TMA_INIT(k, o) "shfl.sync.idx.b32 z" #k ", %12, " #k ", 31, 0xffffffff;\nadd.u32 d" #k ", %4, " STR(o) ";\n"
#define TMA_PREP(k) "add.u32 d" #k ", d" #k ", dd;\nadd.u32 b" #k ", %0, z" #k ";\n"
#define PSRC "and.b32 sq, sq, 0x3fe;\nand.b32 sr, sr, 0x3fe;\nmad.lo.u32 sq, sq, 4, %7;\nmad.lo.u32 sr, sr, 4, %7;\n"
#define TA 1
#define TB 2
#define TC 5
#define TD 6
__device__ __forceinline__ void produce(const CUtensorMap* tm, uint32_t& fb, uint32_t& par, uint32_t bend, uint32_t d0, uint32_t ps,
                                        uint32_t pe, uint32_t psrc, uint32_t tbase, uint32_t lim, uint32_t taug, uint32_t taus, int lz
) {
    asm volatile(
        "{\n.reg .pred p, pl, ok;\n.reg .b32 a<4>, r<8>, d<8>, b<8>, z<8>, sq, sr, ps, lim, tgt, tgu, c, dd, t0;\n"
        ".reg .b64 st, tm;\n"
        "elect.sync _|pl, 0xffffffff;\n"
        TMA_INIT(0, 0) TMA_INIT(1, SM_ODD) TMA_INIT(2, 1024) TMA_INIT(3, SM_ODD + 1024)
        TMA_INIT(4, 4096) TMA_INIT(5, SM_ODD + 4096) TMA_INIT(6, 5120) TMA_INIT(7, SM_ODD + 5120)
        "mov.b64 {a0, a1}, %2;\n"
        "add.u32 a0, a0, %12;\n"
        "add.u32 a1, a1, %12;\n"
        "shfl.sync.idx.b32 a0, a0, 0, 31, 0xffffffff;\n"
        "shfl.sync.idx.b32 a1, a1, 0, 31, 0xffffffff;\n"
        "mov.b64 tm, {a0, a1};\n"
        "mov.u32 ps, %5;\n"
        "mov.u32 lim, %9;\n"
        "mov.u32 dd, 0;\n"
        "ld.shared.u16 sq, [ps];\n"
        "ld.shared.u16 sr, [ps+4];\n"
        PSRC
        "ld.shared.v2.u32 {a0, a1}, [sq];\n"
        "ld.shared.v2.u32 {a2, a3}, [sr];\n"
        "ld.shared.u16 sq, [ps+8];\n"
        "ld.shared.u16 sr, [ps+12];\n"
        "mbarrier.test_wait.parity.shared.b64 ok, [%0+8], %1;\n"
        "setp.ge.u32 p, ps, %6;\n"
        "@p bra.uni PEND;\n"
        "PLOOP:\n"
        "mov.u32 t0, %%clock;\n"
        PSRC
        "shl.b32 r0, a0, 3;\nand.b32 r0, r0, 0x7fff8;\nshr.u32 r1, a0, 13;\nand.b32 r1, r1, 0x7fff8;\n"
        "shl.b32 r2, a1, 3;\nand.b32 r2, r2, 0x7fff8;\nshr.u32 r3, a1, 13;\nand.b32 r3, r3, 0x7fff8;\n"
        "shl.b32 r4, a2, 3;\nand.b32 r4, r4, 0x7fff8;\nshr.u32 r5, a2, 13;\nand.b32 r5, r5, 0x7fff8;\n"
        "shl.b32 r6, a3, 3;\nand.b32 r6, r6, 0x7fff8;\nshr.u32 r7, a3, 13;\nand.b32 r7, r7, 0x7fff8;\n"
        "add.u32 tgt, r" STR(TA) ", r" STR(TB) ";\nmul.lo.u32 tgt, tgt, %11;\nshr.u32 tgt, tgt, 8;\nadd.u32 tgt, tgt, %8;\n"
        "add.u32 tgu, r" STR(TC) ", r" STR(TD) ";\nmul.lo.u32 tgu, tgu, %11;\nshr.u32 tgu, tgu, 8;\nadd.u32 tgu, tgu, %8;\n"
        "min.u32 tgt, tgt, lim;\n"
        "add.u32 lim, lim, %10;\n"
        "min.u32 tgu, tgu, lim;\n"
        "add.u32 lim, lim, %10;\n"
        "ld.shared.v2.u32 {a0, a1}, [sq];\n"
        "ld.shared.v2.u32 {a2, a3}, [sr];\n"
        "ld.shared.u16 sq, [ps+16];\n"
        "ld.shared.u16 sr, [ps+20];\n"
        "add.u32 ps, ps, 8;\n"
        TMA_PREP(0) TMA_PREP(1) TMA_PREP(2) TMA_PREP(3) TMA_PREP(4) TMA_PREP(5) TMA_PREP(6) TMA_PREP(7)
        "sub.s32 c, t0, tgt;\n"
        "setp.ge.and.s32 p, c, 0, ok;\n"
        "@!p bra.uni PSLP;\n"
        "PRES:\n"
        "@pl mbarrier.arrive.expect_tx.shared.b64 _, [%0], 8192;\n"
        TMA_ROW(0) TMA_ROW(1) TMA_ROW(2) TMA_ROW(3)
        "PSL2:\n"
        "mov.u32 c, %%clock;\n"
        "sub.s32 c, c, tgu;\n"
        "setp.lt.s32 p, c, 0;\n"
        "@p nanosleep.u32 " STR(PSLEEP) ";\n"
        "@p bra.uni PSL2;\n"
        TMA_ROW(4) TMA_ROW(5) TMA_ROW(6) TMA_ROW(7)
        "setp.eq.u32 p, %0, %3;\n"
        "selp.b32 c, " STR(16 - NP * 16) ", 16, p;\n"
        "add.u32 %0, %0, c;\n"
        "shl.b32 dd, c, 9;\n"
        "selp.b32 c, 1, 0, p;\n"
        "xor.b32 %1, %1, c;\n"
        "mbarrier.test_wait.parity.shared.b64 ok, [%0+8], %1;\n"
        "setp.lt.u32 p, ps, %6;\n"
        "@p bra.uni PLOOP;\n"
        "bra.uni PEND;\n"
        "PSLP:\n"
        "mov.u32 c, %%clock;\n"
        "sub.s32 c, c, tgt;\n"
        "setp.lt.s32 p, c, 0;\n"
        "@p nanosleep.u32 " STR(PSLEEP) ";\n"
        "@p bra.uni PSLP;\n"
        "@ok bra.uni PRES;\n"
        "mov.u32 c, 0;\n"
        "PW:\n"
        "mbarrier.try_wait.parity.shared.b64 p, [%0+8], %1;\n"
        "@p bra.uni PRES;\n"
        "add.u32 c, c, 1;\n"
        "setp.lt.u32 p, c, 4000000;\n"
        "@p bra.uni PW;\n"
        "trap;\n"
        "PEND:\n}"
        : "+r"(fb), "+r"(par)
        : "l"(tm), "r"(bend), "r"(d0), "r"(ps), "r"(pe), "r"(psrc), "r"(tbase), "r"(lim), "r"(taug), "r"(taus), "r"(lz)
        : "memory");
}
#define GCODE(g) ((((g) >> 1) + 1) << 12 | ((g) & 1) << 15)
#define WG_SYNC(w) asm volatile("bar.sync %0, 128;" ::"r"((w) + 1) : "memory")
__global__ void __launch_bounds__(NT, 1)
main_kernel(const __grid_constant__ CUtensorMap tmx, const __grid_constant__ CUtensorMap tmw,
            const __grid_constant__ CUtensorMap tmo, const __nv_bfloat16* __restrict__ x, const int* __restrict__ src,
            const int* __restrict__ dst, const __nv_bfloat16* __restrict__ sh, const __nv_bfloat16* __restrict__ ea,
            const __nv_bfloat16* __restrict__ cg, const __nv_bfloat16* __restrict__ wr,
            const __nv_bfloat16* __restrict__ wout, __nv_bfloat16* __restrict__ out, int N, int E, int npb,
            unsigned npb_magic, int chunk, int fast_ok, int bsh, int tau16, int toff) {
    extern __shared__ __align__(1024) unsigned char smem[];
    const uint32_t sb = s2u(smem);
    int* s_int = (int*)(smem + SM_MISC + MI_INT);
    int* s_hist = (int*)(smem + SC_HIST);
    const int tid = threadIdx.x;
    const int warp = __shfl_sync(0xffffffffu, tid >> 5, 0), lane = tid & 31;
    const int g = lane >> 2, t = lane & 3;

    TLSTAMP(0);
    const int nbins = gridDim.x;
    const int bin = blockIdx.x;
    const int node0 = bin * npb, hpb = npb >> 1;
    const int ebeg = min(E, bin * chunk), eend = min(E, ebeg + chunk);
    int pd[EPS], ps[EPS];
#pragma unroll
    for (int k = 0; k < EPS; k++) {
        const int e = ebeg + tid + k * NT;
        pd[k] = e < eend ? __ldg(dst + e) : -1;
        ps[k] = e < eend ? __ldg(src + e) : 0;
    }
    int2* st_ent = (int2*)(smem + SC_ENT);
    unsigned char* st_bin = smem + SC_BIN;
    int* s_loc = s_hist + MAXBINS;
    int* s_del = s_loc + MAXBINS;
    if (lane < 2) mbar_init(sb + SM_BAR + (warp * 2 + lane) * 8, 3 + lane);
    if (tid < MAXBINS) s_hist[tid] = 0;
    if (tid == 0) {
        mbar_init(sb + SM_MISC + MI_WBAR, 4);
        asm volatile("prefetch.tensormap [%0];" ::"l"(&tmx) : "memory");
    }
    if (tid < 2 * (NBK + 1)) ((uint4*)(smem + SC_CNT))[tid] = make_uint4(0, 0, 0, 0);
#pragma unroll
    for (int k = 0; k < TS / 2; k++) ((uint4*)(smem + SM_BT))[tid + k * NT] = make_uint4(0, 0, 0, 0);
    if (tid < 8) ((uint4*)(smem + SM_BT))[tid + TS / 2 * NT] = make_uint4(0, 0, 0, 0);
    __syncthreads();
    TLSTAMP(1);
    for (int rb = ebeg;; rb += NT * EPS) {
        const bool last = rb + NT * EPS >= eend;
        int pb[EPS], pr[EPS];
#pragma unroll
        for (int k = 0; k < EPS; k++) {
            pb[k] = pd[k] >= 0 ? (int)__umulhi((unsigned)pd[k], npb_magic) : -1;
            if (pb[k] >= 0) pr[k] = atomicAdd(&s_hist[pb[k]], 1);
        }
        if (tid == 0) asm volatile("mov.u32 %0, %%globaltimer_lo;" : "=r"(s_int[3]));
        __syncthreads();
        TLSTAMP(6);
        const int now = s_int[3];
        int gbase = 0;
        if (warp == NW - 1) {
            int v[MAXBINS / 32], sum = 0;
#pragma unroll
            for (int c = 0; c < MAXBINS / 32; c++) {
                v[c] = s_hist[lane * (MAXBINS / 32) + c];
                sum += v[c];
            }
            int run = warp_incl_scan(sum, lane) - sum;
#pragma unroll
            for (int c = 0; c < MAXBINS / 32; c++) {
                s_loc[lane * (MAXBINS / 32) + c] = run;
                run += v[c];
            }
        } else if (tid < nbins) {
            if (bin == TBIN && last) __stcg(&g_bincnt[tid * 32 + 1], now | 1);
            gbase = atomicAdd(&g_bincnt[tid * 32], s_hist[tid] + (last ? 1 << 22 : 0));
        }
        __syncthreads();
#pragma unroll
        for (int k = 0; k < EPS; k++) {
            if (pb[k] >= 0) {
                const int pos = s_loc[pb[k]] + pr[k];
                st_ent[pos] = make_int2(ps[k], (rb + tid + k * NT) | ((pd[k] - pb[k] * npb) << 24) | 0x80000000);
                st_bin[pos] = pb[k];
            }
        }
        if (tid < nbins) s_del[tid] = (gbase & 0x3fffff) - s_loc[tid];
        __syncthreads();
        TLSTAMP(8);
        const int n = min(eend - rb, NT * EPS);
#pragma unroll
        for (int k = 0; k < EPS; k++) {
            const int i = tid + k * NT;
            if (i < n) {
                const int b = st_bin[i];
                const int gpos = i + s_del[b];
                if (gpos < BINCAP) __stcg(&g_bin[b * BINCAP + gpos], st_ent[i]);
            }
        }
        if (last) break;
        if (tid < MAXBINS) s_hist[tid] = 0;
#pragma unroll
        for (int k = 0; k < EPS; k++) {
            const int e = rb + NT * EPS + tid + k * NT;
            pd[k] = e < eend ? dst[e] : -1;
            ps[k] = e < eend ? src[e] : 0;
        }
        __syncthreads();
    }
    TLSTAMP(5);
    int2 ent[KS];
    uint2 wv;
    int rank[KS];
    {
        int cnt = 0;
        if (lane == 0) {
            int tsum;
            for (int spin = 0;; spin++) {
                asm volatile("ld.relaxed.gpu.global.v2.s32 {%0,%1}, [%2];" : "=r"(cnt), "=r"(tsum) : "l"(&g_bincnt[bin * 32]) : "memory");
                if ((cnt >> 22) >= nbins && tsum) break;
                if (spin > 10000000) __trap();
            }
            if (tid == 0) s_int[3] = tsum;
        }
        cnt = __shfl_sync(0xffffffffu, cnt, 0) & 0x3fffff;
        if (tid == 0) s_int[0] = cnt;
        const int n = min(cnt, BINCAP);
        unsigned pend = 0;
#pragma unroll
        for (int k = 0; k < KS; k++) {
            ent[k] = make_int2(0, 0);
            if (tid + k * NT < n) pend |= 1u << k;
        }
        int2* gp = &g_bin[bin * BINCAP + tid];
        for (int spin = 0; __any_sync(0xffffffffu, pend); spin++) {
#pragma unroll
            for (int k = 0; k < KS; k++)
                if ((pend >> k) & 1)
                    asm volatile("ld.relaxed.gpu.global.v2.s32 {%0,%1}, [%2];"
                                 : "=r"(ent[k].x), "=r"(ent[k].y)
                                 : "l"(gp + k * NT)
                                 : "memory");
#pragma unroll
            for (int k = 0; k < KS; k++)
                if (ent[k].y < 0) pend &= ~(1u << k);
            if (spin > 10000000) __trap();
        }
        TLSTAMP(2);
        asm volatile("ld.global.nc.v2.u32 {%0,%1}, [%2];" : "=r"(wv.x), "=r"(wv.y) : "l"((const uint2*)wr + tid));
#pragma unroll
        for (int k = 0; k < KS; k++) {
            if (ent[k].y < 0) {
                if (fast_ok) {
                    const int dl = (ent[k].y >> 24) & 127, w = dl >= hpb;
                    const int loc = dl - (w ? hpb : 0), gr = GSZ == 6 ? min(loc * 43 >> 8, 5) : loc >> 3, sft = (gr & 1) * 16;
                    const int cw = (w * (NBK + 1) + (ent[k].x >> bsh)) * 4 + (gr >> 1);
                    const unsigned old = atomicAdd((unsigned*)(smem + SC_CNT) + cw, 1u << sft);
                    rank[k] = ((old >> sft) & 0xffff) | GCODE(gr);
                    ent[k].x |= cw << 16;
                    ent[k].y = (ent[k].y & 0x80ffffff) | ((loc - gr * GSZ) << 24);
                }
                __stcg(gp + k * NT, make_int2(0, 0));
            }
        }
    }
    __syncthreads();
    if (tid == 0) *(int2*)&g_bincnt[bin * 32] = make_int2(0, 0);
    TLSTAMP(9);
    if (warp < 2) {
        uint4* cp = (uint4*)(smem + SC_CNT) + warp * (NBK + 1) + lane * (NBK / 32);
        uint4 v[NBK / 32];
        uint32_t s[3] = {0, 0, 0}, r[3], tot[3], base[3];
#pragma unroll
        for (int c = 0; c < NBK / 32; c++) {
            v[c] = cp[c];
            s[0] += v[c].x;
            s[1] += v[c].y;
            s[2] += v[c].z;
        }
        uint32_t sum = 0;
#pragma unroll
        for (int i = 0; i < 3; i++) {
            r[i] = warp_incl_scan(s[i], lane);
            tot[i] = __shfl_sync(0xffffffffu, r[i], 31);
            r[i] -= s[i];
            const uint32_t p = (tot[i] + 0x00030003u) & 0xfffcfffcu;
            base[i] = sum * 0x10001u + (p << 16);
            sum += (p & 0xffff) + (p >> 16);
        }
        auto blocks = [](const uint32_t(&a)[3]) {
            constexpr uint32_t c = (3 - CE) * 0x10001u;
            const uint32_t q = (((a[0] + c) >> 2) & 0x3fff3fffu) + (((a[1] + c) >> 2) & 0x3fff3fffu) + (((a[2] + c) >> 2) & 0x3fff3fffu);
            return (q & 0xffff) + (q >> 16);
        };
#pragma unroll
        for (int c = 0; c < NBK / 32; c++) {
            cp[c] = make_uint4(r[0] + base[0], r[1] + base[1], r[2] + base[2], blocks(r));
            r[0] += v[c].x;
            r[1] += v[c].y;
            r[2] += v[c].z;
        }
        const bool ok = sum + 4 <= LCAP;
        const int nst = sum >> 2;
        const int npr = (nst + 3) >> 2;
        const uint32_t tw = g < 2 ? tot[0] : g < 4 ? tot[1] : tot[2], bw = g < 2 ? base[0] : g < 4 ? base[1] : base[2];
        const int le = g < 6 ? ((tw + bw) >> ((g & 1) * 16)) & 0xffff : sum;
        const bool tailb = t == 0 && (le & 3) >= 1 && (le & 3) <= CE;
        const unsigned tm = __ballot_sync(0xffffffffu, tailb);
        if (ok) {
            {
                const int i = (le & ~3) + t;
                if (i >= le) {
                    ((unsigned short*)(smem + SM_SRC))[warp * LCAP + i] = min(node0, N - 1);
                    ((uint32_t*)(smem + SM_EID))[warp * LCAP + i] = 0x80000000u;
                }
            }
            if (tailb) {
                const int i = blocks(tot) + __popc(tm & ((1u << lane) - 1));
                ((unsigned short*)(smem + SM_SEQ))[warp * SEQCAP + i] = (le >> 2) * 2 | GCODE(g);
            }
            ((unsigned short*)(smem + SM_SEQ))[warp * SEQCAP + nst + lane] = nst * 2 | (lane < (-nst & 3) ? GCODE(0) : 0x7c01);
        }
        if (lane < NP - 1 - npr % NP) {
            mbar_arrive_cnt(sb + SM_BAR + (warp * NP + lane) * 16, 3);
            mbar_arrive_cnt(sb + SM_BAR + (warp * NP + lane) * 16 + 8, 4);
        }
        if (lane == 0) s_int[1 + warp] = ok ? npr : -1;
    }
    __syncthreads();
    TLSTAMP(10);
    const bool fast = s_int[0] <= BINCAP && fast_ok && (s_int[1] | s_int[2]) >= 0;
    if (fast) {
        int pos[KS];
#pragma unroll
        for (int k = 0; k < KS; k++)
            if (ent[k].y < 0) pos[k] = ((uint32_t*)(smem + SC_CNT))[ent[k].x >> 16];
#pragma unroll
        for (int k = 0; k < KS; k++) {
            if (ent[k].y < 0) {
                const int w = (ent[k].x >> 16) >= (NBK + 1) * 4;
                const int p = (((uint32_t)pos[k] >> ((rank[k] >> 11) & 16)) & 0xffff) + (rank[k] & 0xfff);
                ((unsigned short*)(smem + SM_SRC))[w * LCAP + p] = ent[k].x;
                ((uint32_t*)(smem + SM_EID))[w * LCAP + p] = ent[k].y & 0x7fffffff;
                if ((p & 3) == CE) {
                    const int i = atomicAdd((int*)(smem + SC_CNT) + ((ent[k].x >> 16) | 3), 1);
                    ((unsigned short*)(smem + SM_SEQ))[w * SEQCAP + i] = (p >> 2) * 2 | (rank[k] & 0xf000);
                }
            }
        }
    }
    sts_v2(sb + SM_WR + ((tid >> 1) & 15) * 256 + (tid >> 5) * 16 + (tid & 1) * 8, wv.x, wv.y);
    FENCE_ASYNC();
    TLSTAMP(15);
    __syncthreads();
    TLSTAMP(3);

    if (fast && warp >= 12) {
        asm volatile("setmaxnreg.dec.sync.aligned.u32 %0;" ::"n"(HREG));
        const int w = warp & 1, j = (warp >> 1) & 1;
        const int npr = __shfl_sync(0xffffffffu, s_int[1 + w], 0);
        const uint32_t bar0 = sb + SM_BAR + w * NP * 16;
        const int blk = (lane >> 4) * 2 + (t >> 1);
        uint32_t fseq = sb + SM_SEQ + w * SEQCAP * 2 + j * 8 + blk * 2;
        const uint32_t feid = sb + SM_EID + w * LCAP * 4 + (g & 3) * 4;
        uint32_t pea = sb + SM_EA + w * 4096 + j * 512 + (lane ^ ((lane >> 3) & 1)) * 16;
        const uint32_t psd = sb + SM_SIDE + (warp - 12) * 512 + (lane >> 1) * 16 + (lane & 1) * 4;
        const uint32_t pt = sb + SM_BT + w * (TS * 256) + j * 512 + blk * BT_B + ((lane ^ (lane >> 3)) & 1) * BT_K + (g & 3) * 4;
        const char* gea = (const char*)ea + (lane & 1) * 16;
        uint32_t es, va[2], ta[2], old[2] = {pt, pt}, dea = 2048;
        auto ids = [&]() {
            es = lds_u32(feid + (lds_u16(fseq) & 0x3fe) * 8);
            fseq += 16;
        };
        uint32_t wf[4];
        {
            const uint2* cp = (const uint2*)cg + (g & 3) * 4 + (t & 1) * 2;
            uint2 c0 = make_uint2(0, 0), c1 = c0;
            if ((g >> 2) == (t >> 1)) c0 = __ldg(cp), c1 = __ldg(cp + 1);
            wf[0] = __byte_perm(c0.x, c1.x, 0x5410), wf[1] = __byte_perm(c0.x, c1.x, 0x7632);
            wf[2] = __byte_perm(c0.y, c1.y, 0x5410), wf[3] = __byte_perm(c0.y, c1.y, 0x7632);
        }
        static_assert((TS / 2 + 1) % NP == 0, "the slot of pair m + 1 - TS / 2 is the slot of pair m + 2");
        uint32_t vf = bar0 + (NP - 1 - npr % NP + j) % NP * 16;
        uint32_t pe = NP - 1 - npr % NP + j < NP;
        auto run = [&](auto odd) {
            auto fetch = [&](int i) {
                asm volatile(
                    "{\n.reg .pred p, q;\n.reg .b32 e;\n.reg .b64 a;\n"
                    "setp.lt.s32 p, %0, 0;\n"
                    "and.b32 e, %0, 0xffffff;\n"
                    "mad.wide.u32 a, e, 32, %1;\n"
                    "cp.async.cg.shared.global [%2], [a], 16, p;\n"
                    "}" ::"r"(es), "l"(gea), "r"(pea + i * 1024) : "memory");
                va[i] = psd + (es & 1) * 8;
                ta[i] = pt + ((es & 0x7000000) >> 18);
                if (odd.value) {
                    cp_async4(va[i] + i * 256, (const char*)sh + (size_t)(es & 0xffffff) * 8 + (lane & 1) * 4, (int)es >= 0 ? 4 : 0);
                } else {
                    asm volatile(
                        "{\n.reg .pred p, q;\n.reg .b32 e;\n.reg .b64 a;\n"
                        "setp.lt.s32 p, %0, 0;\n"
                        "setp.eq.u32 q, %3, 0;\n"
                        "and.b32 e, %0, 0xfffffe;\n"
                        "mad.wide.u32 a, e, 8, %1;\n"
                        "@q cp.async.cg.shared.global [%2], [a], 16, p;\n"
                        "}" ::"r"(es), "l"(sh), "r"(psd + i * 256), "r"(lane & 1) : "memory");
                }
                asm volatile("cp.async.commit_group;" ::: "memory");
                if (i) pea += dea, dea = -dea;
            };
            ids();
            fetch(0);
            ids();
            fetch(1);
#pragma unroll 1
            for (int m = (npr + 1 - j) >> 1; m > 0;) {
#pragma unroll
                for (int i = 0; i < 2; i++) {
                    asm volatile("cp.async.wait_group 1;" ::: "memory");
                    __syncwarp();
                    const uint32_t v = lds_u32(va[i] + i * 256);
                    ids();
                    float d0[4], d1[4];
                    mma_diag(d0, v, wf[0], wf[1]);
                    mma_diag(d1, v, wf[2], wf[3]);
                    uint32_t vn = vf + 32;
                    if (vn >= bar0 + NP * 16) vn -= NP * 16, pe ^= 1;
                    TWAIT(vn + 8, pe);
#pragma unroll
                    for (int k = 0; k < 4; k++) sts_u32(old[i] + i * 1024 + k * 16, 0);
                    old[i] = ta[i];
                    sts_u32(old[i] + i * 1024, pack_bf16(d0[0], d0[1]));
                    sts_u32(old[i] + i * 1024 + 16, pack_bf16(d0[2], d0[3]));
                    sts_u32(old[i] + i * 1024 + 32, pack_bf16(d1[0], d1[1]));
                    sts_u32(old[i] + i * 1024 + 48, pack_bf16(d1[2], d1[3]));
                    FENCE_ASYNC();
                    fetch(i);
                    __syncwarp();
                    if (lane == 0) mbar_arrive(vf);
                    vf = vn;
                    if (--m <= 0) break;
                }
            }
        };
        if (E & 1) run(std::true_type()); else run(std::false_type());
        asm volatile("cp.async.wait_group 0;" ::: "memory");
        TLMAX(13);
    } else if (fast && warp >= 8) {
        asm volatile("setmaxnreg.dec.sync.aligned.u32 %0;" ::"n"(PREG));
        const int w = warp & 1, j = (warp >> 1) & 1;
        const int nst = 2 * __shfl_sync(0xffffffffu, s_int[1 + w], 0);
        const uint32_t bar0 = sb + SM_BAR + w * NP * 16, ring = sb + w * RING_BYTES + j * 4096;
        const uint32_t pseq = sb + SM_SEQ + w * SEQCAP * 2 + j * 2;
        unsigned now;
        asm volatile("mov.u32 %0, %%globaltimer_lo;" : "=r"(now));
        const int ago = min(max((int)(now - s_int[3]), 0), 1 << 16) * 7 >> 2;
        const unsigned tbase = __shfl_sync(0xffffffffu, (unsigned)clock() - ago, 0) + (unsigned)toff;
        const unsigned taug = __shfl_sync(0xffffffffu, (N * tau16 >> 4) / max(nst, 1), 0);
        uint32_t fb = bar0 + (NP - 1 - (nst >> 1) % NP) * 16, par = 1;
        produce(&tmx, fb, par, bar0 + NP * 16 - 16, ring - j * 2048 + (fb - bar0) * 512, pseq, pseq + nst * 4, sb + SM_SRC + w * LCAP * 2, tbase,
                tbase + (N * tau16 >> 8), taug, tau16, lane & (E >> 31)
        );
        if (elect()) {
            const uint32_t d = ring + (NP - 1) * 8192;
            mbar_wait(fb + 8, par);
            mbar_arrive_cnt(fb, 1 + j);
            mbar_expect_tx(sb + SM_MISC + MI_WBAR, 8192);
            tma_2d(d + SM_EVEN, &tmw, sb + SM_MISC + MI_WBAR, w * 64, j * 32);
            tma_2d(d + SM_ODD, &tmw, sb + SM_MISC + MI_WBAR, w * 64, j * 32 + 64);
        }
        TLMAX(12);
    } else if (fast) {
        asm volatile("setmaxnreg.inc.sync.aligned.u32 %0;" ::"n"(CREG));
        const int w = warp >> 2, wq = warp & 3;
        const int nst = __shfl_sync(0xffffffffu, s_int[1 + w], 0);
        const uint32_t ring = sb + w * RING_BYTES;
        float acc[2][NJ][4];
        {
            const int e = (lane >> 1) & 3, m = lane >> 3;
            const int line = 2 * ((lane & 1) + 2 * ((m >> 1) ^ (e >> 1))), ch = 2 * wq + (m & 1);
            const uint32_t xb = ring + (e & 1 ? SM_ODD : SM_EVEN) + (e >> 1) * 1024 + line * 128;
            consume(acc, xb + ((ch ^ ((line + (e & 1)) & 7)) * 16), xb + 128 + ((ch ^ ((line + 1 + (e & 1)) & 7)) * 16),
                    (NP - 1 - nst % NP) * 8192, sb + SM_BAR + w * NP * 16, (((sb + SM_EA + w * 4096) & 0x3ffff) >> 4) | (1 << 16),
                    (((sb + SM_BT + w * (TS * 256)) & 0x3ffff) >> 4) | (BT_K / 16 << 16), sb + SM_SEQ + w * SEQCAP * 2, lane & (E >> 31),
                    sb + SM_WR + wq * 512 + ((lane >> 3) & 1) * 256 + (lane >> 4) * 128 + (lane & 7) * 16);
        }
        TLMAX(11);
#pragma unroll
        for (int h = 0; h < 2; h++) {
            const uint32_t tb = ring + (h ? SM_ODD : SM_EVEN) + wq * (NJ * 256) + lane * 16;
#pragma unroll
            for (int j = 0; j + 1 < NJ; j += 2)
                stsm4(tb + j * 256, pack_bf16(acc[h][j][0], acc[h][j][1]), pack_bf16(acc[h][j][2], acc[h][j][3]),
                      pack_bf16(acc[h][j + 1][0], acc[h][j + 1][1]), pack_bf16(acc[h][j + 1][2], acc[h][j + 1][3]));
            if (NJ & 1)
                stsm2(tb + (NJ - 1) * 256, pack_bf16(acc[h][NJ - 1][0], acc[h][NJ - 1][1]),
                      pack_bf16(acc[h][NJ - 1][2], acc[h][NJ - 1][3]));
        }
        FENCE_ASYNC();
        WG_SYNC(w);
        mbar_wait_u(sb + SM_MISC + MI_WBAR, 0);
        float o[2][NJ][4];
        asm volatile("wgmma.fence.sync.aligned;" ::: "memory");
#pragma unroll
        for (int hh = 0; hh < 2; hh++) {
#pragma unroll
            for (int ks = 0; ks < 8; ks++) {
                const uint32_t rg = ks >> 2 ? SM_ODD : SM_EVEN;
                const uint64_t da = (uint64_t)(((sb + rg + hh * RING_BYTES + (NS - 2) * 4096 + (ks & 3) * 2048) & 0x3ffff) >> 4) |
                                    (64ull << 32) | (1ull << 62);
                const uint64_t db = (uint64_t)(((ring + rg + (ks & 3) * (NJ * 256)) & 0x3ffff) >> 4) | (8ull << 16) | (16ull << 32);
                wgmma_out(o[hh], da, db, ks);
            }
            asm volatile("wgmma.commit_group.sync.aligned;" ::: "memory");
        }
        const int nb = 2 * hpb;
#pragma unroll
        for (int hh = 0; hh < 2; hh++) {
            if (hh == 0) {
                asm volatile("wgmma.wait_group.sync.aligned 1;" ::: "memory");
            } else {
                asm volatile("wgmma.wait_group.sync.aligned 0;" ::: "memory");
                WG_SYNC(w);
            }
#pragma unroll
            for (int j = 0; j < NJ; j++)
#pragma unroll
                for (int k = 0; k < 4; k++) asm volatile("" : "+f"(o[hh][j][k])::"memory");
            const uint32_t b0 = ring + SM_EVEN + (hh ? 0 : 20480);
            const uint32_t b1 = hh ? b0 : ring + SM_ODD + 20480 + 896 - (nb * 128 & ~1023);
            const int r = (lane & 7) + (lane >> 4) * 8;
            const uint32_t co = r * 128 + (((2 * wq + ((lane >> 3) & 1)) ^ (lane & 7)) * 16);
#pragma unroll
            for (int j = 0; j + 1 < NJ; j += 2)
                stsm4t((8 * j + r < nb ? b0 : b1) + co + j * 1024, pack_bf16(o[hh][j][0], o[hh][j][1]),
                       pack_bf16(o[hh][j][2], o[hh][j][3]), pack_bf16(o[hh][j + 1][0], o[hh][j + 1][1]),
                       pack_bf16(o[hh][j + 1][2], o[hh][j + 1][3]));
            if (NJ & 1)
                stsm2t(b1 + co + (NJ - 1) * 1024, pack_bf16(o[hh][NJ - 1][0], o[hh][NJ - 1][1]),
                       pack_bf16(o[hh][NJ - 1][2], o[hh][NJ - 1][3]));
            FENCE_ASYNC();
            WG_SYNC(w);
            if (wq < 2 && elect()) {
                const int row = (node0 + w * hpb) * 4 + wq * nb;
                if (row < N * 4) tma_store(&tmo, wq ? b1 + nb * 128 : b0, hh * 64, row);
                asm volatile("cp.async.bulk.commit_group;" ::: "memory");
                if (hh) asm volatile("cp.async.bulk.wait_group.read 0;" ::: "memory");
            }
        }
    } else {
        float* accs = (float*)smem;
        constexpr int NACC = SM_EID / 2048;
        const int nnodes = max(0, min(npb, N - node0));
#pragma unroll 1
        for (int nb = 0; nb < nnodes; nb += NACC) {
            __syncthreads();
            for (int i = tid; i < NACC * 512; i += NT) accs[i] = 0.f;
            __syncthreads();
#pragma unroll 1
            for (int base = warp * 32; base < E; base += NT) {
                const int e = base + lane;
                int dl = e < E ? dst[e] - node0 - nb : -1;
                if (dl + nb >= nnodes) dl = -1;
                unsigned mask = __ballot_sync(0xffffffffu, dl >= 0 && dl < NACC);
#pragma unroll 1
                while (mask) {
                    const int l = __ffs(mask) - 1;
                    mask &= mask - 1;
                    const int ee = __shfl_sync(0xffffffffu, e, l);
                    const int dd = __shfl_sync(0xffffffffu, dl, l);
                    slow_edge(ee, src[ee], accs + dd * 512, x, sh, ea, cg, wr, lane);
                }
            }
            __syncthreads();
#pragma unroll 1
            for (int nl = warp; nl < NACC && nb + nl < nnodes; nl += NW)
                slow_out(accs + nl * 512, wout, out + (size_t)(node0 + nb + nl) * 512, lane);
        }
        __syncthreads();
    }

    TLMAX(4);
}

typedef CUresult (*EncodeTiledFn)(CUtensorMap*, CUtensorMapDataType, cuuint32_t, void*, const cuuint64_t*,
                                  const cuuint64_t*, const cuuint32_t*, const cuuint32_t*, CUtensorMapInterleave,
                                  CUtensorMapSwizzle, CUtensorMapL2promotion, CUtensorMapFloatOOBfill);

extern "C" void kernel_launch(void* const* d_in, const int* in_sizes, int n_in, void* d_out, int out_size) {
    const __nv_bfloat16* x = (const __nv_bfloat16*)d_in[0];
    const int* src = (const int*)d_in[1];
    const int* dst = (const int*)d_in[2];
    const __nv_bfloat16* sh = (const __nv_bfloat16*)d_in[3];
    const __nv_bfloat16* ea = (const __nv_bfloat16*)d_in[4];
    const __nv_bfloat16* cg = (const __nv_bfloat16*)d_in[5];
    const __nv_bfloat16* wr = (const __nv_bfloat16*)d_in[6];
    const __nv_bfloat16* wout = (const __nv_bfloat16*)d_in[7];
    __nv_bfloat16* out = (__nv_bfloat16*)d_out;
    const int N = in_sizes[0] / 512;
    const int E = in_sizes[1];

    static int num_sms = 0;
    static EncodeTiledFn encode = nullptr;
    if (num_sms == 0) {
        int dev = 0;
        cudaGetDevice(&dev);
        cudaDeviceGetAttribute(&num_sms, cudaDevAttrMultiProcessorCount, dev);
        cudaFuncSetAttribute(main_kernel, cudaFuncAttributeMaxDynamicSharedMemorySize, SM_TOTAL);
        void* fn = nullptr;
        cudaDriverEntryPointQueryResult qr;
        cudaGetDriverEntryPoint("cuTensorMapEncodeTiled", &fn, cudaEnableDefault, &qr);
        encode = (EncodeTiledFn)fn;
    }
    const int nbins = num_sms < MAXBINS ? num_sms : MAXBINS;
    int npb = ((N + nbins - 1) / nbins + 1) & ~1;
    if (npb < 32) npb = 32;
    const int fast_ok = npb <= 2 * HPB;
    auto map2d = [&](CUtensorMap* tm, const void* p, int d0, int d1, int b1) {
        const cuuint64_t gd[2] = {(cuuint64_t)d0, (cuuint64_t)d1};
        const cuuint64_t gs[1] = {(cuuint64_t)d0 * 2};
        const cuuint32_t bx[2] = {64, (cuuint32_t)b1};
        const cuuint32_t es[2] = {1, 1};
        encode(tm, CU_TENSOR_MAP_DATA_TYPE_BFLOAT16, 2, (void*)p, gd, gs, bx, es, CU_TENSOR_MAP_INTERLEAVE_NONE,
               CU_TENSOR_MAP_SWIZZLE_128B, CU_TENSOR_MAP_L2_PROMOTION_NONE, CU_TENSOR_MAP_FLOAT_OOB_FILL_NONE);
    };
    CUtensorMap tmx, tmw, tmo;
    map2d(&tmx, x, 64, N * 8, 8);
    map2d(&tmw, wout, 128, 128, 32);
    map2d(&tmo, out, 128, N * 4, fast_ok ? npb : 2);
    const unsigned npb_magic = (unsigned)((0x100000000ull + npb - 1) / npb);
    const int chunk = (E + nbins - 1) / nbins;
    int bsh = 0;
    while (((N - 1) >> bsh) >= NBK) bsh++;
    int tau16 = (int)fmin((double)PACE * 16.0 * chunk / N, 100000.0), toff = TOFF;
    main_kernel<<<nbins, NT, SM_TOTAL, cudaStreamPerThread>>>(tmx, tmw, tmo, x, src, dst, sh, ea, cg, wr, wout, out, N, E,
                                                              npb, npb_magic, chunk, fast_ok, bsh, tau16, toff);
}
```

```cpp
#include <cuda_runtime.h>
#include <cuda.h>
#include <cuda_bf16.h>
#include <stdint.h>
#include <stdlib.h>
#include <type_traits>

#define MAXBINS 256
#define NW 16
#define NT (NW * 32)
#define HPB 38
#define BINCAP 3072
#define LCAP 1472
#define NBK 160
#define CE 2
#define GSZ 6
#define NS 10
#define RING_BYTES 40960
static_assert(RING_BYTES == NS * 4096, "ring");
#define NP (NS / 2)
#define CREG 224
#define PREG 24
#define HREG 40
#define TS 8
#define SM_EVEN 0
#define SM_MISC (2 * RING_BYTES)
#define SM_ODD (SM_MISC + 128)
#define SM_EA (SM_BT + TS * 4096 + 128)
#define SM_BT (SM_ODD + 2 * RING_BYTES)
#define BT_B (TS * 512 + 16)
#define BT_K (4 * BT_B)
#define SM_WR (SM_EA + 8192)
#define SM_SIDE (SM_WR + 4352)
#define SM_EID (SM_SIDE + 2048)
#define SM_SRC (SM_EID + 2 * LCAP * 4)
#define SEQCAP (LCAP / 4 + 40)
#define SM_SEQ (SM_SRC + 2 * LCAP * 2)
#define SM_BAR ((SM_SEQ + 2 * SEQCAP * 2 + 63) / 64 * 64)
#define SM_TOTAL (SM_BAR + NW * (NP > 5 ? 32 : 16))
#define DUMB (2 * NP * 16)
#define MI_WBAR 32
#define MI_INT 0
#define EPS ((2464 + NT - 1) / NT)
#define KS (BINCAP / NT)
#define SC_ENT 0
#define SC_BIN (SC_ENT + NT * EPS * 8)
#define SC_HIST (SC_BIN + NT * EPS)
#define SC_CNT (SC_HIST + 3 * MAXBINS * 4)
static_assert(SC_HIST % 16 == 0 && SC_CNT + 2 * (NBK + 1) * 16 <= SM_MISC, "scratch");
static_assert(SM_TOTAL <= 232448 && SM_BAR % 16 == 0 && SM_SEQ % 16 == 0 && SM_SRC % 16 == 0 && SM_EA % 256 == 0, "smem");
#define PACE 19.1
#define TOFF 10600
#define PSLEEP 20

__device__ int2 g_bin[MAXBINS * BINCAP];
__device__ __align__(128) int g_bincnt[MAXBINS * 32];
#define TLSTAMP(i)
#define TLMAX(i)

__device__ __forceinline__ uint32_t pack_bf16(float lo, float hi) {
    uint32_t r;
    asm("cvt.rn.bf16x2.f32 %0, %1, %2;" : "=r"(r) : "f"(hi), "f"(lo));
    return r;
}
__device__ __forceinline__ void mma1688_z(float (&d)[4], uint32_t a0, uint32_t a1, uint32_t b0) {
    asm("mma.sync.aligned.m16n8k8.row.col.f32.bf16.bf16.f32 {%0,%1,%2,%3}, {%4,%5}, {%6}, {%7,%7,%7,%7};"
        : "=f"(d[0]), "=f"(d[1]), "=f"(d[2]), "=f"(d[3])
        : "r"(a0), "r"(a1), "r"(b0), "f"(0.f));
}
__device__ __forceinline__ void mma_diag(float (&d)[4], uint32_t a, uint32_t b0, uint32_t b1) {
    asm("mma.sync.aligned.m16n8k16.row.col.f32.bf16.bf16.f32 {%0,%1,%2,%3}, {%4,%8,%8,%4}, {%5,%6}, {%7,%7,%7,%7};"
        : "=f"(d[0]), "=f"(d[1]), "=f"(d[2]), "=f"(d[3])
        : "r"(a), "r"(b0), "r"(b1), "f"(0.f), "r"(0));
}
__device__ __forceinline__ uint32_t s2u(const void* p) { return (uint32_t)__cvta_generic_to_shared(p); }
__device__ __forceinline__ void mbar_init(uint32_t a, int c) {
    asm volatile("mbarrier.init.shared.b64 [%0], %1;" ::"r"(a), "r"(c));
}
__device__ __forceinline__ void mbar_expect_tx(uint32_t a, int bytes) {
    asm volatile("mbarrier.arrive.expect_tx.shared.b64 _, [%0], %1;" ::"r"(a), "r"(bytes) : "memory");
}
__device__ __forceinline__ void mbar_arrive(uint32_t a) {
    asm volatile("mbarrier.arrive.shared.b64 _, [%0];" ::"r"(a) : "memory");
}
__device__ __forceinline__ void mbar_arrive_cnt(uint32_t a, int c) {
    asm volatile("mbarrier.arrive.shared.b64 _, [%0], %1;" ::"r"(a), "r"(c) : "memory");
}
__device__ __forceinline__ void mbar_wait(uint32_t a, int parity) {
    asm volatile(
        "{\n.reg .pred p;\n.reg .u32 c;\n"
        "mov.u32 c, 0;\n"
        "LAB_WAIT:\n"
        "mbarrier.try_wait.parity.shared.b64 p, [%0], %1, 2000;\n"
        "@p bra DONE;\n"
        "add.u32 c, c, 1;\n"
        "setp.lt.u32 p, c, 2000000;\n"
        "@p bra LAB_WAIT;\n"
        "trap;\n"
        "DONE:\n}" ::"r"(a),
        "r"(parity)
        : "memory");
}
__device__ __forceinline__ void mbar_wait_u(uint32_t a, int parity) {
    asm volatile(
        "{\n.reg .pred p;\n.reg .u32 c;\n"
        "mov.u32 c, 0;\n"
        "LAB_WAIT:\n"
        "mbarrier.try_wait.parity.shared.b64 p, [%0], %1, 2000;\n"
        "@p bra.uni DONE;\n"
        "add.u32 c, c, 1;\n"
        "setp.lt.u32 p, c, 2000000;\n"
        "@p bra.uni LAB_WAIT;\n"
        "trap;\n"
        "DONE:\n}" ::"r"(a),
        "r"(parity)
        : "memory");
}
__device__ __forceinline__ void mbar_spin_u(uint32_t a, int parity) {
    asm volatile(
        "{\n.reg .pred p;\n.reg .u32 c;\n"
        "mov.u32 c, 0;\n"
        "LAB_WAIT:\n"
        "mbarrier.test_wait.parity.shared.b64 p, [%0], %1;\n"
        "@p bra.uni DONE;\n"
        "add.u32 c, c, 1;\n"
        "setp.lt.u32 p, c, 20000000;\n"
        "@p bra.uni LAB_WAIT;\n"
        "trap;\n"
        "DONE:\n}" ::"r"(a),
        "r"(parity)
        : "memory");
}
__device__ __forceinline__ void mbar_lean(uint32_t a, int parity) {
    asm volatile(
        "{\n.reg .pred p;\n.reg .u32 c;\n"
        "mov.u32 c, 0;\n"
        "LAB_WAIT:\n"
        "mbarrier.try_wait.parity.shared.b64 p, [%0], %1;\n"
        "@p bra DONE;\n"
        "add.u32 c, c, 1;\n"
        "setp.lt.u32 p, c, 4000000;\n"
        "@p bra LAB_WAIT;\n"
        "trap;\n"
        "DONE:\n}" ::"r"(a),
        "r"(parity)
        : "memory");
}
__device__ __forceinline__ void mbar_lean_u(uint32_t a, int parity) {
    asm volatile(
        "{\n.reg .pred p;\n.reg .u32 c;\n"
        "mov.u32 c, 0;\n"
        "LAB_WAIT:\n"
        "mbarrier.try_wait.parity.shared.b64 p, [%0], %1;\n"
        "@p bra.uni DONE;\n"
        "add.u32 c, c, 1;\n"
        "setp.lt.u32 p, c, 4000000;\n"
        "@p bra.uni LAB_WAIT;\n"
        "trap;\n"
        "DONE:\n}" ::"r"(a),
        "r"(parity)
        : "memory");
}
__device__ __forceinline__ bool mbar_test(uint32_t a, int parity) {
    uint32_t p;
    asm volatile("{\n.reg .pred P;\nmbarrier.test_wait.parity.shared.b64 P, [%1], %2;\nselp.u32 %0, 1, 0, P;\n}"
                 : "=r"(p)
                 : "r"(a), "r"(parity)
                 : "memory");
    return p;
}
__device__ __forceinline__ bool elect() {
    uint32_t p;
    asm volatile("{\n.reg .pred P;\nelect.sync _|P, 0xffffffff;\nselp.u32 %0, 1, 0, P;\n}" : "=r"(p));
    return p;
}
__device__ __forceinline__ void tma_2d(uint32_t dst, const CUtensorMap* tm, uint32_t bar, int c0, int c1) {
    asm volatile(
        "cp.async.bulk.tensor.2d.shared::cluster.global.mbarrier::complete_tx::bytes [%0], [%1, {%3, %4}], [%2];" ::"r"(dst),
        "l"(tm), "r"(bar), "r"(c0), "r"(c1)
        : "memory");
}
__device__ __forceinline__ void tma_row(uint32_t dst, const CUtensorMap* tm, uint32_t bar, int row8) {
    tma_2d(dst, tm, bar, 0, row8);
}
__device__ __forceinline__ void tma_store(const CUtensorMap* tm, uint32_t src, int c0, int c1) {
    asm volatile("cp.async.bulk.tensor.2d.global.shared::cta.bulk_group [%0, {%2, %3}], [%1];" ::"l"(tm), "r"(src),
                 "r"(c0), "r"(c1)
                 : "memory");
}
__device__ __forceinline__ uint2 lds_v2(uint32_t a) {
    uint2 v;
    asm volatile("ld.shared.v2.u32 {%0,%1}, [%2];" : "=r"(v.x), "=r"(v.y) : "r"(a));
    return v;
}
__device__ __forceinline__ uint4 lds_v4(uint32_t a) {
    uint4 v;
    asm volatile("ld.shared.v4.u32 {%0,%1,%2,%3}, [%4];" : "=r"(v.x), "=r"(v.y), "=r"(v.z), "=r"(v.w) : "r"(a));
    return v;
}
__device__ __forceinline__ uint32_t lds_u32(uint32_t a) {
    uint32_t v;
    asm volatile("ld.shared.u32 %0, [%1];" : "=r"(v) : "r"(a));
    return v;
}
__device__ __forceinline__ uint32_t lds_u16(uint32_t a) {
    uint32_t v;
    asm volatile("ld.shared.u16 %0, [%1];" : "=r"(v) : "r"(a));
    return v;
}
__device__ __forceinline__ void sts_v2(uint32_t a, uint32_t x, uint32_t y) {
    asm volatile("st.shared.v2.u32 [%0], {%1,%2};" ::"r"(a), "r"(x), "r"(y) : "memory");
}
__device__ __forceinline__ void sts_v4(uint32_t a, uint4 v) {
    asm volatile("st.shared.v4.u32 [%0], {%1,%2,%3,%4};" ::"r"(a), "r"(v.x), "r"(v.y), "r"(v.z), "r"(v.w) : "memory");
}
__device__ __forceinline__ void stsm4(uint32_t a, uint32_t r0, uint32_t r1, uint32_t r2, uint32_t r3) {
    asm volatile("stmatrix.sync.aligned.m8n8.x4.shared.b16 [%0], {%1,%2,%3,%4};" ::"r"(a), "r"(r0), "r"(r1), "r"(r2), "r"(r3)
                 : "memory");
}
__device__ __forceinline__ void stsm2(uint32_t a, uint32_t r0, uint32_t r1) {
    asm volatile("stmatrix.sync.aligned.m8n8.x2.shared.b16 [%0], {%1,%2};" ::"r"(a), "r"(r0), "r"(r1) : "memory");
}
__device__ __forceinline__ void stsm4t(uint32_t a, uint32_t r0, uint32_t r1, uint32_t r2, uint32_t r3) {
    asm volatile("stmatrix.sync.aligned.m8n8.x4.trans.shared.b16 [%0], {%1,%2,%3,%4};" ::"r"(a), "r"(r0), "r"(r1), "r"(r2),
                 "r"(r3)
                 : "memory");
}
__device__ __forceinline__ void stsm2t(uint32_t a, uint32_t r0, uint32_t r1) {
    asm volatile("stmatrix.sync.aligned.m8n8.x2.trans.shared.b16 [%0], {%1,%2};" ::"r"(a), "r"(r0), "r"(r1) : "memory");
}
__device__ __forceinline__ void cp_async16(uint32_t d, const void* s, int n) {
    asm volatile("cp.async.cg.shared.global [%0], [%1], 16, %2;" ::"r"(d), "l"(s), "r"(n) : "memory");
}
__device__ __forceinline__ void cp_async4(uint32_t d, const void* s, int n) {
    asm volatile("cp.async.ca.shared.global [%0], [%1], 4, %2;" ::"r"(d), "l"(s), "r"(n) : "memory");
}
__device__ __forceinline__ void sts_u32(uint32_t a, uint32_t x) {
    asm volatile("st.shared.u32 [%0], %1;" ::"r"(a), "r"(x) : "memory");
}
#define FENCE_ASYNC() asm volatile("fence.proxy.async.shared::cta;" ::: "memory")
__device__ __forceinline__ int warp_incl_scan(int v, int lane) {
#pragma unroll
    for (int o = 1; o < 32; o <<= 1) {
        const int y = __shfl_up_sync(0xffffffffu, v, o);
        if (lane >= o) v += y;
    }
    return v;
}

#define STR2(x) #x
#define STR(x) STR2(x)
#define NJ 19
__device__ __forceinline__ void consume(float (&acc)[2][NJ][4], uint32_t xa0, uint32_t xa1, uint32_t so0, uint32_t bar0,
                                        uint32_t ea0, uint32_t d0, uint32_t pl0, int lz, const uint32_t (&wa)[8]) {
    asm volatile(
        "{\n"
        ".reg .pred p, pf, plead, pok, t0, t1, t2, u0, u1, u2;\n"
        ".reg .b32 ca, cb, cz, rbar;\n"
        "mov.b32 cz, 0;\n"
        "mov.b32 ca, 0x20002000;\n"
        "mov.b32 cb, 0x30003000;\n"
        ".reg .b32 cnt, so, q, qe, bar, nbar, pl, ctl, ctm, ix, iy, dl, v0, v1, v2, v3, pp;\n"
        ".reg .b16 sl, sh;\n"
        ".reg .b32 hXa0, hXa1, hXa2, hXa3, hXa4, hXa5, hXa6, hXa7, hXb0, hXb1, hXb2, hXb3, hXb4, hXb5, hXb6, hXb7, hYa0, hYa1, hYa2, hYa3, hYa4, hYa5, hYa6, hYa7, hYb0, hYb1, hYb2, hYb3, hYb4, hYb5, hYb6, hYb7, hLa0, hLa1, hLa2, hLa3, hLa4, hLa5, hLa6, hLa7, hLb0, hLb1, hLb2, hLb3, hLb4, hLb5, hLb6, hLb7;\n"
        ".reg .b32 pX0, pX1, pX2, pX3, pY0, pY1, pY2, pY3;\n"
        ".reg .f32 r0, r1, r2, r3, r4, r5, r6, r7, r8, r9, r10, r11, r12, r13, r14, r15;\n"
        ".reg .b64 daX, dbX, daY, dbY, de0, de1;\n"
        ".reg .b32 dh<6>, eb0, par, npar, wa<8>, uz, bend;\n"
        "add.u32 wa0, %160, %159;\n"
        "add.u32 wa1, %161, %159;\n"
        "add.u32 wa2, %162, %159;\n"
        "add.u32 wa3, %163, %159;\n"
        "add.u32 wa4, %164, %159;\n"
        "add.u32 wa5, %165, %159;\n"
        "add.u32 wa6, %166, %159;\n"
        "add.u32 wa7, %167, %159;\n"
        "mov.f32 %0, 0f00000000;\n"
        "mov.f32 %1, 0f00000000;\n"
        "mov.f32 %2, 0f00000000;\n"
        "mov.f32 %3, 0f00000000;\n"
        "mov.f32 %4, 0f00000000;\n"
        "mov.f32 %5, 0f00000000;\n"
        "mov.f32 %6, 0f00000000;\n"
        "mov.f32 %7, 0f00000000;\n"
        "mov.f32 %8, 0f00000000;\n"
        "mov.f32 %9, 0f00000000;\n"
        "mov.f32 %10, 0f00000000;\n"
        "mov.f32 %11, 0f00000000;\n"
        "mov.f32 %12, 0f00000000;\n"
        "mov.f32 %13, 0f00000000;\n"
        "mov.f32 %14, 0f00000000;\n"
        "mov.f32 %15, 0f00000000;\n"
        "mov.f32 %16, 0f00000000;\n"
        "mov.f32 %17, 0f00000000;\n"
        "mov.f32 %18, 0f00000000;\n"
        "mov.f32 %19, 0f00000000;\n"
        "mov.f32 %20, 0f00000000;\n"
        "mov.f32 %21, 0f00000000;\n"
        "mov.f32 %22, 0f00000000;\n"
        "mov.f32 %23, 0f00000000;\n"
        "mov.f32 %24, 0f00000000;\n"
        "mov.f32 %25, 0f00000000;\n"
        "mov.f32 %26, 0f00000000;\n"
        "mov.f32 %27, 0f00000000;\n"
        "mov.f32 %28, 0f00000000;\n"
        "mov.f32 %29, 0f00000000;\n"
        "mov.f32 %30, 0f00000000;\n"
        "mov.f32 %31, 0f00000000;\n"
        "mov.f32 %32, 0f00000000;\n"
        "mov.f32 %33, 0f00000000;\n"
        "mov.f32 %34, 0f00000000;\n"
        "mov.f32 %35, 0f00000000;\n"
        "mov.f32 %36, 0f00000000;\n"
        "mov.f32 %37, 0f00000000;\n"
        "mov.f32 %38, 0f00000000;\n"
        "mov.f32 %39, 0f00000000;\n"
        "mov.f32 %40, 0f00000000;\n"
        "mov.f32 %41, 0f00000000;\n"
        "mov.f32 %42, 0f00000000;\n"
        "mov.f32 %43, 0f00000000;\n"
        "mov.f32 %44, 0f00000000;\n"
        "mov.f32 %45, 0f00000000;\n"
        "mov.f32 %46, 0f00000000;\n"
        "mov.f32 %47, 0f00000000;\n"
        "mov.f32 %48, 0f00000000;\n"
        "mov.f32 %49, 0f00000000;\n"
        "mov.f32 %50, 0f00000000;\n"
        "mov.f32 %51, 0f00000000;\n"
        "mov.f32 %52, 0f00000000;\n"
        "mov.f32 %53, 0f00000000;\n"
        "mov.f32 %54, 0f00000000;\n"
        "mov.f32 %55, 0f00000000;\n"
        "mov.f32 %56, 0f00000000;\n"
        "mov.f32 %57, 0f00000000;\n"
        "mov.f32 %58, 0f00000000;\n"
        "mov.f32 %59, 0f00000000;\n"
        "mov.f32 %60, 0f00000000;\n"
        "mov.f32 %61, 0f00000000;\n"
        "mov.f32 %62, 0f00000000;\n"
        "mov.f32 %63, 0f00000000;\n"
        "mov.f32 %64, 0f00000000;\n"
        "mov.f32 %65, 0f00000000;\n"
        "mov.f32 %66, 0f00000000;\n"
        "mov.f32 %67, 0f00000000;\n"
        "mov.f32 %68, 0f00000000;\n"
        "mov.f32 %69, 0f00000000;\n"
        "mov.f32 %70, 0f00000000;\n"
        "mov.f32 %71, 0f00000000;\n"
        "mov.f32 %72, 0f00000000;\n"
        "mov.f32 %73, 0f00000000;\n"
        "mov.f32 %74, 0f00000000;\n"
        "mov.f32 %75, 0f00000000;\n"
        "mov.f32 %76, 0f00000000;\n"
        "mov.f32 %77, 0f00000000;\n"
        "mov.f32 %78, 0f00000000;\n"
        "mov.f32 %79, 0f00000000;\n"
        "mov.f32 %80, 0f00000000;\n"
        "mov.f32 %81, 0f00000000;\n"
        "mov.f32 %82, 0f00000000;\n"
        "mov.f32 %83, 0f00000000;\n"
        "mov.f32 %84, 0f00000000;\n"
        "mov.f32 %85, 0f00000000;\n"
        "mov.f32 %86, 0f00000000;\n"
        "mov.f32 %87, 0f00000000;\n"
        "mov.f32 %88, 0f00000000;\n"
        "mov.f32 %89, 0f00000000;\n"
        "mov.f32 %90, 0f00000000;\n"
        "mov.f32 %91, 0f00000000;\n"
        "mov.f32 %92, 0f00000000;\n"
        "mov.f32 %93, 0f00000000;\n"
        "mov.f32 %94, 0f00000000;\n"
        "mov.f32 %95, 0f00000000;\n"
        "mov.f32 %96, 0f00000000;\n"
        "mov.f32 %97, 0f00000000;\n"
        "mov.f32 %98, 0f00000000;\n"
        "mov.f32 %99, 0f00000000;\n"
        "mov.f32 %100, 0f00000000;\n"
        "mov.f32 %101, 0f00000000;\n"
        "mov.f32 %102, 0f00000000;\n"
        "mov.f32 %103, 0f00000000;\n"
        "mov.f32 %104, 0f00000000;\n"
        "mov.f32 %105, 0f00000000;\n"
        "mov.f32 %106, 0f00000000;\n"
        "mov.f32 %107, 0f00000000;\n"
        "mov.f32 %108, 0f00000000;\n"
        "mov.f32 %109, 0f00000000;\n"
        "mov.f32 %110, 0f00000000;\n"
        "mov.f32 %111, 0f00000000;\n"
        "mov.f32 %112, 0f00000000;\n"
        "mov.f32 %113, 0f00000000;\n"
        "mov.f32 %114, 0f00000000;\n"
        "mov.f32 %115, 0f00000000;\n"
        "mov.f32 %116, 0f00000000;\n"
        "mov.f32 %117, 0f00000000;\n"
        "mov.f32 %118, 0f00000000;\n"
        "mov.f32 %119, 0f00000000;\n"
        "mov.f32 %120, 0f00000000;\n"
        "mov.f32 %121, 0f00000000;\n"
        "mov.f32 %122, 0f00000000;\n"
        "mov.f32 %123, 0f00000000;\n"
        "mov.f32 %124, 0f00000000;\n"
        "mov.f32 %125, 0f00000000;\n"
        "mov.f32 %126, 0f00000000;\n"
        "mov.f32 %127, 0f00000000;\n"
        "mov.f32 %128, 0f00000000;\n"
        "mov.f32 %129, 0f00000000;\n"
        "mov.f32 %130, 0f00000000;\n"
        "mov.f32 %131, 0f00000000;\n"
        "mov.f32 %132, 0f00000000;\n"
        "mov.f32 %133, 0f00000000;\n"
        "mov.f32 %134, 0f00000000;\n"
        "mov.f32 %135, 0f00000000;\n"
        "mov.f32 %136, 0f00000000;\n"
        "mov.f32 %137, 0f00000000;\n"
        "mov.f32 %138, 0f00000000;\n"
        "mov.f32 %139, 0f00000000;\n"
        "mov.f32 %140, 0f00000000;\n"
        "mov.f32 %141, 0f00000000;\n"
        "mov.f32 %142, 0f00000000;\n"
        "mov.f32 %143, 0f00000000;\n"
        "mov.f32 %144, 0f00000000;\n"
        "mov.f32 %145, 0f00000000;\n"
        "mov.f32 %146, 0f00000000;\n"
        "mov.f32 %147, 0f00000000;\n"
        "mov.f32 %148, 0f00000000;\n"
        "mov.f32 %149, 0f00000000;\n"
        "mov.f32 %150, 0f00000000;\n"
        "mov.f32 %151, 0f00000000;\n"
        "setp.ne.u32 pf, 0, 0;\n"
        "add.u32 v0, %154, %159;\n"
        "shfl.sync.idx.b32 so, v0, 0, 31, 0xffffffff;\n"
        "mov.u32 npar, 0;\n"
        "shfl.sync.idx.b32 uz, %159, 7, 31, 0xffffffff;\n"
        "add.u32 bend, %155, " STR(NP * 16) ";\n"
        "add.u32 v0, %159, 8;\n"
        "shfl.sync.idx.b32 dh0, v0, 0, 31, 0xffffffff;\n"
        "shfl.sync.idx.b32 dh1, v0, 1, 31, 0xffffffff;\n"
        "shfl.sync.idx.b32 dh2, v0, 2, 31, 0xffffffff;\n"
        "shfl.sync.idx.b32 dh3, v0, 3, 31, 0xffffffff;\n"
        "add.u32 v0, %159, 0xc0000010;\n"
        "shfl.sync.idx.b32 dh4, v0, 4, 31, 0xffffffff;\n"
        "shfl.sync.idx.b32 dh5, v0, 5, 31, 0xffffffff;\n"
        "add.u32 v0, %159, %156;\n"
        "shfl.sync.idx.b32 eb0, v0, 0, 31, 0xffffffff;\n"
        "mov.u32 q, 0;\n"
        "mov.u32 pl, %158;\n"
        "shr.u32 nbar, so, 9;\n"
        "add.u32 nbar, nbar, %155;\n"
        "elect.sync _|plead, 0xffffffff;\n"
        "mov.b64 de0, {%156, dh4};\n"
        "mov.b64 de1, {eb0, dh5};\n"
        "mov.b32 hLa0, 0;\n"
        "mov.b32 hLa1, 0;\n"
        "mov.b32 hLa2, 0;\n"
        "mov.b32 hLa3, 0;\n"
        "mov.b32 hLa4, 0;\n"
        "mov.b32 hLa5, 0;\n"
        "mov.b32 hLa6, 0;\n"
        "mov.b32 hLa7, 0;\n"
        "mov.b32 hLb0, 0;\n"
        "mov.b32 hLb1, 0;\n"
        "mov.b32 hLb2, 0;\n"
        "mov.b32 hLb3, 0;\n"
        "mov.b32 hLb4, 0;\n"
        "mov.b32 hLb5, 0;\n"
        "mov.b32 hLb6, 0;\n"
        "mov.b32 hLb7, 0;\n"
        "mov.b32 pY0, 0;\n"
        "mov.b32 pY1, 0;\n"
        "mov.b32 pY2, 0;\n"
        "mov.b32 pY3, 0;\n"
        "mov.u32 ctm, 0x10001000;\n"
        "add.u32 rbar, %155, " STR(DUMB) ";\n"
        "mov.b64 daX, {%157, dh0};\n"
        "mov.b64 dbX, {%157, dh1};\n"
        "mov.b64 daY, {%157, dh2};\n"
        "mov.b64 dbY, {%157, dh3};\n"
        "mov.u32 bar, nbar;\n"
        "mov.u32 par, npar;\n"
        "sub.u32 so, bar, %155;\n"
        "shl.b32 so, so, 9;\n"
        "add.u32 v0, %152, so;\n"
        "add.u32 v1, %153, so;\n"
        "add.u32 nbar, nbar, 16;\n"
        "setp.eq.u32 p, nbar, bend;\n"
        "selp.b32 nbar, %155, nbar, p;\n"
        "@p xor.b32 npar, npar, 1;\n"
        "SLOW:\n"
        "mov.u32 cnt, 0;\n"
        "W1:\n"
        "mbarrier.try_wait.parity.shared.b64 p, [bar], par;\n"
        "@p bra.uni RES;\n"
        "add.u32 cnt, cnt, 1;\n"
        "setp.lt.u32 p, cnt, 4000000;\n"
        "@p bra.uni W1;\n"
        "trap;\n"
        "CX:\n"
        "mbarrier.test_wait.parity.shared.b64 pok, [nbar], npar;\n"
        "and.b32 dl, q, 0x60;\n"
        "add.u32 dl, dl, %157;\n"
        "add.u32 v3, dl, 0;\n"
        "mov.b64 {v2, dh0}, daX;\n"
        "mov.b64 daX, {v3, dh0};\n"
        "add.u32 v3, dl, 257;\n"
        "mov.b64 {v2, dh1}, dbX;\n"
        "mov.b64 dbX, {v3, dh1};\n"
        "add.u32 v3, dl, 514;\n"
        "mov.b64 {v2, dh2}, daY;\n"
        "mov.b64 daY, {v3, dh2};\n"
        "add.u32 v3, dl, 771;\n"
        "mov.b64 {v2, dh3}, dbY;\n"
        "mov.b64 dbY, {v3, dh3};\n"
        "add.u32 q, q, 32;\n"
        "and.b32 qe, q, 0xe0;\n"
        "add.u32 v3, qe, %156;\n"
        "mov.b64 {v2, dh4}, de0;\n"
        "mov.b64 de0, {v3, dh4};\n"
        "mov.b64 {v2, dh5}, de1;\n"
        "mov.b64 de1, {v3, dh5};\n"
        "setp.lt.f16x2 t0|u0, ctl, cz;\n"
        "abs.f16x2 v3, ctl;\n"
        "setp.ge.f16x2 t1|u1, v3, ca;\n"
        "setp.geu.f16x2 t2|u2, v3, cb;\n"
        "wgmma.wait_group.sync.aligned 2;\n"
        "cvt.rn.bf16x2.f32 pX0, r1, r0;\n"
        "cvt.rn.bf16x2.f32 pX1, r3, r2;\n"
        "cvt.rn.bf16x2.f32 pX2, r9, r8;\n"
        "cvt.rn.bf16x2.f32 pX3, r11, r10;\n"
        "cvt.rn.bf16x2.f32 pY0, r5, r4;\n"
        "cvt.rn.bf16x2.f32 pY1, r7, r6;\n"
        "cvt.rn.bf16x2.f32 pY2, r13, r12;\n"
        "cvt.rn.bf16x2.f32 pY3, r15, r14;\n"
        "mov.b32 {sl, sh}, pX0;\n"
        "mov.b32 pp, {sl, sl};\n"
        "mul.rn.bf16x2 hXa0, hLa0, pp;\n"
        "mul.rn.bf16x2 hXa2, hLa2, pp;\n"
        "mov.b32 {sl, sh}, pX1;\n"
        "mov.b32 pp, {sl, sl};\n"
        "mul.rn.bf16x2 hXa1, hLa1, pp;\n"
        "mul.rn.bf16x2 hXa3, hLa3, pp;\n"
        "mov.b32 {sl, sh}, pX2;\n"
        "mov.b32 pp, {sl, sl};\n"
        "mul.rn.bf16x2 hXa4, hLa4, pp;\n"
        "mul.rn.bf16x2 hXa6, hLa6, pp;\n"
        "mov.b32 {sl, sh}, pX3;\n"
        "mov.b32 pp, {sl, sl};\n"
        "mul.rn.bf16x2 hXa5, hLa5, pp;\n"
        "mul.rn.bf16x2 hXa7, hLa7, pp;\n"
        "mov.b32 {sl, sh}, pX0;\n"
        "mov.b32 pp, {sh, sh};\n"
        "mul.rn.bf16x2 hXb0, hLb0, pp;\n"
        "mul.rn.bf16x2 hXb2, hLb2, pp;\n"
        "mov.b32 {sl, sh}, pX1;\n"
        "mov.b32 pp, {sh, sh};\n"
        "mul.rn.bf16x2 hXb1, hLb1, pp;\n"
        "mul.rn.bf16x2 hXb3, hLb3, pp;\n"
        "mov.b32 {sl, sh}, pX2;\n"
        "mov.b32 pp, {sh, sh};\n"
        "mul.rn.bf16x2 hXb4, hLb4, pp;\n"
        "mul.rn.bf16x2 hXb6, hLb6, pp;\n"
        "mov.b32 {sl, sh}, pX3;\n"
        "mov.b32 pp, {sh, sh};\n"
        "mul.rn.bf16x2 hXb5, hLb5, pp;\n"
        "mul.rn.bf16x2 hXb7, hLb7, pp;\n"
        "ldmatrix.sync.aligned.m8n8.x4.trans.shared.b16 {hLa0,hLa1,hLa2,hLa3}, [v0+4096];\n"
        "ldmatrix.sync.aligned.m8n8.x4.trans.shared.b16 {hLa4,hLa5,hLa6,hLa7}, [v1+4096];\n"
        "ldmatrix.sync.aligned.m8n8.x4.trans.shared.b16 {hLb0,hLb1,hLb2,hLb3}, [v0+6144];\n"
        "ldmatrix.sync.aligned.m8n8.x4.trans.shared.b16 {hLb4,hLb5,hLb6,hLb7}, [v1+6144];\n"
        "@t2 bra.uni T4X;\n"
        "@t1 bra.uni T2X;\n"
        "@t0 bra.uni L1X;\n"
        "L0X:\n"
        "wgmma.fence.sync.aligned;\n"
        "wgmma.mma_async.sync.aligned.m64n24k16.f32.bf16.bf16 {%0,%1,%2,%3,%4,%5,%6,%7,%8,%9,%10,%11}, {hXa0,hXa1,hXa2,hXa3}, daX, 1, 1, 1, 0;\n"
        "wgmma.mma_async.sync.aligned.m64n24k16.f32.bf16.bf16 {%76,%77,%78,%79,%80,%81,%82,%83,%84,%85,%86,%87}, {hXa4,hXa5,hXa6,hXa7}, daX, 1, 1, 1, 0;\n"
        "wgmma.commit_group.sync.aligned;\n"
        "@u2 bra.uni T4Xb;\n"
        "@u1 bra.uni T2Xb;\n"
        "@u0 bra.uni L1Xb;\n"
        "bra.uni L0Xb;\n"
        "L1X:\n"
        "wgmma.fence.sync.aligned;\n"
        "wgmma.mma_async.sync.aligned.m64n24k16.f32.bf16.bf16 {%12,%13,%14,%15,%16,%17,%18,%19,%20,%21,%22,%23}, {hXa0,hXa1,hXa2,hXa3}, daX, 1, 1, 1, 0;\n"
        "wgmma.mma_async.sync.aligned.m64n24k16.f32.bf16.bf16 {%88,%89,%90,%91,%92,%93,%94,%95,%96,%97,%98,%99}, {hXa4,hXa5,hXa6,hXa7}, daX, 1, 1, 1, 0;\n"
        "wgmma.commit_group.sync.aligned;\n"
        "@u2 bra.uni T4Xb;\n"
        "@u1 bra.uni T2Xb;\n"
        "@u0 bra.uni L1Xb;\n"
        "bra.uni L0Xb;\n"
        "T2X:\n"
        "@t0 bra.uni L3X;\n"
        "L2X:\n"
        "wgmma.fence.sync.aligned;\n"
        "wgmma.mma_async.sync.aligned.m64n24k16.f32.bf16.bf16 {%24,%25,%26,%27,%28,%29,%30,%31,%32,%33,%34,%35}, {hXa0,hXa1,hXa2,hXa3}, daX, 1, 1, 1, 0;\n"
        "wgmma.mma_async.sync.aligned.m64n24k16.f32.bf16.bf16 {%100,%101,%102,%103,%104,%105,%106,%107,%108,%109,%110,%111}, {hXa4,hXa5,hXa6,hXa7}, daX, 1, 1, 1, 0;\n"
        "wgmma.commit_group.sync.aligned;\n"
        "@u2 bra.uni T4Xb;\n"
        "@u1 bra.uni T2Xb;\n"
        "@u0 bra.uni L1Xb;\n"
        "bra.uni L0Xb;\n"
        "L3X:\n"
        "wgmma.fence.sync.aligned;\n"
        "wgmma.mma_async.sync.aligned.m64n24k16.f32.bf16.bf16 {%36,%37,%38,%39,%40,%41,%42,%43,%44,%45,%46,%47}, {hXa0,hXa1,hXa2,hXa3}, daX, 1, 1, 1, 0;\n"
        "wgmma.mma_async.sync.aligned.m64n24k16.f32.bf16.bf16 {%112,%113,%114,%115,%116,%117,%118,%119,%120,%121,%122,%123}, {hXa4,hXa5,hXa6,hXa7}, daX, 1, 1, 1, 0;\n"
        "wgmma.commit_group.sync.aligned;\n"
        "@u2 bra.uni T4Xb;\n"
        "@u1 bra.uni T2Xb;\n"
        "@u0 bra.uni L1Xb;\n"
        "bra.uni L0Xb;\n"
        "T4X:\n"
        "@!t1 bra.uni LEXIT;\n"
        "@t0 bra.uni L5X;\n"
        "L4X:\n"
        "wgmma.fence.sync.aligned;\n"
        "wgmma.mma_async.sync.aligned.m64n24k16.f32.bf16.bf16 {%48,%49,%50,%51,%52,%53,%54,%55,%56,%57,%58,%59}, {hXa0,hXa1,hXa2,hXa3}, daX, 1, 1, 1, 0;\n"
        "wgmma.mma_async.sync.aligned.m64n24k16.f32.bf16.bf16 {%124,%125,%126,%127,%128,%129,%130,%131,%132,%133,%134,%135}, {hXa4,hXa5,hXa6,hXa7}, daX, 1, 1, 1, 0;\n"
        "wgmma.commit_group.sync.aligned;\n"
        "@u2 bra.uni T4Xb;\n"
        "@u1 bra.uni T2Xb;\n"
        "@u0 bra.uni L1Xb;\n"
        "bra.uni L0Xb;\n"
        "L5X:\n"
        "wgmma.fence.sync.aligned;\n"
        "wgmma.mma_async.sync.aligned.m64n32k16.f32.bf16.bf16 {%60,%61,%62,%63,%64,%65,%66,%67,%68,%69,%70,%71,%72,%73,%74,%75}, {hXa0,hXa1,hXa2,hXa3}, daX, 1, 1, 1, 0;\n"
        "wgmma.mma_async.sync.aligned.m64n32k16.f32.bf16.bf16 {%136,%137,%138,%139,%140,%141,%142,%143,%144,%145,%146,%147,%148,%149,%150,%151}, {hXa4,hXa5,hXa6,hXa7}, daX, 1, 1, 1, 0;\n"
        "wgmma.commit_group.sync.aligned;\n"
        "@u2 bra.uni T4Xb;\n"
        "@u1 bra.uni T2Xb;\n"
        "@u0 bra.uni L1Xb;\n"
        "L0Xb:\n"
        "wgmma.fence.sync.aligned;\n"
        "wgmma.mma_async.sync.aligned.m64n24k16.f32.bf16.bf16 {%0,%1,%2,%3,%4,%5,%6,%7,%8,%9,%10,%11}, {hXb0,hXb1,hXb2,hXb3}, dbX, 1, 1, 1, 0;\n"
        "wgmma.mma_async.sync.aligned.m64n24k16.f32.bf16.bf16 {%76,%77,%78,%79,%80,%81,%82,%83,%84,%85,%86,%87}, {hXb4,hXb5,hXb6,hXb7}, dbX, 1, 1, 1, 0;\n"
        "wgmma.commit_group.sync.aligned;\n"
        "bra.uni CY;\n"
        "L1Xb:\n"
        "wgmma.fence.sync.aligned;\n"
        "wgmma.mma_async.sync.aligned.m64n24k16.f32.bf16.bf16 {%12,%13,%14,%15,%16,%17,%18,%19,%20,%21,%22,%23}, {hXb0,hXb1,hXb2,hXb3}, dbX, 1, 1, 1, 0;\n"
        "wgmma.mma_async.sync.aligned.m64n24k16.f32.bf16.bf16 {%88,%89,%90,%91,%92,%93,%94,%95,%96,%97,%98,%99}, {hXb4,hXb5,hXb6,hXb7}, dbX, 1, 1, 1, 0;\n"
        "wgmma.commit_group.sync.aligned;\n"
        "bra.uni CY;\n"
        "T2Xb:\n"
        "@u0 bra.uni L3Xb;\n"
        "L2Xb:\n"
        "wgmma.fence.sync.aligned;\n"
        "wgmma.mma_async.sync.aligned.m64n24k16.f32.bf16.bf16 {%24,%25,%26,%27,%28,%29,%30,%31,%32,%33,%34,%35}, {hXb0,hXb1,hXb2,hXb3}, dbX, 1, 1, 1, 0;\n"
        "wgmma.mma_async.sync.aligned.m64n24k16.f32.bf16.bf16 {%100,%101,%102,%103,%104,%105,%106,%107,%108,%109,%110,%111}, {hXb4,hXb5,hXb6,hXb7}, dbX, 1, 1, 1, 0;\n"
        "wgmma.commit_group.sync.aligned;\n"
        "bra.uni CY;\n"
        "L3Xb:\n"
        "wgmma.fence.sync.aligned;\n"
        "wgmma.mma_async.sync.aligned.m64n24k16.f32.bf16.bf16 {%36,%37,%38,%39,%40,%41,%42,%43,%44,%45,%46,%47}, {hXb0,hXb1,hXb2,hXb3}, dbX, 1, 1, 1, 0;\n"
        "wgmma.mma_async.sync.aligned.m64n24k16.f32.bf16.bf16 {%112,%113,%114,%115,%116,%117,%118,%119,%120,%121,%122,%123}, {hXb4,hXb5,hXb6,hXb7}, dbX, 1, 1, 1, 0;\n"
        "wgmma.commit_group.sync.aligned;\n"
        "bra.uni CY;\n"
        "T4Xb:\n"
        "@u0 bra.uni L5Xb;\n"
        "L4Xb:\n"
        "wgmma.fence.sync.aligned;\n"
        "wgmma.mma_async.sync.aligned.m64n24k16.f32.bf16.bf16 {%48,%49,%50,%51,%52,%53,%54,%55,%56,%57,%58,%59}, {hXb0,hXb1,hXb2,hXb3}, dbX, 1, 1, 1, 0;\n"
        "wgmma.mma_async.sync.aligned.m64n24k16.f32.bf16.bf16 {%124,%125,%126,%127,%128,%129,%130,%131,%132,%133,%134,%135}, {hXb4,hXb5,hXb6,hXb7}, dbX, 1, 1, 1, 0;\n"
        "wgmma.commit_group.sync.aligned;\n"
        "bra.uni CY;\n"
        "L5Xb:\n"
        "wgmma.fence.sync.aligned;\n"
        "wgmma.mma_async.sync.aligned.m64n32k16.f32.bf16.bf16 {%60,%61,%62,%63,%64,%65,%66,%67,%68,%69,%70,%71,%72,%73,%74,%75}, {hXb0,hXb1,hXb2,hXb3}, dbX, 1, 1, 1, 0;\n"
        "wgmma.mma_async.sync.aligned.m64n32k16.f32.bf16.bf16 {%136,%137,%138,%139,%140,%141,%142,%143,%144,%145,%146,%147,%148,%149,%150,%151}, {hXb4,hXb5,hXb6,hXb7}, dbX, 1, 1, 1, 0;\n"
        "wgmma.commit_group.sync.aligned;\n"
        "bra.uni CY;\n"
        "CY:\n"
        "mov.u32 rbar, bar;\n"
        "mov.u32 bar, nbar;\n"
        "mov.u32 par, npar;\n"
        "sub.u32 so, bar, %155;\n"
        "shl.b32 so, so, 9;\n"
        "add.u32 v0, %152, so;\n"
        "add.u32 v1, %153, so;\n"
        "add.u32 nbar, nbar, 16;\n"
        "setp.eq.u32 p, nbar, bend;\n"
        "selp.b32 nbar, %155, nbar, p;\n"
        "@p xor.b32 npar, npar, 1;\n"
        "@!pok bra.uni SLOW;\n"
        "RES:\n"
        "wgmma.wait_group.sync.aligned 2;\n"
        "lop3.b32 v2, hLa3, hLa7, hLb3, 0x80;\n"
        "lop3.b32 v2, v2, hLb7, uz, 0x80;\n"
        "add.u32 v2, v2, rbar;\n"
        "@plead mbarrier.arrive.shared.b64 _, [v2+8];\n"
        "setp.lt.f16x2 t0|u0, ctm, cz;\n"
        "abs.f16x2 v3, ctm;\n"
        "setp.ge.f16x2 t1|u1, v3, ca;\n"
        "setp.geu.f16x2 t2|u2, v3, cb;\n"
        "ld.shared.v2.u32 {ctl, ctm}, [pl];\n"
        "add.u32 pl, pl, 8;\n"
        "mov.b32 {sl, sh}, pY0;\n"
        "mov.b32 pp, {sl, sl};\n"
        "mul.rn.bf16x2 hYa0, hLa0, pp;\n"
        "mul.rn.bf16x2 hYa2, hLa2, pp;\n"
        "mov.b32 {sl, sh}, pY1;\n"
        "mov.b32 pp, {sl, sl};\n"
        "mul.rn.bf16x2 hYa1, hLa1, pp;\n"
        "mul.rn.bf16x2 hYa3, hLa3, pp;\n"
        "mov.b32 {sl, sh}, pY2;\n"
        "mov.b32 pp, {sl, sl};\n"
        "mul.rn.bf16x2 hYa4, hLa4, pp;\n"
        "mul.rn.bf16x2 hYa6, hLa6, pp;\n"
        "mov.b32 {sl, sh}, pY3;\n"
        "mov.b32 pp, {sl, sl};\n"
        "mul.rn.bf16x2 hYa5, hLa5, pp;\n"
        "mul.rn.bf16x2 hYa7, hLa7, pp;\n"
        "mov.b32 {sl, sh}, pY0;\n"
        "mov.b32 pp, {sh, sh};\n"
        "mul.rn.bf16x2 hYb0, hLb0, pp;\n"
        "mul.rn.bf16x2 hYb2, hLb2, pp;\n"
        "mov.b32 {sl, sh}, pY1;\n"
        "mov.b32 pp, {sh, sh};\n"
        "mul.rn.bf16x2 hYb1, hLb1, pp;\n"
        "mul.rn.bf16x2 hYb3, hLb3, pp;\n"
        "mov.b32 {sl, sh}, pY2;\n"
        "mov.b32 pp, {sh, sh};\n"
        "mul.rn.bf16x2 hYb4, hLb4, pp;\n"
        "mul.rn.bf16x2 hYb6, hLb6, pp;\n"
        "mov.b32 {sl, sh}, pY3;\n"
        "mov.b32 pp, {sh, sh};\n"
        "mul.rn.bf16x2 hYb5, hLb5, pp;\n"
        "mul.rn.bf16x2 hYb7, hLb7, pp;\n"
        "ldmatrix.sync.aligned.m8n8.x4.trans.shared.b16 {hLa0,hLa1,hLa2,hLa3}, [v0+0];\n"
        "ldmatrix.sync.aligned.m8n8.x4.trans.shared.b16 {hLa4,hLa5,hLa6,hLa7}, [v1+0];\n"
        "ldmatrix.sync.aligned.m8n8.x4.trans.shared.b16 {hLb0,hLb1,hLb2,hLb3}, [v0+2048];\n"
        "ldmatrix.sync.aligned.m8n8.x4.trans.shared.b16 {hLb4,hLb5,hLb6,hLb7}, [v1+2048];\n"
        "wgmma.wait_group.sync.aligned 0;\n"
        "@t2 bra.uni T4Y;\n"
        "@t1 bra.uni T2Y;\n"
        "@t0 bra.uni L1Y;\n"
        "L0Y:\n"
        "wgmma.fence.sync.aligned;\n"
        "wgmma.mma_async.sync.aligned.m64n16k16.f32.bf16.bf16 {r0,r1,r2,r3,r4,r5,r6,r7}, {wa0,wa1,wa2,wa3}, de0, pf, 1, 1, 0;\n"
        "wgmma.mma_async.sync.aligned.m64n16k16.f32.bf16.bf16 {r8,r9,r10,r11,r12,r13,r14,r15}, {wa4,wa5,wa6,wa7}, de1, pf, 1, 1, 0;\n"
        "wgmma.commit_group.sync.aligned;\n"
        "wgmma.mma_async.sync.aligned.m64n24k16.f32.bf16.bf16 {%0,%1,%2,%3,%4,%5,%6,%7,%8,%9,%10,%11}, {hYa0,hYa1,hYa2,hYa3}, daY, 1, 1, 1, 0;\n"
        "wgmma.mma_async.sync.aligned.m64n24k16.f32.bf16.bf16 {%76,%77,%78,%79,%80,%81,%82,%83,%84,%85,%86,%87}, {hYa4,hYa5,hYa6,hYa7}, daY, 1, 1, 1, 0;\n"
        "wgmma.commit_group.sync.aligned;\n"
        "@u2 bra.uni T4Yb;\n"
        "@u1 bra.uni T2Yb;\n"
        "@u0 bra.uni L1Yb;\n"
        "bra.uni L0Yb;\n"
        "L1Y:\n"
        "wgmma.fence.sync.aligned;\n"
        "wgmma.mma_async.sync.aligned.m64n16k16.f32.bf16.bf16 {r0,r1,r2,r3,r4,r5,r6,r7}, {wa0,wa1,wa2,wa3}, de0, pf, 1, 1, 0;\n"
        "wgmma.mma_async.sync.aligned.m64n16k16.f32.bf16.bf16 {r8,r9,r10,r11,r12,r13,r14,r15}, {wa4,wa5,wa6,wa7}, de1, pf, 1, 1, 0;\n"
        "wgmma.commit_group.sync.aligned;\n"
        "wgmma.mma_async.sync.aligned.m64n24k16.f32.bf16.bf16 {%12,%13,%14,%15,%16,%17,%18,%19,%20,%21,%22,%23}, {hYa0,hYa1,hYa2,hYa3}, daY, 1, 1, 1, 0;\n"
        "wgmma.mma_async.sync.aligned.m64n24k16.f32.bf16.bf16 {%88,%89,%90,%91,%92,%93,%94,%95,%96,%97,%98,%99}, {hYa4,hYa5,hYa6,hYa7}, daY, 1, 1, 1, 0;\n"
        "wgmma.commit_group.sync.aligned;\n"
        "@u2 bra.uni T4Yb;\n"
        "@u1 bra.uni T2Yb;\n"
        "@u0 bra.uni L1Yb;\n"
        "bra.uni L0Yb;\n"
        "T2Y:\n"
        "@t0 bra.uni L3Y;\n"
        "L2Y:\n"
        "wgmma.fence.sync.aligned;\n"
        "wgmma.mma_async.sync.aligned.m64n16k16.f32.bf16.bf16 {r0,r1,r2,r3,r4,r5,r6,r7}, {wa0,wa1,wa2,wa3}, de0, pf, 1, 1, 0;\n"
        "wgmma.mma_async.sync.aligned.m64n16k16.f32.bf16.bf16 {r8,r9,r10,r11,r12,r13,r14,r15}, {wa4,wa5,wa6,wa7}, de1, pf, 1, 1, 0;\n"
        "wgmma.commit_group.sync.aligned;\n"
        "wgmma.mma_async.sync.aligned.m64n24k16.f32.bf16.bf16 {%24,%25,%26,%27,%28,%29,%30,%31,%32,%33,%34,%35}, {hYa0,hYa1,hYa2,hYa3}, daY, 1, 1, 1, 0;\n"
        "wgmma.mma_async.sync.aligned.m64n24k16.f32.bf16.bf16 {%100,%101,%102,%103,%104,%105,%106,%107,%108,%109,%110,%111}, {hYa4,hYa5,hYa6,hYa7}, daY, 1, 1, 1, 0;\n"
        "wgmma.commit_group.sync.aligned;\n"
        "@u2 bra.uni T4Yb;\n"
        "@u1 bra.uni T2Yb;\n"
        "@u0 bra.uni L1Yb;\n"
        "bra.uni L0Yb;\n"
        "L3Y:\n"
        "wgmma.fence.sync.aligned;\n"
        "wgmma.mma_async.sync.aligned.m64n16k16.f32.bf16.bf16 {r0,r1,r2,r3,r4,r5,r6,r7}, {wa0,wa1,wa2,wa3}, de0, pf, 1, 1, 0;\n"
        "wgmma.mma_async.sync.aligned.m64n16k16.f32.bf16.bf16 {r8,r9,r10,r11,r12,r13,r14,r15}, {wa4,wa5,wa6,wa7}, de1, pf, 1, 1, 0;\n"
        "wgmma.commit_group.sync.aligned;\n"
        "wgmma.mma_async.sync.aligned.m64n24k16.f32.bf16.bf16 {%36,%37,%38,%39,%40,%41,%42,%43,%44,%45,%46,%47}, {hYa0,hYa1,hYa2,hYa3}, daY, 1, 1, 1, 0;\n"
        "wgmma.mma_async.sync.aligned.m64n24k16.f32.bf16.bf16 {%112,%113,%114,%115,%116,%117,%118,%119,%120,%121,%122,%123}, {hYa4,hYa5,hYa6,hYa7}, daY, 1, 1, 1, 0;\n"
        "wgmma.commit_group.sync.aligned;\n"
        "@u2 bra.uni T4Yb;\n"
        "@u1 bra.uni T2Yb;\n"
        "@u0 bra.uni L1Yb;\n"
        "bra.uni L0Yb;\n"
        "T4Y:\n"
        "@t0 bra.uni L5Y;\n"
        "L4Y:\n"
        "wgmma.fence.sync.aligned;\n"
        "wgmma.mma_async.sync.aligned.m64n16k16.f32.bf16.bf16 {r0,r1,r2,r3,r4,r5,r6,r7}, {wa0,wa1,wa2,wa3}, de0, pf, 1, 1, 0;\n"
        "wgmma.mma_async.sync.aligned.m64n16k16.f32.bf16.bf16 {r8,r9,r10,r11,r12,r13,r14,r15}, {wa4,wa5,wa6,wa7}, de1, pf, 1, 1, 0;\n"
        "wgmma.commit_group.sync.aligned;\n"
        "wgmma.mma_async.sync.aligned.m64n24k16.f32.bf16.bf16 {%48,%49,%50,%51,%52,%53,%54,%55,%56,%57,%58,%59}, {hYa0,hYa1,hYa2,hYa3}, daY, 1, 1, 1, 0;\n"
        "wgmma.mma_async.sync.aligned.m64n24k16.f32.bf16.bf16 {%124,%125,%126,%127,%128,%129,%130,%131,%132,%133,%134,%135}, {hYa4,hYa5,hYa6,hYa7}, daY, 1, 1, 1, 0;\n"
        "wgmma.commit_group.sync.aligned;\n"
        "@u2 bra.uni T4Yb;\n"
        "@u1 bra.uni T2Yb;\n"
        "@u0 bra.uni L1Yb;\n"
        "bra.uni L0Yb;\n"
        "L5Y:\n"
        "wgmma.fence.sync.aligned;\n"
        "wgmma.mma_async.sync.aligned.m64n16k16.f32.bf16.bf16 {r0,r1,r2,r3,r4,r5,r6,r7}, {wa0,wa1,wa2,wa3}, de0, pf, 1, 1, 0;\n"
        "wgmma.mma_async.sync.aligned.m64n16k16.f32.bf16.bf16 {r8,r9,r10,r11,r12,r13,r14,r15}, {wa4,wa5,wa6,wa7}, de1, pf, 1, 1, 0;\n"
        "wgmma.commit_group.sync.aligned;\n"
        "wgmma.mma_async.sync.aligned.m64n32k16.f32.bf16.bf16 {%60,%61,%62,%63,%64,%65,%66,%67,%68,%69,%70,%71,%72,%73,%74,%75}, {hYa0,hYa1,hYa2,hYa3}, daY, 1, 1, 1, 0;\n"
        "wgmma.mma_async.sync.aligned.m64n32k16.f32.bf16.bf16 {%136,%137,%138,%139,%140,%141,%142,%143,%144,%145,%146,%147,%148,%149,%150,%151}, {hYa4,hYa5,hYa6,hYa7}, daY, 1, 1, 1, 0;\n"
        "wgmma.commit_group.sync.aligned;\n"
        "@u2 bra.uni T4Yb;\n"
        "@u1 bra.uni T2Yb;\n"
        "@u0 bra.uni L1Yb;\n"
        "L0Yb:\n"
        "wgmma.fence.sync.aligned;\n"
        "wgmma.mma_async.sync.aligned.m64n24k16.f32.bf16.bf16 {%0,%1,%2,%3,%4,%5,%6,%7,%8,%9,%10,%11}, {hYb0,hYb1,hYb2,hYb3}, dbY, 1, 1, 1, 0;\n"
        "wgmma.mma_async.sync.aligned.m64n24k16.f32.bf16.bf16 {%76,%77,%78,%79,%80,%81,%82,%83,%84,%85,%86,%87}, {hYb4,hYb5,hYb6,hYb7}, dbY, 1, 1, 1, 0;\n"
        "wgmma.commit_group.sync.aligned;\n"
        "bra.uni CX;\n"
        "L1Yb:\n"
        "wgmma.fence.sync.aligned;\n"
        "wgmma.mma_async.sync.aligned.m64n24k16.f32.bf16.bf16 {%12,%13,%14,%15,%16,%17,%18,%19,%20,%21,%22,%23}, {hYb0,hYb1,hYb2,hYb3}, dbY, 1, 1, 1, 0;\n"
        "wgmma.mma_async.sync.aligned.m64n24k16.f32.bf16.bf16 {%88,%89,%90,%91,%92,%93,%94,%95,%96,%97,%98,%99}, {hYb4,hYb5,hYb6,hYb7}, dbY, 1, 1, 1, 0;\n"
        "wgmma.commit_group.sync.aligned;\n"
        "bra.uni CX;\n"
        "T2Yb:\n"
        "@u0 bra.uni L3Yb;\n"
        "L2Yb:\n"
        "wgmma.fence.sync.aligned;\n"
        "wgmma.mma_async.sync.aligned.m64n24k16.f32.bf16.bf16 {%24,%25,%26,%27,%28,%29,%30,%31,%32,%33,%34,%35}, {hYb0,hYb1,hYb2,hYb3}, dbY, 1, 1, 1, 0;\n"
        "wgmma.mma_async.sync.aligned.m64n24k16.f32.bf16.bf16 {%100,%101,%102,%103,%104,%105,%106,%107,%108,%109,%110,%111}, {hYb4,hYb5,hYb6,hYb7}, dbY, 1, 1, 1, 0;\n"
        "wgmma.commit_group.sync.aligned;\n"
        "bra.uni CX;\n"
        "L3Yb:\n"
        "wgmma.fence.sync.aligned;\n"
        "wgmma.mma_async.sync.aligned.m64n24k16.f32.bf16.bf16 {%36,%37,%38,%39,%40,%41,%42,%43,%44,%45,%46,%47}, {hYb0,hYb1,hYb2,hYb3}, dbY, 1, 1, 1, 0;\n"
        "wgmma.mma_async.sync.aligned.m64n24k16.f32.bf16.bf16 {%112,%113,%114,%115,%116,%117,%118,%119,%120,%121,%122,%123}, {hYb4,hYb5,hYb6,hYb7}, dbY, 1, 1, 1, 0;\n"
        "wgmma.commit_group.sync.aligned;\n"
        "bra.uni CX;\n"
        "T4Yb:\n"
        "@u0 bra.uni L5Yb;\n"
        "L4Yb:\n"
        "wgmma.fence.sync.aligned;\n"
        "wgmma.mma_async.sync.aligned.m64n24k16.f32.bf16.bf16 {%48,%49,%50,%51,%52,%53,%54,%55,%56,%57,%58,%59}, {hYb0,hYb1,hYb2,hYb3}, dbY, 1, 1, 1, 0;\n"
        "wgmma.mma_async.sync.aligned.m64n24k16.f32.bf16.bf16 {%124,%125,%126,%127,%128,%129,%130,%131,%132,%133,%134,%135}, {hYb4,hYb5,hYb6,hYb7}, dbY, 1, 1, 1, 0;\n"
        "wgmma.commit_group.sync.aligned;\n"
        "bra.uni CX;\n"
        "L5Yb:\n"
        "wgmma.fence.sync.aligned;\n"
        "wgmma.mma_async.sync.aligned.m64n32k16.f32.bf16.bf16 {%60,%61,%62,%63,%64,%65,%66,%67,%68,%69,%70,%71,%72,%73,%74,%75}, {hYb0,hYb1,hYb2,hYb3}, dbY, 1, 1, 1, 0;\n"
        "wgmma.mma_async.sync.aligned.m64n32k16.f32.bf16.bf16 {%136,%137,%138,%139,%140,%141,%142,%143,%144,%145,%146,%147,%148,%149,%150,%151}, {hYb4,hYb5,hYb6,hYb7}, dbY, 1, 1, 1, 0;\n"
        "wgmma.commit_group.sync.aligned;\n"
        "bra.uni CX;\n"
        "LEXIT:\n"
        "wgmma.wait_group.sync.aligned 0;\n"
        "}\n"
        : "=f"(acc[0][0][0]), "=f"(acc[0][0][1]), "=f"(acc[0][0][2]), "=f"(acc[0][0][3]),
          "=f"(acc[0][1][0]), "=f"(acc[0][1][1]), "=f"(acc[0][1][2]), "=f"(acc[0][1][3]),
          "=f"(acc[0][2][0]), "=f"(acc[0][2][1]), "=f"(acc[0][2][2]), "=f"(acc[0][2][3]),
          "=f"(acc[0][3][0]), "=f"(acc[0][3][1]), "=f"(acc[0][3][2]), "=f"(acc[0][3][3]),
          "=f"(acc[0][4][0]), "=f"(acc[0][4][1]), "=f"(acc[0][4][2]), "=f"(acc[0][4][3]),
          "=f"(acc[0][5][0]), "=f"(acc[0][5][1]), "=f"(acc[0][5][2]), "=f"(acc[0][5][3]),
          "=f"(acc[0][6][0]), "=f"(acc[0][6][1]), "=f"(acc[0][6][2]), "=f"(acc[0][6][3]),
          "=f"(acc[0][7][0]), "=f"(acc[0][7][1]), "=f"(acc[0][7][2]), "=f"(acc[0][7][3]),
          "=f"(acc[0][8][0]), "=f"(acc[0][8][1]), "=f"(acc[0][8][2]), "=f"(acc[0][8][3]),
          "=f"(acc[0][9][0]), "=f"(acc[0][9][1]), "=f"(acc[0][9][2]), "=f"(acc[0][9][3]),
          "=f"(acc[0][10][0]), "=f"(acc[0][10][1]), "=f"(acc[0][10][2]), "=f"(acc[0][10][3]),
          "=f"(acc[0][11][0]), "=f"(acc[0][11][1]), "=f"(acc[0][11][2]), "=f"(acc[0][11][3]),
          "=f"(acc[0][12][0]), "=f"(acc[0][12][1]), "=f"(acc[0][12][2]), "=f"(acc[0][12][3]),
          "=f"(acc[0][13][0]), "=f"(acc[0][13][1]), "=f"(acc[0][13][2]), "=f"(acc[0][13][3]),
          "=f"(acc[0][14][0]), "=f"(acc[0][14][1]), "=f"(acc[0][14][2]), "=f"(acc[0][14][3]),
          "=f"(acc[0][15][0]), "=f"(acc[0][15][1]), "=f"(acc[0][15][2]), "=f"(acc[0][15][3]),
          "=f"(acc[0][16][0]), "=f"(acc[0][16][1]), "=f"(acc[0][16][2]), "=f"(acc[0][16][3]),
          "=f"(acc[0][17][0]), "=f"(acc[0][17][1]), "=f"(acc[0][17][2]), "=f"(acc[0][17][3]),
          "=f"(acc[0][18][0]), "=f"(acc[0][18][1]), "=f"(acc[0][18][2]), "=f"(acc[0][18][3]),
          "=f"(acc[1][0][0]), "=f"(acc[1][0][1]), "=f"(acc[1][0][2]), "=f"(acc[1][0][3]),
          "=f"(acc[1][1][0]), "=f"(acc[1][1][1]), "=f"(acc[1][1][2]), "=f"(acc[1][1][3]),
          "=f"(acc[1][2][0]), "=f"(acc[1][2][1]), "=f"(acc[1][2][2]), "=f"(acc[1][2][3]),
          "=f"(acc[1][3][0]), "=f"(acc[1][3][1]), "=f"(acc[1][3][2]), "=f"(acc[1][3][3]),
          "=f"(acc[1][4][0]), "=f"(acc[1][4][1]), "=f"(acc[1][4][2]), "=f"(acc[1][4][3]),
          "=f"(acc[1][5][0]), "=f"(acc[1][5][1]), "=f"(acc[1][5][2]), "=f"(acc[1][5][3]),
          "=f"(acc[1][6][0]), "=f"(acc[1][6][1]), "=f"(acc[1][6][2]), "=f"(acc[1][6][3]),
          "=f"(acc[1][7][0]), "=f"(acc[1][7][1]), "=f"(acc[1][7][2]), "=f"(acc[1][7][3]),
          "=f"(acc[1][8][0]), "=f"(acc[1][8][1]), "=f"(acc[1][8][2]), "=f"(acc[1][8][3]),
          "=f"(acc[1][9][0]), "=f"(acc[1][9][1]), "=f"(acc[1][9][2]), "=f"(acc[1][9][3]),
          "=f"(acc[1][10][0]), "=f"(acc[1][10][1]), "=f"(acc[1][10][2]), "=f"(acc[1][10][3]),
          "=f"(acc[1][11][0]), "=f"(acc[1][11][1]), "=f"(acc[1][11][2]), "=f"(acc[1][11][3]),
          "=f"(acc[1][12][0]), "=f"(acc[1][12][1]), "=f"(acc[1][12][2]), "=f"(acc[1][12][3]),
          "=f"(acc[1][13][0]), "=f"(acc[1][13][1]), "=f"(acc[1][13][2]), "=f"(acc[1][13][3]),
          "=f"(acc[1][14][0]), "=f"(acc[1][14][1]), "=f"(acc[1][14][2]), "=f"(acc[1][14][3]),
          "=f"(acc[1][15][0]), "=f"(acc[1][15][1]), "=f"(acc[1][15][2]), "=f"(acc[1][15][3]),
          "=f"(acc[1][16][0]), "=f"(acc[1][16][1]), "=f"(acc[1][16][2]), "=f"(acc[1][16][3]),
          "=f"(acc[1][17][0]), "=f"(acc[1][17][1]), "=f"(acc[1][17][2]), "=f"(acc[1][17][3]),
          "=f"(acc[1][18][0]), "=f"(acc[1][18][1]), "=f"(acc[1][18][2]), "=f"(acc[1][18][3])
        : "r"(xa0), "r"(xa1), "r"(so0), "r"(bar0), "r"(ea0), "r"(d0), "r"(pl0), "r"(lz), "r"(wa[0]), "r"(wa[1]), "r"(wa[2]),
          "r"(wa[3]), "r"(wa[4]), "r"(wa[5]), "r"(wa[6]), "r"(wa[7])
        : "memory");
}
__device__ __forceinline__ void wgmma_out(float (&o)[NJ][4], uint64_t da, uint64_t db, int acc) {
    asm volatile(
        "{\n.reg .pred p;\nsetp.ne.b32 p, %78, 0;\n"
        "wgmma.mma_async.sync.aligned.m64n152k16.f32.bf16.bf16 {%0,%1,%2,%3,%4,%5,%6,%7,%8,%9,%10,%11,%12,%13,%14,%15,%16,%17,%18,%19,%20,%21,%22,%23,%24,%25,%26,%27,%28,%29,%30,%31,%32,%33,%34,%35,%36,%37,%38,%39,%40,%41,%42,%43,%44,%45,%46,%47,%48,%49,%50,%51,%52,%53,%54,%55,%56,%57,%58,%59,%60,%61,%62,%63,%64,%65,%66,%67,%68,%69,%70,%71,%72,%73,%74,%75}, %76, %77, p, 1, 1, 1, 1;\n}"
        : "+f"(o[0][0]), "+f"(o[0][1]), "+f"(o[0][2]), "+f"(o[0][3]),
          "+f"(o[1][0]), "+f"(o[1][1]), "+f"(o[1][2]), "+f"(o[1][3]),
          "+f"(o[2][0]), "+f"(o[2][1]), "+f"(o[2][2]), "+f"(o[2][3]),
          "+f"(o[3][0]), "+f"(o[3][1]), "+f"(o[3][2]), "+f"(o[3][3]),
          "+f"(o[4][0]), "+f"(o[4][1]), "+f"(o[4][2]), "+f"(o[4][3]),
          "+f"(o[5][0]), "+f"(o[5][1]), "+f"(o[5][2]), "+f"(o[5][3]),
          "+f"(o[6][0]), "+f"(o[6][1]), "+f"(o[6][2]), "+f"(o[6][3]),
          "+f"(o[7][0]), "+f"(o[7][1]), "+f"(o[7][2]), "+f"(o[7][3]),
          "+f"(o[8][0]), "+f"(o[8][1]), "+f"(o[8][2]), "+f"(o[8][3]),
          "+f"(o[9][0]), "+f"(o[9][1]), "+f"(o[9][2]), "+f"(o[9][3]),
          "+f"(o[10][0]), "+f"(o[10][1]), "+f"(o[10][2]), "+f"(o[10][3]),
          "+f"(o[11][0]), "+f"(o[11][1]), "+f"(o[11][2]), "+f"(o[11][3]),
          "+f"(o[12][0]), "+f"(o[12][1]), "+f"(o[12][2]), "+f"(o[12][3]),
          "+f"(o[13][0]), "+f"(o[13][1]), "+f"(o[13][2]), "+f"(o[13][3]),
          "+f"(o[14][0]), "+f"(o[14][1]), "+f"(o[14][2]), "+f"(o[14][3]),
          "+f"(o[15][0]), "+f"(o[15][1]), "+f"(o[15][2]), "+f"(o[15][3]),
          "+f"(o[16][0]), "+f"(o[16][1]), "+f"(o[16][2]), "+f"(o[16][3]),
          "+f"(o[17][0]), "+f"(o[17][1]), "+f"(o[17][2]), "+f"(o[17][3]),
          "+f"(o[18][0]), "+f"(o[18][1]), "+f"(o[18][2]), "+f"(o[18][3])
        : "l"(da), "l"(db), "r"(acc));
}

__device__ __forceinline__ void slow_edge(int ee, int s, float* accn, const __nv_bfloat16* __restrict__ x,
                                          const __nv_bfloat16* __restrict__ sh, const __nv_bfloat16* __restrict__ ea,
                                          const __nv_bfloat16* __restrict__ cg, const __nv_bfloat16* __restrict__ wr,
                                          int lane) {
    float rwv[4] = {0.f, 0.f, 0.f, 0.f};
#pragma unroll 4
    for (int d = 0; d < 16; d++) {
        const float a = __bfloat162float(ea[(size_t)ee * 16 + d]);
        const uint2 wv = *(const uint2*)(wr + d * 128 + lane * 4);
        rwv[0] += a * __uint_as_float(wv.x << 16);
        rwv[1] += a * __uint_as_float(wv.x & 0xffff0000u);
        rwv[2] += a * __uint_as_float(wv.y << 16);
        rwv[3] += a * __uint_as_float(wv.y & 0xffff0000u);
    }
    float A = 0.f;
#pragma unroll
    for (int v = 0; v < 4; v++)
        A += __bfloat162float(cg[((lane >> 2) & 3) * 16 + v * 4 + (lane & 3)]) * __bfloat162float(sh[(size_t)ee * 4 + v]);
    float m[4][4];
#pragma unroll
    for (int w = 0; w < 4; w++)
#pragma unroll
        for (int j = 0; j < 4; j++) m[w][j] = 0.f;
#pragma unroll
    for (int u = 0; u < 4; u++) {
        const uint2 xv = *(const uint2*)(x + (size_t)s * 512 + u * 128 + lane * 4);
        const float x0 = __uint_as_float(xv.x << 16), x1 = __uint_as_float(xv.x & 0xffff0000u);
        const float x2 = __uint_as_float(xv.y << 16), x3 = __uint_as_float(xv.y & 0xffff0000u);
#pragma unroll
        for (int w = 0; w < 4; w++) {
            const float a = __shfl_sync(0xffffffffu, A, u * 4 + w);
            m[w][0] += a * x0;
            m[w][1] += a * x1;
            m[w][2] += a * x2;
            m[w][3] += a * x3;
        }
    }
#pragma unroll
    for (int w = 0; w < 4; w++)
#pragma unroll
        for (int j = 0; j < 4; j++) atomicAdd(accn + w * 128 + lane * 4 + j, m[w][j] * rwv[j]);
}

__device__ __forceinline__ void slow_out(const float* accn, const __nv_bfloat16* __restrict__ wout,
                                         __nv_bfloat16* __restrict__ outn, int lane) {
    float o[4][4];
#pragma unroll
    for (int w = 0; w < 4; w++)
#pragma unroll
        for (int j = 0; j < 4; j++) o[w][j] = 0.f;
#pragma unroll 2
    for (int c = 0; c < 128; c++) {
        const uint2 wv = *(const uint2*)(wout + c * 128 + lane * 4);
        const float w0 = __uint_as_float(wv.x << 16), w1 = __uint_as_float(wv.x & 0xffff0000u);
        const float w2 = __uint_as_float(wv.y << 16), w3 = __uint_as_float(wv.y & 0xffff0000u);
#pragma unroll
        for (int w = 0; w < 4; w++) {
            const float a = __bfloat162float(__float2bfloat16(accn[w * 128 + c]));
            o[w][0] += a * w0;
            o[w][1] += a * w1;
            o[w][2] += a * w2;
            o[w][3] += a * w3;
        }
    }
#pragma unroll
    for (int w = 0; w < 4; w++)
        *(uint2*)(outn + w * 128 + lane * 4) = make_uint2(pack_bf16(o[w][0], o[w][1]), pack_bf16(o[w][2], o[w][3]));
}

static_assert(NW > 2 * NP, "barriers");
#define FPOS 1
#define EMASK 0xffffff
#define TBIN 0
#define PW 0
#define TWAIT mbar_lean_u
#define PWAIT mbar_lean
#define TMA_ROW(k) "@pl cp.async.bulk.tensor.2d.shared::cluster.global.mbarrier::complete_tx::bytes [d" #k "], [tm, {z" #k ", r" #k "}], [b" #k "];\n"
#define TMA_INIT(k, o) "shfl.sync.idx.b32 z" #k ", %11, " #k ", 31, 0xffffffff;\nadd.u32 m" #k ", %2, " STR(o) ";\nadd.u32 m" #k ", m" #k ", %11;\nshfl.sync.idx.b32 m" #k ", m" #k ", 0, 31, 0xffffffff;\n"
#define TMA_PREP(k) "mad.lo.u32 d" #k ", dd, 512, m" #k ";\nadd.u32 b" #k ", dd, z" #k ";\n"
#define RDCLK(c) "mov.u64 ck, %%clock64;\ncvt.u32.u64 " c ", ck;\n"
#define REC 48
__device__ __forceinline__ void produce(const CUtensorMap* tm, uint32_t bar, uint32_t d0, uint32_t ps, int nit, uint32_t psrc,
                                        uint32_t tbase, uint32_t lim, uint32_t taug32, uint32_t taus, uint32_t n, int lz, uint32_t rec0,
                                        uint32_t rec
) {
    asm volatile(
        "{\n.reg .pred p, pl, ok, odd;\n.reg .b32 a<8>, r<8>, d<8>, b<8>, z<8>, m<8>, ps, lim, n, it, pr, pe, tgt, tgu, c, dd, dn, par, t0;\n"
        ".reg .b64 st, tm, ck;\n"
        "elect.sync _|pl, 0xffffffff;\n"
        TMA_INIT(0, 0) TMA_INIT(1, SM_ODD) TMA_INIT(2, 1024) TMA_INIT(3, SM_ODD + 1024)
        TMA_INIT(4, 4096) TMA_INIT(5, SM_ODD + 4096) TMA_INIT(6, 5120) TMA_INIT(7, SM_ODD + 5120)
        "mov.b64 {a0, a1}, %0;\n"
        "add.u32 a0, a0, %11;\n"
        "add.u32 a1, a1, %11;\n"
        "shfl.sync.idx.b32 a0, a0, 0, 31, 0xffffffff;\n"
        "shfl.sync.idx.b32 a1, a1, 0, 31, 0xffffffff;\n"
        "mov.b64 tm, {a0, a1};\n"
        "mov.u32 ps, %3;\n"
        "mov.u32 it, %4;\n"
        "mov.u32 lim, %7;\n"
        "mov.u32 n, %10;\n"
        "and.b32 c, ps, 4;\n"
        "setp.ne.u32 odd, c, 0;\n"
        "setp.le.s32 p, it, 0;\n"
        "@p bra.uni PEND;\n"
        "PBAT:\n"
        "ld.shared.u16 c, [ps];\n"
        "add.u32 ps, ps, 128;\n"
        "mul.lo.u32 par, n, " STR(65536 / NP + 1) ";\n"
        "shr.u32 par, par, 16;\n"
        "mad.lo.s32 dn, par, " STR(-NP) ", n;\n"
        "add.u32 n, n, 16;\n"
        "mad.lo.u32 dn, dn, 16, %1;\n"
        "lop3.b32 par, par, 1, 0, 0x0c;\n"
        "selp.b32 dn, par, dn, odd;\n"
        "and.b32 c, c, 0x3fe;\n"
        "mad.lo.u32 c, c, 4, %5;\n"
        "ld.shared.v2.u32 {a4, a5}, [c];\n"
        "min.s32 pe, it, 16;\n"
        "mad.lo.u32 pe, pe, " STR(REC) ", %12;\n"
        "sub.s32 it, it, 16;\n"
        "mov.u32 pr, %12;\n"
        "shl.b32 a0, a4, 3;\nand.b32 a0, a0, 0x7fff8;\nshr.u32 a1, a4, 13;\nand.b32 a1, a1, 0x7fff8;\n"
        "shl.b32 a2, a5, 3;\nand.b32 a2, a2, 0x7fff8;\nshr.u32 a3, a5, 13;\nand.b32 a3, a3, 0x7fff8;\n"
        "add.u32 tgt, a1, a2;\nmul.lo.u32 tgt, tgt, %9;\nshr.u32 tgt, tgt, 8;\nadd.u32 tgt, tgt, %6;\n"
        "min.u32 tgt, tgt, lim;\n"
        "add.u32 lim, lim, %8;\n"
        "st.shared.v4.u32 [%13], {a0, a1, a2, a3};\n"
        "selp.b32 c, 24, 32, odd;\n"
        "add.u32 c, c, %13;\n"
        "st.shared.v2.u32 [c], {tgt, dn};\n"
        "bar.warp.sync 0xffffffff;\n"
        "ld.shared.v4.u32 {a0, a1, a2, a3}, [pr];\n"
        "ld.shared.v4.u32 {a4, a5, a6, a7}, [pr+16];\n"
        "ld.shared.v4.u32 {tgt, dn, tgu, par}, [pr+32];\n"
        "PLOOP:\n"
        "mov.u32 dd, dn;\n"
        "mbarrier.test_wait.parity.shared.b64 ok, [dn+8], par;\n"
        TMA_PREP(0)
        "mov.u32 r0, a0;\nmov.u32 r1, a1;\nmov.u32 r2, a2;\nmov.u32 r3, a3;\n"
        "mov.u32 r4, a4;\nmov.u32 r5, a5;\nmov.u32 r6, a6;\nmov.u32 r7, a7;\n"
        "ld.shared.v4.u32 {a0, a1, a2, a3}, [pr+" STR(REC) "];\n"
        "ld.shared.v4.u32 {a4, a5, a6, a7}, [pr+" STR(REC + 16) "];\n"
        TMA_PREP(1) TMA_PREP(2) TMA_PREP(3) TMA_PREP(4) TMA_PREP(5) TMA_PREP(6) TMA_PREP(7)
        RDCLK("c")
        "sub.s32 c, c, tgt;\n"
        "setp.ge.and.s32 p, c, 0, ok;\n"
        "@!p bra.uni PSLP;\n"
        "PRES:\n"
        "@pl mbarrier.arrive.expect_tx.shared.b64 _, [b0], 8192;\n"
        TMA_ROW(0) TMA_ROW(1) TMA_ROW(2) TMA_ROW(3)
        RDCLK("c")
        "sub.s32 c, c, tgu;\n"
        "setp.lt.s32 p, c, 0;\n"
        "@p bra.uni PSL2;\n"
        "PRE2:\n"
        "ld.shared.v4.u32 {tgt, dn, tgu, par}, [pr+" STR(REC + 32) "];\n"
        "add.u32 pr, pr, " STR(REC) ";\n"
        TMA_ROW(4) TMA_ROW(5) TMA_ROW(6) TMA_ROW(7)
        "setp.lt.u32 p, pr, pe;\n"
        "@p bra.uni PLOOP;\n"
        "setp.gt.s32 p, it, 0;\n"
        "@p bra.uni PBAT;\n"
        "bra.uni PEND;\n"
        "PSL2:\n"
        "nanosleep.u32 " STR(PSLEEP) ";\n"
        RDCLK("c")
        "sub.s32 c, c, tgu;\n"
        "setp.lt.s32 p, c, 0;\n"
        "@p bra.uni PSL2;\n"
        "bra.uni PRE2;\n"
        "PSL1:\n"
        "nanosleep.u32 " STR(PSLEEP) ";\n"
        RDCLK("c")
        "sub.s32 c, c, tgt;\n"
        "PSLP:\n"
        "setp.lt.s32 p, c, 0;\n"
        "@p bra.uni PSL1;\n"
        "@ok bra.uni PRES;\n"
        "mov.u32 c, 0;\n"
        "PW:\n"
        "mbarrier.try_wait.parity.shared.b64 p, [b0+8], par;\n"
        "@p bra.uni PRES;\n"
        "add.u32 c, c, 1;\n"
        "setp.lt.u32 p, c, 4000000;\n"
        "@p bra.uni PW;\n"
        "trap;\n"
        "PEND:\n}"
        :
        : "l"(tm), "r"(bar), "r"(d0), "r"(ps), "r"(nit), "r"(psrc), "r"(tbase), "r"(lim), "r"(taug32), "r"(taus), "r"(n), "r"(lz),
          "r"(rec0), "r"(rec)
        : "memory");
}
#define GCODE(g) ((((g) >> 1) + 1) << 12 | ((g) & 1) << 15)
#define WG_SYNC(w) asm volatile("bar.sync %0, 128;" ::"r"((w) + 1) : "memory")
__global__ void __launch_bounds__(NT, 1)
main_kernel(const __grid_constant__ CUtensorMap tmx, const __grid_constant__ CUtensorMap tmw,
            const __grid_constant__ CUtensorMap tmo, const __nv_bfloat16* __restrict__ x, const int* __restrict__ src,
            const int* __restrict__ dst, const __nv_bfloat16* __restrict__ sh, const __nv_bfloat16* __restrict__ ea,
            const __nv_bfloat16* __restrict__ cg, const __nv_bfloat16* __restrict__ wr,
            const __nv_bfloat16* __restrict__ wout, __nv_bfloat16* __restrict__ out, int N, int E, int npb,
            unsigned npb_magic, int chunk, int fast_ok, int bsh, int tau16, int toff) {
    extern __shared__ __align__(1024) unsigned char smem[];
    const uint32_t sb = s2u(smem);
    int* s_int = (int*)(smem + SM_MISC + MI_INT);
    int* s_hist = (int*)(smem + SC_HIST);
    const int tid = threadIdx.x;
    const int warp = __shfl_sync(0xffffffffu, tid >> 5, 0), lane = tid & 31;
    const int g = lane >> 2, t = lane & 3;

    TLSTAMP(0);
    const int nbins = gridDim.x;
    const int bin = blockIdx.x;
    const int node0 = bin * npb, hpb = npb >> 1;
    const int ebeg = min(E, bin * chunk), eend = min(E, ebeg + chunk);
    int pd[EPS], ps[EPS];
#pragma unroll
    for (int k = 0; k < EPS; k++) {
        const int e = ebeg + tid + k * NT;
        pd[k] = e < eend ? __ldg(dst + e) : -1;
        ps[k] = e < eend ? __ldg(src + e) : 0;
    }
    int2* st_ent = (int2*)(smem + SC_ENT);
    unsigned char* st_bin = smem + SC_BIN;
    int* s_loc = s_hist + MAXBINS;
    int* s_del = s_loc + MAXBINS;
    if (lane < 2) mbar_init(sb + SM_BAR + (warp * 2 + lane) * 8, 3 + lane);
    if (tid < MAXBINS) s_hist[tid] = 0;
    if (tid == 0) {
        mbar_init(sb + SM_MISC + MI_WBAR, 4);
        asm volatile("prefetch.tensormap [%0];" ::"l"(&tmx) : "memory");
    }
    if (tid < 2 * (NBK + 1)) ((uint4*)(smem + SC_CNT))[tid] = make_uint4(0, 0, 0, 0);
#pragma unroll
    for (int k = 0; k < TS / 2; k++) ((uint4*)(smem + SM_BT))[tid + k * NT] = make_uint4(0, 0, 0, 0);
    if (tid < 8) ((uint4*)(smem + SM_BT))[tid + TS / 2 * NT] = make_uint4(0, 0, 0, 0);
    __syncthreads();
    TLSTAMP(1);
    for (int rb = ebeg;; rb += NT * EPS) {
        const bool last = rb + NT * EPS >= eend;
        int pb[EPS], pr[EPS];
#pragma unroll
        for (int k = 0; k < EPS; k++) {
            pb[k] = pd[k] >= 0 ? (int)__umulhi((unsigned)pd[k], npb_magic) : -1;
            if (pb[k] >= 0) pr[k] = atomicAdd(&s_hist[pb[k]], 1);
        }
        if (tid == 0) asm volatile("mov.u32 %0, %%globaltimer_lo;" : "=r"(s_int[3]));
        __syncthreads();
        TLSTAMP(6);
        const int now = s_int[3];
        int gbase = 0;
        if (warp == NW - 1) {
            int v[MAXBINS / 32], sum = 0;
#pragma unroll
            for (int c = 0; c < MAXBINS / 32; c++) {
                v[c] = s_hist[lane * (MAXBINS / 32) + c];
                sum += v[c];
            }
            int run = warp_incl_scan(sum, lane) - sum;
#pragma unroll
            for (int c = 0; c < MAXBINS / 32; c++) {
                s_loc[lane * (MAXBINS / 32) + c] = run;
                run += v[c];
            }
        } else if (tid < nbins) {
            if (bin == TBIN && last) __stcg(&g_bincnt[tid * 32 + 1], now | 1);
            gbase = atomicAdd(&g_bincnt[tid * 32], s_hist[tid] + (last ? 1 << 22 : 0));
        }
        __syncthreads();
#pragma unroll
        for (int k = 0; k < EPS; k++) {
            if (pb[k] >= 0) {
                const int pos = s_loc[pb[k]] + pr[k];
                st_ent[pos] = make_int2(ps[k], (rb + tid + k * NT) | ((pd[k] - pb[k] * npb) << 24) | 0x80000000);
                st_bin[pos] = pb[k];
            }
        }
        if (tid < nbins) s_del[tid] = (gbase & 0x3fffff) - s_loc[tid];
        __syncthreads();
        TLSTAMP(8);
        const int n = min(eend - rb, NT * EPS);
#pragma unroll
        for (int k = 0; k < EPS; k++) {
            const int i = tid + k * NT;
            if (i < n) {
                const int b = st_bin[i];
                const int gpos = i + s_del[b];
                if (gpos < BINCAP) __stcg(&g_bin[b * BINCAP + gpos], st_ent[i]);
            }
        }
        if (last) break;
        if (tid < MAXBINS) s_hist[tid] = 0;
#pragma unroll
        for (int k = 0; k < EPS; k++) {
            const int e = rb + NT * EPS + tid + k * NT;
            pd[k] = e < eend ? dst[e] : -1;
            ps[k] = e < eend ? src[e] : 0;
        }
        __syncthreads();
    }
    TLSTAMP(5);
    int2 ent[KS];
    uint2 wv;
    int rank[KS];
    {
        int cnt = 0;
        if (lane == 0) {
            int tsum;
            for (int spin = 0;; spin++) {
                asm volatile("ld.relaxed.gpu.global.v2.s32 {%0,%1}, [%2];" : "=r"(cnt), "=r"(tsum) : "l"(&g_bincnt[bin * 32]) : "memory");
                if ((cnt >> 22) >= nbins && tsum) break;
                if (spin > 10000000) __trap();
            }
            if (tid == 0) s_int[3] = tsum;
        }
        cnt = __shfl_sync(0xffffffffu, cnt, 0) & 0x3fffff;
        if (tid == 0) s_int[0] = cnt;
        const int n = min(cnt, BINCAP);
        unsigned pend = 0;
#pragma unroll
        for (int k = 0; k < KS; k++) {
            ent[k] = make_int2(0, 0);
            if (tid + k * NT < n) pend |= 1u << k;
        }
        int2* gp = &g_bin[bin * BINCAP + tid];
        for (int spin = 0; __any_sync(0xffffffffu, pend); spin++) {
#pragma unroll
            for (int k = 0; k < KS; k++)
                if ((pend >> k) & 1)
                    asm volatile("ld.relaxed.gpu.global.v2.s32 {%0,%1}, [%2];"
                                 : "=r"(ent[k].x), "=r"(ent[k].y)
                                 : "l"(gp + k * NT)
                                 : "memory");
#pragma unroll
            for (int k = 0; k < KS; k++)
                if (ent[k].y < 0) pend &= ~(1u << k);
            if (spin > 10000000) __trap();
        }
        TLSTAMP(2);
        asm volatile("ld.global.nc.v2.u32 {%0,%1}, [%2];" : "=r"(wv.x), "=r"(wv.y) : "l"((const uint2*)wr + tid));
#pragma unroll
        for (int k = 0; k < KS; k++) {
            if (ent[k].y < 0) {
                if (fast_ok) {
                    const int dl = (ent[k].y >> 24) & 127, w = dl >= hpb;
                    const int loc = dl - (w ? hpb : 0), gr = GSZ == 6 ? min(loc * 43 >> 8, 5) : loc >> 3, sft = (gr & 1) * 16;
                    const int cw = (w * (NBK + 1) + (ent[k].x >> bsh)) * 4 + (gr >> 1);
                    const unsigned old = atomicAdd((unsigned*)(smem + SC_CNT) + cw, 1u << sft);
                    rank[k] = ((old >> sft) & 0xffff) | GCODE(gr);
                    ent[k].x |= cw << 16;
                    ent[k].y = (ent[k].y & 0x80ffffff) | ((loc - gr * GSZ) << 24);
                }
                __stcg(gp + k * NT, make_int2(0, 0));
            }
        }
    }
    __syncthreads();
    if (tid == 0) *(int2*)&g_bincnt[bin * 32] = make_int2(0, 0);
    TLSTAMP(9);
    sts_v2(sb + SM_WR + ((tid >> 1) & 15) * 272 + (tid >> 5) * 16 + (tid & 1) * 8, wv.x, wv.y);
    if (warp < 2) {
        uint4* cp = (uint4*)(smem + SC_CNT) + warp * (NBK + 1) + lane * (NBK / 32);
        uint4 v[NBK / 32];
        uint32_t s[3] = {0, 0, 0}, r[3], tot[3], base[3];
#pragma unroll
        for (int c = 0; c < NBK / 32; c++) {
            v[c] = cp[c];
            s[0] += v[c].x;
            s[1] += v[c].y;
            s[2] += v[c].z;
        }
        uint32_t sum = 0;
#pragma unroll
        for (int i = 0; i < 3; i++) {
            r[i] = warp_incl_scan(s[i], lane);
            tot[i] = __shfl_sync(0xffffffffu, r[i], 31);
            r[i] -= s[i];
            const uint32_t p = (tot[i] + 0x00030003u) & 0xfffcfffcu;
            base[i] = sum * 0x10001u + (p << 16);
            sum += (p & 0xffff) + (p >> 16);
        }
        auto blocks = [](const uint32_t(&a)[3]) {
            constexpr uint32_t c = (3 - CE) * 0x10001u;
            const uint32_t q = (((a[0] + c) >> 2) & 0x3fff3fffu) + (((a[1] + c) >> 2) & 0x3fff3fffu) + (((a[2] + c) >> 2) & 0x3fff3fffu);
            return (q & 0xffff) + (q >> 16);
        };
#pragma unroll
        for (int c = 0; c < NBK / 32; c++) {
            cp[c] = make_uint4(r[0] + base[0], r[1] + base[1], r[2] + base[2], blocks(r));
            r[0] += v[c].x;
            r[1] += v[c].y;
            r[2] += v[c].z;
        }
        const bool ok = sum + 4 <= LCAP;
        const int nst = sum >> 2;
        const int npr = (nst + 3) >> 2;
        const uint32_t tw = g < 2 ? tot[0] : g < 4 ? tot[1] : tot[2], bw = g < 2 ? base[0] : g < 4 ? base[1] : base[2];
        const int le = g < 6 ? ((tw + bw) >> ((g & 1) * 16)) & 0xffff : sum;
        const bool tailb = t == 0 && (le & 3) >= 1 && (le & 3) <= CE;
        const unsigned tm = __ballot_sync(0xffffffffu, tailb);
        if (ok) {
            {
                const int i = (le & ~3) + t;
                if (i >= le) {
                    ((unsigned short*)(smem + SM_SRC))[warp * LCAP + i] = min(node0, N - 1);
                    ((uint32_t*)(smem + SM_EID))[warp * LCAP + i] = 0x80000000u;
                }
            }
            if (tailb) {
                const int i = blocks(tot) + __popc(tm & ((1u << lane) - 1));
                ((unsigned short*)(smem + SM_SEQ))[warp * SEQCAP + i] = (le >> 2) * 2 | GCODE(g);
            }
            ((unsigned short*)(smem + SM_SEQ))[warp * SEQCAP + nst + lane] = nst * 2 | (lane < (-nst & 3) ? GCODE(0) : 0x7c01);
        }
        if (lane < NP - 1 - npr % NP) {
            mbar_arrive_cnt(sb + SM_BAR + (warp * NP + lane) * 16, 3);
            mbar_arrive_cnt(sb + SM_BAR + (warp * NP + lane) * 16 + 8, 4);
        }
        if (lane == 0) s_int[1 + warp] = ok ? npr : -1;
    }
    __syncthreads();
    TLSTAMP(10);
    uint32_t wa[8];
#pragma unroll
    for (int h = 0; h < 2; h++)
        asm volatile("ldmatrix.sync.aligned.m8n8.x4.trans.shared.b16 {%0,%1,%2,%3}, [%4];"
                     : "=r"(wa[h * 4]), "=r"(wa[h * 4 + 1]), "=r"(wa[h * 4 + 2]), "=r"(wa[h * 4 + 3])
                     : "r"(sb + SM_WR + (h * 8 + (warp & 3) * 2 + ((lane >> 3) & 1)) * 272 + (lane >> 4) * 128 + (lane & 7) * 16));
    const bool fast = s_int[0] <= BINCAP && fast_ok && (s_int[1] | s_int[2]) >= 0;
    if (fast) {
        int pos[KS];
#pragma unroll
        for (int k = 0; k < KS; k++)
            if (ent[k].y < 0) pos[k] = ((uint32_t*)(smem + SC_CNT))[ent[k].x >> 16];
#pragma unroll
        for (int k = 0; k < KS; k++) {
            if (ent[k].y < 0) {
                const int w = (ent[k].x >> 16) >= (NBK + 1) * 4;
                const int p = (((uint32_t)pos[k] >> ((rank[k] >> 11) & 16)) & 0xffff) + (rank[k] & 0xfff);
                ((unsigned short*)(smem + SM_SRC))[w * LCAP + p] = ent[k].x;
                ((uint32_t*)(smem + SM_EID))[w * LCAP + p] = ent[k].y & 0x7fffffff;
                if ((p & 3) == CE) {
                    const int i = atomicAdd((int*)(smem + SC_CNT) + ((ent[k].x >> 16) | 3), 1);
                    ((unsigned short*)(smem + SM_SEQ))[w * SEQCAP + i] = (p >> 2) * 2 | (rank[k] & 0xf000);
                }
            }
        }
    }
    FENCE_ASYNC();
    TLSTAMP(15);
    __syncthreads();
    TLSTAMP(3);

    if (fast && warp >= 12) {
        asm volatile("setmaxnreg.dec.sync.aligned.u32 %0;" ::"n"(HREG));
        const int w = warp & 1, j = (warp >> 1) & 1;
        const int npr = __shfl_sync(0xffffffffu, s_int[1 + w], 0);
        const uint32_t bar0 = sb + SM_BAR + w * NP * 16;
        const int blk = (lane >> 4) * 2 + (t >> 1);
        uint32_t fseq = sb + SM_SEQ + w * SEQCAP * 2 + j * 8 + blk * 2;
        const uint32_t feid = sb + SM_EID + w * LCAP * 4 + (g & 3) * 4;
        uint32_t pea = sb + SM_EA + w * 4096 + j * 512 + (lane ^ ((lane >> 3) & 1)) * 16;
        const uint32_t psd = sb + SM_SIDE + (warp - 12) * 512 + (lane >> 1) * 16 + (lane & 1) * 4;
        const uint32_t pt = sb + SM_BT + w * (TS * 256) + j * 512 + blk * BT_B + ((lane ^ (lane >> 3)) & 1) * BT_K + (g & 3) * 4;
        const char* gea = (const char*)ea + (lane & 1) * 16;
        uint32_t es, va[2], ta[2], old[2] = {pt, pt}, dea = 2048;
        auto ids = [&]() {
            es = lds_u32(feid + (lds_u16(fseq) & 0x3fe) * 8);
            fseq += 16;
        };
        uint32_t wf[4];
        {
            const uint2* cp = (const uint2*)cg + (g & 3) * 4 + (t & 1) * 2;
            uint2 c0 = make_uint2(0, 0), c1 = c0;
            if ((g >> 2) == (t >> 1)) c0 = __ldg(cp), c1 = __ldg(cp + 1);
            wf[0] = __byte_perm(c0.x, c1.x, 0x5410), wf[1] = __byte_perm(c0.x, c1.x, 0x7632);
            wf[2] = __byte_perm(c0.y, c1.y, 0x5410), wf[3] = __byte_perm(c0.y, c1.y, 0x7632);
        }
        uint32_t vf = bar0 + (NP - 1 - npr % NP + j) % NP * 16;
        uint32_t pe = NP - 1 - npr % NP + j < NP;
        auto run = [&](auto odd) {
            auto fetch = [&](int i) {
                asm volatile(
                    "{\n.reg .pred p, q;\n.reg .b32 e;\n.reg .b64 a;\n"
                    "setp.lt.s32 p, %0, 0;\n"
                    "and.b32 e, %0, " STR(EMASK) ";\n"
                    "mad.wide.u32 a, e, 32, %1;\n"
                    "cp.async.cg.shared.global [%2], [a], 16, p;\n"
                    "}" ::"r"(es), "l"(gea), "r"(pea + i * 1024) : "memory");
                va[i] = psd + (es & 1) * 8;
                ta[i] = pt + ((es & 0x7000000) >> 18);
                if (odd.value) {
                    cp_async4(va[i] + i * 256, (const char*)sh + (size_t)(es & 0xffffff) * 8 + (lane & 1) * 4, (int)es >= 0 ? 4 : 0);
                } else {
                    asm volatile(
                        "{\n.reg .pred p, q;\n.reg .b32 e;\n.reg .b64 a;\n"
                        "setp.lt.s32 p, %0, 0;\n"
                        "setp.eq.u32 q, %3, 0;\n"
                        "and.b32 e, %0, " STR(EMASK - 1) ";\n"
                        "mad.wide.u32 a, e, 8, %1;\n"
                        "@q cp.async.cg.shared.global [%2], [a], 16, p;\n"
                        "}" ::"r"(es), "l"(sh), "r"(psd + i * 256), "r"(lane & 1) : "memory");
                }
                asm volatile("cp.async.commit_group;" ::: "memory");
                if (i) pea += dea, dea = -dea;
            };
            ids();
            fetch(0);
            ids();
            fetch(1);
#pragma unroll 1
            for (int m = (npr + 1 - j) >> 1; m > 0;) {
#pragma unroll
                for (int i = 0; i < 2; i++) {
                    asm volatile("cp.async.wait_group 1;" ::: "memory");
                    __syncwarp();
                    const uint32_t v = lds_u32(va[i] + i * 256);
                    ids();
                    float d0[4], d1[4];
                    mma_diag(d0, v, wf[0], wf[1]);
                    mma_diag(d1, v, wf[2], wf[3]);
                    uint32_t vn = vf + 32;
                    if (vn >= bar0 + NP * 16) vn -= NP * 16, pe ^= 1;
                    TWAIT(vn + 8, pe);
#pragma unroll
                    for (int k = 0; k < 4; k++) sts_u32(old[i] + i * 1024 + k * 16, 0);
                    old[i] = ta[i];
                    sts_u32(old[i] + i * 1024, pack_bf16(d0[0], d0[1]));
                    sts_u32(old[i] + i * 1024 + 16, pack_bf16(d0[2], d0[3]));
                    sts_u32(old[i] + i * 1024 + 32, pack_bf16(d1[0], d1[1]));
                    sts_u32(old[i] + i * 1024 + 48, pack_bf16(d1[2], d1[3]));
                    FENCE_ASYNC();
                    fetch(i);
                    __syncwarp();
                    if (lane == 0) mbar_arrive(vf);
                    vf = vn;
                    if (--m <= 0) break;
                }
            }
        };
        if (E & 1) run(std::true_type()); else run(std::false_type());
        asm volatile("cp.async.wait_group 0;" ::: "memory");
        TLMAX(13);
    } else if (fast && warp >= 8) {
        asm volatile("setmaxnreg.dec.sync.aligned.u32 %0;" ::"n"(PREG));
        const int w = warp & 1, j = (warp >> 1) & 1;
        const int nst = 2 * __shfl_sync(0xffffffffu, s_int[1 + w], 0);
        const uint32_t bar0 = sb + SM_BAR + w * NP * 16, ring = sb + w * RING_BYTES + j * 4096;
        const uint32_t pseq = sb + SM_SEQ + w * SEQCAP * 2 + j * 2;
        unsigned now;
        asm volatile("mov.u32 %0, %%globaltimer_lo;" : "=r"(now));
        const int ago = min(max((int)(now - s_int[3]), 0), 1 << 16) * 7 >> 2;
        const unsigned tbase = __shfl_sync(0xffffffffu, (unsigned)clock() - ago, 0) + (unsigned)toff;
        const unsigned taug = __shfl_sync(0xffffffffu, (N * tau16 >> 4) / max(nst, 1), 0);
        const int k0 = NP - 1 - (nst >> 1) % NP;
        const uint32_t rec = sb + SM_WR + (warp - 8) * (16 * REC);
        produce(&tmx, bar0, ring - j * 2048 - bar0 * 512, pseq + lane * 4, nst >> 1, sb + SM_SRC + w * LCAP * 2, tbase,
                tbase + (N * tau16 >> 8) + lane * taug, taug * 32, tau16, k0 + (lane >> 1), lane & (E >> 31), rec,
                rec + (lane >> 1) * REC + (lane & 1) * 16
        );
        if (elect()) {
            const uint32_t d = ring + (NP - 1) * 8192;
            const uint32_t fb = bar0 + (NP - 1) * 16, par = ~(lds_u32(sb + SM_MISC + MI_INT + 4 + w * 4) / NP) & 1;
            mbar_wait(fb + 8, par);
            mbar_arrive_cnt(fb, 1 + j);
            mbar_expect_tx(sb + SM_MISC + MI_WBAR, 8192);
            tma_2d(d + SM_EVEN, &tmw, sb + SM_MISC + MI_WBAR, w * 64, j * 32);
            tma_2d(d + SM_ODD, &tmw, sb + SM_MISC + MI_WBAR, w * 64, j * 32 + 64);
        }
        TLMAX(12);
    } else if (fast) {
        asm volatile("setmaxnreg.inc.sync.aligned.u32 %0;" ::"n"(CREG));
        const int w = warp >> 2, wq = warp & 3;
        const int nst = __shfl_sync(0xffffffffu, s_int[1 + w], 0);
        const uint32_t ring = sb + w * RING_BYTES;
        float acc[2][NJ][4];
        {
            const int e = (lane >> 1) & 3, m = lane >> 3;
            const int line = 2 * ((lane & 1) + 2 * ((m >> 1) ^ (e >> 1))), ch = 2 * wq + (m & 1);
            const uint32_t xb = ring + (e & 1 ? SM_ODD : SM_EVEN) + (e >> 1) * 1024 + line * 128;
            consume(acc, xb + ((ch ^ ((line + (e & 1)) & 7)) * 16), xb + 128 + ((ch ^ ((line + 1 + (e & 1)) & 7)) * 16),
                    (NP - 1 - nst % NP) * 8192, sb + SM_BAR + w * NP * 16, (((sb + SM_EA + w * 4096) & 0x3ffff) >> 4) | (1 << 16),
                    (((sb + SM_BT + w * (TS * 256)) & 0x3ffff) >> 4) | (BT_K / 16 << 16), sb + SM_SEQ + w * SEQCAP * 2, lane & (E >> 31),
                    wa);
        }
        TLMAX(11);
#pragma unroll
        for (int h = 0; h < 2; h++) {
            const uint32_t tb = ring + (h ? SM_ODD : SM_EVEN) + wq * (NJ * 256) + lane * 16;
#pragma unroll
            for (int j = 0; j + 1 < NJ; j += 2)
                stsm4(tb + j * 256, pack_bf16(acc[h][j][0], acc[h][j][1]), pack_bf16(acc[h][j][2], acc[h][j][3]),
                      pack_bf16(acc[h][j + 1][0], acc[h][j + 1][1]), pack_bf16(acc[h][j + 1][2], acc[h][j + 1][3]));
            if (NJ & 1)
                stsm2(tb + (NJ - 1) * 256, pack_bf16(acc[h][NJ - 1][0], acc[h][NJ - 1][1]),
                      pack_bf16(acc[h][NJ - 1][2], acc[h][NJ - 1][3]));
        }
        FENCE_ASYNC();
        WG_SYNC(w);
        mbar_wait_u(sb + SM_MISC + MI_WBAR, 0);
        float o[2][NJ][4];
        asm volatile("wgmma.fence.sync.aligned;" ::: "memory");
#pragma unroll
        for (int hh = 0; hh < 2; hh++) {
#pragma unroll
            for (int ks = 0; ks < 8; ks++) {
                const uint32_t rg = ks >> 2 ? SM_ODD : SM_EVEN;
                const uint64_t da = (uint64_t)(((sb + rg + hh * RING_BYTES + (NS - 2) * 4096 + (ks & 3) * 2048) & 0x3ffff) >> 4) |
                                    (64ull << 32) | (1ull << 62);
                const uint64_t db = (uint64_t)(((ring + rg + (ks & 3) * (NJ * 256)) & 0x3ffff) >> 4) | (8ull << 16) | (16ull << 32);
                wgmma_out(o[hh], da, db, ks);
            }
            asm volatile("wgmma.commit_group.sync.aligned;" ::: "memory");
        }
        const int nb = 2 * hpb;
#pragma unroll
        for (int hh = 0; hh < 2; hh++) {
            if (hh == 0) {
                asm volatile("wgmma.wait_group.sync.aligned 1;" ::: "memory");
            } else {
                asm volatile("wgmma.wait_group.sync.aligned 0;" ::: "memory");
                WG_SYNC(w);
            }
#pragma unroll
            for (int j = 0; j < NJ; j++)
#pragma unroll
                for (int k = 0; k < 4; k++) asm volatile("" : "+f"(o[hh][j][k])::"memory");
            const uint32_t b0 = ring + SM_EVEN + (hh ? 0 : 20480);
            const uint32_t b1 = hh ? b0 : ring + SM_ODD + 20480 + 896 - (nb * 128 & ~1023);
            const int r = (lane & 7) + (lane >> 4) * 8;
            const uint32_t co = r * 128 + (((2 * wq + ((lane >> 3) & 1)) ^ (lane & 7)) * 16);
#pragma unroll
            for (int j = 0; j + 1 < NJ; j += 2)
                stsm4t((8 * j + r < nb ? b0 : b1) + co + j * 1024, pack_bf16(o[hh][j][0], o[hh][j][1]),
                       pack_bf16(o[hh][j][2], o[hh][j][3]), pack_bf16(o[hh][j + 1][0], o[hh][j + 1][1]),
                       pack_bf16(o[hh][j + 1][2], o[hh][j + 1][3]));
            if (NJ & 1)
                stsm2t(b1 + co + (NJ - 1) * 1024, pack_bf16(o[hh][NJ - 1][0], o[hh][NJ - 1][1]),
                       pack_bf16(o[hh][NJ - 1][2], o[hh][NJ - 1][3]));
            FENCE_ASYNC();
            WG_SYNC(w);
            if (wq < 2 && elect()) {
                const int row = (node0 + w * hpb) * 4 + wq * nb;
                if (row < N * 4) tma_store(&tmo, wq ? b1 + nb * 128 : b0, hh * 64, row);
                asm volatile("cp.async.bulk.commit_group;" ::: "memory");
                if (hh) asm volatile("cp.async.bulk.wait_group.read 0;" ::: "memory");
            }
        }
    } else {
        float* accs = (float*)smem;
        constexpr int NACC = SM_EID / 2048;
        const int nnodes = max(0, min(npb, N - node0));
#pragma unroll 1
        for (int nb = 0; nb < nnodes; nb += NACC) {
            __syncthreads();
            for (int i = tid; i < NACC * 512; i += NT) accs[i] = 0.f;
            __syncthreads();
#pragma unroll 1
            for (int base = warp * 32; base < E; base += NT) {
                const int e = base + lane;
                int dl = e < E ? dst[e] - node0 - nb : -1;
                if (dl + nb >= nnodes) dl = -1;
                unsigned mask = __ballot_sync(0xffffffffu, dl >= 0 && dl < NACC);
#pragma unroll 1
                while (mask) {
                    const int l = __ffs(mask) - 1;
                    mask &= mask - 1;
                    const int ee = __shfl_sync(0xffffffffu, e, l);
                    const int dd = __shfl_sync(0xffffffffu, dl, l);
                    slow_edge(ee, src[ee], accs + dd * 512, x, sh, ea, cg, wr, lane);
                }
            }
            __syncthreads();
#pragma unroll 1
            for (int nl = warp; nl < NACC && nb + nl < nnodes; nl += NW)
                slow_out(accs + nl * 512, wout, out + (size_t)(node0 + nb + nl) * 512, lane);
        }
        __syncthreads();
    }

    TLMAX(4);
}

typedef CUresult (*EncodeTiledFn)(CUtensorMap*, CUtensorMapDataType, cuuint32_t, void*, const cuuint64_t*,
                                  const cuuint64_t*, const cuuint32_t*, const cuuint32_t*, CUtensorMapInterleave,
                                  CUtensorMapSwizzle, CUtensorMapL2promotion, CUtensorMapFloatOOBfill);

extern "C" void kernel_launch(void* const* d_in, const int* in_sizes, int n_in, void* d_out, int out_size) {
    const __nv_bfloat16* x = (const __nv_bfloat16*)d_in[0];
    const int* src = (const int*)d_in[1];
    const int* dst = (const int*)d_in[2];
    const __nv_bfloat16* sh = (const __nv_bfloat16*)d_in[3];
    const __nv_bfloat16* ea = (const __nv_bfloat16*)d_in[4];
    const __nv_bfloat16* cg = (const __nv_bfloat16*)d_in[5];
    const __nv_bfloat16* wr = (const __nv_bfloat16*)d_in[6];
    const __nv_bfloat16* wout = (const __nv_bfloat16*)d_in[7];
    __nv_bfloat16* out = (__nv_bfloat16*)d_out;
    const int N = in_sizes[0] / 512;
    const int E = in_sizes[1];

    static int num_sms = 0;
    static EncodeTiledFn encode = nullptr;
    if (num_sms == 0) {
        int dev = 0;
        cudaGetDevice(&dev);
        cudaDeviceGetAttribute(&num_sms, cudaDevAttrMultiProcessorCount, dev);
        cudaFuncSetAttribute(main_kernel, cudaFuncAttributeMaxDynamicSharedMemorySize, SM_TOTAL);
        void* fn = nullptr;
        cudaDriverEntryPointQueryResult qr;
        cudaGetDriverEntryPoint("cuTensorMapEncodeTiled", &fn, cudaEnableDefault, &qr);
        encode = (EncodeTiledFn)fn;
    }
    const int nbins = num_sms < MAXBINS ? num_sms : MAXBINS;
    int npb = ((N + nbins - 1) / nbins + 1) & ~1;
    if (npb < 32) npb = 32;
    const int fast_ok = npb <= 2 * HPB;
    auto map2d = [&](CUtensorMap* tm, const void* p, int d0, int d1, int b1) {
        const cuuint64_t gd[2] = {(cuuint64_t)d0, (cuuint64_t)d1};
        const cuuint64_t gs[1] = {(cuuint64_t)d0 * 2};
        const cuuint32_t bx[2] = {64, (cuuint32_t)b1};
        const cuuint32_t es[2] = {1, 1};
        encode(tm, CU_TENSOR_MAP_DATA_TYPE_BFLOAT16, 2, (void*)p, gd, gs, bx, es, CU_TENSOR_MAP_INTERLEAVE_NONE,
               CU_TENSOR_MAP_SWIZZLE_128B, CU_TENSOR_MAP_L2_PROMOTION_NONE, CU_TENSOR_MAP_FLOAT_OOB_FILL_NONE);
    };
    CUtensorMap tmx, tmw, tmo;
    map2d(&tmx, x, 64, N * 8, 8);
    map2d(&tmw, wout, 128, 128, 32);
    map2d(&tmo, out, 128, N * 4, fast_ok ? npb : 2);
    const unsigned npb_magic = (unsigned)((0x100000000ull + npb - 1) / npb);
    const int chunk = (E + nbins - 1) / nbins;
    int bsh = 0;
    while (((N - 1) >> bsh) >= NBK) bsh++;
    int tau16 = (int)fmin((double)PACE * 16.0 * chunk / N, 100000.0), toff = TOFF;
    main_kernel<<<nbins, NT, SM_TOTAL, cudaStreamPerThread>>>(tmx, tmw, tmo, x, src, dst, sh, ea, cg, wr, wout, out, N, E,
                                                              npb, npb_magic, chunk, fast_ok, bsh, tau16, toff);
}
```

```cpp
#include <cuda_runtime.h>
#include <cuda.h>
#include <cuda_bf16.h>
#include <stdint.h>
#include <stdlib.h>
#include <type_traits>

#define MAXBINS 256
#define NW 16
#define NT (NW * 32)
#define HPB 38
#define BINCAP 3072
#define LCAP 1472
#define NBK 160
#define CE 2
#define GSZ 6
#define NS 10
#define RING_BYTES 40960
static_assert(RING_BYTES == NS * 4096, "ring");
#define NP (NS / 2)
#define CREG 224
#define PREG 24
#define HREG 40
#define TS 8
#define SM_EVEN 0
#define SM_MISC (2 * RING_BYTES)
#define SM_ODD (SM_MISC + 128)
#define SM_EA (SM_BT + TS * 4096 + 128)
#define SM_BT (SM_ODD + 2 * RING_BYTES)
#define BT_B (TS * 512 + 16)
#define BT_K (4 * BT_B)
#define SM_WR (SM_EA + 8192)
#define SM_SIDE (SM_WR + 4352)
#define SM_EID (SM_SIDE + 2048)
#define SM_SRC (SM_EID + 2 * LCAP * 4)
#define SEQCAP (LCAP / 4 + 40)
#define SM_SEQ (SM_SRC + 2 * LCAP * 2)
#define SM_BAR ((SM_SEQ + 2 * SEQCAP * 2 + 63) / 64 * 64)
#define SM_TOTAL (SM_BAR + NW * (NP > 5 ? 32 : 16))
#define DUMB (2 * NP * 16)
#define MI_WBAR 32
#define MI_INT 0
#define EPS ((2464 + NT - 1) / NT)
#define KS (BINCAP / NT)
#define SC_ENT 0
#define SC_BIN (SC_ENT + NT * EPS * 8)
#define SC_HIST (SC_BIN + NT * EPS)
#define SC_CNT (SC_HIST + 3 * MAXBINS * 4)
static_assert(SC_HIST % 16 == 0 && SC_CNT + 2 * (NBK + 1) * 16 <= SM_MISC, "scratch");
static_assert(SM_TOTAL <= 232448 && SM_BAR % 16 == 0 && SM_SEQ % 16 == 0 && SM_SRC % 16 == 0 && SM_EA % 256 == 0, "smem");
#define PACE 18.6
#define TOFF 10400
#define PSLEEP 20

__device__ int2 g_bin[MAXBINS * BINCAP];
__device__ __align__(128) int g_bincnt[MAXBINS * 32];
#define TLSTAMP(i)
#define TLMAX(i)

__device__ __forceinline__ uint32_t pack_bf16(float lo, float hi) {
    uint32_t r;
    asm("cvt.rn.bf16x2.f32 %0, %1, %2;" : "=r"(r) : "f"(hi), "f"(lo));
    return r;
}
__device__ __forceinline__ void mma1688_z(float (&d)[4], uint32_t a0, uint32_t a1, uint32_t b0) {
    asm("mma.sync.aligned.m16n8k8.row.col.f32.bf16.bf16.f32 {%0,%1,%2,%3}, {%4,%5}, {%6}, {%7,%7,%7,%7};"
        : "=f"(d[0]), "=f"(d[1]), "=f"(d[2]), "=f"(d[3])
        : "r"(a0), "r"(a1), "r"(b0), "f"(0.f));
}
__device__ __forceinline__ void mma_diag(float (&d)[4], uint32_t a, uint32_t b0, uint32_t b1) {
    asm("mma.sync.aligned.m16n8k16.row.col.f32.bf16.bf16.f32 {%0,%1,%2,%3}, {%4,%8,%8,%4}, {%5,%6}, {%7,%7,%7,%7};"
        : "=f"(d[0]), "=f"(d[1]), "=f"(d[2]), "=f"(d[3])
        : "r"(a), "r"(b0), "r"(b1), "f"(0.f), "r"(0));
}
__device__ __forceinline__ uint32_t s2u(const void* p) { return (uint32_t)__cvta_generic_to_shared(p); }
__device__ __forceinline__ void mbar_init(uint32_t a, int c) {
    asm volatile("mbarrier.init.shared.b64 [%0], %1;" ::"r"(a), "r"(c));
}
__device__ __forceinline__ void mbar_expect_tx(uint32_t a, int bytes) {
    asm volatile("mbarrier.arrive.expect_tx.shared.b64 _, [%0], %1;" ::"r"(a), "r"(bytes) : "memory");
}
__device__ __forceinline__ void mbar_arrive(uint32_t a) {
    asm volatile("mbarrier.arrive.shared.b64 _, [%0];" ::"r"(a) : "memory");
}
__device__ __forceinline__ void mbar_arrive_cnt(uint32_t a, int c) {
    asm volatile("mbarrier.arrive.shared.b64 _, [%0], %1;" ::"r"(a), "r"(c) : "memory");
}
__device__ __forceinline__ void mbar_wait(uint32_t a, int parity) {
    asm volatile(
        "{\n.reg .pred p;\n.reg .u32 c;\n"
        "mov.u32 c, 0;\n"
        "LAB_WAIT:\n"
        "mbarrier.try_wait.parity.shared.b64 p, [%0], %1, 2000;\n"
        "@p bra DONE;\n"
        "add.u32 c, c, 1;\n"
        "setp.lt.u32 p, c, 2000000;\n"
        "@p bra LAB_WAIT;\n"
        "trap;\n"
        "DONE:\n}" ::"r"(a),
        "r"(parity)
        : "memory");
}
__device__ __forceinline__ void mbar_wait_u(uint32_t a, int parity) {
    asm volatile(
        "{\n.reg .pred p;\n.reg .u32 c;\n"
        "mov.u32 c, 0;\n"
        "LAB_WAIT:\n"
        "mbarrier.try_wait.parity.shared.b64 p, [%0], %1, 2000;\n"
        "@p bra.uni DONE;\n"
        "add.u32 c, c, 1;\n"
        "setp.lt.u32 p, c, 2000000;\n"
        "@p bra.uni LAB_WAIT;\n"
        "trap;\n"
        "DONE:\n}" ::"r"(a),
        "r"(parity)
        : "memory");
}
__device__ __forceinline__ void mbar_spin_u(uint32_t a, int parity) {
    asm volatile(
        "{\n.reg .pred p;\n.reg .u32 c;\n"
        "mov.u32 c, 0;\n"
        "LAB_WAIT:\n"
        "mbarrier.test_wait.parity.shared.b64 p, [%0], %1;\n"
        "@p bra.uni DONE;\n"
        "add.u32 c, c, 1;\n"
        "setp.lt.u32 p, c, 20000000;\n"
        "@p bra.uni LAB_WAIT;\n"
        "trap;\n"
        "DONE:\n}" ::"r"(a),
        "r"(parity)
        : "memory");
}
__device__ __forceinline__ void mbar_lean(uint32_t a, int parity) {
    asm volatile(
        "{\n.reg .pred p;\n.reg .u32 c;\n"
        "mov.u32 c, 0;\n"
        "LAB_WAIT:\n"
        "mbarrier.try_wait.parity.shared.b64 p, [%0], %1;\n"
        "@p bra DONE;\n"
        "add.u32 c, c, 1;\n"
        "setp.lt.u32 p, c, 4000000;\n"
        "@p bra LAB_WAIT;\n"
        "trap;\n"
        "DONE:\n}" ::"r"(a),
        "r"(parity)
        : "memory");
}
__device__ __forceinline__ void mbar_lean_u(uint32_t a, int parity) {
    asm volatile(
        "{\n.reg .pred p;\n.reg .u32 c;\n"
        "mov.u32 c, 0;\n"
        "LAB_WAIT:\n"
        "mbarrier.try_wait.parity.shared.b64 p, [%0], %1;\n"
        "@p bra.uni DONE;\n"
        "add.u32 c, c, 1;\n"
        "setp.lt.u32 p, c, 4000000;\n"
        "@p bra.uni LAB_WAIT;\n"
        "trap;\n"
        "DONE:\n}" ::"r"(a),
        "r"(parity)
        : "memory");
}
__device__ __forceinline__ bool mbar_test(uint32_t a, int parity) {
    uint32_t p;
    asm volatile("{\n.reg .pred P;\nmbarrier.test_wait.parity.shared.b64 P, [%1], %2;\nselp.u32 %0, 1, 0, P;\n}"
                 : "=r"(p)
                 : "r"(a), "r"(parity)
                 : "memory");
    return p;
}
__device__ __forceinline__ bool elect() {
    uint32_t p;
    asm volatile("{\n.reg .pred P;\nelect.sync _|P, 0xffffffff;\nselp.u32 %0, 1, 0, P;\n}" : "=r"(p));
    return p;
}
__device__ __forceinline__ void tma_2d(uint32_t dst, const CUtensorMap* tm, uint32_t bar, int c0, int c1) {
    asm volatile(
        "cp.async.bulk.tensor.2d.shared::cluster.global.mbarrier::complete_tx::bytes [%0], [%1, {%3, %4}], [%2];" ::"r"(dst),
        "l"(tm), "r"(bar), "r"(c0), "r"(c1)
        : "memory");
}
__device__ __forceinline__ void tma_row(uint32_t dst, const CUtensorMap* tm, uint32_t bar, int row8) {
    tma_2d(dst, tm, bar, 0, row8);
}
__device__ __forceinline__ void tma_store(const CUtensorMap* tm, uint32_t src, int c0, int c1) {
    asm volatile("cp.async.bulk.tensor.2d.global.shared::cta.bulk_group [%0, {%2, %3}], [%1];" ::"l"(tm), "r"(src),
                 "r"(c0), "r"(c1)
                 : "memory");
}
__device__ __forceinline__ uint2 lds_v2(uint32_t a) {
    uint2 v;
    asm volatile("ld.shared.v2.u32 {%0,%1}, [%2];" : "=r"(v.x), "=r"(v.y) : "r"(a));
    return v;
}
__device__ __forceinline__ uint4 lds_v4(uint32_t a) {
    uint4 v;
    asm volatile("ld.shared.v4.u32 {%0,%1,%2,%3}, [%4];" : "=r"(v.x), "=r"(v.y), "=r"(v.z), "=r"(v.w) : "r"(a));
    return v;
}
__device__ __forceinline__ uint32_t lds_u32(uint32_t a) {
    uint32_t v;
    asm volatile("ld.shared.u32 %0, [%1];" : "=r"(v) : "r"(a));
    return v;
}
__device__ __forceinline__ uint32_t lds_u16(uint32_t a) {
    uint32_t v;
    asm volatile("ld.shared.u16 %0, [%1];" : "=r"(v) : "r"(a));
    return v;
}
__device__ __forceinline__ void sts_v2(uint32_t a, uint32_t x, uint32_t y) {
    asm volatile("st.shared.v2.u32 [%0], {%1,%2};" ::"r"(a), "r"(x), "r"(y) : "memory");
}
__device__ __forceinline__ void sts_v4(uint32_t a, uint4 v) {
    asm volatile("st.shared.v4.u32 [%0], {%1,%2,%3,%4};" ::"r"(a), "r"(v.x), "r"(v.y), "r"(v.z), "r"(v.w) : "memory");
}
__device__ __forceinline__ void stsm4(uint32_t a, uint32_t r0, uint32_t r1, uint32_t r2, uint32_t r3) {
    asm volatile("stmatrix.sync.aligned.m8n8.x4.shared.b16 [%0], {%1,%2,%3,%4};" ::"r"(a), "r"(r0), "r"(r1), "r"(r2), "r"(r3)
                 : "memory");
}
__device__ __forceinline__ void stsm2(uint32_t a, uint32_t r0, uint32_t r1) {
    asm volatile("stmatrix.sync.aligned.m8n8.x2.shared.b16 [%0], {%1,%2};" ::"r"(a), "r"(r0), "r"(r1) : "memory");
}
__device__ __forceinline__ void stsm4t(uint32_t a, uint32_t r0, uint32_t r1, uint32_t r2, uint32_t r3) {
    asm volatile("stmatrix.sync.aligned.m8n8.x4.trans.shared.b16 [%0], {%1,%2,%3,%4};" ::"r"(a), "r"(r0), "r"(r1), "r"(r2),
                 "r"(r3)
                 : "memory");
}
__device__ __forceinline__ void stsm2t(uint32_t a, uint32_t r0, uint32_t r1) {
    asm volatile("stmatrix.sync.aligned.m8n8.x2.trans.shared.b16 [%0], {%1,%2};" ::"r"(a), "r"(r0), "r"(r1) : "memory");
}
__device__ __forceinline__ void cp_async16(uint32_t d, const void* s, int n) {
    asm volatile("cp.async.cg.shared.global [%0], [%1], 16, %2;" ::"r"(d), "l"(s), "r"(n) : "memory");
}
__device__ __forceinline__ void cp_async4(uint32_t d, const void* s, int n) {
    asm volatile("cp.async.ca.shared.global [%0], [%1], 4, %2;" ::"r"(d), "l"(s), "r"(n) : "memory");
}
__device__ __forceinline__ void sts_u32(uint32_t a, uint32_t x) {
    asm volatile("st.shared.u32 [%0], %1;" ::"r"(a), "r"(x) : "memory");
}
#define FENCE_ASYNC() asm volatile("fence.proxy.async.shared::cta;" ::: "memory")
__device__ __forceinline__ int warp_incl_scan(int v, int lane) {
#pragma unroll
    for (int o = 1; o < 32; o <<= 1) {
        const int y = __shfl_up_sync(0xffffffffu, v, o);
        if (lane >= o) v += y;
    }
    return v;
}

#define STR2(x) #x
#define STR(x) STR2(x)
#define NJ 19
__device__ __forceinline__ void consume(float (&acc)[2][NJ][4], uint32_t xa0, uint32_t xa1, uint32_t so0, uint32_t bar0,
                                        uint32_t ea0, uint32_t d0, uint32_t pl0, int lz, const uint32_t (&wa)[8]) {
    asm volatile(
        "{\n"
        ".reg .pred p, pf, plead, pok, t0, t1, t2, u0, u1, u2;\n"
        ".reg .b32 ca, cb, cz, rbar;\n"
        "mov.b32 cz, 0;\n"
        "mov.b32 ca, 0x20002000;\n"
        "mov.b32 cb, 0x30003000;\n"
        ".reg .b32 cnt, so, q, qe, bar, nbar, pl, ctl, ctm, ix, iy, dl, v0, v1, v2, v3, pp;\n"
        ".reg .b16 sl, sh;\n"
        ".reg .b32 hXa0, hXa1, hXa2, hXa3, hXa4, hXa5, hXa6, hXa7, hXb0, hXb1, hXb2, hXb3, hXb4, hXb5, hXb6, hXb7, hYa0, hYa1, hYa2, hYa3, hYa4, hYa5, hYa6, hYa7, hYb0, hYb1, hYb2, hYb3, hYb4, hYb5, hYb6, hYb7, hLa0, hLa1, hLa2, hLa3, hLa4, hLa5, hLa6, hLa7, hLb0, hLb1, hLb2, hLb3, hLb4, hLb5, hLb6, hLb7;\n"
        ".reg .b32 pX0, pX1, pX2, pX3, pY0, pY1, pY2, pY3;\n"
        ".reg .f32 r0, r1, r2, r3, r4, r5, r6, r7, r8, r9, r10, r11, r12, r13, r14, r15;\n"
        ".reg .b64 daX, dbX, daY, dbY, de0, de1;\n"
        ".reg .b32 dh<6>, eb0, par, npar, wa<8>, uz, bend;\n"
        "add.u32 wa0, %160, %159;\n"
        "add.u32 wa1, %161, %159;\n"
        "add.u32 wa2, %162, %159;\n"
        "add.u32 wa3, %163, %159;\n"
        "add.u32 wa4, %164, %159;\n"
        "add.u32 wa5, %165, %159;\n"
        "add.u32 wa6, %166, %159;\n"
        "add.u32 wa7, %167, %159;\n"
        "mov.f32 %0, 0f00000000;\n"
        "mov.f32 %1, 0f00000000;\n"
        "mov.f32 %2, 0f00000000;\n"
        "mov.f32 %3, 0f00000000;\n"
        "mov.f32 %4, 0f00000000;\n"
        "mov.f32 %5, 0f00000000;\n"
        "mov.f32 %6, 0f00000000;\n"
        "mov.f32 %7, 0f00000000;\n"
        "mov.f32 %8, 0f00000000;\n"
        "mov.f32 %9, 0f00000000;\n"
        "mov.f32 %10, 0f00000000;\n"
        "mov.f32 %11, 0f00000000;\n"
        "mov.f32 %12, 0f00000000;\n"
        "mov.f32 %13, 0f00000000;\n"
        "mov.f32 %14, 0f00000000;\n"
        "mov.f32 %15, 0f00000000;\n"
        "mov.f32 %16, 0f00000000;\n"
        "mov.f32 %17, 0f00000000;\n"
        "mov.f32 %18, 0f00000000;\n"
        "mov.f32 %19, 0f00000000;\n"
        "mov.f32 %20, 0f00000000;\n"
        "mov.f32 %21, 0f00000000;\n"
        "mov.f32 %22, 0f00000000;\n"
        "mov.f32 %23, 0f00000000;\n"
        "mov.f32 %24, 0f00000000;\n"
        "mov.f32 %25, 0f00000000;\n"
        "mov.f32 %26, 0f00000000;\n"
        "mov.f32 %27, 0f00000000;\n"
        "mov.f32 %28, 0f00000000;\n"
        "mov.f32 %29, 0f00000000;\n"
        "mov.f32 %30, 0f00000000;\n"
        "mov.f32 %31, 0f00000000;\n"
        "mov.f32 %32, 0f00000000;\n"
        "mov.f32 %33, 0f00000000;\n"
        "mov.f32 %34, 0f00000000;\n"
        "mov.f32 %35, 0f00000000;\n"
        "mov.f32 %36, 0f00000000;\n"
        "mov.f32 %37, 0f00000000;\n"
        "mov.f32 %38, 0f00000000;\n"
        "mov.f32 %39, 0f00000000;\n"
        "mov.f32 %40, 0f00000000;\n"
        "mov.f32 %41, 0f00000000;\n"
        "mov.f32 %42, 0f00000000;\n"
        "mov.f32 %43, 0f00000000;\n"
        "mov.f32 %44, 0f00000000;\n"
        "mov.f32 %45, 0f00000000;\n"
        "mov.f32 %46, 0f00000000;\n"
        "mov.f32 %47, 0f00000000;\n"
        "mov.f32 %48, 0f00000000;\n"
        "mov.f32 %49, 0f00000000;\n"
        "mov.f32 %50, 0f00000000;\n"
        "mov.f32 %51, 0f00000000;\n"
        "mov.f32 %52, 0f00000000;\n"
        "mov.f32 %53, 0f00000000;\n"
        "mov.f32 %54, 0f00000000;\n"
        "mov.f32 %55, 0f00000000;\n"
        "mov.f32 %56, 0f00000000;\n"
        "mov.f32 %57, 0f00000000;\n"
        "mov.f32 %58, 0f00000000;\n"
        "mov.f32 %59, 0f00000000;\n"
        "mov.f32 %60, 0f00000000;\n"
        "mov.f32 %61, 0f00000000;\n"
        "mov.f32 %62, 0f00000000;\n"
        "mov.f32 %63, 0f00000000;\n"
        "mov.f32 %64, 0f00000000;\n"
        "mov.f32 %65, 0f00000000;\n"
        "mov.f32 %66, 0f00000000;\n"
        "mov.f32 %67, 0f00000000;\n"
        "mov.f32 %68, 0f00000000;\n"
        "mov.f32 %69, 0f00000000;\n"
        "mov.f32 %70, 0f00000000;\n"
        "mov.f32 %71, 0f00000000;\n"
        "mov.f32 %72, 0f00000000;\n"
        "mov.f32 %73, 0f00000000;\n"
        "mov.f32 %74, 0f00000000;\n"
        "mov.f32 %75, 0f00000000;\n"
        "mov.f32 %76, 0f00000000;\n"
        "mov.f32 %77, 0f00000000;\n"
        "mov.f32 %78, 0f00000000;\n"
        "mov.f32 %79, 0f00000000;\n"
        "mov.f32 %80, 0f00000000;\n"
        "mov.f32 %81, 0f00000000;\n"
        "mov.f32 %82, 0f00000000;\n"
        "mov.f32 %83, 0f00000000;\n"
        "mov.f32 %84, 0f00000000;\n"
        "mov.f32 %85, 0f00000000;\n"
        "mov.f32 %86, 0f00000000;\n"
        "mov.f32 %87, 0f00000000;\n"
        "mov.f32 %88, 0f00000000;\n"
        "mov.f32 %89, 0f00000000;\n"
        "mov.f32 %90, 0f00000000;\n"
        "mov.f32 %91, 0f00000000;\n"
        "mov.f32 %92, 0f00000000;\n"
        "mov.f32 %93, 0f00000000;\n"
        "mov.f32 %94, 0f00000000;\n"
        "mov.f32 %95, 0f00000000;\n"
        "mov.f32 %96, 0f00000000;\n"
        "mov.f32 %97, 0f00000000;\n"
        "mov.f32 %98, 0f00000000;\n"
        "mov.f32 %99, 0f00000000;\n"
        "mov.f32 %100, 0f00000000;\n"
        "mov.f32 %101, 0f00000000;\n"
        "mov.f32 %102, 0f00000000;\n"
        "mov.f32 %103, 0f00000000;\n"
        "mov.f32 %104, 0f00000000;\n"
        "mov.f32 %105, 0f00000000;\n"
        "mov.f32 %106, 0f00000000;\n"
        "mov.f32 %107, 0f00000000;\n"
        "mov.f32 %108, 0f00000000;\n"
        "mov.f32 %109, 0f00000000;\n"
        "mov.f32 %110, 0f00000000;\n"
        "mov.f32 %111, 0f00000000;\n"
        "mov.f32 %112, 0f00000000;\n"
        "mov.f32 %113, 0f00000000;\n"
        "mov.f32 %114, 0f00000000;\n"
        "mov.f32 %115, 0f00000000;\n"
        "mov.f32 %116, 0f00000000;\n"
        "mov.f32 %117, 0f00000000;\n"
        "mov.f32 %118, 0f00000000;\n"
        "mov.f32 %119, 0f00000000;\n"
        "mov.f32 %120, 0f00000000;\n"
        "mov.f32 %121, 0f00000000;\n"
        "mov.f32 %122, 0f00000000;\n"
        "mov.f32 %123, 0f00000000;\n"
        "mov.f32 %124, 0f00000000;\n"
        "mov.f32 %125, 0f00000000;\n"
        "mov.f32 %126, 0f00000000;\n"
        "mov.f32 %127, 0f00000000;\n"
        "mov.f32 %128, 0f00000000;\n"
        "mov.f32 %129, 0f00000000;\n"
        "mov.f32 %130, 0f00000000;\n"
        "mov.f32 %131, 0f00000000;\n"
        "mov.f32 %132, 0f00000000;\n"
        "mov.f32 %133, 0f00000000;\n"
        "mov.f32 %134, 0f00000000;\n"
        "mov.f32 %135, 0f00000000;\n"
        "mov.f32 %136, 0f00000000;\n"
        "mov.f32 %137, 0f00000000;\n"
        "mov.f32 %138, 0f00000000;\n"
        "mov.f32 %139, 0f00000000;\n"
        "mov.f32 %140, 0f00000000;\n"
        "mov.f32 %141, 0f00000000;\n"
        "mov.f32 %142, 0f00000000;\n"
        "mov.f32 %143, 0f00000000;\n"
        "mov.f32 %144, 0f00000000;\n"
        "mov.f32 %145, 0f00000000;\n"
        "mov.f32 %146, 0f00000000;\n"
        "mov.f32 %147, 0f00000000;\n"
        "mov.f32 %148, 0f00000000;\n"
        "mov.f32 %149, 0f00000000;\n"
        "mov.f32 %150, 0f00000000;\n"
        "mov.f32 %151, 0f00000000;\n"
        "setp.ne.u32 pf, 0, 0;\n"
        "add.u32 v0, %154, %159;\n"
        "shfl.sync.idx.b32 so, v0, 0, 31, 0xffffffff;\n"
        "mov.u32 npar, 0;\n"
        "shfl.sync.idx.b32 uz, %159, 7, 31, 0xffffffff;\n"
        "add.u32 bend, %155, " STR(NP * 16) ";\n"
        "add.u32 v0, %159, 8;\n"
        "shfl.sync.idx.b32 dh0, v0, 0, 31, 0xffffffff;\n"
        "shfl.sync.idx.b32 dh1, v0, 1, 31, 0xffffffff;\n"
        "shfl.sync.idx.b32 dh2, v0, 2, 31, 0xffffffff;\n"
        "shfl.sync.idx.b32 dh3, v0, 3, 31, 0xffffffff;\n"
        "add.u32 v0, %159, 0xc0000010;\n"
        "shfl.sync.idx.b32 dh4, v0, 4, 31, 0xffffffff;\n"
        "shfl.sync.idx.b32 dh5, v0, 5, 31, 0xffffffff;\n"
        "add.u32 v0, %159, %156;\n"
        "shfl.sync.idx.b32 eb0, v0, 0, 31, 0xffffffff;\n"
        "mov.u32 q, 0;\n"
        "mov.u32 pl, %158;\n"
        "shr.u32 nbar, so, 9;\n"
        "add.u32 nbar, nbar, %155;\n"
        "elect.sync _|plead, 0xffffffff;\n"
        "mov.b64 de0, {%156, dh4};\n"
        "mov.b64 de1, {eb0, dh5};\n"
        "mov.b32 hYa0, 0;\n"
        "mov.b32 hYa1, 0;\n"
        "mov.b32 hYa2, 0;\n"
        "mov.b32 hYa3, 0;\n"
        "mov.b32 hYa4, 0;\n"
        "mov.b32 hYa5, 0;\n"
        "mov.b32 hYa6, 0;\n"
        "mov.b32 hYa7, 0;\n"
        "mov.b32 hYb0, 0;\n"
        "mov.b32 hYb1, 0;\n"
        "mov.b32 hYb2, 0;\n"
        "mov.b32 hYb3, 0;\n"
        "mov.b32 hYb4, 0;\n"
        "mov.b32 hYb5, 0;\n"
        "mov.b32 hYb6, 0;\n"
        "mov.b32 hYb7, 0;\n"
        "mov.u32 ctm, 0x10001000;\n"
        "setp.lt.f16x2 t0|u0, ctm, cz;\n"
        "abs.f16x2 v3, ctm;\n"
        "setp.ge.f16x2 t1|u1, v3, ca;\n"
        "setp.geu.f16x2 t2|u2, v3, cb;\n"
        "ld.shared.v2.u32 {ctl, ctm}, [pl];\n"
        "add.u32 pl, pl, 8;\n"
        "add.u32 rbar, %155, " STR(DUMB) ";\n"
        "mov.b64 daX, {%157, dh0};\n"
        "mov.b64 dbX, {%157, dh1};\n"
        "mov.b64 daY, {%157, dh2};\n"
        "mov.b64 dbY, {%157, dh3};\n"
        "mov.u32 bar, nbar;\n"
        "mov.u32 par, npar;\n"
        "sub.u32 so, bar, %155;\n"
        "shl.b32 so, so, 9;\n"
        "add.u32 v0, %152, so;\n"
        "add.u32 v1, %153, so;\n"
        "add.u32 nbar, nbar, 16;\n"
        "setp.eq.u32 p, nbar, bend;\n"
        "selp.b32 nbar, %155, nbar, p;\n"
        "@p xor.b32 npar, npar, 1;\n"
        "SLOW:\n"
        "mov.u32 cnt, 0;\n"
        "W1:\n"
        "mbarrier.try_wait.parity.shared.b64 p, [bar], par;\n"
        "@p bra.uni RES;\n"
        "add.u32 cnt, cnt, 1;\n"
        "setp.lt.u32 p, cnt, 4000000;\n"
        "@p bra.uni W1;\n"
        "trap;\n"
        "CX:\n"
        "mbarrier.test_wait.parity.shared.b64 pok, [nbar], npar;\n"
        "and.b32 dl, q, 0x60;\n"
        "add.u32 dl, dl, %157;\n"
        "add.u32 v3, dl, 0;\n"
        "mov.b64 {v2, dh0}, daX;\n"
        "mov.b64 daX, {v3, dh0};\n"
        "add.u32 v3, dl, 257;\n"
        "mov.b64 {v2, dh1}, dbX;\n"
        "mov.b64 dbX, {v3, dh1};\n"
        "add.u32 v3, dl, 514;\n"
        "mov.b64 {v2, dh2}, daY;\n"
        "mov.b64 daY, {v3, dh2};\n"
        "add.u32 v3, dl, 771;\n"
        "mov.b64 {v2, dh3}, dbY;\n"
        "mov.b64 dbY, {v3, dh3};\n"
        "add.u32 q, q, 32;\n"
        "and.b32 qe, q, 0xe0;\n"
        "add.u32 v3, qe, %156;\n"
        "mov.b64 {v2, dh4}, de0;\n"
        "mov.b64 de0, {v3, dh4};\n"
        "mov.b64 {v2, dh5}, de1;\n"
        "mov.b64 de1, {v3, dh5};\n"
        "setp.lt.f16x2 t0|u0, ctl, cz;\n"
        "abs.f16x2 v3, ctl;\n"
        "setp.ge.f16x2 t1|u1, v3, ca;\n"
        "setp.geu.f16x2 t2|u2, v3, cb;\n"
        "wgmma.wait_group.sync.aligned 2;\n"
        "cvt.rn.bf16x2.f32 pX0, r1, r0;\n"
        "cvt.rn.bf16x2.f32 pX1, r3, r2;\n"
        "cvt.rn.bf16x2.f32 pX2, r9, r8;\n"
        "cvt.rn.bf16x2.f32 pX3, r11, r10;\n"
        "cvt.rn.bf16x2.f32 pY0, r5, r4;\n"
        "cvt.rn.bf16x2.f32 pY1, r7, r6;\n"
        "cvt.rn.bf16x2.f32 pY2, r13, r12;\n"
        "cvt.rn.bf16x2.f32 pY3, r15, r14;\n"
        "mov.b32 {sl, sh}, pX0;\n"
        "mov.b32 pp, {sl, sl};\n"
        "mul.rn.bf16x2 hXa0, hLa0, pp;\n"
        "mul.rn.bf16x2 hXa2, hLa2, pp;\n"
        "mov.b32 {sl, sh}, pX1;\n"
        "mov.b32 pp, {sl, sl};\n"
        "mul.rn.bf16x2 hXa1, hLa1, pp;\n"
        "mul.rn.bf16x2 hXa3, hLa3, pp;\n"
        "mov.b32 {sl, sh}, pX2;\n"
        "mov.b32 pp, {sl, sl};\n"
        "mul.rn.bf16x2 hXa4, hLa4, pp;\n"
        "mul.rn.bf16x2 hXa6, hLa6, pp;\n"
        "mov.b32 {sl, sh}, pX3;\n"
        "mov.b32 pp, {sl, sl};\n"
        "mul.rn.bf16x2 hXa5, hLa5, pp;\n"
        "mul.rn.bf16x2 hXa7, hLa7, pp;\n"
        "mov.b32 {sl, sh}, pX0;\n"
        "mov.b32 pp, {sh, sh};\n"
        "mul.rn.bf16x2 hXb0, hLb0, pp;\n"
        "mul.rn.bf16x2 hXb2, hLb2, pp;\n"
        "mov.b32 {sl, sh}, pX1;\n"
        "mov.b32 pp, {sh, sh};\n"
        "mul.rn.bf16x2 hXb1, hLb1, pp;\n"
        "mul.rn.bf16x2 hXb3, hLb3, pp;\n"
        "mov.b32 {sl, sh}, pX2;\n"
        "mov.b32 pp, {sh, sh};\n"
        "mul.rn.bf16x2 hXb4, hLb4, pp;\n"
        "mul.rn.bf16x2 hXb6, hLb6, pp;\n"
        "mov.b32 {sl, sh}, pX3;\n"
        "mov.b32 pp, {sh, sh};\n"
        "mul.rn.bf16x2 hXb5, hLb5, pp;\n"
        "mul.rn.bf16x2 hXb7, hLb7, pp;\n"
        "ldmatrix.sync.aligned.m8n8.x4.trans.shared.b16 {hLa0,hLa1,hLa2,hLa3}, [v0+4096];\n"
        "ldmatrix.sync.aligned.m8n8.x4.trans.shared.b16 {hLa4,hLa5,hLa6,hLa7}, [v1+4096];\n"
        "ldmatrix.sync.aligned.m8n8.x4.trans.shared.b16 {hLb0,hLb1,hLb2,hLb3}, [v0+6144];\n"
        "ldmatrix.sync.aligned.m8n8.x4.trans.shared.b16 {hLb4,hLb5,hLb6,hLb7}, [v1+6144];\n"
        "@t2 bra.uni T4X;\n"
        "@t1 bra.uni T2X;\n"
        "@t0 bra.uni L1X;\n"
        "L0X:\n"
        "wgmma.fence.sync.aligned;\n"
        "wgmma.mma_async.sync.aligned.m64n24k16.f32.bf16.bf16 {%0,%1,%2,%3,%4,%5,%6,%7,%8,%9,%10,%11}, {hXa0,hXa1,hXa2,hXa3}, daX, 1, 1, 1, 0;\n"
        "wgmma.mma_async.sync.aligned.m64n24k16.f32.bf16.bf16 {%76,%77,%78,%79,%80,%81,%82,%83,%84,%85,%86,%87}, {hXa4,hXa5,hXa6,hXa7}, daX, 1, 1, 1, 0;\n"
        "wgmma.commit_group.sync.aligned;\n"
        "@u2 bra.uni T4Xb;\n"
        "@u1 bra.uni T2Xb;\n"
        "@u0 bra.uni L1Xb;\n"
        "bra.uni L0Xb;\n"
        "L1X:\n"
        "wgmma.fence.sync.aligned;\n"
        "wgmma.mma_async.sync.aligned.m64n24k16.f32.bf16.bf16 {%12,%13,%14,%15,%16,%17,%18,%19,%20,%21,%22,%23}, {hXa0,hXa1,hXa2,hXa3}, daX, 1, 1, 1, 0;\n"
        "wgmma.mma_async.sync.aligned.m64n24k16.f32.bf16.bf16 {%88,%89,%90,%91,%92,%93,%94,%95,%96,%97,%98,%99}, {hXa4,hXa5,hXa6,hXa7}, daX, 1, 1, 1, 0;\n"
        "wgmma.commit_group.sync.aligned;\n"
        "@u2 bra.uni T4Xb;\n"
        "@u1 bra.uni T2Xb;\n"
        "@u0 bra.uni L1Xb;\n"
        "bra.uni L0Xb;\n"
        "T2X:\n"
        "@t0 bra.uni L3X;\n"
        "L2X:\n"
        "wgmma.fence.sync.aligned;\n"
        "wgmma.mma_async.sync.aligned.m64n24k16.f32.bf16.bf16 {%24,%25,%26,%27,%28,%29,%30,%31,%32,%33,%34,%35}, {hXa0,hXa1,hXa2,hXa3}, daX, 1, 1, 1, 0;\n"
        "wgmma.mma_async.sync.aligned.m64n24k16.f32.bf16.bf16 {%100,%101,%102,%103,%104,%105,%106,%107,%108,%109,%110,%111}, {hXa4,hXa5,hXa6,hXa7}, daX, 1, 1, 1, 0;\n"
        "wgmma.commit_group.sync.aligned;\n"
        "@u2 bra.uni T4Xb;\n"
        "@u1 bra.uni T2Xb;\n"
        "@u0 bra.uni L1Xb;\n"
        "bra.uni L0Xb;\n"
        "L3X:\n"
        "wgmma.fence.sync.aligned;\n"
        "wgmma.mma_async.sync.aligned.m64n24k16.f32.bf16.bf16 {%36,%37,%38,%39,%40,%41,%42,%43,%44,%45,%46,%47}, {hXa0,hXa1,hXa2,hXa3}, daX, 1, 1, 1, 0;\n"
        "wgmma.mma_async.sync.aligned.m64n24k16.f32.bf16.bf16 {%112,%113,%114,%115,%116,%117,%118,%119,%120,%121,%122,%123}, {hXa4,hXa5,hXa6,hXa7}, daX, 1, 1, 1, 0;\n"
        "wgmma.commit_group.sync.aligned;\n"
        "@u2 bra.uni T4Xb;\n"
        "@u1 bra.uni T2Xb;\n"
        "@u0 bra.uni L1Xb;\n"
        "bra.uni L0Xb;\n"
        "T4X:\n"
        "@!t1 bra.uni LEXIT;\n"
        "@t0 bra.uni L5X;\n"
        "L4X:\n"
        "wgmma.fence.sync.aligned;\n"
        "wgmma.mma_async.sync.aligned.m64n24k16.f32.bf16.bf16 {%48,%49,%50,%51,%52,%53,%54,%55,%56,%57,%58,%59}, {hXa0,hXa1,hXa2,hXa3}, daX, 1, 1, 1, 0;\n"
        "wgmma.mma_async.sync.aligned.m64n24k16.f32.bf16.bf16 {%124,%125,%126,%127,%128,%129,%130,%131,%132,%133,%134,%135}, {hXa4,hXa5,hXa6,hXa7}, daX, 1, 1, 1, 0;\n"
        "wgmma.commit_group.sync.aligned;\n"
        "@u2 bra.uni T4Xb;\n"
        "@u1 bra.uni T2Xb;\n"
        "@u0 bra.uni L1Xb;\n"
        "bra.uni L0Xb;\n"
        "L5X:\n"
        "wgmma.fence.sync.aligned;\n"
        "wgmma.mma_async.sync.aligned.m64n32k16.f32.bf16.bf16 {%60,%61,%62,%63,%64,%65,%66,%67,%68,%69,%70,%71,%72,%73,%74,%75}, {hXa0,hXa1,hXa2,hXa3}, daX, 1, 1, 1, 0;\n"
        "wgmma.mma_async.sync.aligned.m64n32k16.f32.bf16.bf16 {%136,%137,%138,%139,%140,%141,%142,%143,%144,%145,%146,%147,%148,%149,%150,%151}, {hXa4,hXa5,hXa6,hXa7}, daX, 1, 1, 1, 0;\n"
        "wgmma.commit_group.sync.aligned;\n"
        "@u2 bra.uni T4Xb;\n"
        "@u1 bra.uni T2Xb;\n"
        "@u0 bra.uni L1Xb;\n"
        "L0Xb:\n"
        "wgmma.fence.sync.aligned;\n"
        "wgmma.mma_async.sync.aligned.m64n24k16.f32.bf16.bf16 {%0,%1,%2,%3,%4,%5,%6,%7,%8,%9,%10,%11}, {hXb0,hXb1,hXb2,hXb3}, dbX, 1, 1, 1, 0;\n"
        "wgmma.mma_async.sync.aligned.m64n24k16.f32.bf16.bf16 {%76,%77,%78,%79,%80,%81,%82,%83,%84,%85,%86,%87}, {hXb4,hXb5,hXb6,hXb7}, dbX, 1, 1, 1, 0;\n"
        "wgmma.commit_group.sync.aligned;\n"
        "bra.uni CY;\n"
        "L1Xb:\n"
        "wgmma.fence.sync.aligned;\n"
        "wgmma.mma_async.sync.aligned.m64n24k16.f32.bf16.bf16 {%12,%13,%14,%15,%16,%17,%18,%19,%20,%21,%22,%23}, {hXb0,hXb1,hXb2,hXb3}, dbX, 1, 1, 1, 0;\n"
        "wgmma.mma_async.sync.aligned.m64n24k16.f32.bf16.bf16 {%88,%89,%90,%91,%92,%93,%94,%95,%96,%97,%98,%99}, {hXb4,hXb5,hXb6,hXb7}, dbX, 1, 1, 1, 0;\n"
        "wgmma.commit_group.sync.aligned;\n"
        "bra.uni CY;\n"
        "T2Xb:\n"
        "@u0 bra.uni L3Xb;\n"
        "L2Xb:\n"
        "wgmma.fence.sync.aligned;\n"
        "wgmma.mma_async.sync.aligned.m64n24k16.f32.bf16.bf16 {%24,%25,%26,%27,%28,%29,%30,%31,%32,%33,%34,%35}, {hXb0,hXb1,hXb2,hXb3}, dbX, 1, 1, 1, 0;\n"
        "wgmma.mma_async.sync.aligned.m64n24k16.f32.bf16.bf16 {%100,%101,%102,%103,%104,%105,%106,%107,%108,%109,%110,%111}, {hXb4,hXb5,hXb6,hXb7}, dbX, 1, 1, 1, 0;\n"
        "wgmma.commit_group.sync.aligned;\n"
        "bra.uni CY;\n"
        "L3Xb:\n"
        "wgmma.fence.sync.aligned;\n"
        "wgmma.mma_async.sync.aligned.m64n24k16.f32.bf16.bf16 {%36,%37,%38,%39,%40,%41,%42,%43,%44,%45,%46,%47}, {hXb0,hXb1,hXb2,hXb3}, dbX, 1, 1, 1, 0;\n"
        "wgmma.mma_async.sync.aligned.m64n24k16.f32.bf16.bf16 {%112,%113,%114,%115,%116,%117,%118,%119,%120,%121,%122,%123}, {hXb4,hXb5,hXb6,hXb7}, dbX, 1, 1, 1, 0;\n"
        "wgmma.commit_group.sync.aligned;\n"
        "bra.uni CY;\n"
        "T4Xb:\n"
        "@u0 bra.uni L5Xb;\n"
        "L4Xb:\n"
        "wgmma.fence.sync.aligned;\n"
        "wgmma.mma_async.sync.aligned.m64n24k16.f32.bf16.bf16 {%48,%49,%50,%51,%52,%53,%54,%55,%56,%57,%58,%59}, {hXb0,hXb1,hXb2,hXb3}, dbX, 1, 1, 1, 0;\n"
        "wgmma.mma_async.sync.aligned.m64n24k16.f32.bf16.bf16 {%124,%125,%126,%127,%128,%129,%130,%131,%132,%133,%134,%135}, {hXb4,hXb5,hXb6,hXb7}, dbX, 1, 1, 1, 0;\n"
        "wgmma.commit_group.sync.aligned;\n"
        "bra.uni CY;\n"
        "L5Xb:\n"
        "wgmma.fence.sync.aligned;\n"
        "wgmma.mma_async.sync.aligned.m64n32k16.f32.bf16.bf16 {%60,%61,%62,%63,%64,%65,%66,%67,%68,%69,%70,%71,%72,%73,%74,%75}, {hXb0,hXb1,hXb2,hXb3}, dbX, 1, 1, 1, 0;\n"
        "wgmma.mma_async.sync.aligned.m64n32k16.f32.bf16.bf16 {%136,%137,%138,%139,%140,%141,%142,%143,%144,%145,%146,%147,%148,%149,%150,%151}, {hXb4,hXb5,hXb6,hXb7}, dbX, 1, 1, 1, 0;\n"
        "wgmma.commit_group.sync.aligned;\n"
        "bra.uni CY;\n"
        "CY:\n"
        "mov.u32 rbar, bar;\n"
        "mov.u32 bar, nbar;\n"
        "mov.u32 par, npar;\n"
        "sub.u32 so, bar, %155;\n"
        "shl.b32 so, so, 9;\n"
        "add.u32 v0, %152, so;\n"
        "add.u32 v1, %153, so;\n"
        "add.u32 nbar, nbar, 16;\n"
        "setp.eq.u32 p, nbar, bend;\n"
        "selp.b32 nbar, %155, nbar, p;\n"
        "@p xor.b32 npar, npar, 1;\n"
        "wgmma.wait_group.sync.aligned 2;\n"
        "lop3.b32 v2, hLa3, hLa7, hLb3, 0x80;\n"
        "lop3.b32 v2, v2, hLb7, uz, 0x80;\n"
        "add.u32 v2, v2, rbar;\n"
        "@plead mbarrier.arrive.shared.b64 _, [v2+8];\n"
        "setp.lt.f16x2 t0|u0, ctm, cz;\n"
        "abs.f16x2 v3, ctm;\n"
        "setp.ge.f16x2 t1|u1, v3, ca;\n"
        "setp.geu.f16x2 t2|u2, v3, cb;\n"
        "ld.shared.v2.u32 {ctl, ctm}, [pl];\n"
        "add.u32 pl, pl, 8;\n"
        "mov.b32 {sl, sh}, pY0;\n"
        "mov.b32 pp, {sl, sl};\n"
        "mul.rn.bf16x2 hYa0, hLa0, pp;\n"
        "mul.rn.bf16x2 hYa2, hLa2, pp;\n"
        "mov.b32 {sl, sh}, pY1;\n"
        "mov.b32 pp, {sl, sl};\n"
        "mul.rn.bf16x2 hYa1, hLa1, pp;\n"
        "mul.rn.bf16x2 hYa3, hLa3, pp;\n"
        "mov.b32 {sl, sh}, pY2;\n"
        "mov.b32 pp, {sl, sl};\n"
        "mul.rn.bf16x2 hYa4, hLa4, pp;\n"
        "mul.rn.bf16x2 hYa6, hLa6, pp;\n"
        "mov.b32 {sl, sh}, pY3;\n"
        "mov.b32 pp, {sl, sl};\n"
        "mul.rn.bf16x2 hYa5, hLa5, pp;\n"
        "mul.rn.bf16x2 hYa7, hLa7, pp;\n"
        "mov.b32 {sl, sh}, pY0;\n"
        "mov.b32 pp, {sh, sh};\n"
        "mul.rn.bf16x2 hYb0, hLb0, pp;\n"
        "mul.rn.bf16x2 hYb2, hLb2, pp;\n"
        "mov.b32 {sl, sh}, pY1;\n"
        "mov.b32 pp, {sh, sh};\n"
        "mul.rn.bf16x2 hYb1, hLb1, pp;\n"
        "mul.rn.bf16x2 hYb3, hLb3, pp;\n"
        "mov.b32 {sl, sh}, pY2;\n"
        "mov.b32 pp, {sh, sh};\n"
        "mul.rn.bf16x2 hYb4, hLb4, pp;\n"
        "mul.rn.bf16x2 hYb6, hLb6, pp;\n"
        "mov.b32 {sl, sh}, pY3;\n"
        "mov.b32 pp, {sh, sh};\n"
        "mul.rn.bf16x2 hYb5, hLb5, pp;\n"
        "mul.rn.bf16x2 hYb7, hLb7, pp;\n"
        "@!pok bra.uni SLOW;\n"
        "RES:\n"
        "ldmatrix.sync.aligned.m8n8.x4.trans.shared.b16 {hLa0,hLa1,hLa2,hLa3}, [v0+0];\n"
        "ldmatrix.sync.aligned.m8n8.x4.trans.shared.b16 {hLa4,hLa5,hLa6,hLa7}, [v1+0];\n"
        "ldmatrix.sync.aligned.m8n8.x4.trans.shared.b16 {hLb0,hLb1,hLb2,hLb3}, [v0+2048];\n"
        "ldmatrix.sync.aligned.m8n8.x4.trans.shared.b16 {hLb4,hLb5,hLb6,hLb7}, [v1+2048];\n"
        "wgmma.wait_group.sync.aligned 0;\n"
        "@t2 bra.uni T4Y;\n"
        "@t1 bra.uni T2Y;\n"
        "@t0 bra.uni L1Y;\n"
        "L0Y:\n"
        "wgmma.fence.sync.aligned;\n"
        "wgmma.mma_async.sync.aligned.m64n16k16.f32.bf16.bf16 {r0,r1,r2,r3,r4,r5,r6,r7}, {wa0,wa1,wa2,wa3}, de0, pf, 1, 1, 0;\n"
        "wgmma.mma_async.sync.aligned.m64n16k16.f32.bf16.bf16 {r8,r9,r10,r11,r12,r13,r14,r15}, {wa4,wa5,wa6,wa7}, de1, pf, 1, 1, 0;\n"
        "wgmma.commit_group.sync.aligned;\n"
        "wgmma.mma_async.sync.aligned.m64n24k16.f32.bf16.bf16 {%0,%1,%2,%3,%4,%5,%6,%7,%8,%9,%10,%11}, {hYa0,hYa1,hYa2,hYa3}, daY, 1, 1, 1, 0;\n"
        "wgmma.mma_async.sync.aligned.m64n24k16.f32.bf16.bf16 {%76,%77,%78,%79,%80,%81,%82,%83,%84,%85,%86,%87}, {hYa4,hYa5,hYa6,hYa7}, daY, 1, 1, 1, 0;\n"
        "wgmma.commit_group.sync.aligned;\n"
        "@u2 bra.uni T4Yb;\n"
        "@u1 bra.uni T2Yb;\n"
        "@u0 bra.uni L1Yb;\n"
        "bra.uni L0Yb;\n"
        "L1Y:\n"
        "wgmma.fence.sync.aligned;\n"
        "wgmma.mma_async.sync.aligned.m64n16k16.f32.bf16.bf16 {r0,r1,r2,r3,r4,r5,r6,r7}, {wa0,wa1,wa2,wa3}, de0, pf, 1, 1, 0;\n"
        "wgmma.mma_async.sync.aligned.m64n16k16.f32.bf16.bf16 {r8,r9,r10,r11,r12,r13,r14,r15}, {wa4,wa5,wa6,wa7}, de1, pf, 1, 1, 0;\n"
        "wgmma.commit_group.sync.aligned;\n"
        "wgmma.mma_async.sync.aligned.m64n24k16.f32.bf16.bf16 {%12,%13,%14,%15,%16,%17,%18,%19,%20,%21,%22,%23}, {hYa0,hYa1,hYa2,hYa3}, daY, 1, 1, 1, 0;\n"
        "wgmma.mma_async.sync.aligned.m64n24k16.f32.bf16.bf16 {%88,%89,%90,%91,%92,%93,%94,%95,%96,%97,%98,%99}, {hYa4,hYa5,hYa6,hYa7}, daY, 1, 1, 1, 0;\n"
        "wgmma.commit_group.sync.aligned;\n"
        "@u2 bra.uni T4Yb;\n"
        "@u1 bra.uni T2Yb;\n"
        "@u0 bra.uni L1Yb;\n"
        "bra.uni L0Yb;\n"
        "T2Y:\n"
        "@t0 bra.uni L3Y;\n"
        "L2Y:\n"
        "wgmma.fence.sync.aligned;\n"
        "wgmma.mma_async.sync.aligned.m64n16k16.f32.bf16.bf16 {r0,r1,r2,r3,r4,r5,r6,r7}, {wa0,wa1,wa2,wa3}, de0, pf, 1, 1, 0;\n"
        "wgmma.mma_async.sync.aligned.m64n16k16.f32.bf16.bf16 {r8,r9,r10,r11,r12,r13,r14,r15}, {wa4,wa5,wa6,wa7}, de1, pf, 1, 1, 0;\n"
        "wgmma.commit_group.sync.aligned;\n"
        "wgmma.mma_async.sync.aligned.m64n24k16.f32.bf16.bf16 {%24,%25,%26,%27,%28,%29,%30,%31,%32,%33,%34,%35}, {hYa0,hYa1,hYa2,hYa3}, daY, 1, 1, 1, 0;\n"
        "wgmma.mma_async.sync.aligned.m64n24k16.f32.bf16.bf16 {%100,%101,%102,%103,%104,%105,%106,%107,%108,%109,%110,%111}, {hYa4,hYa5,hYa6,hYa7}, daY, 1, 1, 1, 0;\n"
        "wgmma.commit_group.sync.aligned;\n"
        "@u2 bra.uni T4Yb;\n"
        "@u1 bra.uni T2Yb;\n"
        "@u0 bra.uni L1Yb;\n"
        "bra.uni L0Yb;\n"
        "L3Y:\n"
        "wgmma.fence.sync.aligned;\n"
        "wgmma.mma_async.sync.aligned.m64n16k16.f32.bf16.bf16 {r0,r1,r2,r3,r4,r5,r6,r7}, {wa0,wa1,wa2,wa3}, de0, pf, 1, 1, 0;\n"
        "wgmma.mma_async.sync.aligned.m64n16k16.f32.bf16.bf16 {r8,r9,r10,r11,r12,r13,r14,r15}, {wa4,wa5,wa6,wa7}, de1, pf, 1, 1, 0;\n"
        "wgmma.commit_group.sync.aligned;\n"
        "wgmma.mma_async.sync.aligned.m64n24k16.f32.bf16.bf16 {%36,%37,%38,%39,%40,%41,%42,%43,%44,%45,%46,%47}, {hYa0,hYa1,hYa2,hYa3}, daY, 1, 1, 1, 0;\n"
        "wgmma.mma_async.sync.aligned.m64n24k16.f32.bf16.bf16 {%112,%113,%114,%115,%116,%117,%118,%119,%120,%121,%122,%123}, {hYa4,hYa5,hYa6,hYa7}, daY, 1, 1, 1, 0;\n"
        "wgmma.commit_group.sync.aligned;\n"
        "@u2 bra.uni T4Yb;\n"
        "@u1 bra.uni T2Yb;\n"
        "@u0 bra.uni L1Yb;\n"
        "bra.uni L0Yb;\n"
        "T4Y:\n"
        "@t0 bra.uni L5Y;\n"
        "L4Y:\n"
        "wgmma.fence.sync.aligned;\n"
        "wgmma.mma_async.sync.aligned.m64n16k16.f32.bf16.bf16 {r0,r1,r2,r3,r4,r5,r6,r7}, {wa0,wa1,wa2,wa3}, de0, pf, 1, 1, 0;\n"
        "wgmma.mma_async.sync.aligned.m64n16k16.f32.bf16.bf16 {r8,r9,r10,r11,r12,r13,r14,r15}, {wa4,wa5,wa6,wa7}, de1, pf, 1, 1, 0;\n"
        "wgmma.commit_group.sync.aligned;\n"
        "wgmma.mma_async.sync.aligned.m64n24k16.f32.bf16.bf16 {%48,%49,%50,%51,%52,%53,%54,%55,%56,%57,%58,%59}, {hYa0,hYa1,hYa2,hYa3}, daY, 1, 1, 1, 0;\n"
        "wgmma.mma_async.sync.aligned.m64n24k16.f32.bf16.bf16 {%124,%125,%126,%127,%128,%129,%130,%131,%132,%133,%134,%135}, {hYa4,hYa5,hYa6,hYa7}, daY, 1, 1, 1, 0;\n"
        "wgmma.commit_group.sync.aligned;\n"
        "@u2 bra.uni T4Yb;\n"
        "@u1 bra.uni T2Yb;\n"
        "@u0 bra.uni L1Yb;\n"
        "bra.uni L0Yb;\n"
        "L5Y:\n"
        "wgmma.fence.sync.aligned;\n"
        "wgmma.mma_async.sync.aligned.m64n16k16.f32.bf16.bf16 {r0,r1,r2,r3,r4,r5,r6,r7}, {wa0,wa1,wa2,wa3}, de0, pf, 1, 1, 0;\n"
        "wgmma.mma_async.sync.aligned.m64n16k16.f32.bf16.bf16 {r8,r9,r10,r11,r12,r13,r14,r15}, {wa4,wa5,wa6,wa7}, de1, pf, 1, 1, 0;\n"
        "wgmma.commit_group.sync.aligned;\n"
        "wgmma.mma_async.sync.aligned.m64n32k16.f32.bf16.bf16 {%60,%61,%62,%63,%64,%65,%66,%67,%68,%69,%70,%71,%72,%73,%74,%75}, {hYa0,hYa1,hYa2,hYa3}, daY, 1, 1, 1, 0;\n"
        "wgmma.mma_async.sync.aligned.m64n32k16.f32.bf16.bf16 {%136,%137,%138,%139,%140,%141,%142,%143,%144,%145,%146,%147,%148,%149,%150,%151}, {hYa4,hYa5,hYa6,hYa7}, daY, 1, 1, 1, 0;\n"
        "wgmma.commit_group.sync.aligned;\n"
        "@u2 bra.uni T4Yb;\n"
        "@u1 bra.uni T2Yb;\n"
        "@u0 bra.uni L1Yb;\n"
        "L0Yb:\n"
        "wgmma.fence.sync.aligned;\n"
        "wgmma.mma_async.sync.aligned.m64n24k16.f32.bf16.bf16 {%0,%1,%2,%3,%4,%5,%6,%7,%8,%9,%10,%11}, {hYb0,hYb1,hYb2,hYb3}, dbY, 1, 1, 1, 0;\n"
        "wgmma.mma_async.sync.aligned.m64n24k16.f32.bf16.bf16 {%76,%77,%78,%79,%80,%81,%82,%83,%84,%85,%86,%87}, {hYb4,hYb5,hYb6,hYb7}, dbY, 1, 1, 1, 0;\n"
        "wgmma.commit_group.sync.aligned;\n"
        "bra.uni CX;\n"
        "L1Yb:\n"
        "wgmma.fence.sync.aligned;\n"
        "wgmma.mma_async.sync.aligned.m64n24k16.f32.bf16.bf16 {%12,%13,%14,%15,%16,%17,%18,%19,%20,%21,%22,%23}, {hYb0,hYb1,hYb2,hYb3}, dbY, 1, 1, 1, 0;\n"
        "wgmma.mma_async.sync.aligned.m64n24k16.f32.bf16.bf16 {%88,%89,%90,%91,%92,%93,%94,%95,%96,%97,%98,%99}, {hYb4,hYb5,hYb6,hYb7}, dbY, 1, 1, 1, 0;\n"
        "wgmma.commit_group.sync.aligned;\n"
        "bra.uni CX;\n"
        "T2Yb:\n"
        "@u0 bra.uni L3Yb;\n"
        "L2Yb:\n"
        "wgmma.fence.sync.aligned;\n"
        "wgmma.mma_async.sync.aligned.m64n24k16.f32.bf16.bf16 {%24,%25,%26,%27,%28,%29,%30,%31,%32,%33,%34,%35}, {hYb0,hYb1,hYb2,hYb3}, dbY, 1, 1, 1, 0;\n"
        "wgmma.mma_async.sync.aligned.m64n24k16.f32.bf16.bf16 {%100,%101,%102,%103,%104,%105,%106,%107,%108,%109,%110,%111}, {hYb4,hYb5,hYb6,hYb7}, dbY, 1, 1, 1, 0;\n"
        "wgmma.commit_group.sync.aligned;\n"
        "bra.uni CX;\n"
        "L3Yb:\n"
        "wgmma.fence.sync.aligned;\n"
        "wgmma.mma_async.sync.aligned.m64n24k16.f32.bf16.bf16 {%36,%37,%38,%39,%40,%41,%42,%43,%44,%45,%46,%47}, {hYb0,hYb1,hYb2,hYb3}, dbY, 1, 1, 1, 0;\n"
        "wgmma.mma_async.sync.aligned.m64n24k16.f32.bf16.bf16 {%112,%113,%114,%115,%116,%117,%118,%119,%120,%121,%122,%123}, {hYb4,hYb5,hYb6,hYb7}, dbY, 1, 1, 1, 0;\n"
        "wgmma.commit_group.sync.aligned;\n"
        "bra.uni CX;\n"
        "T4Yb:\n"
        "@u0 bra.uni L5Yb;\n"
        "L4Yb:\n"
        "wgmma.fence.sync.aligned;\n"
        "wgmma.mma_async.sync.aligned.m64n24k16.f32.bf16.bf16 {%48,%49,%50,%51,%52,%53,%54,%55,%56,%57,%58,%59}, {hYb0,hYb1,hYb2,hYb3}, dbY, 1, 1, 1, 0;\n"
        "wgmma.mma_async.sync.aligned.m64n24k16.f32.bf16.bf16 {%124,%125,%126,%127,%128,%129,%130,%131,%132,%133,%134,%135}, {hYb4,hYb5,hYb6,hYb7}, dbY, 1, 1, 1, 0;\n"
        "wgmma.commit_group.sync.aligned;\n"
        "bra.uni CX;\n"
        "L5Yb:\n"
        "wgmma.fence.sync.aligned;\n"
        "wgmma.mma_async.sync.aligned.m64n32k16.f32.bf16.bf16 {%60,%61,%62,%63,%64,%65,%66,%67,%68,%69,%70,%71,%72,%73,%74,%75}, {hYb0,hYb1,hYb2,hYb3}, dbY, 1, 1, 1, 0;\n"
        "wgmma.mma_async.sync.aligned.m64n32k16.f32.bf16.bf16 {%136,%137,%138,%139,%140,%141,%142,%143,%144,%145,%146,%147,%148,%149,%150,%151}, {hYb4,hYb5,hYb6,hYb7}, dbY, 1, 1, 1, 0;\n"
        "wgmma.commit_group.sync.aligned;\n"
        "bra.uni CX;\n"
        "LEXIT:\n"
        "wgmma.wait_group.sync.aligned 0;\n"
        "}\n"
        : "=f"(acc[0][0][0]), "=f"(acc[0][0][1]), "=f"(acc[0][0][2]), "=f"(acc[0][0][3]),
          "=f"(acc[0][1][0]), "=f"(acc[0][1][1]), "=f"(acc[0][1][2]), "=f"(acc[0][1][3]),
          "=f"(acc[0][2][0]), "=f"(acc[0][2][1]), "=f"(acc[0][2][2]), "=f"(acc[0][2][3]),
          "=f"(acc[0][3][0]), "=f"(acc[0][3][1]), "=f"(acc[0][3][2]), "=f"(acc[0][3][3]),
          "=f"(acc[0][4][0]), "=f"(acc[0][4][1]), "=f"(acc[0][4][2]), "=f"(acc[0][4][3]),
          "=f"(acc[0][5][0]), "=f"(acc[0][5][1]), "=f"(acc[0][5][2]), "=f"(acc[0][5][3]),
          "=f"(acc[0][6][0]), "=f"(acc[0][6][1]), "=f"(acc[0][6][2]), "=f"(acc[0][6][3]),
          "=f"(acc[0][7][0]), "=f"(acc[0][7][1]), "=f"(acc[0][7][2]), "=f"(acc[0][7][3]),
          "=f"(acc[0][8][0]), "=f"(acc[0][8][1]), "=f"(acc[0][8][2]), "=f"(acc[0][8][3]),
          "=f"(acc[0][9][0]), "=f"(acc[0][9][1]), "=f"(acc[0][9][2]), "=f"(acc[0][9][3]),
          "=f"(acc[0][10][0]), "=f"(acc[0][10][1]), "=f"(acc[0][10][2]), "=f"(acc[0][10][3]),
          "=f"(acc[0][11][0]), "=f"(acc[0][11][1]), "=f"(acc[0][11][2]), "=f"(acc[0][11][3]),
          "=f"(acc[0][12][0]), "=f"(acc[0][12][1]), "=f"(acc[0][12][2]), "=f"(acc[0][12][3]),
          "=f"(acc[0][13][0]), "=f"(acc[0][13][1]), "=f"(acc[0][13][2]), "=f"(acc[0][13][3]),
          "=f"(acc[0][14][0]), "=f"(acc[0][14][1]), "=f"(acc[0][14][2]), "=f"(acc[0][14][3]),
          "=f"(acc[0][15][0]), "=f"(acc[0][15][1]), "=f"(acc[0][15][2]), "=f"(acc[0][15][3]),
          "=f"(acc[0][16][0]), "=f"(acc[0][16][1]), "=f"(acc[0][16][2]), "=f"(acc[0][16][3]),
          "=f"(acc[0][17][0]), "=f"(acc[0][17][1]), "=f"(acc[0][17][2]), "=f"(acc[0][17][3]),
          "=f"(acc[0][18][0]), "=f"(acc[0][18][1]), "=f"(acc[0][18][2]), "=f"(acc[0][18][3]),
          "=f"(acc[1][0][0]), "=f"(acc[1][0][1]), "=f"(acc[1][0][2]), "=f"(acc[1][0][3]),
          "=f"(acc[1][1][0]), "=f"(acc[1][1][1]), "=f"(acc[1][1][2]), "=f"(acc[1][1][3]),
          "=f"(acc[1][2][0]), "=f"(acc[1][2][1]), "=f"(acc[1][2][2]), "=f"(acc[1][2][3]),
          "=f"(acc[1][3][0]), "=f"(acc[1][3][1]), "=f"(acc[1][3][2]), "=f"(acc[1][3][3]),
          "=f"(acc[1][4][0]), "=f"(acc[1][4][1]), "=f"(acc[1][4][2]), "=f"(acc[1][4][3]),
          "=f"(acc[1][5][0]), "=f"(acc[1][5][1]), "=f"(acc[1][5][2]), "=f"(acc[1][5][3]),
          "=f"(acc[1][6][0]), "=f"(acc[1][6][1]), "=f"(acc[1][6][2]), "=f"(acc[1][6][3]),
          "=f"(acc[1][7][0]), "=f"(acc[1][7][1]), "=f"(acc[1][7][2]), "=f"(acc[1][7][3]),
          "=f"(acc[1][8][0]), "=f"(acc[1][8][1]), "=f"(acc[1][8][2]), "=f"(acc[1][8][3]),
          "=f"(acc[1][9][0]), "=f"(acc[1][9][1]), "=f"(acc[1][9][2]), "=f"(acc[1][9][3]),
          "=f"(acc[1][10][0]), "=f"(acc[1][10][1]), "=f"(acc[1][10][2]), "=f"(acc[1][10][3]),
          "=f"(acc[1][11][0]), "=f"(acc[1][11][1]), "=f"(acc[1][11][2]), "=f"(acc[1][11][3]),
          "=f"(acc[1][12][0]), "=f"(acc[1][12][1]), "=f"(acc[1][12][2]), "=f"(acc[1][12][3]),
          "=f"(acc[1][13][0]), "=f"(acc[1][13][1]), "=f"(acc[1][13][2]), "=f"(acc[1][13][3]),
          "=f"(acc[1][14][0]), "=f"(acc[1][14][1]), "=f"(acc[1][14][2]), "=f"(acc[1][14][3]),
          "=f"(acc[1][15][0]), "=f"(acc[1][15][1]), "=f"(acc[1][15][2]), "=f"(acc[1][15][3]),
          "=f"(acc[1][16][0]), "=f"(acc[1][16][1]), "=f"(acc[1][16][2]), "=f"(acc[1][16][3]),
          "=f"(acc[1][17][0]), "=f"(acc[1][17][1]), "=f"(acc[1][17][2]), "=f"(acc[1][17][3]),
          "=f"(acc[1][18][0]), "=f"(acc[1][18][1]), "=f"(acc[1][18][2]), "=f"(acc[1][18][3])
        : "r"(xa0), "r"(xa1), "r"(so0), "r"(bar0), "r"(ea0), "r"(d0), "r"(pl0), "r"(lz), "r"(wa[0]), "r"(wa[1]), "r"(wa[2]),
          "r"(wa[3]), "r"(wa[4]), "r"(wa[5]), "r"(wa[6]), "r"(wa[7])
        : "memory");
}
__device__ __forceinline__ void wgmma_out(float (&o)[NJ][4], uint64_t da, uint64_t db, int acc) {
    asm volatile(
        "{\n.reg .pred p;\nsetp.ne.b32 p, %78, 0;\n"
        "wgmma.mma_async.sync.aligned.m64n152k16.f32.bf16.bf16 {%0,%1,%2,%3,%4,%5,%6,%7,%8,%9,%10,%11,%12,%13,%14,%15,%16,%17,%18,%19,%20,%21,%22,%23,%24,%25,%26,%27,%28,%29,%30,%31,%32,%33,%34,%35,%36,%37,%38,%39,%40,%41,%42,%43,%44,%45,%46,%47,%48,%49,%50,%51,%52,%53,%54,%55,%56,%57,%58,%59,%60,%61,%62,%63,%64,%65,%66,%67,%68,%69,%70,%71,%72,%73,%74,%75}, %76, %77, p, 1, 1, 1, 1;\n}"
        : "+f"(o[0][0]), "+f"(o[0][1]), "+f"(o[0][2]), "+f"(o[0][3]),
          "+f"(o[1][0]), "+f"(o[1][1]), "+f"(o[1][2]), "+f"(o[1][3]),
          "+f"(o[2][0]), "+f"(o[2][1]), "+f"(o[2][2]), "+f"(o[2][3]),
          "+f"(o[3][0]), "+f"(o[3][1]), "+f"(o[3][2]), "+f"(o[3][3]),
          "+f"(o[4][0]), "+f"(o[4][1]), "+f"(o[4][2]), "+f"(o[4][3]),
          "+f"(o[5][0]), "+f"(o[5][1]), "+f"(o[5][2]), "+f"(o[5][3]),
          "+f"(o[6][0]), "+f"(o[6][1]), "+f"(o[6][2]), "+f"(o[6][3]),
          "+f"(o[7][0]), "+f"(o[7][1]), "+f"(o[7][2]), "+f"(o[7][3]),
          "+f"(o[8][0]), "+f"(o[8][1]), "+f"(o[8][2]), "+f"(o[8][3]),
          "+f"(o[9][0]), "+f"(o[9][1]), "+f"(o[9][2]), "+f"(o[9][3]),
          "+f"(o[10][0]), "+f"(o[10][1]), "+f"(o[10][2]), "+f"(o[10][3]),
          "+f"(o[11][0]), "+f"(o[11][1]), "+f"(o[11][2]), "+f"(o[11][3]),
          "+f"(o[12][0]), "+f"(o[12][1]), "+f"(o[12][2]), "+f"(o[12][3]),
          "+f"(o[13][0]), "+f"(o[13][1]), "+f"(o[13][2]), "+f"(o[13][3]),
          "+f"(o[14][0]), "+f"(o[14][1]), "+f"(o[14][2]), "+f"(o[14][3]),
          "+f"(o[15][0]), "+f"(o[15][1]), "+f"(o[15][2]), "+f"(o[15][3]),
          "+f"(o[16][0]), "+f"(o[16][1]), "+f"(o[16][2]), "+f"(o[16][3]),
          "+f"(o[17][0]), "+f"(o[17][1]), "+f"(o[17][2]), "+f"(o[17][3]),
          "+f"(o[18][0]), "+f"(o[18][1]), "+f"(o[18][2]), "+f"(o[18][3])
        : "l"(da), "l"(db), "r"(acc));
}
__device__ __forceinline__ void slow_edge(int ee, int s, float* accn, const __nv_bfloat16* __restrict__ x,
                                          const __nv_bfloat16* __restrict__ sh, const __nv_bfloat16* __restrict__ ea,
                                          const __nv_bfloat16* __restrict__ cg, const __nv_bfloat16* __restrict__ wr,
                                          int lane) {
    float rwv[4] = {0.f, 0.f, 0.f, 0.f};
#pragma unroll 4
    for (int d = 0; d < 16; d++) {
        const float a = __bfloat162float(ea[(size_t)ee * 16 + d]);
        const uint2 wv = *(const uint2*)(wr + d * 128 + lane * 4);
        rwv[0] += a * __uint_as_float(wv.x << 16);
        rwv[1] += a * __uint_as_float(wv.x & 0xffff0000u);
        rwv[2] += a * __uint_as_float(wv.y << 16);
        rwv[3] += a * __uint_as_float(wv.y & 0xffff0000u);
    }
    float A = 0.f;
#pragma unroll
    for (int v = 0; v < 4; v++)
        A += __bfloat162float(cg[((lane >> 2) & 3) * 16 + v * 4 + (lane & 3)]) * __bfloat162float(sh[(size_t)ee * 4 + v]);
    float m[4][4];
#pragma unroll
    for (int w = 0; w < 4; w++)
#pragma unroll
        for (int j = 0; j < 4; j++) m[w][j] = 0.f;
#pragma unroll
    for (int u = 0; u < 4; u++) {
        const uint2 xv = *(const uint2*)(x + (size_t)s * 512 + u * 128 + lane * 4);
        const float x0 = __uint_as_float(xv.x << 16), x1 = __uint_as_float(xv.x & 0xffff0000u);
        const float x2 = __uint_as_float(xv.y << 16), x3 = __uint_as_float(xv.y & 0xffff0000u);
#pragma unroll
        for (int w = 0; w < 4; w++) {
            const float a = __shfl_sync(0xffffffffu, A, u * 4 + w);
            m[w][0] += a * x0;
            m[w][1] += a * x1;
            m[w][2] += a * x2;
            m[w][3] += a * x3;
        }
    }
#pragma unroll
    for (int w = 0; w < 4; w++)
#pragma unroll
        for (int j = 0; j < 4; j++) atomicAdd(accn + w * 128 + lane * 4 + j, m[w][j] * rwv[j]);
}

__device__ __forceinline__ void slow_out(const float* accn, const __nv_bfloat16* __restrict__ wout,
                                         __nv_bfloat16* __restrict__ outn, int lane) {
    float o[4][4];
#pragma unroll
    for (int w = 0; w < 4; w++)
#pragma unroll
        for (int j = 0; j < 4; j++) o[w][j] = 0.f;
#pragma unroll 2
    for (int c = 0; c < 128; c++) {
        const uint2 wv = *(const uint2*)(wout + c * 128 + lane * 4);
        const float w0 = __uint_as_float(wv.x << 16), w1 = __uint_as_float(wv.x & 0xffff0000u);
        const float w2 = __uint_as_float(wv.y << 16), w3 = __uint_as_float(wv.y & 0xffff0000u);
#pragma unroll
        for (int w = 0; w < 4; w++) {
            const float a = __bfloat162float(__float2bfloat16(accn[w * 128 + c]));
            o[w][0] += a * w0;
            o[w][1] += a * w1;
            o[w][2] += a * w2;
            o[w][3] += a * w3;
        }
    }
#pragma unroll
    for (int w = 0; w < 4; w++)
        *(uint2*)(outn + w * 128 + lane * 4) = make_uint2(pack_bf16(o[w][0], o[w][1]), pack_bf16(o[w][2], o[w][3]));
}

static_assert(NW > 2 * NP, "barriers");
#define SHD
#define FPOS 1
#define EMASK 0xffffff
#define TBIN 0
#define PW 0
#define TWAIT mbar_lean_u
#define PWAIT mbar_lean
#define TMA_ROW(k) "@pl cp.async.bulk.tensor.2d.shared::cluster.global.mbarrier::complete_tx::bytes [d" #k "], [tm, {r" #k ", z" #k "}], [b" #k "];\n"
#define REC 32
#define TMA_INIT(k, o) "shfl.sync.idx.b32 z" #k ", %11, " #k ", 31, 0xffffffff;\nadd.u32 m" #k ", %2, " STR(o) ";\nadd.u32 m" #k ", m" #k ", %11;\nshfl.sync.idx.b32 m" #k ", m" #k ", 0, 31, 0xffffffff;\n"
#define TMA_PREP(k) "mad.lo.u32 d" #k ", dd, 512, m" #k ";\nadd.u32 b" #k ", dd, z" #k ";\n"
#define RDCLK(c) "mov.u64 ck, %%clock64;\ncvt.u32.u64 " c ", ck;\n"
__device__ __forceinline__ void produce(const CUtensorMap* tm, uint32_t bar, uint32_t d0, uint32_t ps, int nit, uint32_t psrc,
                                        uint32_t tbase, uint32_t lim, uint32_t taug32, uint32_t taus, uint32_t n, int lz, uint32_t rec0,
                                        uint32_t rec
) {
    asm volatile(
        "{\n.reg .pred p, pl, ok, odd;\n.reg .b32 a<6>, r<8>, d<8>, b<8>, z<8>, m<8>, ps, lim, n, it, pr, pe, tgt, tgu, c, dd, dn, par, t0;\n"
        ".reg .b64 st, tm, ck;\n"
        "elect.sync _|pl, 0xffffffff;\n"
        TMA_INIT(0, 0) TMA_INIT(1, SM_ODD) TMA_INIT(2, 1024) TMA_INIT(3, SM_ODD + 1024)
        TMA_INIT(4, 4096) TMA_INIT(5, SM_ODD + 4096) TMA_INIT(6, 5120) TMA_INIT(7, SM_ODD + 5120)
        "mov.b64 {a0, a1}, %0;\n"
        "add.u32 a0, a0, %11;\n"
        "add.u32 a1, a1, %11;\n"
        "shfl.sync.idx.b32 a0, a0, 0, 31, 0xffffffff;\n"
        "shfl.sync.idx.b32 a1, a1, 0, 31, 0xffffffff;\n"
        "mov.b64 tm, {a0, a1};\n"
        "mov.u32 ps, %3;\n"
        "mov.u32 it, %4;\n"
        "mov.u32 lim, %7;\n"
        "mov.u32 n, %10;\n"
        "and.b32 c, ps, 4;\n"
        "setp.ne.u32 odd, c, 0;\n"
        "setp.le.s32 p, it, 0;\n"
        "@p bra.uni PEND;\n"
        "PBAT:\n"
        "ld.shared.u16 c, [ps];\n"
        "add.u32 ps, ps, 128;\n"
        "mul.lo.u32 par, n, " STR(65536 / NP + 1) ";\n"
        "shr.u32 par, par, 16;\n"
        "mad.lo.s32 dn, par, " STR(-NP) ", n;\n"
        "add.u32 n, n, 16;\n"
        "not.b32 par, par;\n"
        "selp.b32 dn, par, dn, odd;\n"
        "and.b32 c, c, 0x3fe;\n"
        "mad.lo.u32 c, c, 4, %5;\n"
        "ld.shared.v2.u32 {a0, a1}, [c];\n"
        "min.s32 pe, it, 16;\n"
        "mad.lo.u32 pe, pe, " STR(REC) ", %12;\n"
        "sub.s32 it, it, 16;\n"
        "mov.u32 pr, %12;\n"
        "shr.u32 a2, a0, 16;\nand.b32 a3, a1, 0xffff;\n"
        "add.u32 tgt, a2, a3;\nmul.lo.u32 tgt, tgt, %9;\nshr.u32 tgt, tgt, 5;\nadd.u32 tgt, tgt, %6;\n"
        "min.u32 tgt, tgt, lim;\n"
        "add.u32 lim, lim, %8;\n"
        "lop3.b32 tgt, tgt, dn, 7, 0xd8;\n"
        "st.shared.v2.u32 [%13], {a0, a1};\n"
        "selp.b32 c, 12, 16, odd;\n"
        "add.u32 c, c, %13;\n"
        "st.shared.u32 [c], tgt;\n"
        "bar.warp.sync 0xffffffff;\n"
        "ld.shared.v4.u32 {a0, a1, a2, a3}, [pr];\n"
        "ld.shared.v2.u32 {a4, a5}, [pr+16];\n"
        "PLOOP:\n"
        "mov.u32 tgt, a4;\n"
        "mov.u32 tgu, a5;\n"
        "and.b32 dd, tgt, 7;\n"
        "mad.lo.u32 dd, dd, 16, %1;\n"
        "and.b32 par, tgu, 1;\n"
        "mbarrier.test_wait.parity.shared.b64 ok, [dd+8], par;\n"
        "prmt.b32 r0, a0, 0, 0x4104;\nprmt.b32 r1, a0, 0, 0x4324;\nprmt.b32 r2, a1, 0, 0x4104;\nprmt.b32 r3, a1, 0, 0x4324;\n"
        "prmt.b32 r4, a2, 0, 0x4104;\nprmt.b32 r5, a2, 0, 0x4324;\nprmt.b32 r6, a3, 0, 0x4104;\nprmt.b32 r7, a3, 0, 0x4324;\n"
        "ld.shared.v4.u32 {a0, a1, a2, a3}, [pr+" STR(REC) "];\n"
        "ld.shared.v2.u32 {a4, a5}, [pr+" STR(REC + 16) "];\n"
        "add.u32 pr, pr, " STR(REC) ";\n"
        TMA_PREP(0) TMA_PREP(1) TMA_PREP(2) TMA_PREP(3) TMA_PREP(4) TMA_PREP(5) TMA_PREP(6) TMA_PREP(7)
        RDCLK("c")
        "sub.s32 c, c, tgt;\n"
        "setp.ge.and.s32 p, c, 0, ok;\n"
        "@!p bra.uni PSLP;\n"
        "PRES:\n"
        "@pl mbarrier.arrive.expect_tx.shared.b64 _, [b0], 8192;\n"
        TMA_ROW(0) TMA_ROW(1) TMA_ROW(2) TMA_ROW(3)
        RDCLK("c")
        "sub.s32 c, c, tgu;\n"
        "setp.lt.s32 p, c, 0;\n"
        "@p bra.uni PSL2;\n"
        "PRE2:\n"
        TMA_ROW(4) TMA_ROW(5) TMA_ROW(6) TMA_ROW(7)
        "setp.lt.u32 p, pr, pe;\n"
        "@p bra.uni PLOOP;\n"
        "setp.gt.s32 p, it, 0;\n"
        "@p bra.uni PBAT;\n"
        "bra.uni PEND;\n"
        "PSL2:\n"
        "nanosleep.u32 " STR(PSLEEP) ";\n"
        RDCLK("c")
        "sub.s32 c, c, tgu;\n"
        "setp.lt.s32 p, c, 0;\n"
        "@p bra.uni PSL2;\n"
        "bra.uni PRE2;\n"
        "PSL1:\n"
        "nanosleep.u32 " STR(PSLEEP) ";\n"
        RDCLK("c")
        "sub.s32 c, c, tgt;\n"
        "PSLP:\n"
        "setp.lt.s32 p, c, 0;\n"
        "@p bra.uni PSL1;\n"
        "@ok bra.uni PRES;\n"
        "mov.u32 c, 0;\n"
        "PW:\n"
        "mbarrier.try_wait.parity.shared.b64 p, [b0+8], par;\n"
        "@p bra.uni PRES;\n"
        "add.u32 c, c, 1;\n"
        "setp.lt.u32 p, c, 4000000;\n"
        "@p bra.uni PW;\n"
        "trap;\n"
        "PEND:\n}"
        :
        : "l"(tm), "r"(bar), "r"(d0), "r"(ps), "r"(nit), "r"(psrc), "r"(tbase), "r"(lim), "r"(taug32), "r"(taus), "r"(n), "r"(lz),
          "r"(rec0), "r"(rec)
        : "memory");
}
#define GCODE(g) ((((g) >> 1) + 1) << 12 | ((g) & 1) << 15)
#define WG_SYNC(w) asm volatile("bar.sync %0, 128;" ::"r"((w) + 1) : "memory")
__global__ void __launch_bounds__(NT, 1)
main_kernel(const __grid_constant__ CUtensorMap tmx, const __grid_constant__ CUtensorMap tmw,
            const __grid_constant__ CUtensorMap tmo, const __nv_bfloat16* __restrict__ x, const int* __restrict__ src,
            const int* __restrict__ dst, const __nv_bfloat16* __restrict__ sh, const __nv_bfloat16* __restrict__ ea,
            const __nv_bfloat16* __restrict__ cg, const __nv_bfloat16* __restrict__ wr,
            const __nv_bfloat16* __restrict__ wout, __nv_bfloat16* __restrict__ out, int N, int E, int npb,
            unsigned npb_magic, int chunk, int fast_ok, int bsh, int tau16, int toff) {
    extern __shared__ __align__(1024) unsigned char smem[];
    const uint32_t sb = s2u(smem);
    int* s_int = (int*)(smem + SM_MISC + MI_INT);
    int* s_hist = (int*)(smem + SC_HIST);
    const int tid = threadIdx.x;
    const int warp = __shfl_sync(0xffffffffu, tid >> 5, 0), lane = tid & 31;
    const int g = lane >> 2, t = lane & 3;

    TLSTAMP(0);
    const int nbins = gridDim.x;
    const int bin = blockIdx.x;
    const int node0 = bin * npb, hpb = npb >> 1;
    const int ebeg = min(E, bin * chunk), eend = min(E, ebeg + chunk);
    int pd[EPS], ps[EPS];
#pragma unroll
    for (int k = 0; k < EPS; k++) {
        const int e = ebeg + tid + k * NT;
        pd[k] = e < eend ? __ldg(dst + e) : -1;
        ps[k] = e < eend ? __ldg(src + e) : 0;
    }
    int2* st_ent = (int2*)(smem + SC_ENT);
    unsigned char* st_bin = smem + SC_BIN;
    int* s_loc = s_hist + MAXBINS;
    int* s_del = s_loc + MAXBINS;
    if (lane < 2) mbar_init(sb + SM_BAR + (warp * 2 + lane) * 8, 3 + lane);
    if (tid < MAXBINS) s_hist[tid] = 0;
    if (tid == 0) {
        mbar_init(sb + SM_MISC + MI_WBAR, 4);
        asm volatile("prefetch.tensormap [%0];" ::"l"(&tmx) : "memory");
    }
    if (tid < 2 * (NBK + 1)) ((uint4*)(smem + SC_CNT))[tid] = make_uint4(0, 0, 0, 0);
#pragma unroll
    for (int k = 0; k < TS / 2; k++) ((uint4*)(smem + SM_BT))[tid + k * NT] = make_uint4(0, 0, 0, 0);
    if (tid < 8) ((uint4*)(smem + SM_BT))[tid + TS / 2 * NT] = make_uint4(0, 0, 0, 0);
    __syncthreads();
    TLSTAMP(1);
    for (int rb = ebeg;; rb += NT * EPS) {
        const bool last = rb + NT * EPS >= eend;
        int pb[EPS], pr[EPS];
#pragma unroll
        for (int k = 0; k < EPS; k++) {
            pb[k] = pd[k] >= 0 ? (int)__umulhi((unsigned)pd[k], npb_magic) : -1;
            if (pb[k] >= 0) pr[k] = atomicAdd(&s_hist[pb[k]], 1);
        }
        if (tid == 0) asm volatile("mov.u32 %0, %%globaltimer_lo;" : "=r"(s_int[3]));
        __syncthreads();
        TLSTAMP(6);
        const int now = s_int[3];
        int gbase = 0;
        if (warp == NW - 1) {
            int v[MAXBINS / 32], sum = 0;
#pragma unroll
            for (int c = 0; c < MAXBINS / 32; c++) {
                v[c] = s_hist[lane * (MAXBINS / 32) + c];
                sum += v[c];
            }
            int run = warp_incl_scan(sum, lane) - sum;
#pragma unroll
            for (int c = 0; c < MAXBINS / 32; c++) {
                s_loc[lane * (MAXBINS / 32) + c] = run;
                run += v[c];
            }
        } else if (tid < nbins) {
            if (bin == TBIN && last) __stcg(&g_bincnt[tid * 32 + 1], now | 1);
            gbase = atomicAdd(&g_bincnt[tid * 32], s_hist[tid] + (last ? 1 << 22 : 0));
        }
        __syncthreads();
#pragma unroll
        for (int k = 0; k < EPS; k++) {
            if (pb[k] >= 0) {
                const int pos = s_loc[pb[k]] + pr[k];
                st_ent[pos] = make_int2(ps[k], (rb + tid + k * NT) | ((pd[k] - pb[k] * npb) << 24) | 0x80000000);
                st_bin[pos] = pb[k];
            }
        }
        if (tid < nbins) s_del[tid] = (gbase & 0x3fffff) - s_loc[tid];
        __syncthreads();
        TLSTAMP(8);
        const int n = min(eend - rb, NT * EPS);
#pragma unroll
        for (int k = 0; k < EPS; k++) {
            const int i = tid + k * NT;
            if (i < n) {
                const int b = st_bin[i];
                const int gpos = i + s_del[b];
                if (gpos < BINCAP) __stcg(&g_bin[b * BINCAP + gpos], st_ent[i]);
            }
        }
        if (last) break;
        if (tid < MAXBINS) s_hist[tid] = 0;
#pragma unroll
        for (int k = 0; k < EPS; k++) {
            const int e = rb + NT * EPS + tid + k * NT;
            pd[k] = e < eend ? dst[e] : -1;
            ps[k] = e < eend ? src[e] : 0;
        }
        __syncthreads();
    }
    TLSTAMP(5);
    int2 ent[KS];
    uint2 wv;
    int rank[KS];
    {
        int cnt = 0;
        if (lane == 0) {
            int tsum;
            for (int spin = 0;; spin++) {
                asm volatile("ld.relaxed.gpu.global.v2.s32 {%0,%1}, [%2];" : "=r"(cnt), "=r"(tsum) : "l"(&g_bincnt[bin * 32]) : "memory");
                if ((cnt >> 22) >= nbins && tsum) break;
                if (spin > 10000000) __trap();
            }
            if (tid == 0) s_int[3] = tsum;
        }
        cnt = __shfl_sync(0xffffffffu, cnt, 0) & 0x3fffff;
        if (tid == 0) s_int[0] = cnt;
        const int n = min(cnt, BINCAP);
        unsigned pend = 0;
#pragma unroll
        for (int k = 0; k < KS; k++) {
            ent[k] = make_int2(0, 0);
            if (tid + k * NT < n) pend |= 1u << k;
        }
        int2* gp = &g_bin[bin * BINCAP + tid];
        for (int spin = 0; __any_sync(0xffffffffu, pend); spin++) {
#pragma unroll
            for (int k = 0; k < KS; k++)
                if ((pend >> k) & 1)
                    asm volatile("ld.relaxed.gpu.global.v2.s32 {%0,%1}, [%2];"
                                 : "=r"(ent[k].x), "=r"(ent[k].y)
                                 : "l"(gp + k * NT)
                                 : "memory");
#pragma unroll
            for (int k = 0; k < KS; k++)
                if (ent[k].y < 0) pend &= ~(1u << k);
            if (spin > 10000000) __trap();
        }
        TLSTAMP(2);
        asm volatile("ld.global.nc.v2.u32 {%0,%1}, [%2];" : "=r"(wv.x), "=r"(wv.y) : "l"((const uint2*)wr + tid));
#pragma unroll
        for (int k = 0; k < KS; k++) {
            if (ent[k].y < 0) {
                if (fast_ok) {
                    const int dl = (ent[k].y >> 24) & 127, w = dl >= hpb;
                    const int loc = dl - (w ? hpb : 0), gr = GSZ == 6 ? min(loc * 43 >> 8, 5) : loc >> 3, sft = (gr & 1) * 16;
                    const int cw = (w * (NBK + 1) + (ent[k].x >> bsh)) * 4 + (gr >> 1);
                    const unsigned old = atomicAdd((unsigned*)(smem + SC_CNT) + cw, 1u << sft);
                    rank[k] = ((old >> sft) & 0xffff) | GCODE(gr);
                    ent[k].x |= cw << 16;
                    ent[k].y = (ent[k].y & 0x80ffffff) | ((loc - gr * GSZ) << 24);
                }
                __stcg(gp + k * NT, make_int2(0, 0));
            }
        }
    }
    __syncthreads();
    if (tid == 0) *(int2*)&g_bincnt[bin * 32] = make_int2(0, 0);
    TLSTAMP(9);
    sts_v2(sb + SM_WR + ((tid >> 1) & 15) * 272 + (tid >> 5) * 16 + (tid & 1) * 8, wv.x, wv.y);
    if (warp < 2) {
        uint4* cp = (uint4*)(smem + SC_CNT) + warp * (NBK + 1) + lane * (NBK / 32);
        uint4 v[NBK / 32];
        uint32_t s[3] = {0, 0, 0}, r[3], tot[3], base[3];
#pragma unroll
        for (int c = 0; c < NBK / 32; c++) {
            v[c] = cp[c];
            s[0] += v[c].x;
            s[1] += v[c].y;
            s[2] += v[c].z;
        }
        uint32_t sum = 0;
#pragma unroll
        for (int i = 0; i < 3; i++) {
            r[i] = warp_incl_scan(s[i], lane);
            tot[i] = __shfl_sync(0xffffffffu, r[i], 31);
            r[i] -= s[i];
            const uint32_t p = (tot[i] + 0x00030003u) & 0xfffcfffcu;
            base[i] = sum * 0x10001u + (p << 16);
            sum += (p & 0xffff) + (p >> 16);
        }
        auto blocks = [](const uint32_t(&a)[3]) {
            constexpr uint32_t c = (3 - CE) * 0x10001u;
            const uint32_t q = (((a[0] + c) >> 2) & 0x3fff3fffu) + (((a[1] + c) >> 2) & 0x3fff3fffu) + (((a[2] + c) >> 2) & 0x3fff3fffu);
            return (q & 0xffff) + (q >> 16);
        };
#pragma unroll
        for (int c = 0; c < NBK / 32; c++) {
            cp[c] = make_uint4(r[0] + base[0], r[1] + base[1], r[2] + base[2], blocks(r));
            r[0] += v[c].x;
            r[1] += v[c].y;
            r[2] += v[c].z;
        }
        const bool ok = sum + 4 <= LCAP;
        const int nst = sum >> 2;
        const int npr = (nst + 3) >> 2;
        const uint32_t tw = g < 2 ? tot[0] : g < 4 ? tot[1] : tot[2], bw = g < 2 ? base[0] : g < 4 ? base[1] : base[2];
        const int le = g < 6 ? ((tw + bw) >> ((g & 1) * 16)) & 0xffff : sum;
        const bool tailb = t == 0 && (le & 3) >= 1 && (le & 3) <= CE;
        const unsigned tm = __ballot_sync(0xffffffffu, tailb);
        if (ok) {
            {
                const int i = (le & ~3) + t;
                if (i >= le) {
                    ((unsigned short*)(smem + SM_SRC))[warp * LCAP + i] = min(node0, N - 1);
                    ((uint32_t*)(smem + SM_EID))[warp * LCAP + i] = 0x80000000u;
                }
            }
            if (tailb) {
                const int i = blocks(tot) + __popc(tm & ((1u << lane) - 1));
                ((unsigned short*)(smem + SM_SEQ))[warp * SEQCAP + i] = (le >> 2) * 2 | GCODE(g);
            }
            ((unsigned short*)(smem + SM_SEQ))[warp * SEQCAP + nst + lane] = nst * 2 | (lane < (-nst & 3) ? GCODE(0) : 0x7c01);
        }
        if (lane < NP - 1 - npr % NP) {
            mbar_arrive_cnt(sb + SM_BAR + (warp * NP + lane) * 16, 3);
            mbar_arrive_cnt(sb + SM_BAR + (warp * NP + lane) * 16 + 8, 4);
        }
        if (lane == 0) s_int[1 + warp] = ok ? npr : -1;
    }
    __syncthreads();
    TLSTAMP(10);
    uint32_t wa[8];
#pragma unroll
    for (int h = 0; h < 2; h++)
        asm volatile("ldmatrix.sync.aligned.m8n8.x4.trans.shared.b16 {%0,%1,%2,%3}, [%4];"
                     : "=r"(wa[h * 4]), "=r"(wa[h * 4 + 1]), "=r"(wa[h * 4 + 2]), "=r"(wa[h * 4 + 3])
                     : "r"(sb + SM_WR + (h * 8 + (warp & 3) * 2 + ((lane >> 3) & 1)) * 272 + (lane >> 4) * 128 + (lane & 7) * 16));
    const bool fast = s_int[0] <= BINCAP && fast_ok && (s_int[1] | s_int[2]) >= 0;
    if (fast) {
        int pos[KS];
#pragma unroll
        for (int k = 0; k < KS; k++)
            if (ent[k].y < 0) pos[k] = ((uint32_t*)(smem + SC_CNT))[ent[k].x >> 16];
#pragma unroll
        for (int k = 0; k < KS; k++) {
            if (ent[k].y < 0) {
                const int w = (ent[k].x >> 16) >= (NBK + 1) * 4;
                const int p = (((uint32_t)pos[k] >> ((rank[k] >> 11) & 16)) & 0xffff) + (rank[k] & 0xfff);
                ((unsigned short*)(smem + SM_SRC))[w * LCAP + p] = ent[k].x;
                ((uint32_t*)(smem + SM_EID))[w * LCAP + p] = ent[k].y & 0x7fffffff;
                if ((p & 3) == CE) {
                    const int i = atomicAdd((int*)(smem + SC_CNT) + ((ent[k].x >> 16) | 3), 1);
                    ((unsigned short*)(smem + SM_SEQ))[w * SEQCAP + i] = (p >> 2) * 2 | (rank[k] & 0xf000);
                }
            }
        }
    }
    FENCE_ASYNC();
    TLSTAMP(15);
    __syncthreads();
    TLSTAMP(3);

    if (fast && warp >= 12) {
        asm volatile("setmaxnreg.dec.sync.aligned.u32 %0;" ::"n"(HREG));
        const int w = warp & 1, j = (warp >> 1) & 1;
        const int npr = __shfl_sync(0xffffffffu, s_int[1 + w], 0);
        const uint32_t bar0 = sb + SM_BAR + w * NP * 16;
        const int blk = (lane >> 4) * 2 + (t >> 1);
        uint32_t fseq = sb + SM_SEQ + w * SEQCAP * 2 + j * 8 + blk * 2;
        const uint32_t feid = sb + SM_EID + w * LCAP * 4 + (g & 3) * 4;
        uint32_t pea = sb + SM_EA + w * 4096 + j * 512 + (lane ^ ((lane >> 3) & 1)) * 16;
        const uint32_t psd = sb + SM_SIDE + (warp - 12) * 512 + (lane >> 1) * 16 + (lane & 1) * 4;
        const uint32_t pt = sb + SM_BT + w * (TS * 256) + j * 512 + blk * BT_B + ((lane ^ (lane >> 3)) & 1) * BT_K + (g & 3) * 4;
        const char* gea = (const char*)ea + (lane & 1) * 16;
        uint32_t es, va[2], ta[2], old[2] = {pt, pt}, dea = 2048;
        auto ids = [&]() {
            es = lds_u32(feid + (lds_u16(fseq) & 0x3fe) * 8);
            fseq += 16;
        };
        uint32_t wf[4];
        {
            const uint2* cp = (const uint2*)cg + (g & 3) * 4 + (t & 1) * 2;
            uint2 c0 = make_uint2(0, 0), c1 = c0;
            if ((g >> 2) == (t >> 1)) c0 = __ldg(cp), c1 = __ldg(cp + 1);
            wf[0] = __byte_perm(c0.x, c1.x, 0x5410), wf[1] = __byte_perm(c0.x, c1.x, 0x7632);
            wf[2] = __byte_perm(c0.y, c1.y, 0x5410), wf[3] = __byte_perm(c0.y, c1.y, 0x7632);
        }
        uint32_t vf = bar0 + (NP - 1 - npr % NP + j) % NP * 16;
        uint32_t pe = NP - 1 - npr % NP + j < NP;
        auto run = [&](auto odd) {
            auto fetch = [&](int i) {
                asm volatile(
                    "{\n.reg .pred p, q;\n.reg .b32 e;\n.reg .b64 a;\n"
                    "setp.lt.s32 p, %0, 0;\n"
                    "and.b32 e, %0, " STR(EMASK) ";\n"
                    "mad.wide.u32 a, e, 32, %1;\n"
                    "cp.async.cg.shared.global [%2], [a], 16, p;\n"
                    "}" ::"r"(es), "l"(gea), "r"(pea + i * 1024) : "memory");
                va[i] = psd + (es & 1) * 8;
                ta[i] = pt + ((es & 0x7000000) >> 18);
                if (odd.value) {
                    cp_async4(va[i] + i * 256, (const char*)sh + (size_t)(es & 0xffffff) * 8 + (lane & 1) * 4, (int)es >= 0 ? 4 : 0);
                } else {
                    asm volatile(
                        "{\n.reg .pred p, q;\n.reg .b32 e;\n.reg .b64 a;\n"
                        "setp.lt.s32 p, %0, 0;\n"
                        "setp.eq.u32 q, %3, 0;\n"
                        "and.b32 e, %0, " STR(EMASK - 1) ";\n"
                        "mad.wide.u32 a, e, 8, %1;\n"
                        "cp.async.cg.shared.global [%2], [a], 16, p;\n"
                        "}" ::"r"(es), "l"(sh), "r"((psd & ~15) + i * 256), "r"(0) : "memory");
                }
                asm volatile("cp.async.commit_group;" ::: "memory");
                if (i) pea += dea, dea = -dea;
            };
            ids();
            fetch(0);
            ids();
            fetch(1);
#pragma unroll 1
            for (int m = (npr + 1 - j) >> 1; m > 0;) {
#pragma unroll
                for (int i = 0; i < 2; i++) {
                    asm volatile("cp.async.wait_group 1;" ::: "memory");
                    __syncwarp();
                    const uint32_t v = lds_u32(va[i] + i * 256);
                    ids();
                    float d0[4], d1[4];
                    mma_diag(d0, v, wf[0], wf[1]);
                    mma_diag(d1, v, wf[2], wf[3]);
                    uint32_t vn = vf + 32;
                    if (vn >= bar0 + NP * 16) vn -= NP * 16, pe ^= 1;
                    TWAIT(vn + 8, pe);
#pragma unroll
                    for (int k = 0; k < 4; k++) sts_u32(old[i] + i * 1024 + k * 16, 0);
                    old[i] = ta[i];
                    sts_u32(old[i] + i * 1024, pack_bf16(d0[0], d0[1]));
                    sts_u32(old[i] + i * 1024 + 16, pack_bf16(d0[2], d0[3]));
                    sts_u32(old[i] + i * 1024 + 32, pack_bf16(d1[0], d1[1]));
                    sts_u32(old[i] + i * 1024 + 48, pack_bf16(d1[2], d1[3]));
                    FENCE_ASYNC();
                    fetch(i);
                    __syncwarp();
                    if (lane == 0) mbar_arrive(vf);
                    vf = vn;
                    if (--m <= 0) break;
                }
            }
        };
        if (E & 1) run(std::true_type()); else run(std::false_type());
        asm volatile("cp.async.wait_group 0;" ::: "memory");
        TLMAX(13);
    } else if (fast && warp >= 8) {
        asm volatile("setmaxnreg.dec.sync.aligned.u32 %0;" ::"n"(PREG));
        const int w = warp & 1, j = (warp >> 1) & 1;
        const int nst = 2 * __shfl_sync(0xffffffffu, s_int[1 + w], 0);
        const uint32_t bar0 = sb + SM_BAR + w * NP * 16, ring = sb + w * RING_BYTES + j * 4096;
        const uint32_t pseq = sb + SM_SEQ + w * SEQCAP * 2 + j * 2;
        unsigned now;
        asm volatile("mov.u32 %0, %%globaltimer_lo;" : "=r"(now));
        const int ago = min(max((int)(now - s_int[3]), 0), 1 << 16) * 7 >> 2;
        const unsigned tbase = __shfl_sync(0xffffffffu, (unsigned)clock() - ago, 0) + (unsigned)toff;
        const unsigned taug = __shfl_sync(0xffffffffu, (N * tau16 >> 4) / max(nst, 1), 0);
        const int k0 = NP - 1 - (nst >> 1) % NP;
        const uint32_t rec = sb + SM_WR + (warp - 8) * (16 * REC);
        produce(&tmx, bar0, ring - j * 2048 - bar0 * 512, pseq + lane * 4, nst >> 1, sb + SM_SRC + w * LCAP * 2, tbase,
                tbase + (N * tau16 >> 8) + lane * taug, taug * 32, tau16, k0 + (lane >> 1), lane & (E >> 31), rec,
                rec + (lane >> 1) * REC + (lane & 1) * 8
        );
        if (elect()) {
            const uint32_t d = ring + (NP - 1) * 8192;
            const uint32_t fb = bar0 + (NP - 1) * 16, par = ~(lds_u32(sb + SM_MISC + MI_INT + 4 + w * 4) / NP) & 1;
            mbar_wait(fb + 8, par);
            mbar_arrive_cnt(fb, 1 + j);
            mbar_expect_tx(sb + SM_MISC + MI_WBAR, 8192);
            tma_2d(d + SM_EVEN, &tmw, sb + SM_MISC + MI_WBAR, w * 64, j * 32);
            tma_2d(d + SM_ODD, &tmw, sb + SM_MISC + MI_WBAR, w * 64, j * 32 + 64);
        }
        TLMAX(12);
    } else if (fast) {
        asm volatile("setmaxnreg.inc.sync.aligned.u32 %0;" ::"n"(CREG));
        const int w = warp >> 2, wq = warp & 3;
        const int nst = __shfl_sync(0xffffffffu, s_int[1 + w], 0);
        const uint32_t ring = sb + w * RING_BYTES;
        float acc[2][NJ][4];
        {
            const int e = (lane >> 1) & 3, m = lane >> 3;
            const int line = 2 * ((lane & 1) + 2 * ((m >> 1) ^ (e >> 1))), ch = 2 * wq + (m & 1);
            const uint32_t xb = ring + (e & 1 ? SM_ODD : SM_EVEN) + (e >> 1) * 1024 + line * 128;
            consume(acc, xb + ((ch ^ ((line + (e & 1)) & 7)) * 16), xb + 128 + ((ch ^ ((line + 1 + (e & 1)) & 7)) * 16),
                    (NP - 1 - nst % NP) * 8192, sb + SM_BAR + w * NP * 16, (((sb + SM_EA + w * 4096) & 0x3ffff) >> 4) | (1 << 16),
                    (((sb + SM_BT + w * (TS * 256)) & 0x3ffff) >> 4) | (BT_K / 16 << 16), sb + SM_SEQ + w * SEQCAP * 2, lane & (E >> 31),
                    wa);
        }
        TLMAX(11);
#pragma unroll
        for (int h = 0; h < 2; h++) {
            const uint32_t tb = ring + (h ? SM_ODD : SM_EVEN) + wq * (NJ * 256) + lane * 16;
#pragma unroll
            for (int j = 0; j + 1 < NJ; j += 2)
                stsm4(tb + j * 256, pack_bf16(acc[h][j][0], acc[h][j][1]), pack_bf16(acc[h][j][2], acc[h][j][3]),
                      pack_bf16(acc[h][j + 1][0], acc[h][j + 1][1]), pack_bf16(acc[h][j + 1][2], acc[h][j + 1][3]));
            if (NJ & 1)
                stsm2(tb + (NJ - 1) * 256, pack_bf16(acc[h][NJ - 1][0], acc[h][NJ - 1][1]),
                      pack_bf16(acc[h][NJ - 1][2], acc[h][NJ - 1][3]));
        }
        FENCE_ASYNC();
        WG_SYNC(w);
        mbar_wait_u(sb + SM_MISC + MI_WBAR, 0);
        float o[2][NJ][4];
        asm volatile("wgmma.fence.sync.aligned;" ::: "memory");
#pragma unroll
        for (int hh = 0; hh < 2; hh++) {
#pragma unroll
            for (int ks = 0; ks < 8; ks++) {
                const uint32_t rg = ks >> 2 ? SM_ODD : SM_EVEN;
                const uint64_t da = (uint64_t)(((sb + rg + hh * RING_BYTES + (NS - 2) * 4096 + (ks & 3) * 2048) & 0x3ffff) >> 4) |
                                    (64ull << 32) | (1ull << 62);
                const uint64_t db = (uint64_t)(((ring + rg + (ks & 3) * (NJ * 256)) & 0x3ffff) >> 4) | (8ull << 16) | (16ull << 32);
                wgmma_out(o[hh], da, db, ks);
            }
            asm volatile("wgmma.commit_group.sync.aligned;" ::: "memory");
        }
        const int nb = 2 * hpb;
#pragma unroll
        for (int hh = 0; hh < 2; hh++) {
            if (hh == 0) {
                asm volatile("wgmma.wait_group.sync.aligned 1;" ::: "memory");
            } else {
                asm volatile("wgmma.wait_group.sync.aligned 0;" ::: "memory");
                WG_SYNC(w);
            }
#pragma unroll
            for (int j = 0; j < NJ; j++)
#pragma unroll
                for (int k = 0; k < 4; k++) asm volatile("" : "+f"(o[hh][j][k])::"memory");
            const uint32_t b0 = ring + SM_EVEN + (hh ? 0 : 20480);
            const uint32_t b1 = hh ? b0 : ring + SM_ODD + 20480 + 896 - (nb * 128 & ~1023);
            const int r = (lane & 7) + (lane >> 4) * 8;
            const uint32_t co = r * 128 + (((2 * wq + ((lane >> 3) & 1)) ^ (lane & 7)) * 16);
#pragma unroll
            for (int j = 0; j + 1 < NJ; j += 2)
                stsm4t((8 * j + r < nb ? b0 : b1) + co + j * 1024, pack_bf16(o[hh][j][0], o[hh][j][1]),
                       pack_bf16(o[hh][j][2], o[hh][j][3]), pack_bf16(o[hh][j + 1][0], o[hh][j + 1][1]),
                       pack_bf16(o[hh][j + 1][2], o[hh][j + 1][3]));
            if (NJ & 1)
                stsm2t(b1 + co + (NJ - 1) * 1024, pack_bf16(o[hh][NJ - 1][0], o[hh][NJ - 1][1]),
                       pack_bf16(o[hh][NJ - 1][2], o[hh][NJ - 1][3]));
            FENCE_ASYNC();
            WG_SYNC(w);
            if (wq < 2 && elect()) {
                const int row = (node0 + w * hpb) * 4 + wq * nb;
                if (row < N * 4) tma_store(&tmo, wq ? b1 + nb * 128 : b0, hh * 64, row);
                asm volatile("cp.async.bulk.commit_group;" ::: "memory");
                if (hh) asm volatile("cp.async.bulk.wait_group.read 0;" ::: "memory");
            }
        }
    } else {
        float* accs = (float*)smem;
        constexpr int NACC = SM_EID / 2048;
        const int nnodes = max(0, min(npb, N - node0));
#pragma unroll 1
        for (int nb = 0; nb < nnodes; nb += NACC) {
            __syncthreads();
            for (int i = tid; i < NACC * 512; i += NT) accs[i] = 0.f;
            __syncthreads();
#pragma unroll 1
            for (int base = warp * 32; base < E; base += NT) {
                const int e = base + lane;
                int dl = e < E ? dst[e] - node0 - nb : -1;
                if (dl + nb >= nnodes) dl = -1;
                unsigned mask = __ballot_sync(0xffffffffu, dl >= 0 && dl < NACC);
#pragma unroll 1
                while (mask) {
                    const int l = __ffs(mask) - 1;
                    mask &= mask - 1;
                    const int ee = __shfl_sync(0xffffffffu, e, l);
                    const int dd = __shfl_sync(0xffffffffu, dl, l);
                    slow_edge(ee, src[ee], accs + dd * 512, x, sh, ea, cg, wr, lane);
                }
            }
            __syncthreads();
#pragma unroll 1
            for (int nl = warp; nl < NACC && nb + nl < nnodes; nl += NW)
                slow_out(accs + nl * 512, wout, out + (size_t)(node0 + nb + nl) * 512, lane);
        }
        __syncthreads();
    }

    TLMAX(4);
}

typedef CUresult (*EncodeTiledFn)(CUtensorMap*, CUtensorMapDataType, cuuint32_t, void*, const cuuint64_t*,
                                  const cuuint64_t*, const cuuint32_t*, const cuuint32_t*, CUtensorMapInterleave,
                                  CUtensorMapSwizzle, CUtensorMapL2promotion, CUtensorMapFloatOOBfill);

extern "C" void kernel_launch(void* const* d_in, const int* in_sizes, int n_in, void* d_out, int out_size) {
    const __nv_bfloat16* x = (const __nv_bfloat16*)d_in[0];
    const int* src = (const int*)d_in[1];
    const int* dst = (const int*)d_in[2];
    const __nv_bfloat16* sh = (const __nv_bfloat16*)d_in[3];
    const __nv_bfloat16* ea = (const __nv_bfloat16*)d_in[4];
    const __nv_bfloat16* cg = (const __nv_bfloat16*)d_in[5];
    const __nv_bfloat16* wr = (const __nv_bfloat16*)d_in[6];
    const __nv_bfloat16* wout = (const __nv_bfloat16*)d_in[7];
    __nv_bfloat16* out = (__nv_bfloat16*)d_out;
    const int N = in_sizes[0] / 512;
    const int E = in_sizes[1];

    static int num_sms = 0;
    static EncodeTiledFn encode = nullptr;
    if (num_sms == 0) {
        int dev = 0;
        cudaGetDevice(&dev);
        cudaDeviceGetAttribute(&num_sms, cudaDevAttrMultiProcessorCount, dev);
        cudaFuncSetAttribute(main_kernel, cudaFuncAttributeMaxDynamicSharedMemorySize, SM_TOTAL);
        void* fn = nullptr;
        cudaDriverEntryPointQueryResult qr;
        cudaGetDriverEntryPoint("cuTensorMapEncodeTiled", &fn, cudaEnableDefault, &qr);
        encode = (EncodeTiledFn)fn;
    }
    const int nbins = num_sms < MAXBINS ? num_sms : MAXBINS;
    int npb = ((N + nbins - 1) / nbins + 1) & ~1;
    if (npb < 32) npb = 32;
    const int fast_ok = npb <= 2 * HPB;
    auto map2d = [&](CUtensorMap* tm, const void* p, int d0, int d1, int b1) {
        const cuuint64_t gd[2] = {(cuuint64_t)d0, (cuuint64_t)d1};
        const cuuint64_t gs[1] = {(cuuint64_t)d0 * 2};
        const cuuint32_t bx[2] = {64, (cuuint32_t)b1};
        const cuuint32_t es[2] = {1, 1};
        encode(tm, CU_TENSOR_MAP_DATA_TYPE_BFLOAT16, 2, (void*)p, gd, gs, bx, es, CU_TENSOR_MAP_INTERLEAVE_NONE,
               CU_TENSOR_MAP_SWIZZLE_128B, CU_TENSOR_MAP_L2_PROMOTION_NONE, CU_TENSOR_MAP_FLOAT_OOB_FILL_NONE);
    };
    CUtensorMap tmx, tmw, tmo;
    {
        const cuuint64_t gd[2] = {(cuuint64_t)N * 256 - 224, 8};
        const cuuint64_t gs[1] = {128};
        const cuuint32_t bx[2] = {32, 8};
        const cuuint32_t es[2] = {1, 1};
        encode(&tmx, CU_TENSOR_MAP_DATA_TYPE_UINT32, 2, (void*)x, gd, gs, bx, es, CU_TENSOR_MAP_INTERLEAVE_NONE,
               CU_TENSOR_MAP_SWIZZLE_128B, CU_TENSOR_MAP_L2_PROMOTION_NONE, CU_TENSOR_MAP_FLOAT_OOB_FILL_NONE);
    }
    map2d(&tmw, wout, 128, 128, 32);
    map2d(&tmo, out, 128, N * 4, fast_ok ? npb : 2);
    const unsigned npb_magic = (unsigned)((0x100000000ull + npb - 1) / npb);
    const int chunk = (E + nbins - 1) / nbins;
    int bsh = 0;
    while (((N - 1) >> bsh) >= NBK) bsh++;
    int tau16 = (int)fmin((double)PACE * 16.0 * chunk / N, 100000.0), toff = TOFF;
    main_kernel<<<nbins, NT, SM_TOTAL, cudaStreamPerThread>>>(tmx, tmw, tmo, x, src, dst, sh, ea, cg, wr, wout, out, N, E,
                                                              npb, npb_magic, chunk, fast_ok, bsh, tau16, toff);
}
```

```cpp
#include <cuda_runtime.h>
#include <cuda.h>
#include <cuda_bf16.h>
#include <stdint.h>
#include <stdlib.h>
#include <type_traits>

#define MAXBINS 160
#define NW 16
#define NT (NW * 32)
#define HPB 38
#define GCAP 280
#define GEXT 72
#define NGR 6
#define LNUL (2 * (NGR * GCAP + GEXT))
#define NBK 160
#define CE 2
#define GSZ 6
#define NS 10
#define RING_BYTES 40960
static_assert(RING_BYTES == NS * 4096, "ring");
#define NP (NS / 2)
#define CREG 224
#define PREG 24
#define HREG 40
#define TS 8
#define SM_EVEN 0
#define SM_MISC (2 * RING_BYTES)
#define SM_ODD (SM_MISC + 128)
#define SM_EA (SM_BT + TS * 4096 + 128)
#define SM_BT (SM_ODD + 2 * RING_BYTES)
#define BT_B (TS * 512 + 16)
#define BT_K (4 * BT_B)
#define SM_SIDE (SM_EA + 8192)
#define SM_EID (SM_SIDE + 2048)
#define SM_SRC (SM_EID + (LNUL + 4) * 4)
#define SEQCAP 408
#define SM_SEQ (SM_SRC + (LNUL + 8) * 2)
#define SM_BAR ((SM_SEQ + 2 * SEQCAP * 2 + 63) / 64 * 64)
#define SM_TOTAL (SM_BAR + NW * (NP > 5 ? 32 : 16))
#define DUMB (2 * NP * 16)
#define MI_INT 0
#define EPS 5
#define SC_ENT 0
#define SC_EXT (SC_ENT + MAXBINS * 128)
#define SC_TAB (SC_EXT + MAXBINS * 64)
#define SC_HIST (SC_TAB + 320)
#define SC_BLK (SC_HIST + MAXBINS * 4 + 128)
#define SC_END (SC_BLK + 2 * (NBK + 2) * 4)
#define SC_WR SC_END
#define SC_CNT (SC_WR + 4352)
static_assert(SC_END % 16 == 0 && SC_HIST % 16 == 0 && SC_END - SC_HIST <= NT * 16 && SC_CNT + 16384 <= SM_MISC && SC_TAB <= 4 * NT * 16 && 2 * HPB <= 80 && MAXBINS <= 128 + 2 * NW, "scratch");
static_assert(LNUL >= 3072 && LNUL + 8 <= 4096 && GCAP % 4 == 0 && GEXT % 4 == 0, "lists");
static_assert(SM_TOTAL <= 232448 && SM_BAR % 16 == 0 && SM_SEQ % 16 == 0 && SM_SRC % 16 == 0 && SM_EA % 256 == 0, "smem");
#define PACE 18.6
#define TOFF 9600
#define PSLEEP 20

#define GEX (MAXBINS * MAXBINS * 8)
__device__ __align__(128) uint4 g_bin[GEX + GEX / 2];
#define STR2(x) #x
#define STR(x) STR2(x)
#define TLINIT()
#define TLEND()
#define TLX 0
#define TLSTAMP(i)
#define TLMAX(i)

__device__ __forceinline__ uint32_t pack_bf16(float lo, float hi) {
    uint32_t r;
    asm("cvt.rn.bf16x2.f32 %0, %1, %2;" : "=r"(r) : "f"(hi), "f"(lo));
    return r;
}
__device__ __forceinline__ void mma1688_z(float (&d)[4], uint32_t a0, uint32_t a1, uint32_t b0) {
    asm("mma.sync.aligned.m16n8k8.row.col.f32.bf16.bf16.f32 {%0,%1,%2,%3}, {%4,%5}, {%6}, {%7,%7,%7,%7};"
        : "=f"(d[0]), "=f"(d[1]), "=f"(d[2]), "=f"(d[3])
        : "r"(a0), "r"(a1), "r"(b0), "f"(0.f));
}
__device__ __forceinline__ void mma_diag(float (&d)[4], uint32_t a, uint32_t b0, uint32_t b1) {
    asm("mma.sync.aligned.m16n8k16.row.col.f32.bf16.bf16.f32 {%0,%1,%2,%3}, {%4,%8,%8,%4}, {%5,%6}, {%7,%7,%7,%7};"
        : "=f"(d[0]), "=f"(d[1]), "=f"(d[2]), "=f"(d[3])
        : "r"(a), "r"(b0), "r"(b1), "f"(0.f), "r"(0));
}
__device__ __forceinline__ uint32_t s2u(const void* p) { return (uint32_t)__cvta_generic_to_shared(p); }
__device__ __forceinline__ void mbar_init(uint32_t a, int c) {
    asm volatile("mbarrier.init.shared.b64 [%0], %1;" ::"r"(a), "r"(c));
}
__device__ __forceinline__ void mbar_expect_tx(uint32_t a, int bytes) {
    asm volatile("mbarrier.arrive.expect_tx.shared.b64 _, [%0], %1;" ::"r"(a), "r"(bytes) : "memory");
}
__device__ __forceinline__ void mbar_arrive(uint32_t a) {
    asm volatile("mbarrier.arrive.shared.b64 _, [%0];" ::"r"(a) : "memory");
}
__device__ __forceinline__ void mbar_arrive_cnt(uint32_t a, int c) {
    asm volatile("mbarrier.arrive.shared.b64 _, [%0], %1;" ::"r"(a), "r"(c) : "memory");
}
__device__ __forceinline__ void mbar_wait(uint32_t a, int parity) {
    asm volatile(
        "{\n.reg .pred p;\n.reg .u32 c;\n"
        "mov.u32 c, 0;\n"
        "LAB_WAIT:\n"
        "mbarrier.try_wait.parity.shared.b64 p, [%0], %1, 2000;\n"
        "@p bra DONE;\n"
        "add.u32 c, c, 1;\n"
        "setp.lt.u32 p, c, 2000000;\n"
        "@p bra LAB_WAIT;\n"
        "trap;\n"
        "DONE:\n}" ::"r"(a),
        "r"(parity)
        : "memory");
}
__device__ __forceinline__ void mbar_wait_u(uint32_t a, int parity) {
    asm volatile(
        "{\n.reg .pred p;\n.reg .u32 c;\n"
        "mov.u32 c, 0;\n"
        "LAB_WAIT:\n"
        "mbarrier.try_wait.parity.shared.b64 p, [%0], %1, 2000;\n"
        "@p bra.uni DONE;\n"
        "add.u32 c, c, 1;\n"
        "setp.lt.u32 p, c, 2000000;\n"
        "@p bra.uni LAB_WAIT;\n"
        "trap;\n"
        "DONE:\n}" ::"r"(a),
        "r"(parity)
        : "memory");
}
__device__ __forceinline__ void mbar_spin_u(uint32_t a, int parity) {
    asm volatile(
        "{\n.reg .pred p;\n.reg .u32 c;\n"
        "mov.u32 c, 0;\n"
        "LAB_WAIT:\n"
        "mbarrier.test_wait.parity.shared.b64 p, [%0], %1;\n"
        "@p bra.uni DONE;\n"
        "add.u32 c, c, 1;\n"
        "setp.lt.u32 p, c, 20000000;\n"
        "@p bra.uni LAB_WAIT;\n"
        "trap;\n"
        "DONE:\n}" ::"r"(a),
        "r"(parity)
        : "memory");
}
__device__ __forceinline__ void mbar_lean(uint32_t a, int parity) {
    asm volatile(
        "{\n.reg .pred p;\n.reg .u32 c;\n"
        "mov.u32 c, 0;\n"
        "LAB_WAIT:\n"
        "mbarrier.try_wait.parity.shared.b64 p, [%0], %1;\n"
        "@p bra DONE;\n"
        "add.u32 c, c, 1;\n"
        "setp.lt.u32 p, c, 4000000;\n"
        "@p bra LAB_WAIT;\n"
        "trap;\n"
        "DONE:\n}" ::"r"(a),
        "r"(parity)
        : "memory");
}
__device__ __forceinline__ void mbar_lean_u(uint32_t a, int parity) {
    asm volatile(
        "{\n.reg .pred p;\n.reg .u32 c;\n"
        "mov.u32 c, 0;\n"
        "LAB_WAIT:\n"
        "mbarrier.try_wait.parity.shared.b64 p, [%0], %1;\n"
        "@p bra.uni DONE;\n"
        "add.u32 c, c, 1;\n"
        "setp.lt.u32 p, c, 4000000;\n"
        "@p bra.uni LAB_WAIT;\n"
        "trap;\n"
        "DONE:\n}" ::"r"(a),
        "r"(parity)
        : "memory");
}
__device__ __forceinline__ bool mbar_test(uint32_t a, int parity) {
    uint32_t p;
    asm volatile("{\n.reg .pred P;\nmbarrier.test_wait.parity.shared.b64 P, [%1], %2;\nselp.u32 %0, 1, 0, P;\n}"
                 : "=r"(p)
                 : "r"(a), "r"(parity)
                 : "memory");
    return p;
}
__device__ __forceinline__ bool elect() {
    uint32_t p;
    asm volatile("{\n.reg .pred P;\nelect.sync _|P, 0xffffffff;\nselp.u32 %0, 1, 0, P;\n}" : "=r"(p));
    return p;
}
__device__ __forceinline__ void tma_2d(uint32_t dst, const CUtensorMap* tm, uint32_t bar, int c0, int c1) {
    asm volatile(
        "cp.async.bulk.tensor.2d.shared::cluster.global.mbarrier::complete_tx::bytes [%0], [%1, {%3, %4}], [%2];" ::"r"(dst),
        "l"(tm), "r"(bar), "r"(c0), "r"(c1)
        : "memory");
}
__device__ __forceinline__ void tma_row(uint32_t dst, const CUtensorMap* tm, uint32_t bar, int row8) {
    tma_2d(dst, tm, bar, 0, row8);
}
__device__ __forceinline__ void tma_store(const CUtensorMap* tm, uint32_t src, int c0, int c1) {
    asm volatile("cp.async.bulk.tensor.2d.global.shared::cta.bulk_group [%0, {%2, %3}], [%1];" ::"l"(tm), "r"(src),
                 "r"(c0), "r"(c1)
                 : "memory");
}
__device__ __forceinline__ uint2 lds_v2(uint32_t a) {
    uint2 v;
    asm volatile("ld.shared.v2.u32 {%0,%1}, [%2];" : "=r"(v.x), "=r"(v.y) : "r"(a));
    return v;
}
__device__ __forceinline__ uint4 lds_v4(uint32_t a) {
    uint4 v;
    asm volatile("ld.shared.v4.u32 {%0,%1,%2,%3}, [%4];" : "=r"(v.x), "=r"(v.y), "=r"(v.z), "=r"(v.w) : "r"(a));
    return v;
}
__device__ __forceinline__ uint32_t lds_u32(uint32_t a) {
    uint32_t v;
    asm volatile("ld.shared.u32 %0, [%1];" : "=r"(v) : "r"(a));
    return v;
}
__device__ __forceinline__ uint32_t lds_u16(uint32_t a) {
    uint32_t v;
    asm volatile("ld.shared.u16 %0, [%1];" : "=r"(v) : "r"(a));
    return v;
}
__device__ __forceinline__ void sts_v2(uint32_t a, uint32_t x, uint32_t y) {
    asm volatile("st.shared.v2.u32 [%0], {%1,%2};" ::"r"(a), "r"(x), "r"(y) : "memory");
}
__device__ __forceinline__ void sts_v4(uint32_t a, uint4 v) {
    asm volatile("st.shared.v4.u32 [%0], {%1,%2,%3,%4};" ::"r"(a), "r"(v.x), "r"(v.y), "r"(v.z), "r"(v.w) : "memory");
}
__device__ __forceinline__ void stsm4(uint32_t a, uint32_t r0, uint32_t r1, uint32_t r2, uint32_t r3) {
    asm volatile("stmatrix.sync.aligned.m8n8.x4.shared.b16 [%0], {%1,%2,%3,%4};" ::"r"(a), "r"(r0), "r"(r1), "r"(r2), "r"(r3)
                 : "memory");
}
__device__ __forceinline__ void stsm2(uint32_t a, uint32_t r0, uint32_t r1) {
    asm volatile("stmatrix.sync.aligned.m8n8.x2.shared.b16 [%0], {%1,%2};" ::"r"(a), "r"(r0), "r"(r1) : "memory");
}
__device__ __forceinline__ void stsm4t(uint32_t a, uint32_t r0, uint32_t r1, uint32_t r2, uint32_t r3) {
    asm volatile("stmatrix.sync.aligned.m8n8.x4.trans.shared.b16 [%0], {%1,%2,%3,%4};" ::"r"(a), "r"(r0), "r"(r1), "r"(r2),
                 "r"(r3)
                 : "memory");
}
__device__ __forceinline__ void stsm2t(uint32_t a, uint32_t r0, uint32_t r1) {
    asm volatile("stmatrix.sync.aligned.m8n8.x2.trans.shared.b16 [%0], {%1,%2};" ::"r"(a), "r"(r0), "r"(r1) : "memory");
}
__device__ __forceinline__ void cp_async16(uint32_t d, const void* s, int n) {
    asm volatile("cp.async.cg.shared.global [%0], [%1], 16, %2;" ::"r"(d), "l"(s), "r"(n) : "memory");
}
__device__ __forceinline__ void cp_async4(uint32_t d, const void* s, int n) {
    asm volatile("cp.async.ca.shared.global [%0], [%1], 4, %2;" ::"r"(d), "l"(s), "r"(n) : "memory");
}
__device__ __forceinline__ void sts_u32(uint32_t a, uint32_t x) {
    asm volatile("st.shared.u32 [%0], %1;" ::"r"(a), "r"(x) : "memory");
}
#define FENCE_ASYNC() asm volatile("fence.proxy.async.shared::cta;" ::: "memory")
__device__ __forceinline__ int warp_incl_scan(int v, int lane) {
#pragma unroll
    for (int o = 1; o < 32; o <<= 1) {
        const int y = __shfl_up_sync(0xffffffffu, v, o);
        if (lane >= o) v += y;
    }
    return v;
}

__device__ __forceinline__ uint32_t atoms_add(uint32_t a, uint32_t v) {
    uint32_t r;
    asm volatile("atom.shared.add.u32 %0, [%1], %2;" : "=r"(r) : "r"(a), "r"(v) : "memory");
    return r;
}
__device__ __forceinline__ void sts_u16(uint32_t a, uint32_t x) {
    asm volatile("{\n.reg .b16 h;\ncvt.u16.u32 h, %1;\nst.shared.u16 [%0], h;\n}" ::"r"(a), "r"(x) : "memory");
}
#define NJ 19
__device__ __forceinline__ void consume(float (&acc)[2][NJ][4], uint32_t xa0, uint32_t xa1, uint32_t so0, uint32_t bar0,
                                        uint32_t ea0, uint32_t d0, uint32_t pl0, int lz, const uint32_t (&wa)[8]) {
    asm volatile(
        "{\n"
        ".reg .pred p, pf, plead, pok, t0, t1, t2, u0, u1, u2;\n"
        ".reg .b32 ca, cb, cz, rbar;\n"
        "mov.b32 cz, 0;\n"
        "mov.b32 ca, 0x20002000;\n"
        "mov.b32 cb, 0x30003000;\n"
        ".reg .b32 cnt, so, q, qe, bar, nbar, pl, ctl, ctm, ix, iy, dl, v0, v1, v2, v3, pp;\n"
        ".reg .b16 sl, sh;\n"
        ".reg .b32 hXa0, hXa1, hXa2, hXa3, hXa4, hXa5, hXa6, hXa7, hXb0, hXb1, hXb2, hXb3, hXb4, hXb5, hXb6, hXb7, hYa0, hYa1, hYa2, hYa3, hYa4, hYa5, hYa6, hYa7, hYb0, hYb1, hYb2, hYb3, hYb4, hYb5, hYb6, hYb7, hLa0, hLa1, hLa2, hLa3, hLa4, hLa5, hLa6, hLa7, hLb0, hLb1, hLb2, hLb3, hLb4, hLb5, hLb6, hLb7;\n"
        ".reg .b32 pX0, pX1, pX2, pX3, pY0, pY1, pY2, pY3;\n"
        ".reg .f32 r0, r1, r2, r3, r4, r5, r6, r7, r8, r9, r10, r11, r12, r13, r14, r15;\n"
        ".reg .b64 daX, dbX, daY, dbY, de0, de1;\n"
        ".reg .b32 dh<6>, eb0, par, npar, wa<8>, uz, bend;\n"
        "add.u32 wa0, %160, %159;\n"
        "add.u32 wa1, %161, %159;\n"
        "add.u32 wa2, %162, %159;\n"
        "add.u32 wa3, %163, %159;\n"
        "add.u32 wa4, %164, %159;\n"
        "add.u32 wa5, %165, %159;\n"
        "add.u32 wa6, %166, %159;\n"
        "add.u32 wa7, %167, %159;\n"
        "mov.f32 %0, 0f00000000;\n"
        "mov.f32 %1, 0f00000000;\n"
        "mov.f32 %2, 0f00000000;\n"
        "mov.f32 %3, 0f00000000;\n"
        "mov.f32 %4, 0f00000000;\n"
        "mov.f32 %5, 0f00000000;\n"
        "mov.f32 %6, 0f00000000;\n"
        "mov.f32 %7, 0f00000000;\n"
        "mov.f32 %8, 0f00000000;\n"
        "mov.f32 %9, 0f00000000;\n"
        "mov.f32 %10, 0f00000000;\n"
        "mov.f32 %11, 0f00000000;\n"
        "mov.f32 %12, 0f00000000;\n"
        "mov.f32 %13, 0f00000000;\n"
        "mov.f32 %14, 0f00000000;\n"
        "mov.f32 %15, 0f00000000;\n"
        "mov.f32 %16, 0f00000000;\n"
        "mov.f32 %17, 0f00000000;\n"
        "mov.f32 %18, 0f00000000;\n"
        "mov.f32 %19, 0f00000000;\n"
        "mov.f32 %20, 0f00000000;\n"
        "mov.f32 %21, 0f00000000;\n"
        "mov.f32 %22, 0f00000000;\n"
        "mov.f32 %23, 0f00000000;\n"
        "mov.f32 %24, 0f00000000;\n"
        "mov.f32 %25, 0f00000000;\n"
        "mov.f32 %26, 0f00000000;\n"
        "mov.f32 %27, 0f00000000;\n"
        "mov.f32 %28, 0f00000000;\n"
        "mov.f32 %29, 0f00000000;\n"
        "mov.f32 %30, 0f00000000;\n"
        "mov.f32 %31, 0f00000000;\n"
        "mov.f32 %32, 0f00000000;\n"
        "mov.f32 %33, 0f00000000;\n"
        "mov.f32 %34, 0f00000000;\n"
        "mov.f32 %35, 0f00000000;\n"
        "mov.f32 %36, 0f00000000;\n"
        "mov.f32 %37, 0f00000000;\n"
        "mov.f32 %38, 0f00000000;\n"
        "mov.f32 %39, 0f00000000;\n"
        "mov.f32 %40, 0f00000000;\n"
        "mov.f32 %41, 0f00000000;\n"
        "mov.f32 %42, 0f00000000;\n"
        "mov.f32 %43, 0f00000000;\n"
        "mov.f32 %44, 0f00000000;\n"
        "mov.f32 %45, 0f00000000;\n"
        "mov.f32 %46, 0f00000000;\n"
        "mov.f32 %47, 0f00000000;\n"
        "mov.f32 %48, 0f00000000;\n"
        "mov.f32 %49, 0f00000000;\n"
        "mov.f32 %50, 0f00000000;\n"
        "mov.f32 %51, 0f00000000;\n"
        "mov.f32 %52, 0f00000000;\n"
        "mov.f32 %53, 0f00000000;\n"
        "mov.f32 %54, 0f00000000;\n"
        "mov.f32 %55, 0f00000000;\n"
        "mov.f32 %56, 0f00000000;\n"
        "mov.f32 %57, 0f00000000;\n"
        "mov.f32 %58, 0f00000000;\n"
        "mov.f32 %59, 0f00000000;\n"
        "mov.f32 %60, 0f00000000;\n"
        "mov.f32 %61, 0f00000000;\n"
        "mov.f32 %62, 0f00000000;\n"
        "mov.f32 %63, 0f00000000;\n"
        "mov.f32 %64, 0f00000000;\n"
        "mov.f32 %65, 0f00000000;\n"
        "mov.f32 %66, 0f00000000;\n"
        "mov.f32 %67, 0f00000000;\n"
        "mov.f32 %68, 0f00000000;\n"
        "mov.f32 %69, 0f00000000;\n"
        "mov.f32 %70, 0f00000000;\n"
        "mov.f32 %71, 0f00000000;\n"
        "mov.f32 %72, 0f00000000;\n"
        "mov.f32 %73, 0f00000000;\n"
        "mov.f32 %74, 0f00000000;\n"
        "mov.f32 %75, 0f00000000;\n"
        "mov.f32 %76, 0f00000000;\n"
        "mov.f32 %77, 0f00000000;\n"
        "mov.f32 %78, 0f00000000;\n"
        "mov.f32 %79, 0f00000000;\n"
        "mov.f32 %80, 0f00000000;\n"
        "mov.f32 %81, 0f00000000;\n"
        "mov.f32 %82, 0f00000000;\n"
        "mov.f32 %83, 0f00000000;\n"
        "mov.f32 %84, 0f00000000;\n"
        "mov.f32 %85, 0f00000000;\n"
        "mov.f32 %86, 0f00000000;\n"
        "mov.f32 %87, 0f00000000;\n"
        "mov.f32 %88, 0f00000000;\n"
        "mov.f32 %89, 0f00000000;\n"
        "mov.f32 %90, 0f00000000;\n"
        "mov.f32 %91, 0f00000000;\n"
        "mov.f32 %92, 0f00000000;\n"
        "mov.f32 %93, 0f00000000;\n"
        "mov.f32 %94, 0f00000000;\n"
        "mov.f32 %95, 0f00000000;\n"
        "mov.f32 %96, 0f00000000;\n"
        "mov.f32 %97, 0f00000000;\n"
        "mov.f32 %98, 0f00000000;\n"
        "mov.f32 %99, 0f00000000;\n"
        "mov.f32 %100, 0f00000000;\n"
        "mov.f32 %101, 0f00000000;\n"
        "mov.f32 %102, 0f00000000;\n"
        "mov.f32 %103, 0f00000000;\n"
        "mov.f32 %104, 0f00000000;\n"
        "mov.f32 %105, 0f00000000;\n"
        "mov.f32 %106, 0f00000000;\n"
        "mov.f32 %107, 0f00000000;\n"
        "mov.f32 %108, 0f00000000;\n"
        "mov.f32 %109, 0f00000000;\n"
        "mov.f32 %110, 0f00000000;\n"
        "mov.f32 %111, 0f00000000;\n"
        "mov.f32 %112, 0f00000000;\n"
        "mov.f32 %113, 0f00000000;\n"
        "mov.f32 %114, 0f00000000;\n"
        "mov.f32 %115, 0f00000000;\n"
        "mov.f32 %116, 0f00000000;\n"
        "mov.f32 %117, 0f00000000;\n"
        "mov.f32 %118, 0f00000000;\n"
        "mov.f32 %119, 0f00000000;\n"
        "mov.f32 %120, 0f00000000;\n"
        "mov.f32 %121, 0f00000000;\n"
        "mov.f32 %122, 0f00000000;\n"
        "mov.f32 %123, 0f00000000;\n"
        "mov.f32 %124, 0f00000000;\n"
        "mov.f32 %125, 0f00000000;\n"
        "mov.f32 %126, 0f00000000;\n"
        "mov.f32 %127, 0f00000000;\n"
        "mov.f32 %128, 0f00000000;\n"
        "mov.f32 %129, 0f00000000;\n"
        "mov.f32 %130, 0f00000000;\n"
        "mov.f32 %131, 0f00000000;\n"
        "mov.f32 %132, 0f00000000;\n"
        "mov.f32 %133, 0f00000000;\n"
        "mov.f32 %134, 0f00000000;\n"
        "mov.f32 %135, 0f00000000;\n"
        "mov.f32 %136, 0f00000000;\n"
        "mov.f32 %137, 0f00000000;\n"
        "mov.f32 %138, 0f00000000;\n"
        "mov.f32 %139, 0f00000000;\n"
        "mov.f32 %140, 0f00000000;\n"
        "mov.f32 %141, 0f00000000;\n"
        "mov.f32 %142, 0f00000000;\n"
        "mov.f32 %143, 0f00000000;\n"
        "mov.f32 %144, 0f00000000;\n"
        "mov.f32 %145, 0f00000000;\n"
        "mov.f32 %146, 0f00000000;\n"
        "mov.f32 %147, 0f00000000;\n"
        "mov.f32 %148, 0f00000000;\n"
        "mov.f32 %149, 0f00000000;\n"
        "mov.f32 %150, 0f00000000;\n"
        "mov.f32 %151, 0f00000000;\n"
        "setp.ne.u32 pf, 0, 0;\n"
        "add.u32 v0, %154, %159;\n"
        "shfl.sync.idx.b32 so, v0, 0, 31, 0xffffffff;\n"
        "mov.u32 npar, 0;\n"
        "shfl.sync.idx.b32 uz, %159, 7, 31, 0xffffffff;\n"
        "add.u32 bend, %155, " STR(NP * 16) ";\n"
        "add.u32 v0, %159, 8;\n"
        "shfl.sync.idx.b32 dh0, v0, 0, 31, 0xffffffff;\n"
        "shfl.sync.idx.b32 dh1, v0, 1, 31, 0xffffffff;\n"
        "shfl.sync.idx.b32 dh2, v0, 2, 31, 0xffffffff;\n"
        "shfl.sync.idx.b32 dh3, v0, 3, 31, 0xffffffff;\n"
        "add.u32 v0, %159, 0xc0000010;\n"
        "shfl.sync.idx.b32 dh4, v0, 4, 31, 0xffffffff;\n"
        "shfl.sync.idx.b32 dh5, v0, 5, 31, 0xffffffff;\n"
        "add.u32 v0, %159, %156;\n"
        "shfl.sync.idx.b32 eb0, v0, 0, 31, 0xffffffff;\n"
        "mov.u32 q, 0;\n"
        "mov.u32 pl, %158;\n"
        "shr.u32 nbar, so, 9;\n"
        "add.u32 nbar, nbar, %155;\n"
        "elect.sync _|plead, 0xffffffff;\n"
        "mov.b64 de0, {%156, dh4};\n"
        "mov.b64 de1, {eb0, dh5};\n"
        "mov.b32 hYa0, 0;\n"
        "mov.b32 hYa1, 0;\n"
        "mov.b32 hYa2, 0;\n"
        "mov.b32 hYa3, 0;\n"
        "mov.b32 hYa4, 0;\n"
        "mov.b32 hYa5, 0;\n"
        "mov.b32 hYa6, 0;\n"
        "mov.b32 hYa7, 0;\n"
        "mov.b32 hYb0, 0;\n"
        "mov.b32 hYb1, 0;\n"
        "mov.b32 hYb2, 0;\n"
        "mov.b32 hYb3, 0;\n"
        "mov.b32 hYb4, 0;\n"
        "mov.b32 hYb5, 0;\n"
        "mov.b32 hYb6, 0;\n"
        "mov.b32 hYb7, 0;\n"
        "mov.u32 ctm, 0x10001000;\n"
        "setp.lt.f16x2 t0|u0, ctm, cz;\n"
        "abs.f16x2 v3, ctm;\n"
        "setp.ge.f16x2 t1|u1, v3, ca;\n"
        "setp.geu.f16x2 t2|u2, v3, cb;\n"
        "ld.shared.v2.u32 {ctl, ctm}, [pl];\n"
        "add.u32 pl, pl, 8;\n"
        "add.u32 rbar, %155, " STR(DUMB) ";\n"
        "mov.b64 daX, {%157, dh0};\n"
        "mov.b64 dbX, {%157, dh1};\n"
        "mov.b64 daY, {%157, dh2};\n"
        "mov.b64 dbY, {%157, dh3};\n"
        "mov.u32 bar, nbar;\n"
        "mov.u32 par, npar;\n"
        "sub.u32 so, bar, %155;\n"
        "shl.b32 so, so, 9;\n"
        "add.u32 v0, %152, so;\n"
        "add.u32 v1, %153, so;\n"
        "add.u32 nbar, nbar, 16;\n"
        "setp.eq.u32 p, nbar, bend;\n"
        "selp.b32 nbar, %155, nbar, p;\n"
        "@p xor.b32 npar, npar, 1;\n"
        "SLOW:\n"
        "mov.u32 cnt, 0;\n"
        "W1:\n"
        "mbarrier.try_wait.parity.shared.b64 p, [bar], par;\n"
        "@p bra.uni RES;\n"
        "add.u32 cnt, cnt, 1;\n"
        "setp.lt.u32 p, cnt, 4000000;\n"
        "@p bra.uni W1;\n"
        "trap;\n"
        "CX:\n"
        "mbarrier.test_wait.parity.shared.b64 pok, [nbar], npar;\n"
        "and.b32 dl, q, 0x60;\n"
        "add.u32 dl, dl, %157;\n"
        "add.u32 v3, dl, 0;\n"
        "mov.b64 {v2, dh0}, daX;\n"
        "mov.b64 daX, {v3, dh0};\n"
        "add.u32 v3, dl, 257;\n"
        "mov.b64 {v2, dh1}, dbX;\n"
        "mov.b64 dbX, {v3, dh1};\n"
        "add.u32 v3, dl, 514;\n"
        "mov.b64 {v2, dh2}, daY;\n"
        "mov.b64 daY, {v3, dh2};\n"
        "add.u32 v3, dl, 771;\n"
        "mov.b64 {v2, dh3}, dbY;\n"
        "mov.b64 dbY, {v3, dh3};\n"
        "add.u32 q, q, 32;\n"
        "and.b32 qe, q, 0xe0;\n"
        "add.u32 v3, qe, %156;\n"
        "mov.b64 {v2, dh4}, de0;\n"
        "mov.b64 de0, {v3, dh4};\n"
        "mov.b64 {v2, dh5}, de1;\n"
        "mov.b64 de1, {v3, dh5};\n"
        "setp.lt.f16x2 t0|u0, ctl, cz;\n"
        "abs.f16x2 v3, ctl;\n"
        "setp.ge.f16x2 t1|u1, v3, ca;\n"
        "setp.geu.f16x2 t2|u2, v3, cb;\n"
        "wgmma.wait_group.sync.aligned 2;\n"
        "cvt.rn.bf16x2.f32 pX0, r1, r0;\n"
        "cvt.rn.bf16x2.f32 pX1, r3, r2;\n"
        "cvt.rn.bf16x2.f32 pX2, r9, r8;\n"
        "cvt.rn.bf16x2.f32 pX3, r11, r10;\n"
        "cvt.rn.bf16x2.f32 pY0, r5, r4;\n"
        "cvt.rn.bf16x2.f32 pY1, r7, r6;\n"
        "cvt.rn.bf16x2.f32 pY2, r13, r12;\n"
        "cvt.rn.bf16x2.f32 pY3, r15, r14;\n"
        "mov.b32 {sl, sh}, pX0;\n"
        "mov.b32 pp, {sl, sl};\n"
        "mul.rn.bf16x2 hXa0, hLa0, pp;\n"
        "mul.rn.bf16x2 hXa2, hLa2, pp;\n"
        "mov.b32 {sl, sh}, pX1;\n"
        "mov.b32 pp, {sl, sl};\n"
        "mul.rn.bf16x2 hXa1, hLa1, pp;\n"
        "mul.rn.bf16x2 hXa3, hLa3, pp;\n"
        "mov.b32 {sl, sh}, pX2;\n"
        "mov.b32 pp, {sl, sl};\n"
        "mul.rn.bf16x2 hXa4, hLa4, pp;\n"
        "mul.rn.bf16x2 hXa6, hLa6, pp;\n"
        "mov.b32 {sl, sh}, pX3;\n"
        "mov.b32 pp, {sl, sl};\n"
        "mul.rn.bf16x2 hXa5, hLa5, pp;\n"
        "mul.rn.bf16x2 hXa7, hLa7, pp;\n"
        "mov.b32 {sl, sh}, pX0;\n"
        "mov.b32 pp, {sh, sh};\n"
        "mul.rn.bf16x2 hXb0, hLb0, pp;\n"
        "mul.rn.bf16x2 hXb2, hLb2, pp;\n"
        "mov.b32 {sl, sh}, pX1;\n"
        "mov.b32 pp, {sh, sh};\n"
        "mul.rn.bf16x2 hXb1, hLb1, pp;\n"
        "mul.rn.bf16x2 hXb3, hLb3, pp;\n"
        "mov.b32 {sl, sh}, pX2;\n"
        "mov.b32 pp, {sh, sh};\n"
        "mul.rn.bf16x2 hXb4, hLb4, pp;\n"
        "mul.rn.bf16x2 hXb6, hLb6, pp;\n"
        "mov.b32 {sl, sh}, pX3;\n"
        "mov.b32 pp, {sh, sh};\n"
        "mul.rn.bf16x2 hXb5, hLb5, pp;\n"
        "mul.rn.bf16x2 hXb7, hLb7, pp;\n"
        "ldmatrix.sync.aligned.m8n8.x4.trans.shared.b16 {hLa0,hLa1,hLa2,hLa3}, [v0+4096];\n"
        "ldmatrix.sync.aligned.m8n8.x4.trans.shared.b16 {hLa4,hLa5,hLa6,hLa7}, [v1+4096];\n"
        "ldmatrix.sync.aligned.m8n8.x4.trans.shared.b16 {hLb0,hLb1,hLb2,hLb3}, [v0+6144];\n"
        "ldmatrix.sync.aligned.m8n8.x4.trans.shared.b16 {hLb4,hLb5,hLb6,hLb7}, [v1+6144];\n"
        "@t2 bra.uni T4X;\n"
        "@t1 bra.uni T2X;\n"
        "@t0 bra.uni L1X;\n"
        "L0X:\n"
        "wgmma.fence.sync.aligned;\n"
        "wgmma.mma_async.sync.aligned.m64n24k16.f32.bf16.bf16 {%0,%1,%2,%3,%4,%5,%6,%7,%8,%9,%10,%11}, {hXa0,hXa1,hXa2,hXa3}, daX, 1, 1, 1, 0;\n"
        "wgmma.mma_async.sync.aligned.m64n24k16.f32.bf16.bf16 {%76,%77,%78,%79,%80,%81,%82,%83,%84,%85,%86,%87}, {hXa4,hXa5,hXa6,hXa7}, daX, 1, 1, 1, 0;\n"
        "wgmma.commit_group.sync.aligned;\n"
        "@u2 bra.uni T4Xb;\n"
        "@u1 bra.uni T2Xb;\n"
        "@u0 bra.uni L1Xb;\n"
        "bra.uni L0Xb;\n"
        "L1X:\n"
        "wgmma.fence.sync.aligned;\n"
        "wgmma.mma_async.sync.aligned.m64n24k16.f32.bf16.bf16 {%12,%13,%14,%15,%16,%17,%18,%19,%20,%21,%22,%23}, {hXa0,hXa1,hXa2,hXa3}, daX, 1, 1, 1, 0;\n"
        "wgmma.mma_async.sync.aligned.m64n24k16.f32.bf16.bf16 {%88,%89,%90,%91,%92,%93,%94,%95,%96,%97,%98,%99}, {hXa4,hXa5,hXa6,hXa7}, daX, 1, 1, 1, 0;\n"
        "wgmma.commit_group.sync.aligned;\n"
        "@u2 bra.uni T4Xb;\n"
        "@u1 bra.uni T2Xb;\n"
        "@u0 bra.uni L1Xb;\n"
        "bra.uni L0Xb;\n"
        "T2X:\n"
        "@t0 bra.uni L3X;\n"
        "L2X:\n"
        "wgmma.fence.sync.aligned;\n"
        "wgmma.mma_async.sync.aligned.m64n24k16.f32.bf16.bf16 {%24,%25,%26,%27,%28,%29,%30,%31,%32,%33,%34,%35}, {hXa0,hXa1,hXa2,hXa3}, daX, 1, 1, 1, 0;\n"
        "wgmma.mma_async.sync.aligned.m64n24k16.f32.bf16.bf16 {%100,%101,%102,%103,%104,%105,%106,%107,%108,%109,%110,%111}, {hXa4,hXa5,hXa6,hXa7}, daX, 1, 1, 1, 0;\n"
        "wgmma.commit_group.sync.aligned;\n"
        "@u2 bra.uni T4Xb;\n"
        "@u1 bra.uni T2Xb;\n"
        "@u0 bra.uni L1Xb;\n"
        "bra.uni L0Xb;\n"
        "L3X:\n"
        "wgmma.fence.sync.aligned;\n"
        "wgmma.mma_async.sync.aligned.m64n24k16.f32.bf16.bf16 {%36,%37,%38,%39,%40,%41,%42,%43,%44,%45,%46,%47}, {hXa0,hXa1,hXa2,hXa3}, daX, 1, 1, 1, 0;\n"
        "wgmma.mma_async.sync.aligned.m64n24k16.f32.bf16.bf16 {%112,%113,%114,%115,%116,%117,%118,%119,%120,%121,%122,%123}, {hXa4,hXa5,hXa6,hXa7}, daX, 1, 1, 1, 0;\n"
        "wgmma.commit_group.sync.aligned;\n"
        "@u2 bra.uni T4Xb;\n"
        "@u1 bra.uni T2Xb;\n"
        "@u0 bra.uni L1Xb;\n"
        "bra.uni L0Xb;\n"
        "T4X:\n"
        "@!t1 bra.uni LEXIT;\n"
        "@t0 bra.uni L5X;\n"
        "L4X:\n"
        "wgmma.fence.sync.aligned;\n"
        "wgmma.mma_async.sync.aligned.m64n24k16.f32.bf16.bf16 {%48,%49,%50,%51,%52,%53,%54,%55,%56,%57,%58,%59}, {hXa0,hXa1,hXa2,hXa3}, daX, 1, 1, 1, 0;\n"
        "wgmma.mma_async.sync.aligned.m64n24k16.f32.bf16.bf16 {%124,%125,%126,%127,%128,%129,%130,%131,%132,%133,%134,%135}, {hXa4,hXa5,hXa6,hXa7}, daX, 1, 1, 1, 0;\n"
        "wgmma.commit_group.sync.aligned;\n"
        "@u2 bra.uni T4Xb;\n"
        "@u1 bra.uni T2Xb;\n"
        "@u0 bra.uni L1Xb;\n"
        "bra.uni L0Xb;\n"
        "L5X:\n"
        "wgmma.fence.sync.aligned;\n"
        "wgmma.mma_async.sync.aligned.m64n32k16.f32.bf16.bf16 {%60,%61,%62,%63,%64,%65,%66,%67,%68,%69,%70,%71,%72,%73,%74,%75}, {hXa0,hXa1,hXa2,hXa3}, daX, 1, 1, 1, 0;\n"
        "wgmma.mma_async.sync.aligned.m64n32k16.f32.bf16.bf16 {%136,%137,%138,%139,%140,%141,%142,%143,%144,%145,%146,%147,%148,%149,%150,%151}, {hXa4,hXa5,hXa6,hXa7}, daX, 1, 1, 1, 0;\n"
        "wgmma.commit_group.sync.aligned;\n"
        "@u2 bra.uni T4Xb;\n"
        "@u1 bra.uni T2Xb;\n"
        "@u0 bra.uni L1Xb;\n"
        "L0Xb:\n"
        "wgmma.fence.sync.aligned;\n"
        "wgmma.mma_async.sync.aligned.m64n24k16.f32.bf16.bf16 {%0,%1,%2,%3,%4,%5,%6,%7,%8,%9,%10,%11}, {hXb0,hXb1,hXb2,hXb3}, dbX, 1, 1, 1, 0;\n"
        "wgmma.mma_async.sync.aligned.m64n24k16.f32.bf16.bf16 {%76,%77,%78,%79,%80,%81,%82,%83,%84,%85,%86,%87}, {hXb4,hXb5,hXb6,hXb7}, dbX, 1, 1, 1, 0;\n"
        "wgmma.commit_group.sync.aligned;\n"
        "bra.uni CY;\n"
        "L1Xb:\n"
        "wgmma.fence.sync.aligned;\n"
        "wgmma.mma_async.sync.aligned.m64n24k16.f32.bf16.bf16 {%12,%13,%14,%15,%16,%17,%18,%19,%20,%21,%22,%23}, {hXb0,hXb1,hXb2,hXb3}, dbX, 1, 1, 1, 0;\n"
        "wgmma.mma_async.sync.aligned.m64n24k16.f32.bf16.bf16 {%88,%89,%90,%91,%92,%93,%94,%95,%96,%97,%98,%99}, {hXb4,hXb5,hXb6,hXb7}, dbX, 1, 1, 1, 0;\n"
        "wgmma.commit_group.sync.aligned;\n"
        "bra.uni CY;\n"
        "T2Xb:\n"
        "@u0 bra.uni L3Xb;\n"
        "L2Xb:\n"
        "wgmma.fence.sync.aligned;\n"
        "wgmma.mma_async.sync.aligned.m64n24k16.f32.bf16.bf16 {%24,%25,%26,%27,%28,%29,%30,%31,%32,%33,%34,%35}, {hXb0,hXb1,hXb2,hXb3}, dbX, 1, 1, 1, 0;\n"
        "wgmma.mma_async.sync.aligned.m64n24k16.f32.bf16.bf16 {%100,%101,%102,%103,%104,%105,%106,%107,%108,%109,%110,%111}, {hXb4,hXb5,hXb6,hXb7}, dbX, 1, 1, 1, 0;\n"
        "wgmma.commit_group.sync.aligned;\n"
        "bra.uni CY;\n"
        "L3Xb:\n"
        "wgmma.fence.sync.aligned;\n"
        "wgmma.mma_async.sync.aligned.m64n24k16.f32.bf16.bf16 {%36,%37,%38,%39,%40,%41,%42,%43,%44,%45,%46,%47}, {hXb0,hXb1,hXb2,hXb3}, dbX, 1, 1, 1, 0;\n"
        "wgmma.mma_async.sync.aligned.m64n24k16.f32.bf16.bf16 {%112,%113,%114,%115,%116,%117,%118,%119,%120,%121,%122,%123}, {hXb4,hXb5,hXb6,hXb7}, dbX, 1, 1, 1, 0;\n"
        "wgmma.commit_group.sync.aligned;\n"
        "bra.uni CY;\n"
        "T4Xb:\n"
        "@u0 bra.uni L5Xb;\n"
        "L4Xb:\n"
        "wgmma.fence.sync.aligned;\n"
        "wgmma.mma_async.sync.aligned.m64n24k16.f32.bf16.bf16 {%48,%49,%50,%51,%52,%53,%54,%55,%56,%57,%58,%59}, {hXb0,hXb1,hXb2,hXb3}, dbX, 1, 1, 1, 0;\n"
        "wgmma.mma_async.sync.aligned.m64n24k16.f32.bf16.bf16 {%124,%125,%126,%127,%128,%129,%130,%131,%132,%133,%134,%135}, {hXb4,hXb5,hXb6,hXb7}, dbX, 1, 1, 1, 0;\n"
        "wgmma.commit_group.sync.aligned;\n"
        "bra.uni CY;\n"
        "L5Xb:\n"
        "wgmma.fence.sync.aligned;\n"
        "wgmma.mma_async.sync.aligned.m64n32k16.f32.bf16.bf16 {%60,%61,%62,%63,%64,%65,%66,%67,%68,%69,%70,%71,%72,%73,%74,%75}, {hXb0,hXb1,hXb2,hXb3}, dbX, 1, 1, 1, 0;\n"
        "wgmma.mma_async.sync.aligned.m64n32k16.f32.bf16.bf16 {%136,%137,%138,%139,%140,%141,%142,%143,%144,%145,%146,%147,%148,%149,%150,%151}, {hXb4,hXb5,hXb6,hXb7}, dbX, 1, 1, 1, 0;\n"
        "wgmma.commit_group.sync.aligned;\n"
        "bra.uni CY;\n"
        "CY:\n"
        "mov.u32 rbar, bar;\n"
        "mov.u32 bar, nbar;\n"
        "mov.u32 par, npar;\n"
        "sub.u32 so, bar, %155;\n"
        "shl.b32 so, so, 9;\n"
        "add.u32 v0, %152, so;\n"
        "add.u32 v1, %153, so;\n"
        "add.u32 nbar, nbar, 16;\n"
        "setp.eq.u32 p, nbar, bend;\n"
        "selp.b32 nbar, %155, nbar, p;\n"
        "@p xor.b32 npar, npar, 1;\n"
        "wgmma.wait_group.sync.aligned 2;\n"
        "lop3.b32 v2, hLa3, hLa7, hLb3, 0x80;\n"
        "lop3.b32 v2, v2, hLb7, uz, 0x80;\n"
        "add.u32 v2, v2, rbar;\n"
        "@plead mbarrier.arrive.shared.b64 _, [v2+8];\n"
        "setp.lt.f16x2 t0|u0, ctm, cz;\n"
        "abs.f16x2 v3, ctm;\n"
        "setp.ge.f16x2 t1|u1, v3, ca;\n"
        "setp.geu.f16x2 t2|u2, v3, cb;\n"
        "ld.shared.v2.u32 {ctl, ctm}, [pl];\n"
        "add.u32 pl, pl, 8;\n"
        "mov.b32 {sl, sh}, pY0;\n"
        "mov.b32 pp, {sl, sl};\n"
        "mul.rn.bf16x2 hYa0, hLa0, pp;\n"
        "mul.rn.bf16x2 hYa2, hLa2, pp;\n"
        "mov.b32 {sl, sh}, pY1;\n"
        "mov.b32 pp, {sl, sl};\n"
        "mul.rn.bf16x2 hYa1, hLa1, pp;\n"
        "mul.rn.bf16x2 hYa3, hLa3, pp;\n"
        "mov.b32 {sl, sh}, pY2;\n"
        "mov.b32 pp, {sl, sl};\n"
        "mul.rn.bf16x2 hYa4, hLa4, pp;\n"
        "mul.rn.bf16x2 hYa6, hLa6, pp;\n"
        "mov.b32 {sl, sh}, pY3;\n"
        "mov.b32 pp, {sl, sl};\n"
        "mul.rn.bf16x2 hYa5, hLa5, pp;\n"
        "mul.rn.bf16x2 hYa7, hLa7, pp;\n"
        "mov.b32 {sl, sh}, pY0;\n"
        "mov.b32 pp, {sh, sh};\n"
        "mul.rn.bf16x2 hYb0, hLb0, pp;\n"
        "mul.rn.bf16x2 hYb2, hLb2, pp;\n"
        "mov.b32 {sl, sh}, pY1;\n"
        "mov.b32 pp, {sh, sh};\n"
        "mul.rn.bf16x2 hYb1, hLb1, pp;\n"
        "mul.rn.bf16x2 hYb3, hLb3, pp;\n"
        "mov.b32 {sl, sh}, pY2;\n"
        "mov.b32 pp, {sh, sh};\n"
        "mul.rn.bf16x2 hYb4, hLb4, pp;\n"
        "mul.rn.bf16x2 hYb6, hLb6, pp;\n"
        "mov.b32 {sl, sh}, pY3;\n"
        "mov.b32 pp, {sh, sh};\n"
        "mul.rn.bf16x2 hYb5, hLb5, pp;\n"
        "mul.rn.bf16x2 hYb7, hLb7, pp;\n"
        "@!pok bra.uni SLOW;\n"
        "RES:\n"
        "ldmatrix.sync.aligned.m8n8.x4.trans.shared.b16 {hLa0,hLa1,hLa2,hLa3}, [v0+0];\n"
        "ldmatrix.sync.aligned.m8n8.x4.trans.shared.b16 {hLa4,hLa5,hLa6,hLa7}, [v1+0];\n"
        "ldmatrix.sync.aligned.m8n8.x4.trans.shared.b16 {hLb0,hLb1,hLb2,hLb3}, [v0+2048];\n"
        "ldmatrix.sync.aligned.m8n8.x4.trans.shared.b16 {hLb4,hLb5,hLb6,hLb7}, [v1+2048];\n"
        "wgmma.wait_group.sync.aligned 0;\n"
        "@t2 bra.uni T4Y;\n"
        "@t1 bra.uni T2Y;\n"
        "@t0 bra.uni L1Y;\n"
        "L0Y:\n"
        "wgmma.fence.sync.aligned;\n"
        "wgmma.mma_async.sync.aligned.m64n16k16.f32.bf16.bf16 {r0,r1,r2,r3,r4,r5,r6,r7}, {wa0,wa1,wa2,wa3}, de0, pf, 1, 1, 0;\n"
        "wgmma.mma_async.sync.aligned.m64n16k16.f32.bf16.bf16 {r8,r9,r10,r11,r12,r13,r14,r15}, {wa4,wa5,wa6,wa7}, de1, pf, 1, 1, 0;\n"
        "wgmma.commit_group.sync.aligned;\n"
        "wgmma.mma_async.sync.aligned.m64n24k16.f32.bf16.bf16 {%0,%1,%2,%3,%4,%5,%6,%7,%8,%9,%10,%11}, {hYa0,hYa1,hYa2,hYa3}, daY, 1, 1, 1, 0;\n"
        "wgmma.mma_async.sync.aligned.m64n24k16.f32.bf16.bf16 {%76,%77,%78,%79,%80,%81,%82,%83,%84,%85,%86,%87}, {hYa4,hYa5,hYa6,hYa7}, daY, 1, 1, 1, 0;\n"
        "wgmma.commit_group.sync.aligned;\n"
        "@u2 bra.uni T4Yb;\n"
        "@u1 bra.uni T2Yb;\n"
        "@u0 bra.uni L1Yb;\n"
        "bra.uni L0Yb;\n"
        "L1Y:\n"
        "wgmma.fence.sync.aligned;\n"
        "wgmma.mma_async.sync.aligned.m64n16k16.f32.bf16.bf16 {r0,r1,r2,r3,r4,r5,r6,r7}, {wa0,wa1,wa2,wa3}, de0, pf, 1, 1, 0;\n"
        "wgmma.mma_async.sync.aligned.m64n16k16.f32.bf16.bf16 {r8,r9,r10,r11,r12,r13,r14,r15}, {wa4,wa5,wa6,wa7}, de1, pf, 1, 1, 0;\n"
        "wgmma.commit_group.sync.aligned;\n"
        "wgmma.mma_async.sync.aligned.m64n24k16.f32.bf16.bf16 {%12,%13,%14,%15,%16,%17,%18,%19,%20,%21,%22,%23}, {hYa0,hYa1,hYa2,hYa3}, daY, 1, 1, 1, 0;\n"
        "wgmma.mma_async.sync.aligned.m64n24k16.f32.bf16.bf16 {%88,%89,%90,%91,%92,%93,%94,%95,%96,%97,%98,%99}, {hYa4,hYa5,hYa6,hYa7}, daY, 1, 1, 1, 0;\n"
        "wgmma.commit_group.sync.aligned;\n"
        "@u2 bra.uni T4Yb;\n"
        "@u1 bra.uni T2Yb;\n"
        "@u0 bra.uni L1Yb;\n"
        "bra.uni L0Yb;\n"
        "T2Y:\n"
        "@t0 bra.uni L3Y;\n"
        "L2Y:\n"
        "wgmma.fence.sync.aligned;\n"
        "wgmma.mma_async.sync.aligned.m64n16k16.f32.bf16.bf16 {r0,r1,r2,r3,r4,r5,r6,r7}, {wa0,wa1,wa2,wa3}, de0, pf, 1, 1, 0;\n"
        "wgmma.mma_async.sync.aligned.m64n16k16.f32.bf16.bf16 {r8,r9,r10,r11,r12,r13,r14,r15}, {wa4,wa5,wa6,wa7}, de1, pf, 1, 1, 0;\n"
        "wgmma.commit_group.sync.aligned;\n"
        "wgmma.mma_async.sync.aligned.m64n24k16.f32.bf16.bf16 {%24,%25,%26,%27,%28,%29,%30,%31,%32,%33,%34,%35}, {hYa0,hYa1,hYa2,hYa3}, daY, 1, 1, 1, 0;\n"
        "wgmma.mma_async.sync.aligned.m64n24k16.f32.bf16.bf16 {%100,%101,%102,%103,%104,%105,%106,%107,%108,%109,%110,%111}, {hYa4,hYa5,hYa6,hYa7}, daY, 1, 1, 1, 0;\n"
        "wgmma.commit_group.sync.aligned;\n"
        "@u2 bra.uni T4Yb;\n"
        "@u1 bra.uni T2Yb;\n"
        "@u0 bra.uni L1Yb;\n"
        "bra.uni L0Yb;\n"
        "L3Y:\n"
        "wgmma.fence.sync.aligned;\n"
        "wgmma.mma_async.sync.aligned.m64n16k16.f32.bf16.bf16 {r0,r1,r2,r3,r4,r5,r6,r7}, {wa0,wa1,wa2,wa3}, de0, pf, 1, 1, 0;\n"
        "wgmma.mma_async.sync.aligned.m64n16k16.f32.bf16.bf16 {r8,r9,r10,r11,r12,r13,r14,r15}, {wa4,wa5,wa6,wa7}, de1, pf, 1, 1, 0;\n"
        "wgmma.commit_group.sync.aligned;\n"
        "wgmma.mma_async.sync.aligned.m64n24k16.f32.bf16.bf16 {%36,%37,%38,%39,%40,%41,%42,%43,%44,%45,%46,%47}, {hYa0,hYa1,hYa2,hYa3}, daY, 1, 1, 1, 0;\n"
        "wgmma.mma_async.sync.aligned.m64n24k16.f32.bf16.bf16 {%112,%113,%114,%115,%116,%117,%118,%119,%120,%121,%122,%123}, {hYa4,hYa5,hYa6,hYa7}, daY, 1, 1, 1, 0;\n"
        "wgmma.commit_group.sync.aligned;\n"
        "@u2 bra.uni T4Yb;\n"
        "@u1 bra.uni T2Yb;\n"
        "@u0 bra.uni L1Yb;\n"
        "bra.uni L0Yb;\n"
        "T4Y:\n"
        "@t0 bra.uni L5Y;\n"
        "L4Y:\n"
        "wgmma.fence.sync.aligned;\n"
        "wgmma.mma_async.sync.aligned.m64n16k16.f32.bf16.bf16 {r0,r1,r2,r3,r4,r5,r6,r7}, {wa0,wa1,wa2,wa3}, de0, pf, 1, 1, 0;\n"
        "wgmma.mma_async.sync.aligned.m64n16k16.f32.bf16.bf16 {r8,r9,r10,r11,r12,r13,r14,r15}, {wa4,wa5,wa6,wa7}, de1, pf, 1, 1, 0;\n"
        "wgmma.commit_group.sync.aligned;\n"
        "wgmma.mma_async.sync.aligned.m64n24k16.f32.bf16.bf16 {%48,%49,%50,%51,%52,%53,%54,%55,%56,%57,%58,%59}, {hYa0,hYa1,hYa2,hYa3}, daY, 1, 1, 1, 0;\n"
        "wgmma.mma_async.sync.aligned.m64n24k16.f32.bf16.bf16 {%124,%125,%126,%127,%128,%129,%130,%131,%132,%133,%134,%135}, {hYa4,hYa5,hYa6,hYa7}, daY, 1, 1, 1, 0;\n"
        "wgmma.commit_group.sync.aligned;\n"
        "@u2 bra.uni T4Yb;\n"
        "@u1 bra.uni T2Yb;\n"
        "@u0 bra.uni L1Yb;\n"
        "bra.uni L0Yb;\n"
        "L5Y:\n"
        "wgmma.fence.sync.aligned;\n"
        "wgmma.mma_async.sync.aligned.m64n16k16.f32.bf16.bf16 {r0,r1,r2,r3,r4,r5,r6,r7}, {wa0,wa1,wa2,wa3}, de0, pf, 1, 1, 0;\n"
        "wgmma.mma_async.sync.aligned.m64n16k16.f32.bf16.bf16 {r8,r9,r10,r11,r12,r13,r14,r15}, {wa4,wa5,wa6,wa7}, de1, pf, 1, 1, 0;\n"
        "wgmma.commit_group.sync.aligned;\n"
        "wgmma.mma_async.sync.aligned.m64n32k16.f32.bf16.bf16 {%60,%61,%62,%63,%64,%65,%66,%67,%68,%69,%70,%71,%72,%73,%74,%75}, {hYa0,hYa1,hYa2,hYa3}, daY, 1, 1, 1, 0;\n"
        "wgmma.mma_async.sync.aligned.m64n32k16.f32.bf16.bf16 {%136,%137,%138,%139,%140,%141,%142,%143,%144,%145,%146,%147,%148,%149,%150,%151}, {hYa4,hYa5,hYa6,hYa7}, daY, 1, 1, 1, 0;\n"
        "wgmma.commit_group.sync.aligned;\n"
        "@u2 bra.uni T4Yb;\n"
        "@u1 bra.uni T2Yb;\n"
        "@u0 bra.uni L1Yb;\n"
        "L0Yb:\n"
        "wgmma.fence.sync.aligned;\n"
        "wgmma.mma_async.sync.aligned.m64n24k16.f32.bf16.bf16 {%0,%1,%2,%3,%4,%5,%6,%7,%8,%9,%10,%11}, {hYb0,hYb1,hYb2,hYb3}, dbY, 1, 1, 1, 0;\n"
        "wgmma.mma_async.sync.aligned.m64n24k16.f32.bf16.bf16 {%76,%77,%78,%79,%80,%81,%82,%83,%84,%85,%86,%87}, {hYb4,hYb5,hYb6,hYb7}, dbY, 1, 1, 1, 0;\n"
        "wgmma.commit_group.sync.aligned;\n"
        "bra.uni CX;\n"
        "L1Yb:\n"
        "wgmma.fence.sync.aligned;\n"
        "wgmma.mma_async.sync.aligned.m64n24k16.f32.bf16.bf16 {%12,%13,%14,%15,%16,%17,%18,%19,%20,%21,%22,%23}, {hYb0,hYb1,hYb2,hYb3}, dbY, 1, 1, 1, 0;\n"
        "wgmma.mma_async.sync.aligned.m64n24k16.f32.bf16.bf16 {%88,%89,%90,%91,%92,%93,%94,%95,%96,%97,%98,%99}, {hYb4,hYb5,hYb6,hYb7}, dbY, 1, 1, 1, 0;\n"
        "wgmma.commit_group.sync.aligned;\n"
        "bra.uni CX;\n"
        "T2Yb:\n"
        "@u0 bra.uni L3Yb;\n"
        "L2Yb:\n"
        "wgmma.fence.sync.aligned;\n"
        "wgmma.mma_async.sync.aligned.m64n24k16.f32.bf16.bf16 {%24,%25,%26,%27,%28,%29,%30,%31,%32,%33,%34,%35}, {hYb0,hYb1,hYb2,hYb3}, dbY, 1, 1, 1, 0;\n"
        "wgmma.mma_async.sync.aligned.m64n24k16.f32.bf16.bf16 {%100,%101,%102,%103,%104,%105,%106,%107,%108,%109,%110,%111}, {hYb4,hYb5,hYb6,hYb7}, dbY, 1, 1, 1, 0;\n"
        "wgmma.commit_group.sync.aligned;\n"
        "bra.uni CX;\n"
        "L3Yb:\n"
        "wgmma.fence.sync.aligned;\n"
        "wgmma.mma_async.sync.aligned.m64n24k16.f32.bf16.bf16 {%36,%37,%38,%39,%40,%41,%42,%43,%44,%45,%46,%47}, {hYb0,hYb1,hYb2,hYb3}, dbY, 1, 1, 1, 0;\n"
        "wgmma.mma_async.sync.aligned.m64n24k16.f32.bf16.bf16 {%112,%113,%114,%115,%116,%117,%118,%119,%120,%121,%122,%123}, {hYb4,hYb5,hYb6,hYb7}, dbY, 1, 1, 1, 0;\n"
        "wgmma.commit_group.sync.aligned;\n"
        "bra.uni CX;\n"
        "T4Yb:\n"
        "@u0 bra.uni L5Yb;\n"
        "L4Yb:\n"
        "wgmma.fence.sync.aligned;\n"
        "wgmma.mma_async.sync.aligned.m64n24k16.f32.bf16.bf16 {%48,%49,%50,%51,%52,%53,%54,%55,%56,%57,%58,%59}, {hYb0,hYb1,hYb2,hYb3}, dbY, 1, 1, 1, 0;\n"
        "wgmma.mma_async.sync.aligned.m64n24k16.f32.bf16.bf16 {%124,%125,%126,%127,%128,%129,%130,%131,%132,%133,%134,%135}, {hYb4,hYb5,hYb6,hYb7}, dbY, 1, 1, 1, 0;\n"
        "wgmma.commit_group.sync.aligned;\n"
        "bra.uni CX;\n"
        "L5Yb:\n"
        "wgmma.fence.sync.aligned;\n"
        "wgmma.mma_async.sync.aligned.m64n32k16.f32.bf16.bf16 {%60,%61,%62,%63,%64,%65,%66,%67,%68,%69,%70,%71,%72,%73,%74,%75}, {hYb0,hYb1,hYb2,hYb3}, dbY, 1, 1, 1, 0;\n"
        "wgmma.mma_async.sync.aligned.m64n32k16.f32.bf16.bf16 {%136,%137,%138,%139,%140,%141,%142,%143,%144,%145,%146,%147,%148,%149,%150,%151}, {hYb4,hYb5,hYb6,hYb7}, dbY, 1, 1, 1, 0;\n"
        "wgmma.commit_group.sync.aligned;\n"
        "bra.uni CX;\n"
        "LEXIT:\n"
        "wgmma.wait_group.sync.aligned 0;\n"
        "}\n"
        : "=f"(acc[0][0][0]), "=f"(acc[0][0][1]), "=f"(acc[0][0][2]), "=f"(acc[0][0][3]),
          "=f"(acc[0][1][0]), "=f"(acc[0][1][1]), "=f"(acc[0][1][2]), "=f"(acc[0][1][3]),
          "=f"(acc[0][2][0]), "=f"(acc[0][2][1]), "=f"(acc[0][2][2]), "=f"(acc[0][2][3]),
          "=f"(acc[0][3][0]), "=f"(acc[0][3][1]), "=f"(acc[0][3][2]), "=f"(acc[0][3][3]),
          "=f"(acc[0][4][0]), "=f"(acc[0][4][1]), "=f"(acc[0][4][2]), "=f"(acc[0][4][3]),
          "=f"(acc[0][5][0]), "=f"(acc[0][5][1]), "=f"(acc[0][5][2]), "=f"(acc[0][5][3]),
          "=f"(acc[0][6][0]), "=f"(acc[0][6][1]), "=f"(acc[0][6][2]), "=f"(acc[0][6][3]),
          "=f"(acc[0][7][0]), "=f"(acc[0][7][1]), "=f"(acc[0][7][2]), "=f"(acc[0][7][3]),
          "=f"(acc[0][8][0]), "=f"(acc[0][8][1]), "=f"(acc[0][8][2]), "=f"(acc[0][8][3]),
          "=f"(acc[0][9][0]), "=f"(acc[0][9][1]), "=f"(acc[0][9][2]), "=f"(acc[0][9][3]),
          "=f"(acc[0][10][0]), "=f"(acc[0][10][1]), "=f"(acc[0][10][2]), "=f"(acc[0][10][3]),
          "=f"(acc[0][11][0]), "=f"(acc[0][11][1]), "=f"(acc[0][11][2]), "=f"(acc[0][11][3]),
          "=f"(acc[0][12][0]), "=f"(acc[0][12][1]), "=f"(acc[0][12][2]), "=f"(acc[0][12][3]),
          "=f"(acc[0][13][0]), "=f"(acc[0][13][1]), "=f"(acc[0][13][2]), "=f"(acc[0][13][3]),
          "=f"(acc[0][14][0]), "=f"(acc[0][14][1]), "=f"(acc[0][14][2]), "=f"(acc[0][14][3]),
          "=f"(acc[0][15][0]), "=f"(acc[0][15][1]), "=f"(acc[0][15][2]), "=f"(acc[0][15][3]),
          "=f"(acc[0][16][0]), "=f"(acc[0][16][1]), "=f"(acc[0][16][2]), "=f"(acc[0][16][3]),
          "=f"(acc[0][17][0]), "=f"(acc[0][17][1]), "=f"(acc[0][17][2]), "=f"(acc[0][17][3]),
          "=f"(acc[0][18][0]), "=f"(acc[0][18][1]), "=f"(acc[0][18][2]), "=f"(acc[0][18][3]),
          "=f"(acc[1][0][0]), "=f"(acc[1][0][1]), "=f"(acc[1][0][2]), "=f"(acc[1][0][3]),
          "=f"(acc[1][1][0]), "=f"(acc[1][1][1]), "=f"(acc[1][1][2]), "=f"(acc[1][1][3]),
          "=f"(acc[1][2][0]), "=f"(acc[1][2][1]), "=f"(acc[1][2][2]), "=f"(acc[1][2][3]),
          "=f"(acc[1][3][0]), "=f"(acc[1][3][1]), "=f"(acc[1][3][2]), "=f"(acc[1][3][3]),
          "=f"(acc[1][4][0]), "=f"(acc[1][4][1]), "=f"(acc[1][4][2]), "=f"(acc[1][4][3]),
          "=f"(acc[1][5][0]), "=f"(acc[1][5][1]), "=f"(acc[1][5][2]), "=f"(acc[1][5][3]),
          "=f"(acc[1][6][0]), "=f"(acc[1][6][1]), "=f"(acc[1][6][2]), "=f"(acc[1][6][3]),
          "=f"(acc[1][7][0]), "=f"(acc[1][7][1]), "=f"(acc[1][7][2]), "=f"(acc[1][7][3]),
          "=f"(acc[1][8][0]), "=f"(acc[1][8][1]), "=f"(acc[1][8][2]), "=f"(acc[1][8][3]),
          "=f"(acc[1][9][0]), "=f"(acc[1][9][1]), "=f"(acc[1][9][2]), "=f"(acc[1][9][3]),
          "=f"(acc[1][10][0]), "=f"(acc[1][10][1]), "=f"(acc[1][10][2]), "=f"(acc[1][10][3]),
          "=f"(acc[1][11][0]), "=f"(acc[1][11][1]), "=f"(acc[1][11][2]), "=f"(acc[1][11][3]),
          "=f"(acc[1][12][0]), "=f"(acc[1][12][1]), "=f"(acc[1][12][2]), "=f"(acc[1][12][3]),
          "=f"(acc[1][13][0]), "=f"(acc[1][13][1]), "=f"(acc[1][13][2]), "=f"(acc[1][13][3]),
          "=f"(acc[1][14][0]), "=f"(acc[1][14][1]), "=f"(acc[1][14][2]), "=f"(acc[1][14][3]),
          "=f"(acc[1][15][0]), "=f"(acc[1][15][1]), "=f"(acc[1][15][2]), "=f"(acc[1][15][3]),
          "=f"(acc[1][16][0]), "=f"(acc[1][16][1]), "=f"(acc[1][16][2]), "=f"(acc[1][16][3]),
          "=f"(acc[1][17][0]), "=f"(acc[1][17][1]), "=f"(acc[1][17][2]), "=f"(acc[1][17][3]),
          "=f"(acc[1][18][0]), "=f"(acc[1][18][1]), "=f"(acc[1][18][2]), "=f"(acc[1][18][3])
        : "r"(xa0), "r"(xa1), "r"(so0), "r"(bar0), "r"(ea0), "r"(d0), "r"(pl0), "r"(lz), "r"(wa[0]), "r"(wa[1]), "r"(wa[2]),
          "r"(wa[3]), "r"(wa[4]), "r"(wa[5]), "r"(wa[6]), "r"(wa[7])
        : "memory");
}
__device__ __forceinline__ void wgmma_out(float (&o)[NJ][4], uint64_t da, uint64_t db, int acc) {
    asm volatile(
        "{\n.reg .pred p;\nsetp.ne.b32 p, %78, 0;\n"
        "wgmma.mma_async.sync.aligned.m64n152k16.f32.bf16.bf16 {%0,%1,%2,%3,%4,%5,%6,%7,%8,%9,%10,%11,%12,%13,%14,%15,%16,%17,%18,%19,%20,%21,%22,%23,%24,%25,%26,%27,%28,%29,%30,%31,%32,%33,%34,%35,%36,%37,%38,%39,%40,%41,%42,%43,%44,%45,%46,%47,%48,%49,%50,%51,%52,%53,%54,%55,%56,%57,%58,%59,%60,%61,%62,%63,%64,%65,%66,%67,%68,%69,%70,%71,%72,%73,%74,%75}, %76, %77, p, 1, 1, 1, 1;\n}"
        : "+f"(o[0][0]), "+f"(o[0][1]), "+f"(o[0][2]), "+f"(o[0][3]),
          "+f"(o[1][0]), "+f"(o[1][1]), "+f"(o[1][2]), "+f"(o[1][3]),
          "+f"(o[2][0]), "+f"(o[2][1]), "+f"(o[2][2]), "+f"(o[2][3]),
          "+f"(o[3][0]), "+f"(o[3][1]), "+f"(o[3][2]), "+f"(o[3][3]),
          "+f"(o[4][0]), "+f"(o[4][1]), "+f"(o[4][2]), "+f"(o[4][3]),
          "+f"(o[5][0]), "+f"(o[5][1]), "+f"(o[5][2]), "+f"(o[5][3]),
          "+f"(o[6][0]), "+f"(o[6][1]), "+f"(o[6][2]), "+f"(o[6][3]),
          "+f"(o[7][0]), "+f"(o[7][1]), "+f"(o[7][2]), "+f"(o[7][3]),
          "+f"(o[8][0]), "+f"(o[8][1]), "+f"(o[8][2]), "+f"(o[8][3]),
          "+f"(o[9][0]), "+f"(o[9][1]), "+f"(o[9][2]), "+f"(o[9][3]),
          "+f"(o[10][0]), "+f"(o[10][1]), "+f"(o[10][2]), "+f"(o[10][3]),
          "+f"(o[11][0]), "+f"(o[11][1]), "+f"(o[11][2]), "+f"(o[11][3]),
          "+f"(o[12][0]), "+f"(o[12][1]), "+f"(o[12][2]), "+f"(o[12][3]),
          "+f"(o[13][0]), "+f"(o[13][1]), "+f"(o[13][2]), "+f"(o[13][3]),
          "+f"(o[14][0]), "+f"(o[14][1]), "+f"(o[14][2]), "+f"(o[14][3]),
          "+f"(o[15][0]), "+f"(o[15][1]), "+f"(o[15][2]), "+f"(o[15][3]),
          "+f"(o[16][0]), "+f"(o[16][1]), "+f"(o[16][2]), "+f"(o[16][3]),
          "+f"(o[17][0]), "+f"(o[17][1]), "+f"(o[17][2]), "+f"(o[17][3]),
          "+f"(o[18][0]), "+f"(o[18][1]), "+f"(o[18][2]), "+f"(o[18][3])
        : "l"(da), "l"(db), "r"(acc));
}

__device__ __forceinline__ void slow_edge(int ee, int s, float* accn, const __nv_bfloat16* __restrict__ x,
                                          const __nv_bfloat16* __restrict__ sh, const __nv_bfloat16* __restrict__ ea,
                                          const __nv_bfloat16* __restrict__ cg, const __nv_bfloat16* __restrict__ wr,
                                          int lane) {
    float rwv[4] = {0.f, 0.f, 0.f, 0.f};
#pragma unroll 4
    for (int d = 0; d < 16; d++) {
        const float a = __bfloat162float(ea[(size_t)ee * 16 + d]);
        const uint2 wv = *(const uint2*)(wr + d * 128 + lane * 4);
        rwv[0] += a * __uint_as_float(wv.x << 16);
        rwv[1] += a * __uint_as_float(wv.x & 0xffff0000u);
        rwv[2] += a * __uint_as_float(wv.y << 16);
        rwv[3] += a * __uint_as_float(wv.y & 0xffff0000u);
    }
    float A = 0.f;
#pragma unroll
    for (int v = 0; v < 4; v++)
        A += __bfloat162float(cg[((lane >> 2) & 3) * 16 + v * 4 + (lane & 3)]) * __bfloat162float(sh[(size_t)ee * 4 + v]);
    float m[4][4];
#pragma unroll
    for (int w = 0; w < 4; w++)
#pragma unroll
        for (int j = 0; j < 4; j++) m[w][j] = 0.f;
#pragma unroll
    for (int u = 0; u < 4; u++) {
        const uint2 xv = *(const uint2*)(x + (size_t)s * 512 + u * 128 + lane * 4);
        const float x0 = __uint_as_float(xv.x << 16), x1 = __uint_as_float(xv.x & 0xffff0000u);
        const float x2 = __uint_as_float(xv.y << 16), x3 = __uint_as_float(xv.y & 0xffff0000u);
#pragma unroll
        for (int w = 0; w < 4; w++) {
            const float a = __shfl_sync(0xffffffffu, A, u * 4 + w);
            m[w][0] += a * x0;
            m[w][1] += a * x1;
            m[w][2] += a * x2;
            m[w][3] += a * x3;
        }
    }
#pragma unroll
    for (int w = 0; w < 4; w++)
#pragma unroll
        for (int j = 0; j < 4; j++) atomicAdd(accn + w * 128 + lane * 4 + j, m[w][j] * rwv[j]);
}

__device__ __forceinline__ void slow_out(const float* accn, const __nv_bfloat16* __restrict__ wout,
                                         __nv_bfloat16* __restrict__ outn, int lane) {
    float o[4][4];
#pragma unroll
    for (int w = 0; w < 4; w++)
#pragma unroll
        for (int j = 0; j < 4; j++) o[w][j] = 0.f;
#pragma unroll 2
    for (int c = 0; c < 128; c++) {
        const uint2 wv = *(const uint2*)(wout + c * 128 + lane * 4);
        const float w0 = __uint_as_float(wv.x << 16), w1 = __uint_as_float(wv.x & 0xffff0000u);
        const float w2 = __uint_as_float(wv.y << 16), w3 = __uint_as_float(wv.y & 0xffff0000u);
#pragma unroll
        for (int w = 0; w < 4; w++) {
            const float a = __bfloat162float(__float2bfloat16(accn[w * 128 + c]));
            o[w][0] += a * w0;
            o[w][1] += a * w1;
            o[w][2] += a * w2;
            o[w][3] += a * w3;
        }
    }
#pragma unroll
    for (int w = 0; w < 4; w++)
        *(uint2*)(outn + w * 128 + lane * 4) = make_uint2(pack_bf16(o[w][0], o[w][1]), pack_bf16(o[w][2], o[w][3]));
}

static_assert(NW > 2 * NP, "barriers");
#define FPOS 1
#define PW 0
#define TWAIT mbar_lean_u
#define PWAIT mbar_lean
#define TMA_ROW(k) "@pl cp.async.bulk.tensor.2d.shared::cluster.global.mbarrier::complete_tx::bytes [d" #k "], [tm, {r" #k ", z" #k "}], [b" #k "];\n"
#define TMA_INIT(k, o) "shfl.sync.idx.b32 z" #k ", %11, " #k ", 31, 0xffffffff;\nadd.u32 m" #k ", %2, " STR(o) ";\nadd.u32 m" #k ", m" #k ", %11;\nshfl.sync.idx.b32 m" #k ", m" #k ", 0, 31, 0xffffffff;\n"
#define TMA_PREP(k) "mad.lo.u32 d" #k ", dd, 512, m" #k ";\nadd.u32 b" #k ", dd, z" #k ";\n"
#define RDCLK(c) "mov.u64 ck, %%clock64;\ncvt.u32.u64 " c ", ck;\n"
#define BCAST(d, k) "selp.b32 " d ", a" #k ", 0, me;\nredux.sync.or.b32 " d ", " d ", 0xffffffff;\n"
#define PTIME(t, x, y, z) "shr.u32 " t ", " x ", 16;\nand.b32 c, " y ", 0xffff;\nadd.u32 " t ", " t ", c;\nmul.lo.u32 " t ", " t ", %9;\nshr.u32 " t ", " t ", 5;\nadd.u32 " t ", " t ", %6;\nmin.u32 " t ", " t ", lim;\nlop3.b32 " t ", " t ", " z ", 7, 0xd8;\n"
#define PROWS(s, x, y) "and.b32 t0, " s ", 0xffc;\nmad.lo.u32 t0, t0, 2, %5;\nld.shared.v2.u32 {" x ", " y "}, [t0];\nshr.u32 t0, " s ", 11;\nand.b32 t0, t0, 6;\nshr.u32 " s ", " s ", 15;\nadd.u32 t0, t0, " s ";\nadd.u32 t0, t0, %13;\nmul.lo.s32 t0, t0, " STR(-NBK * 64) ";\nprmt.b32 t0, t0, 0, 0x1010;\nadd.u16x2 " x ", " x ", t0;\nadd.u16x2 " y ", " y ", t0;\n"
__device__ __forceinline__ void produce(const CUtensorMap* tm, uint32_t bar, uint32_t d0, uint32_t ps, int nit, uint32_t psrc,
                                        uint32_t tbase, uint32_t lim, uint32_t taug64, uint32_t taus, uint32_t n, int lz, int pr0,
                                        int g0
) {
    asm volatile(
        "{\n.reg .pred p, pl, ok, me;\n.reg .b32 a<6>, u<4>, r<8>, d<8>, b<8>, z<8>, m<8>, ps, lim, n, it, pr, pe, tgt, tgu, c, dd, dn, par, t0, t1;\n"
        ".reg .b64 st, tm, ck;\n"
        "elect.sync _|pl, 0xffffffff;\n"
        TMA_INIT(0, 0) TMA_INIT(1, SM_ODD) TMA_INIT(2, 1024) TMA_INIT(3, SM_ODD + 1024)
        TMA_INIT(4, 4096) TMA_INIT(5, SM_ODD + 4096) TMA_INIT(6, 5120) TMA_INIT(7, SM_ODD + 5120)
        "mov.b64 {a0, a1}, %0;\n"
        "add.u32 a0, a0, %11;\n"
        "add.u32 a1, a1, %11;\n"
        "shfl.sync.idx.b32 a0, a0, 0, 31, 0xffffffff;\n"
        "shfl.sync.idx.b32 a1, a1, 0, 31, 0xffffffff;\n"
        "mov.b64 tm, {a0, a1};\n"
        "mov.u32 ps, %3;\n"
        "mov.u32 it, %4;\n"
        "mov.u32 lim, %7;\n"
        "mov.u32 n, %10;\n"
        "mov.u32 pr, %12;\n"
        "setp.le.s32 p, it, 0;\n"
        "bar.sync 0;\n"
        "@p bra.uni PEND;\n"
        "PBAT:\n"
        "ld.shared.u16 c, [ps];\n"
        "ld.shared.u16 t1, [ps+4];\n"
        "add.u32 ps, ps, 256;\n"
        "mul.lo.u32 par, n, " STR(65536 / NP + 1) ";\n"
        "shr.u32 par, par, 16;\n"
        "mad.lo.s32 dn, par, " STR(-NP) ", n;\n"
        "add.u32 n, n, 32;\n"
        "not.b32 par, par;\n"
        PROWS("c", "a0", "a1") PROWS("t1", "a2", "a3")
        "min.s32 pe, it, 32;\n"
        "sub.s32 it, it, 32;\n"
        "add.u32 pe, pe, pr;\n"
        PTIME("a4", "a0", "a1", "dn") PTIME("a5", "a2", "a3", "par")
        "add.u32 lim, lim, %8;\n"
        "PLOOP:\n"
        "setp.eq.u32 me, n, pr;\n"
        "add.u32 pr, pr, 1;\n"
        BCAST("tgt", 4) BCAST("tgu", 5) BCAST("u0", 0) BCAST("u1", 1) BCAST("u2", 2) BCAST("u3", 3)
        "and.b32 dd, tgt, 7;\n"
        "mad.lo.u32 dd, dd, 16, %1;\n"
        "and.b32 par, tgu, 1;\n"
        "mbarrier.test_wait.parity.shared.b64 ok, [dd+8], par;\n"
        "prmt.b32 r0, u0, 0, 0x4104;\nprmt.b32 r1, u0, 0, 0x4324;\nprmt.b32 r2, u1, 0, 0x4104;\nprmt.b32 r3, u1, 0, 0x4324;\n"
        "prmt.b32 r4, u2, 0, 0x4104;\nprmt.b32 r5, u2, 0, 0x4324;\nprmt.b32 r6, u3, 0, 0x4104;\nprmt.b32 r7, u3, 0, 0x4324;\n"
        TMA_PREP(0) TMA_PREP(1) TMA_PREP(2) TMA_PREP(3) TMA_PREP(4) TMA_PREP(5) TMA_PREP(6) TMA_PREP(7)
        RDCLK("c")
        "sub.s32 c, c, tgt;\n"
        "setp.ge.and.s32 p, c, 0, ok;\n"
        "@!p bra.uni PSLP;\n"
        "PRES:\n"
        "@pl mbarrier.arrive.expect_tx.shared.b64 _, [b0], 8192;\n"
        TMA_ROW(0) TMA_ROW(1) TMA_ROW(2) TMA_ROW(3)
        RDCLK("c")
        "sub.s32 c, c, tgu;\n"
        "setp.lt.s32 p, c, 0;\n"
        "@p bra.uni PSL2;\n"
        "PRE2:\n"
        TMA_ROW(4) TMA_ROW(5) TMA_ROW(6) TMA_ROW(7)
        "setp.lt.u32 p, pr, pe;\n"
        "@p bra.uni PLOOP;\n"
        "setp.gt.s32 p, it, 0;\n"
        "@p bra.uni PBAT;\n"
        "bra.uni PEND;\n"
        "PSL2:\n"
        "nanosleep.u32 " STR(PSLEEP) ";\n"
        RDCLK("c")
        "sub.s32 c, c, tgu;\n"
        "setp.lt.s32 p, c, 0;\n"
        "@p bra.uni PSL2;\n"
        "bra.uni PRE2;\n"
        "PSL1:\n"
        "nanosleep.u32 " STR(PSLEEP) ";\n"
        RDCLK("c")
        "sub.s32 c, c, tgt;\n"
        "PSLP:\n"
        "setp.lt.s32 p, c, 0;\n"
        "@p bra.uni PSL1;\n"
        "@ok bra.uni PRES;\n"
        "mov.u32 c, 0;\n"
        "PW:\n"
        "mbarrier.try_wait.parity.shared.b64 p, [b0+8], par;\n"
        "@p bra.uni PRES;\n"
        "add.u32 c, c, 1;\n"
        "setp.lt.u32 p, c, 4000000;\n"
        "@p bra.uni PW;\n"
        "trap;\n"
        "PEND:\n}"
        :
        : "l"(tm), "r"(bar), "r"(d0), "r"(ps), "r"(nit), "r"(psrc), "r"(tbase), "r"(lim), "r"(taug64), "r"(taus), "r"(n), "r"(lz),
          "r"(pr0), "r"(g0)
        : "memory");
}
#define DELAY 2500
#define NULW 0xf0000000
#define DREF 0
#define K0(npr) ((2 * NP - 2 - (npr) % NP) % NP)
#define GCODE(g) ((((g) >> 1) + 1) << 12 | ((g) & 1) << 15)
#define LISTS() asm volatile("bar.sync 0;" ::: "memory")
#define WG_SYNC(w) asm volatile("bar.sync %0, 128;" ::"r"((w) + 1) : "memory")
__global__ void __launch_bounds__(NT, 1)
main_kernel(const int* __restrict__ dst, const int* __restrict__ src, uint4* __restrict__ gbin, int E, int nbins, int fast_ok,
            int npb, unsigned npb_magic, int N, const __grid_constant__ CUtensorMap tme,
            const __grid_constant__ CUtensorMap tmx, const __grid_constant__ CUtensorMap tmw,
            const __grid_constant__ CUtensorMap tmo, const __nv_bfloat16* __restrict__ x,
            const __nv_bfloat16* __restrict__ sh, const __nv_bfloat16* __restrict__ ea,
            const __nv_bfloat16* __restrict__ cg, const __nv_bfloat16* __restrict__ wr,
            const __nv_bfloat16* __restrict__ wout, __nv_bfloat16* __restrict__ out, int tau16, int toff, int delay) {
    extern __shared__ __align__(1024) unsigned char smem[];
    const uint32_t sb = __shfl_sync(0xffffffffu, s2u(smem), 0);
    const int tid = threadIdx.x;
    const int warp = __shfl_sync(0xffffffffu, tid >> 5, 0), lane = tid & 31;
    const int g = lane >> 2, t = lane & 3;

    TLSTAMP(0);
    TLINIT();
    const int bin = blockIdx.x;
    const int node0 = bin * npb, hpb = npb >> 1;
    uint32_t wa[8];
    uint2 c0 = make_uint2(0, 0), c1 = c0;
    bool fast = fast_ok;
    if (fast_ok) {
        int pd[EPS], ps[EPS];
        const int e0 = (warp * nbins + bin) * 32 + lane;
#pragma unroll
        for (int k = 0; k < EPS; k++)
            asm volatile("ld.global.nc.u32 %0, [%1];" : "=r"(pd[k]) : "l"(dst + min(e0 + k * NT * nbins, E - 1)));
#pragma unroll
        for (int k = 0; k < EPS; k++)
            asm volatile("ld.global.nc.u32 %0, [%1];" : "=r"(ps[k]) : "l"(src + min(e0 + k * NT * nbins, E - 1)));
        const unsigned ck0 = clock();
        const uint32_t cnt0 = (sb + SC_CNT + 8191) & ~8191;
        {
            const uint32_t nul = NULW | ((bin & 3) * 8 + (tid & 7)) << 21;
#pragma unroll
            for (int k = 0; k < 4; k++) {
                const int i = tid + k * NT;
                if (i < SC_EXT / 16 ? (tid & 7) != 7 : i < SC_TAB / 16) sts_v4(sb + SC_ENT + i * 16, make_uint4(nul, nul, nul, nul));
            }
            if (warp == NW - 1) {
                uint32_t now;
                asm volatile("mov.u32 %0, %%globaltimer_lo;" : "=r"(now));
                now = __shfl_sync(0xffffffffu, (now & 0x1fffff) | nul, 7);
#pragma unroll
                for (int k = 0; k < MAXBINS / 32; k++) sts_v4(sb + SC_ENT + (k * 32 + lane) * 128 + 112, make_uint4(now, now, now, now));
                if (lane == 0) {
                    asm volatile("prefetch.tensormap [%0];" ::"l"(&tme) : "memory");
                    asm volatile("prefetch.tensormap [%0];" ::"l"(&tmx) : "memory");
                    sts_v2(sb + SM_MISC + MI_INT, 0, now);
                }
            }
            sts_v4(cnt0 + tid * 16, make_uint4(0, 0, 0, 0));
            if (tid < (SC_END - SC_HIST) / 16) {
                const uint32_t v = (tid >> 3) == MAXBINS / 32 ? 0x80000000u : 0;
                sts_v4(sb + SC_HIST + tid * 16, make_uint4(v, v, v, v));
            }
            if (tid < 2 * HPB) {
                const int w = tid >= hpb, loc = tid - (w ? hpb : 0), gr = min(loc * 43 >> 8, NGR - 1);
                sts_u32(sb + SC_TAB + tid * 4, ((w ? NGR : 0) + gr) * (NBK * 64 << 15) + loc - gr * GSZ);
            }
        }
        TLMAX(1);
        __syncthreads();
        {
            const uint32_t z = lds_u32(sb + SM_MISC + MI_INT);
            int pb[EPS], pr[EPS];
            uint32_t v[EPS];
#pragma unroll
            for (int k = 0; k < EPS; k++) {
                pb[k] = (int)__umulhi((unsigned)pd[k], npb_magic + z);
                v[k] = lds_u32(sb + SC_TAB + (pd[k] - pb[k] * npb) * 4);
                pr[k] = atoms_add(sb + SC_HIST + (e0 + k * NT * nbins < E ? pb[k] : MAXBINS + lane) * 4, 4);
            }
            int mx = 0;
#pragma unroll
            for (int k = 0; k < EPS; k++) {
                v[k] += ps[k] * (32768 + z) + (k * NT + tid + 32) * 8;
                asm volatile("{\n.reg .pred p;\nsetp.lt.u32 p, %0, 128;\n@p st.shared.u32 [%1], %2;\n}" ::"r"(pr[k]),
                             "r"(sb + SC_ENT + pb[k] * 128 + pr[k]), "r"(v[k])
                             : "memory");
                mx = max(mx, pr[k]);
            }
            if (mx >= 128) {
#pragma unroll
                for (int k = 0; k < EPS; k++)
                    if (pr[k] >= 128 && pr[k] < 192) sts_u32(sb + SC_EXT - 128 + pb[k] * 64 + pr[k], v[k]);
            }
        }
        FENCE_ASYNC();
        TLMAX(6);
        __syncthreads();
        const unsigned c6 = DREF ? ck0 : clock();
        if (warp == NW - 1 && elect()) {
            tma_store(&tme, sb + SC_ENT, bin * 32, 0);
            asm volatile("cp.async.bulk.commit_group;" ::: "memory");
        }
        if (tid < nbins && lds_u32(sb + SC_HIST + tid * 4) >= 128) {
#pragma unroll 1
            for (int k = 0; k < 4; k++) __stcg(gbin + GEX + (tid * nbins + bin) * 4 + k, lds_v4(sb + SC_EXT + tid * 64 + k * 16));
        }
        uint32_t en[4][4], es[4][4], rank[4][4], ca[4][4];
        uint2 wv;
        asm volatile("ld.global.nc.v2.u32 {%0,%1}, [%2];" : "=r"(wv.x), "=r"(wv.y) : "l"((const uint2*)wr + tid));
        if (warp >= 12 && (g >> 2) == (t >> 1)) {
            const uint2* cp = (const uint2*)cg + (g & 3) * 4 + (t & 1) * 2;
            asm volatile("ld.global.nc.v2.u32 {%0,%1}, [%2];" : "=r"(c0.x), "=r"(c0.y) : "l"(cp));
            asm volatile("ld.global.nc.v2.u32 {%0,%1}, [%2];" : "=r"(c1.x), "=r"(c1.y) : "l"(cp + 1));
        }
        if (elect()) {
#pragma unroll
            for (int k = 0; k < (NP > 5 ? 4 : 2); k++) mbar_init(sb + SM_BAR + (warp * (NP > 5 ? 4 : 2) + k) * 8, 3 + (k & 1));
        }
#pragma unroll
        for (int k = 0; k < TS / 2; k++) sts_v4(sb + SM_BT + (tid + k * NT) * 16, make_uint4(0, 0, 0, 0));
        if (tid < 8) sts_v4(sb + SM_BT + (tid + TS / 2 * NT) * 16, make_uint4(0, 0, 0, 0));
        if (tid < 4) {
            sts_u16(sb + SM_SRC + (LNUL + tid) * 2, N);
            sts_u32(sb + SM_EID + (LNUL + tid) * 4, 0x80000000u);
        }
        FENCE_ASYNC();
        const int sg[4] = {tid >> 3, (tid >> 3) + 64, 128 + (tid >> 4), (tid >> 3) + (lane & 4) * 16};
        const uint4* gp[4];
        gp[0] = gbin + bin * nbins * 8 + tid;
        gp[1] = gp[0] + NT;
        gp[2] = lane & 8 ? gbin + GEX + (bin * nbins + sg[2]) * 4 + (lane & 7) : gbin + (bin * nbins + sg[2]) * 8 + (lane & 7);
        gp[3] = gbin + GEX + (bin * nbins + sg[3]) * 4 + (lane & 3);
        unsigned pend = (sg[0] < nbins) | (sg[1] < nbins) << 1 | (sg[2] < nbins && !(lane & 8)) << 2;
#pragma unroll
        for (int k = 0; k < 4; k++) en[k][0] = en[k][1] = en[k][2] = en[k][3] = NULW | lane << 21;
        auto fetch = [&](int k) {
            asm volatile("{\n.reg .pred p;\nsetp.ne.u32 p, %5, 0;\n@p ld.relaxed.gpu.global.v4.u32 {%0,%1,%2,%3}, [%4];\n}"
                         : "+r"(en[k][0]), "+r"(en[k][1]), "+r"(en[k][2]), "+r"(en[k][3])
                         : "l"(gp[k]), "r"(pend & (1u << k))
                         : "memory");
        };
        int spin = 0;
        auto poll = [&](int k0, int k1) {
            for (;;) {
#pragma unroll
                for (int k = k0; k < k1; k++)
                    if (min(min(en[k][0], en[k][1]), min(en[k][2], en[k][3]))) pend &= ~(1u << k);
                if (!__any_sync(0xffffffffu, pend)) break;
#pragma unroll
                for (int k = k0; k < k1; k++) fetch(k);
                if (++spin > 10000000) __trap();
            }
        };
        auto count = [&](int k) {
#pragma unroll
            for (int c = 0; c < 4; c++) {
                const uint32_t v = en[k][c];
                ca[k][c] = ((v >> 19) & 0x1ffc) | cnt0;
                rank[k][c] = atoms_add(ca[k][c], 1);
                asm volatile("{\n.reg .b32 a, b;\nprmt.b32 a, %1, %2, 0x6540;\nand.b32 b, %1, 0x7f00;\nmad.lo.u32 %0, b, %3, a;\n}"
                             : "=r"(es[k][c])
                             : "r"(v), "r"(sg[k] - nbins), "r"(nbins));
            }
        };
        while ((int)(clock() - c6) < delay) {}
        TLMAX(7);
        fetch(0);
        fetch(1);
        fetch(2);
        poll(0, 3);
        TLMAX(2);
        const bool more = __any_sync(0xffffffffu, (lane & 7) == 7 && min(min(en[0][3], en[1][3]), en[2][3]) < NULW);
        const bool rest = 128 + warp * 2 < nbins;
        if (more) {
            const uint32_t l0 = __shfl_sync(0xffffffffu, en[0][3], lane | 7), l1 = __shfl_sync(0xffffffffu, en[1][3], lane | 7);
            const uint32_t l2 = __shfl_sync(0xffffffffu, en[2][3], (lane & 16) + 7);
            pend = ((lane & 12) == 8 && l2 < NULW) << 2 | ((lane & 4 ? l1 : l0) < NULW) << 3;
            fetch(2);
            fetch(3);
        }
        if (tid == 7 && en[0][3] >= NULW) sts_u32(sb + SM_MISC + MI_INT + 4, en[0][3]);
        count(0);
        count(1);
        if (more) {
            const unsigned ext = pend;
            poll(2, 4);
#pragma unroll
            for (int k = 2; k < 4; k++) {
                if ((ext >> k) & 1) {
                    __stcg((uint4*)gp[k], make_uint4(0, 0, 0, 0));
                    if ((lane & 3) == 3 && en[k][3] < NULW) sts_u32(sb + SM_MISC + MI_INT, 1);
                }
            }
            count(3);
        }
        if (rest) count(2);
        sts_v2(sb + SC_WR + ((tid >> 1) & 15) * 272 + (tid >> 5) * 16 + (tid & 1) * 8, wv.x, wv.y);
        TLMAX(9);
        __syncthreads();
        if (warp < 2 * NGR) {
            const int w = warp >= NGR, gr = warp - w * NGR;
            const uint32_t cp = cnt0 + (warp * NBK + lane * (NBK / 32)) * 4;
            const uint32_t bp = sb + SC_BLK + (w * (NBK + 2) + lane * (NBK / 32)) * 4;
            uint32_t r[NBK / 32 + 1], old[NBK / 32 + 1];
#pragma unroll
            for (int c = 0; c < NBK / 32; c++) r[c + 1] = lds_u32(cp + c * 4);
            r[0] = 0;
#pragma unroll
            for (int c = 1; c < NBK / 32; c++) r[c + 1] += r[c];
            const uint32_t incl = warp_incl_scan(r[NBK / 32], lane), off = incl - r[NBK / 32] + 3 - CE;
            const uint32_t base = warp * GCAP + w * GEXT;
#pragma unroll
            for (int c = 0; c <= NBK / 32; c++) r[c] += off;
#pragma unroll
            for (int c = 0; c < NBK / 32; c++) old[c] = atoms_add(bp + c * 4, (r[c + 1] >> 2) + (r[c] >> 2) * 0x1ffff);
            const bool tailb = (incl & 3) >= 1 && (incl & 3) <= CE;
            if (lane == 31) old[NBK / 32] = atoms_add(bp + NBK / 32 * 4, (r[NBK / 32] >> 2 << 17) + tailb);
            const uint32_t tot = __shfl_sync(0xffffffffu, incl, 31);
            if (tot > GCAP + (gr == NGR - 1 ? GEXT : 0)) {
                sts_u32(sb + SM_MISC + MI_INT, 1);
            } else if (lane < (-tot & 3)) {
                sts_u16(sb + SM_SRC + (base + tot + lane) * 2, N + warp * (NBK * 64));
                sts_u32(sb + SM_EID + (base + tot + lane) * 4, 0x80000000u);
            }
            const uint32_t code = GCODE(gr);
#pragma unroll
            for (int c = 0; c < NBK / 32; c++)
                old[c] = ((old[c] - (r[c] >> 2) + (w * SEQCAP + 1023 - base / 4)) << 17) + r[c] + (base + 1 + code);
            TLMAX(5);
            asm volatile("bar.sync %0, %1;" ::"r"(w + 3), "n"(NGR * 32) : "memory");
#pragma unroll
            for (int c = 0; c < NBK / 32; c++) r[c] = lds_u32(bp + c * 4);
            const uint32_t tw = lds_u32(sb + SC_BLK + (w * (NBK + 2) + NBK) * 4);
#pragma unroll
            for (int c = 0; c < NBK / 32; c++) sts_u32(cp + c * 4, (r[c] & 0xffff0000u) + old[c]);
            const int nst = (tw >> 17) + (tw & 0xffff), npr = (nst + 3) >> 2;
            const uint32_t sq = sb + SM_SEQ + w * SEQCAP * 2;
            if (nst + 32 > SEQCAP) {
                sts_u32(sb + SM_MISC + MI_INT, 1);
            } else {
                if (lane == 31 && tailb) sts_u16(sq + ((tw >> 17) + (old[NBK / 32] & 0xffff)) * 2, ((base + tot + 4) & ~3) | code);
                if (gr == 0) {
                    sts_u16(sq + (nst + lane) * 2, (LNUL + 4) | (lane < (-nst & 3) ? GCODE(0) : 0x7c01));
                    const int k0 = K0(npr);
                    if (lane < k0) {
                        mbar_arrive_cnt(sb + SM_BAR + (w * NP + lane) * 16, 3);
                        mbar_arrive_cnt(sb + SM_BAR + (w * NP + lane) * 16 + 8, 4);
                    }
                    if (lane == 0) sts_v2(sb + SM_MISC + MI_INT + 8 + w * 8, npr, k0);
                }
            }
        } else if (warp == NW - 1 && elect()) {
            asm volatile("cp.async.bulk.global.shared::cta.bulk_group [%0], [%1], %2;" ::"l"(gbin + bin * nbins * 8), "r"(sb + SM_BT),
                         "r"(nbins * 128)
                         : "memory");
            asm volatile("cp.async.bulk.commit_group;" ::: "memory");
            const uint32_t t0 = lds_u32(sb + SM_MISC + MI_INT + 4);
            uint32_t now;
            asm volatile("mov.u32 %0, %%globaltimer_lo;" : "=r"(now));
            sts_u32(sb + SM_MISC + MI_INT + 4, clock() - (min((now - t0) & 0x1fffff, 1u << 16) * 7 >> 2) + toff);
        }
#pragma unroll
        for (int h = 0; h < 2; h++)
            asm volatile("ldmatrix.sync.aligned.m8n8.x4.trans.shared.b16 {%0,%1,%2,%3}, [%4];"
                         : "=r"(wa[h * 4]), "=r"(wa[h * 4 + 1]), "=r"(wa[h * 4 + 2]), "=r"(wa[h * 4 + 3])
                         : "r"(sb + SC_WR + (h * 8 + (warp & 3) * 2 + ((lane >> 3) & 1)) * 272 + (lane >> 4) * 128 + (lane & 7) * 16));
        TLMAX(10);
        __syncthreads();
        auto place = [&](int k) {
#pragma unroll
            for (int c = 0; c < 4; c++) ca[k][c] = lds_u32(ca[k][c]);
#pragma unroll
            for (int c = 0; c < 4; c++) {
                const uint32_t q = ca[k][c] + rank[k][c], p = q & 0xfff;
                asm volatile(
                    "{\n.reg .pred p, q;\n.reg .b32 t;\n.reg .b16 h;\n"
                    "setp.ge.u32 p, %0, " STR(NULW) ";\n"
                    "@!p st.shared.u32 [%1], %2;\n"
                    "shr.u32 t, %0, 15;\ncvt.u16.u32 h, t;\n"
                    "@!p st.shared.u16 [%3], h;\n"
                    "lop3.or.b32 t|q, %5, 3, 0, 0xc0, p;\n"
                    "cvt.u16.u32 h, %5;\n"
                    "@!q st.shared.u16 [%4], h;\n}" ::"r"(en[k][c]),
                    "r"(sb + SM_EID - (4 - CE) * 4 + p * 4), "r"(es[k][c]), "r"(sb + SM_SRC - (4 - CE) * 2 + p * 2),
                    "r"(sb + SM_SEQ - 2048 + (q >> 16) + (p >> 1)), "r"(q)
                    : "memory");
            }
        };
        fast = lds_u32(sb + SM_MISC + MI_INT) == 0;
        if (fast) {
            place(0);
            place(1);
            if (rest) place(2);
            if (more) place(3);
        }
    }
    TLMAX(14);
    asm volatile("cp.async.bulk.wait_group.read 0;" ::: "memory");
    FENCE_ASYNC();
    TLMAX(15);

    if (fast && warp >= 12) {
        asm volatile("setmaxnreg.dec.sync.aligned.u32 %0;" ::"n"(HREG));
        const int w = warp & 1, j = (warp >> 1) & 1;
        const uint2 nk = lds_v2(sb + SM_MISC + MI_INT + 8 + w * 8);
        const int npr = __shfl_sync(0xffffffffu, nk.x, 0), kj = __shfl_sync(0xffffffffu, nk.y, 0) + j;
        const uint32_t bar0 = sb + SM_BAR + w * NP * 16;
        const int blk = (lane >> 4) * 2 + (t >> 1);
        uint32_t fseq = sb + SM_SEQ + w * SEQCAP * 2 + j * 8 + blk * 2;
        const uint32_t feid = sb + SM_EID - 16 + (g & 3) * 4;
        uint32_t pea = sb + SM_EA + w * 4096 + j * 512 + (lane ^ ((lane >> 3) & 1)) * 16;
        const uint32_t psd = sb + SM_SIDE + (warp - 12) * 512 + (lane >> 1) * 16 + (lane & 1) * 4;
        const uint32_t pt = sb + SM_BT + w * (TS * 256) + j * 512 + blk * BT_B + ((lane ^ (lane >> 3)) & 1) * BT_K + (g & 3) * 4;
        const char* gea = (const char*)ea + (lane & 1) * 16;
        uint32_t es, va[2], ta[2], old[2] = {pt, pt}, dea = 2048;
        auto ids = [&]() {
            es = lds_u32(feid + (lds_u16(fseq) & 0xffc) * 4);
            fseq += 16;
        };
        uint32_t wf[4];
        wf[0] = __byte_perm(c0.x, c1.x, 0x5410), wf[1] = __byte_perm(c0.x, c1.x, 0x7632);
        wf[2] = __byte_perm(c0.y, c1.y, 0x5410), wf[3] = __byte_perm(c0.y, c1.y, 0x7632);
        uint32_t vf = bar0 + (kj < NP ? kj : 0) * 16;
        uint32_t pe = kj < NP;
        auto run = [&](auto odd) {
            auto fetch = [&](int i) {
                asm volatile(
                    "{\n.reg .pred p, q;\n.reg .b32 e;\n.reg .b64 a;\n"
                    "setp.lt.s32 p, %0, 0;\n"
                    "and.b32 e, %0, 0x7ffffff8;\n"
                    "mad.wide.u32 a, e, 4, %1;\n"
                    "cp.async.cg.shared.global [%2], [a], 16, p;\n"
                    "}" ::"r"(es), "l"(gea), "r"(pea + i * 1024) : "memory");
                va[i] = psd + (es & 8);
                ta[i] = pt + (es & 7) * 64;
                if (odd.value) {
                    cp_async4(va[i] + i * 256, (const char*)sh + (es & 0x7ffffff8) + (lane & 1) * 4, (int)es >= 0 ? 4 : 0);
                } else {
                    asm volatile(
                        "{\n.reg .pred p;\n.reg .b32 e;\n.reg .b64 a;\n"
                        "setp.lt.s32 p, %0, 0;\n"
                        "and.b32 e, %0, 0x7ffffff0;\n"
                        "mad.wide.u32 a, e, 1, %1;\n"
                        "cp.async.cg.shared.global [%2], [a], 16, p;\n"
                        "}" ::"r"(es), "l"(sh), "r"((psd & ~15) + i * 256) : "memory");
                }
                asm volatile("cp.async.commit_group;" ::: "memory");
                if (i) pea += dea, dea = -dea;
            };
            LISTS();
            ids();
            fetch(0);
            ids();
            fetch(1);
#pragma unroll 1
            for (int m = (npr + 1 - j) >> 1; m > 0;) {
#pragma unroll
                for (int i = 0; i < 2; i++) {
                    asm volatile("cp.async.wait_group 1;" ::: "memory");
                    __syncwarp();
                    const uint32_t v = lds_u32(va[i] + i * 256);
                    ids();
                    float d0[4], d1[4];
                    mma_diag(d0, v, wf[0], wf[1]);
                    mma_diag(d1, v, wf[2], wf[3]);
                    uint32_t vn = vf + 32;
                    if (vn >= bar0 + NP * 16) vn -= NP * 16, pe ^= 1;
                    TWAIT(vn + 8, pe);
#pragma unroll
                    for (int k = 0; k < 4; k++) sts_u32(old[i] + i * 1024 + k * 16, 0);
                    old[i] = ta[i];
                    sts_u32(old[i] + i * 1024, pack_bf16(d0[0], d0[1]));
                    sts_u32(old[i] + i * 1024 + 16, pack_bf16(d0[2], d0[3]));
                    sts_u32(old[i] + i * 1024 + 32, pack_bf16(d1[0], d1[1]));
                    sts_u32(old[i] + i * 1024 + 48, pack_bf16(d1[2], d1[3]));
                    FENCE_ASYNC();
                    fetch(i);
                    __syncwarp();
                    if (lane == 0) mbar_arrive(vf);
                    vf = vn;
                    if (--m <= 0) break;
                }
            }
        };
        if (E & 1) run(std::true_type()); else run(std::false_type());
        asm volatile("cp.async.wait_group 0;" ::: "memory");
        TLMAX(13);
    } else if (fast && warp >= 8) {
        asm volatile("setmaxnreg.dec.sync.aligned.u32 %0;" ::"n"(PREG));
        const int w = warp & 1, j = (warp >> 1) & 1;
        const uint2 nk = lds_v2(sb + SM_MISC + MI_INT + 8 + w * 8);
        const int npr = __shfl_sync(0xffffffffu, nk.x, 0), k0 = __shfl_sync(0xffffffffu, nk.y, 0);
        const uint32_t bar0 = sb + SM_BAR + w * NP * 16, ring = sb + w * RING_BYTES + j * 4096;
        const uint32_t pseq = sb + SM_SEQ + w * SEQCAP * 2 + j * 2;
        const unsigned tbase = lds_u32(sb + SM_MISC + MI_INT + 4);
        const unsigned taug = __float2uint_rz(__fdividef((float)(N * tau16 >> 4), (float)max(npr, 1)));
        produce(&tmx, bar0, ring - j * 2048 - bar0 * 512, pseq + lane * 8, npr, sb + SM_SRC - 8, tbase,
                tbase + (N * tau16 >> 8) + lane * taug, taug * 32, tau16, k0 + lane, lane & (E >> 31), k0 + 32, w * NGR - 2
        );
        if (elect()) {
            const uint32_t d = ring + (NP - 2) * 8192 + j * 4096;
            const uint32_t fb = bar0 + (NP - 2 + j) * 16, par = ~((lds_u32(sb + SM_MISC + MI_INT + 8 + w * 8) + 1) / NP) & 1;
            mbar_wait(fb + 8, par);
            mbar_arrive_cnt(j ? bar0 + DUMB : fb, j ? 1 : 3);
            mbar_expect_tx(bar0 + DUMB, 16384);
            tma_2d(d + SM_EVEN, &tmw, bar0 + DUMB, j * 64, 0);
            tma_2d(d + SM_ODD, &tmw, bar0 + DUMB, j * 64, 64);
        }
        TLMAX(12);
    } else if (fast) {
        const int w = warp >> 2, wq = warp & 3;
        LISTS();
        asm volatile("setmaxnreg.inc.sync.aligned.u32 %0;" ::"n"(CREG));
        const int k0 = __shfl_sync(0xffffffffu, lds_u32(sb + SM_MISC + MI_INT + 12 + w * 8), 0);
        const uint32_t ring = sb + w * RING_BYTES, bar0 = sb + SM_BAR + w * NP * 16;
        float acc[2][NJ][4];
        {
            const int e = (lane >> 1) & 3, m = lane >> 3;
            const int line = 2 * ((lane & 1) + 2 * ((m >> 1) ^ (e >> 1))), ch = 2 * wq + (m & 1);
            const uint32_t xb = ring + (e & 1 ? SM_ODD : SM_EVEN) + (e >> 1) * 1024 + line * 128;
            consume(acc, xb + ((ch ^ ((line + (e & 1)) & 7)) * 16), xb + 128 + ((ch ^ ((line + 1 + (e & 1)) & 7)) * 16),
                    k0 * 8192, bar0, (((sb + SM_EA + w * 4096) & 0x3ffff) >> 4) | (1 << 16),
                    (((sb + SM_BT + w * (TS * 256)) & 0x3ffff) >> 4) | (BT_K / 16 << 16), sb + SM_SEQ + w * SEQCAP * 2, lane & (E >> 31),
                    wa);
        }
        TLMAX(11);
        WG_SYNC(w);
#pragma unroll
        for (int h = 0; h < 2; h++) {
            const uint32_t tb = ring + (h ? SM_ODD : SM_EVEN) + wq * (NJ * 256) + lane * 16;
#pragma unroll
            for (int j = 0; j + 1 < NJ; j += 2)
                stsm4(tb + j * 256, pack_bf16(acc[h][j][0], acc[h][j][1]), pack_bf16(acc[h][j][2], acc[h][j][3]),
                      pack_bf16(acc[h][j + 1][0], acc[h][j + 1][1]), pack_bf16(acc[h][j + 1][2], acc[h][j + 1][3]));
            if (NJ & 1)
                stsm2(tb + (NJ - 1) * 256, pack_bf16(acc[h][NJ - 1][0], acc[h][NJ - 1][1]),
                      pack_bf16(acc[h][NJ - 1][2], acc[h][NJ - 1][3]));
        }
        FENCE_ASYNC();
        WG_SYNC(w);
        mbar_wait_u(bar0 + DUMB, 0);
        float o[2][NJ][4];
        asm volatile("wgmma.fence.sync.aligned;" ::: "memory");
#pragma unroll
        for (int hh = 0; hh < 2; hh++) {
#pragma unroll
            for (int ks = 0; ks < 8; ks++) {
                const uint32_t rg = ks >> 2 ? SM_ODD : SM_EVEN;
                const uint64_t da = (uint64_t)(((ring + rg + (NP - 2 + hh) * 8192 + (ks & 3) * 2048) & 0x3ffff) >> 4) |
                                    (64ull << 32) | (1ull << 62);
                const uint64_t db = (uint64_t)(((ring + rg + (ks & 3) * (NJ * 256)) & 0x3ffff) >> 4) | (8ull << 16) | (16ull << 32);
                wgmma_out(o[hh], da, db, ks);
            }
            asm volatile("wgmma.commit_group.sync.aligned;" ::: "memory");
        }
        const int nb = 2 * hpb;
#pragma unroll
        for (int hh = 0; hh < 2; hh++) {
            if (hh == 0) {
                asm volatile("wgmma.wait_group.sync.aligned 1;" ::: "memory");
            } else {
                asm volatile("wgmma.wait_group.sync.aligned 0;" ::: "memory");
            }
            WG_SYNC(w);
#pragma unroll
            for (int j = 0; j < NJ; j++)
#pragma unroll
                for (int k = 0; k < 4; k++) asm volatile("" : "+f"(o[hh][j][k])::"memory");
            const uint32_t b0 = ring + SM_EVEN + (hh ? 0 : 20480);
            const uint32_t b1 = hh ? b0 : ring + SM_ODD + 20480 + 896 - (nb * 128 & ~1023);
            const int r = (lane & 7) + (lane >> 4) * 8;
            const uint32_t co = r * 128 + (((2 * wq + ((lane >> 3) & 1)) ^ (lane & 7)) * 16);
#pragma unroll
            for (int j = 0; j + 1 < NJ; j += 2)
                stsm4t((8 * j + r < nb ? b0 : b1) + co + j * 1024, pack_bf16(o[hh][j][0], o[hh][j][1]),
                       pack_bf16(o[hh][j][2], o[hh][j][3]), pack_bf16(o[hh][j + 1][0], o[hh][j + 1][1]),
                       pack_bf16(o[hh][j + 1][2], o[hh][j + 1][3]));
            if (NJ & 1)
                stsm2t(b1 + co + (NJ - 1) * 1024, pack_bf16(o[hh][NJ - 1][0], o[hh][NJ - 1][1]),
                       pack_bf16(o[hh][NJ - 1][2], o[hh][NJ - 1][3]));
            FENCE_ASYNC();
            WG_SYNC(w);
            if (wq < 2 && elect()) {
                const int row = (node0 + w * hpb) * 4 + wq * nb;
                if (row < N * 4) tma_store(&tmo, wq ? b1 + nb * 128 : b0, hh * 64, row);
                asm volatile("cp.async.bulk.commit_group;" ::: "memory");
                if (hh) asm volatile("cp.async.bulk.wait_group.read 0;" ::: "memory");
            }
        }
    } else {
        float* accs = (float*)smem;
        constexpr int NACC = SM_EID / 2048;
        const int nnodes = max(0, min(npb, N - node0));
#pragma unroll 1
        for (int nb = 0; nb < nnodes; nb += NACC) {
            __syncthreads();
            for (int i = tid; i < NACC * 512; i += NT) accs[i] = 0.f;
            __syncthreads();
#pragma unroll 1
            for (int base = warp * 32; base < E; base += NT) {
                const int e = base + lane;
                int dl = e < E ? dst[e] - node0 - nb : -1;
                if (dl + nb >= nnodes) dl = -1;
                unsigned mask = __ballot_sync(0xffffffffu, dl >= 0 && dl < NACC);
#pragma unroll 1
                while (mask) {
                    const int l = __ffs(mask) - 1;
                    mask &= mask - 1;
                    const int ee = __shfl_sync(0xffffffffu, e, l);
                    const int dd = __shfl_sync(0xffffffffu, dl, l);
                    slow_edge(ee, src[ee], accs + dd * 512, x, sh, ea, cg, wr, lane);
                }
            }
            __syncthreads();
#pragma unroll 1
            for (int nl = warp; nl < NACC && nb + nl < nnodes; nl += NW)
                slow_out(accs + nl * 512, wout, out + (size_t)(node0 + nb + nl) * 512, lane);
        }
        __syncthreads();
    }

    TLMAX(4);
    TLEND();
}

typedef CUresult (*EncodeTiledFn)(CUtensorMap*, CUtensorMapDataType, cuuint32_t, void*, const cuuint64_t*,
                                  const cuuint64_t*, const cuuint32_t*, const cuuint32_t*, CUtensorMapInterleave,
                                  CUtensorMapSwizzle, CUtensorMapL2promotion, CUtensorMapFloatOOBfill);

extern "C" void kernel_launch(void* const* d_in, const int* in_sizes, int n_in, void* d_out, int out_size) {
    const __nv_bfloat16* x = (const __nv_bfloat16*)d_in[0];
    const int* src = (const int*)d_in[1];
    const int* dst = (const int*)d_in[2];
    const __nv_bfloat16* sh = (const __nv_bfloat16*)d_in[3];
    const __nv_bfloat16* ea = (const __nv_bfloat16*)d_in[4];
    const __nv_bfloat16* cg = (const __nv_bfloat16*)d_in[5];
    const __nv_bfloat16* wr = (const __nv_bfloat16*)d_in[6];
    const __nv_bfloat16* wout = (const __nv_bfloat16*)d_in[7];
    __nv_bfloat16* out = (__nv_bfloat16*)d_out;
    const int N = in_sizes[0] / 512;
    const int E = in_sizes[1];

    static int num_sms = 0;
    static EncodeTiledFn encode = nullptr;
    static uint4* gbin = nullptr;
    if (num_sms == 0) {
        int dev = 0;
        cudaGetDevice(&dev);
        cudaDeviceGetAttribute(&num_sms, cudaDevAttrMultiProcessorCount, dev);
        cudaFuncSetAttribute(main_kernel, cudaFuncAttributeMaxDynamicSharedMemorySize, SM_TOTAL + TLX);
        cudaGetSymbolAddress((void**)&gbin, g_bin);
        void* fn = nullptr;
        cudaDriverEntryPointQueryResult qr;
        cudaGetDriverEntryPoint("cuTensorMapEncodeTiled", &fn, cudaEnableDefault, &qr);
        encode = (EncodeTiledFn)fn;
    }
    const int nbins = num_sms < MAXBINS ? num_sms : MAXBINS;
    int npb = ((N + nbins - 1) / nbins + 1) & ~1;
    if (npb < 32) npb = 32;
    const int fast_ok = E > 0 && npb <= 2 * HPB && N <= NBK * 64 && E <= EPS * NT * nbins;
    auto map2d = [&](CUtensorMap* tm, const void* p, int d0, int d1, int b1) {
        const cuuint64_t gd[2] = {(cuuint64_t)d0, (cuuint64_t)d1};
        const cuuint64_t gs[1] = {(cuuint64_t)d0 * 2};
        const cuuint32_t bx[2] = {64, (cuuint32_t)b1};
        const cuuint32_t es[2] = {1, 1};
        encode(tm, CU_TENSOR_MAP_DATA_TYPE_BFLOAT16, 2, (void*)p, gd, gs, bx, es, CU_TENSOR_MAP_INTERLEAVE_NONE,
               CU_TENSOR_MAP_SWIZZLE_128B, CU_TENSOR_MAP_L2_PROMOTION_NONE, CU_TENSOR_MAP_FLOAT_OOB_FILL_NONE);
    };
    CUtensorMap tme, tmx, tmw, tmo;
    {
        const cuuint64_t gd[2] = {(cuuint64_t)nbins * 32, (cuuint64_t)nbins};
        const cuuint64_t gs[1] = {(cuuint64_t)nbins * 128};
        const cuuint32_t bx[2] = {32, (cuuint32_t)nbins};
        const cuuint32_t es[2] = {1, 1};
        encode(&tme, CU_TENSOR_MAP_DATA_TYPE_UINT32, 2, (void*)gbin, gd, gs, bx, es, CU_TENSOR_MAP_INTERLEAVE_NONE,
               CU_TENSOR_MAP_SWIZZLE_NONE, CU_TENSOR_MAP_L2_PROMOTION_NONE, CU_TENSOR_MAP_FLOAT_OOB_FILL_NONE);
    }
    {
        const cuuint64_t gd[2] = {(cuuint64_t)N * 256 - 224, 8};
        const cuuint64_t gs[1] = {128};
        const cuuint32_t bx[2] = {32, 8};
        const cuuint32_t es[2] = {1, 1};
        encode(&tmx, CU_TENSOR_MAP_DATA_TYPE_UINT32, 2, (void*)x, gd, gs, bx, es, CU_TENSOR_MAP_INTERLEAVE_NONE,
               CU_TENSOR_MAP_SWIZZLE_128B, CU_TENSOR_MAP_L2_PROMOTION_NONE, CU_TENSOR_MAP_FLOAT_OOB_FILL_NONE);
    }
    map2d(&tmw, wout, 128, 128, 64);
    map2d(&tmo, out, 128, N * 4, fast_ok ? npb : 2);
    const unsigned npb_magic = (unsigned)((0x100000000ull + npb - 1) / npb);
    const int chunk = (E + nbins - 1) / nbins;
    int tau16 = (int)fmin((double)PACE * 16.0 * chunk / N, 100000.0), toff = TOFF, delay = DELAY;
    main_kernel<<<nbins, NT, SM_TOTAL + TLX, cudaStreamPerThread>>>(dst, src, gbin, E, nbins, fast_ok, npb, npb_magic, N, tme, tmx, tmw,
                                                              tmo, x, sh, ea, cg, wr, wout, out, tau16, toff, delay);
}
```

```cpp
#include <cuda_runtime.h>
#include <cuda.h>
#include <cuda_bf16.h>
#include <stdint.h>
#include <stdlib.h>
#include <type_traits>

#define MAXBINS 160
#define NW 16
#define NT (NW * 32)
#define HPB 38
#define GCAP 280
#define GEXT 72
#define NGR 6
#define LNUL (2 * (NGR * GCAP + GEXT))
#define NBK 160
#define CE 2
#define GSZ 6
#define NS 10
#define RING_BYTES 40960
static_assert(RING_BYTES == NS * 4096, "ring");
#define NP (NS / 2)
#define CREG 224
#define PREG 24
#define HREG 40
#define TS 8
#define SM_EVEN 0
#define SM_MISC (2 * RING_BYTES)
#define SM_ODD (SM_MISC + 128)
#define SM_EA (SM_BT + TS * 4096 + 128)
#define SM_BT (SM_ODD + 2 * RING_BYTES)
#define BT_B (TS * 512 + 16)
#define BT_K (4 * BT_B)
#define SM_SIDE (SM_EA + 8192)
#define SM_EID (SM_SIDE + 2048)
#define SM_SRC (SM_EID + (LNUL + 4) * 4)
#define SEQCAP 408
#define SM_SEQ (SM_SRC + (LNUL + 8) * 2)
#define SM_BAR ((SM_SEQ + 2 * SEQCAP * 2 + 63) / 64 * 64)
#define SM_TOTAL (SM_BAR + NW * (NP > 5 ? 32 : 16))
#define DUMB (2 * NP * 16)
#define MI_INT 0
#define EPS 5
#define SC_ENT 0
#define SC_EXT (SC_ENT + MAXBINS * 128)
#define SC_TAB (SC_EXT + MAXBINS * 64)
#define SC_HIST (SC_TAB + 320)
#define SC_BLK (SC_HIST + MAXBINS * 4 + 128)
#define SC_END (SC_BLK + 2 * (NBK + 2) * 4)
#define SC_WR SC_END
#define SC_CNT (SC_WR + 4352)
static_assert(SC_END % 16 == 0 && SC_HIST % 16 == 0 && SC_END - SC_HIST <= NT * 16 && SC_CNT + 16384 <= SM_MISC && SC_TAB <= 4 * NT * 16 && 2 * HPB <= 80 && MAXBINS <= 128 + 2 * NW, "scratch");
static_assert(LNUL >= 3072 && LNUL + 8 <= 4096 && GCAP % 4 == 0 && GEXT % 4 == 0, "lists");
static_assert(SM_TOTAL <= 232448 && SM_BAR % 16 == 0 && SM_SEQ % 16 == 0 && SM_SRC % 16 == 0 && SM_EA % 256 == 0, "smem");
#define PACE 18.6
#define PACE2 96
#define BRK 85
#define TOFF 9700
#define PSLEEP 20

#define GEX (MAXBINS * MAXBINS * 8)
__device__ __align__(128) uint4 g_bin[GEX + GEX / 2];
#define STR2(x) #x
#define STR(x) STR2(x)
#define TLINIT()
#define TLEND()
#define TLX 0
#define TLSTAMP(i)
#define TLMAX(i)

__device__ __forceinline__ uint32_t pack_bf16(float lo, float hi) {
    uint32_t r;
    asm("cvt.rn.bf16x2.f32 %0, %1, %2;" : "=r"(r) : "f"(hi), "f"(lo));
    return r;
}
__device__ __forceinline__ void mma1688_z(float (&d)[4], uint32_t a0, uint32_t a1, uint32_t b0) {
    asm("mma.sync.aligned.m16n8k8.row.col.f32.bf16.bf16.f32 {%0,%1,%2,%3}, {%4,%5}, {%6}, {%7,%7,%7,%7};"
        : "=f"(d[0]), "=f"(d[1]), "=f"(d[2]), "=f"(d[3])
        : "r"(a0), "r"(a1), "r"(b0), "f"(0.f));
}
__device__ __forceinline__ void mma_diag(float (&d)[4], uint32_t a, uint32_t b0, uint32_t b1) {
    asm("mma.sync.aligned.m16n8k16.row.col.f32.bf16.bf16.f32 {%0,%1,%2,%3}, {%4,%8,%8,%4}, {%5,%6}, {%7,%7,%7,%7};"
        : "=f"(d[0]), "=f"(d[1]), "=f"(d[2]), "=f"(d[3])
        : "r"(a), "r"(b0), "r"(b1), "f"(0.f), "r"(0));
}
__device__ __forceinline__ uint32_t s2u(const void* p) { return (uint32_t)__cvta_generic_to_shared(p); }
__device__ __forceinline__ void mbar_init(uint32_t a, int c) {
    asm volatile("mbarrier.init.shared.b64 [%0], %1;" ::"r"(a), "r"(c));
}
__device__ __forceinline__ void mbar_expect_tx(uint32_t a, int bytes) {
    asm volatile("mbarrier.arrive.expect_tx.shared.b64 _, [%0], %1;" ::"r"(a), "r"(bytes) : "memory");
}
__device__ __forceinline__ void mbar_arrive(uint32_t a) {
    asm volatile("mbarrier.arrive.shared.b64 _, [%0];" ::"r"(a) : "memory");
}
__device__ __forceinline__ void mbar_arrive_cnt(uint32_t a, int c) {
    asm volatile("mbarrier.arrive.shared.b64 _, [%0], %1;" ::"r"(a), "r"(c) : "memory");
}
__device__ __forceinline__ void mbar_wait(uint32_t a, int parity) {
    asm volatile(
        "{\n.reg .pred p;\n.reg .u32 c;\n"
        "mov.u32 c, 0;\n"
        "LAB_WAIT:\n"
        "mbarrier.try_wait.parity.shared.b64 p, [%0], %1, 2000;\n"
        "@p bra DONE;\n"
        "add.u32 c, c, 1;\n"
        "setp.lt.u32 p, c, 2000000;\n"
        "@p bra LAB_WAIT;\n"
        "trap;\n"
        "DONE:\n}" ::"r"(a),
        "r"(parity)
        : "memory");
}
__device__ __forceinline__ void mbar_wait_u(uint32_t a, int parity) {
    asm volatile(
        "{\n.reg .pred p;\n.reg .u32 c;\n"
        "mov.u32 c, 0;\n"
        "LAB_WAIT:\n"
        "mbarrier.try_wait.parity.shared.b64 p, [%0], %1, 2000;\n"
        "@p bra.uni DONE;\n"
        "add.u32 c, c, 1;\n"
        "setp.lt.u32 p, c, 2000000;\n"
        "@p bra.uni LAB_WAIT;\n"
        "trap;\n"
        "DONE:\n}" ::"r"(a),
        "r"(parity)
        : "memory");
}
__device__ __forceinline__ void mbar_spin_u(uint32_t a, int parity) {
    asm volatile(
        "{\n.reg .pred p;\n.reg .u32 c;\n"
        "mov.u32 c, 0;\n"
        "LAB_WAIT:\n"
        "mbarrier.test_wait.parity.shared.b64 p, [%0], %1;\n"
        "@p bra.uni DONE;\n"
        "add.u32 c, c, 1;\n"
        "setp.lt.u32 p, c, 20000000;\n"
        "@p bra.uni LAB_WAIT;\n"
        "trap;\n"
        "DONE:\n}" ::"r"(a),
        "r"(parity)
        : "memory");
}
__device__ __forceinline__ void mbar_lean(uint32_t a, int parity) {
    asm volatile(
        "{\n.reg .pred p;\n.reg .u32 c;\n"
        "mov.u32 c, 0;\n"
        "LAB_WAIT:\n"
        "mbarrier.try_wait.parity.shared.b64 p, [%0], %1;\n"
        "@p bra DONE;\n"
        "add.u32 c, c, 1;\n"
        "setp.lt.u32 p, c, 4000000;\n"
        "@p bra LAB_WAIT;\n"
        "trap;\n"
        "DONE:\n}" ::"r"(a),
        "r"(parity)
        : "memory");
}
__device__ __forceinline__ void mbar_lean_u(uint32_t a, int parity) {
    asm volatile(
        "{\n.reg .pred p;\n.reg .u32 c;\n"
        "mov.u32 c, 0;\n"
        "LAB_WAIT:\n"
        "mbarrier.try_wait.parity.shared.b64 p, [%0], %1;\n"
        "@p bra.uni DONE;\n"
        "add.u32 c, c, 1;\n"
        "setp.lt.u32 p, c, 4000000;\n"
        "@p bra.uni LAB_WAIT;\n"
        "trap;\n"
        "DONE:\n}" ::"r"(a),
        "r"(parity)
        : "memory");
}
__device__ __forceinline__ bool mbar_test(uint32_t a, int parity) {
    uint32_t p;
    asm volatile("{\n.reg .pred P;\nmbarrier.test_wait.parity.shared.b64 P, [%1], %2;\nselp.u32 %0, 1, 0, P;\n}"
                 : "=r"(p)
                 : "r"(a), "r"(parity)
                 : "memory");
    return p;
}
__device__ __forceinline__ bool elect() {
    uint32_t p;
    asm volatile("{\n.reg .pred P;\nelect.sync _|P, 0xffffffff;\nselp.u32 %0, 1, 0, P;\n}" : "=r"(p));
    return p;
}
__device__ __forceinline__ void tma_2d(uint32_t dst, const CUtensorMap* tm, uint32_t bar, int c0, int c1) {
    asm volatile(
        "cp.async.bulk.tensor.2d.shared::cluster.global.mbarrier::complete_tx::bytes [%0], [%1, {%3, %4}], [%2];" ::"r"(dst),
        "l"(tm), "r"(bar), "r"(c0), "r"(c1)
        : "memory");
}
__device__ __forceinline__ void tma_row(uint32_t dst, const CUtensorMap* tm, uint32_t bar, int row8) {
    tma_2d(dst, tm, bar, 0, row8);
}
__device__ __forceinline__ void tma_store(const CUtensorMap* tm, uint32_t src, int c0, int c1) {
    asm volatile("cp.async.bulk.tensor.2d.global.shared::cta.bulk_group [%0, {%2, %3}], [%1];" ::"l"(tm), "r"(src),
                 "r"(c0), "r"(c1)
                 : "memory");
}
__device__ __forceinline__ uint2 lds_v2(uint32_t a) {
    uint2 v;
    asm volatile("ld.shared.v2.u32 {%0,%1}, [%2];" : "=r"(v.x), "=r"(v.y) : "r"(a));
    return v;
}
__device__ __forceinline__ uint4 lds_v4(uint32_t a) {
    uint4 v;
    asm volatile("ld.shared.v4.u32 {%0,%1,%2,%3}, [%4];" : "=r"(v.x), "=r"(v.y), "=r"(v.z), "=r"(v.w) : "r"(a));
    return v;
}
__device__ __forceinline__ uint32_t lds_u32(uint32_t a) {
    uint32_t v;
    asm volatile("ld.shared.u32 %0, [%1];" : "=r"(v) : "r"(a));
    return v;
}
__device__ __forceinline__ uint32_t lds_u16(uint32_t a) {
    uint32_t v;
    asm volatile("ld.shared.u16 %0, [%1];" : "=r"(v) : "r"(a));
    return v;
}
__device__ __forceinline__ void sts_v2(uint32_t a, uint32_t x, uint32_t y) {
    asm volatile("st.shared.v2.u32 [%0], {%1,%2};" ::"r"(a), "r"(x), "r"(y) : "memory");
}
__device__ __forceinline__ void sts_v4(uint32_t a, uint4 v) {
    asm volatile("st.shared.v4.u32 [%0], {%1,%2,%3,%4};" ::"r"(a), "r"(v.x), "r"(v.y), "r"(v.z), "r"(v.w) : "memory");
}
__device__ __forceinline__ void stsm4(uint32_t a, uint32_t r0, uint32_t r1, uint32_t r2, uint32_t r3) {
    asm volatile("stmatrix.sync.aligned.m8n8.x4.shared.b16 [%0], {%1,%2,%3,%4};" ::"r"(a), "r"(r0), "r"(r1), "r"(r2), "r"(r3)
                 : "memory");
}
__device__ __forceinline__ void stsm2(uint32_t a, uint32_t r0, uint32_t r1) {
    asm volatile("stmatrix.sync.aligned.m8n8.x2.shared.b16 [%0], {%1,%2};" ::"r"(a), "r"(r0), "r"(r1) : "memory");
}
__device__ __forceinline__ void stsm4t(uint32_t a, uint32_t r0, uint32_t r1, uint32_t r2, uint32_t r3) {
    asm volatile("stmatrix.sync.aligned.m8n8.x4.trans.shared.b16 [%0], {%1,%2,%3,%4};" ::"r"(a), "r"(r0), "r"(r1), "r"(r2),
                 "r"(r3)
                 : "memory");
}
__device__ __forceinline__ void stsm2t(uint32_t a, uint32_t r0, uint32_t r1) {
    asm volatile("stmatrix.sync.aligned.m8n8.x2.trans.shared.b16 [%0], {%1,%2};" ::"r"(a), "r"(r0), "r"(r1) : "memory");
}
__device__ __forceinline__ void cp_async16(uint32_t d, const void* s, int n) {
    asm volatile("cp.async.cg.shared.global [%0], [%1], 16, %2;" ::"r"(d), "l"(s), "r"(n) : "memory");
}
__device__ __forceinline__ void cp_async4(uint32_t d, const void* s, int n) {
    asm volatile("cp.async.ca.shared.global [%0], [%1], 4, %2;" ::"r"(d), "l"(s), "r"(n) : "memory");
}
__device__ __forceinline__ void sts_u32(uint32_t a, uint32_t x) {
    asm volatile("st.shared.u32 [%0], %1;" ::"r"(a), "r"(x) : "memory");
}
#define FENCE_ASYNC() asm volatile("fence.proxy.async.shared::cta;" ::: "memory")
__device__ __forceinline__ int warp_incl_scan(int v, int lane) {
#pragma unroll
    for (int o = 1; o < 32; o <<= 1) {
        const int y = __shfl_up_sync(0xffffffffu, v, o);
        if (lane >= o) v += y;
    }
    return v;
}

__device__ __forceinline__ uint32_t atoms_add(uint32_t a, uint32_t v) {
    uint32_t r;
    asm volatile("atom.shared.add.u32 %0, [%1], %2;" : "=r"(r) : "r"(a), "r"(v) : "memory");
    return r;
}
__device__ __forceinline__ void sts_u16(uint32_t a, uint32_t x) {
    asm volatile("{\n.reg .b16 h;\ncvt.u16.u32 h, %1;\nst.shared.u16 [%0], h;\n}" ::"r"(a), "r"(x) : "memory");
}
#define NJ 19
__device__ __forceinline__ void consume(float (&acc)[2][NJ][4], uint32_t xa0, uint32_t xa1, uint32_t so0, uint32_t bar0,
                                        uint32_t ea0, uint32_t d0, uint32_t pl0, int lz, const uint32_t (&wa)[8]) {
    asm volatile(
        "{\n"
        ".reg .pred p, pf, plead, pok, t0, t1, t2, u0, u1, u2;\n"
        ".reg .b32 ca, cb, cz, rbar;\n"
        "mov.b32 cz, 0;\n"
        "mov.b32 ca, 0x20002000;\n"
        "mov.b32 cb, 0x30003000;\n"
        ".reg .b32 cnt, so, q, qe, bar, nbar, pl, ctl, ctm, ix, iy, dl, v0, v1, v2, v3, pp;\n"
        ".reg .b16 sl, sh;\n"
        ".reg .b32 hXa0, hXa1, hXa2, hXa3, hXa4, hXa5, hXa6, hXa7, hXb0, hXb1, hXb2, hXb3, hXb4, hXb5, hXb6, hXb7, hYa0, hYa1, hYa2, hYa3, hYa4, hYa5, hYa6, hYa7, hYb0, hYb1, hYb2, hYb3, hYb4, hYb5, hYb6, hYb7, hLa0, hLa1, hLa2, hLa3, hLa4, hLa5, hLa6, hLa7, hLb0, hLb1, hLb2, hLb3, hLb4, hLb5, hLb6, hLb7;\n"
        ".reg .b32 pX0, pX1, pX2, pX3, pY0, pY1, pY2, pY3;\n"
        ".reg .f32 r0, r1, r2, r3, r4, r5, r6, r7, r8, r9, r10, r11, r12, r13, r14, r15;\n"
        ".reg .b64 daX, dbX, daY, dbY, de0, de1;\n"
        ".reg .b32 dh<6>, eb0, par, npar, wa<8>, uz, bend;\n"
        "add.u32 wa0, %160, %159;\n"
        "add.u32 wa1, %161, %159;\n"
        "add.u32 wa2, %162, %159;\n"
        "add.u32 wa3, %163, %159;\n"
        "add.u32 wa4, %164, %159;\n"
        "add.u32 wa5, %165, %159;\n"
        "add.u32 wa6, %166, %159;\n"
        "add.u32 wa7, %167, %159;\n"
        "mov.f32 %0, 0f00000000;\n"
        "mov.f32 %1, 0f00000000;\n"
        "mov.f32 %2, 0f00000000;\n"
        "mov.f32 %3, 0f00000000;\n"
        "mov.f32 %4, 0f00000000;\n"
        "mov.f32 %5, 0f00000000;\n"
        "mov.f32 %6, 0f00000000;\n"
        "mov.f32 %7, 0f00000000;\n"
        "mov.f32 %8, 0f00000000;\n"
        "mov.f32 %9, 0f00000000;\n"
        "mov.f32 %10, 0f00000000;\n"
        "mov.f32 %11, 0f00000000;\n"
        "mov.f32 %12, 0f00000000;\n"
        "mov.f32 %13, 0f00000000;\n"
        "mov.f32 %14, 0f00000000;\n"
        "mov.f32 %15, 0f00000000;\n"
        "mov.f32 %16, 0f00000000;\n"
        "mov.f32 %17, 0f00000000;\n"
        "mov.f32 %18, 0f00000000;\n"
        "mov.f32 %19, 0f00000000;\n"
        "mov.f32 %20, 0f00000000;\n"
        "mov.f32 %21, 0f00000000;\n"
        "mov.f32 %22, 0f00000000;\n"
        "mov.f32 %23, 0f00000000;\n"
        "mov.f32 %24, 0f00000000;\n"
        "mov.f32 %25, 0f00000000;\n"
        "mov.f32 %26, 0f00000000;\n"
        "mov.f32 %27, 0f00000000;\n"
        "mov.f32 %28, 0f00000000;\n"
        "mov.f32 %29, 0f00000000;\n"
        "mov.f32 %30, 0f00000000;\n"
        "mov.f32 %31, 0f00000000;\n"
        "mov.f32 %32, 0f00000000;\n"
        "mov.f32 %33, 0f00000000;\n"
        "mov.f32 %34, 0f00000000;\n"
        "mov.f32 %35, 0f00000000;\n"
        "mov.f32 %36, 0f00000000;\n"
        "mov.f32 %37, 0f00000000;\n"
        "mov.f32 %38, 0f00000000;\n"
        "mov.f32 %39, 0f00000000;\n"
        "mov.f32 %40, 0f00000000;\n"
        "mov.f32 %41, 0f00000000;\n"
        "mov.f32 %42, 0f00000000;\n"
        "mov.f32 %43, 0f00000000;\n"
        "mov.f32 %44, 0f00000000;\n"
        "mov.f32 %45, 0f00000000;\n"
        "mov.f32 %46, 0f00000000;\n"
        "mov.f32 %47, 0f00000000;\n"
        "mov.f32 %48, 0f00000000;\n"
        "mov.f32 %49, 0f00000000;\n"
        "mov.f32 %50, 0f00000000;\n"
        "mov.f32 %51, 0f00000000;\n"
        "mov.f32 %52, 0f00000000;\n"
        "mov.f32 %53, 0f00000000;\n"
        "mov.f32 %54, 0f00000000;\n"
        "mov.f32 %55, 0f00000000;\n"
        "mov.f32 %56, 0f00000000;\n"
        "mov.f32 %57, 0f00000000;\n"
        "mov.f32 %58, 0f00000000;\n"
        "mov.f32 %59, 0f00000000;\n"
        "mov.f32 %60, 0f00000000;\n"
        "mov.f32 %61, 0f00000000;\n"
        "mov.f32 %62, 0f00000000;\n"
        "mov.f32 %63, 0f00000000;\n"
        "mov.f32 %64, 0f00000000;\n"
        "mov.f32 %65, 0f00000000;\n"
        "mov.f32 %66, 0f00000000;\n"
        "mov.f32 %67, 0f00000000;\n"
        "mov.f32 %68, 0f00000000;\n"
        "mov.f32 %69, 0f00000000;\n"
        "mov.f32 %70, 0f00000000;\n"
        "mov.f32 %71, 0f00000000;\n"
        "mov.f32 %72, 0f00000000;\n"
        "mov.f32 %73, 0f00000000;\n"
        "mov.f32 %74, 0f00000000;\n"
        "mov.f32 %75, 0f00000000;\n"
        "mov.f32 %76, 0f00000000;\n"
        "mov.f32 %77, 0f00000000;\n"
        "mov.f32 %78, 0f00000000;\n"
        "mov.f32 %79, 0f00000000;\n"
        "mov.f32 %80, 0f00000000;\n"
        "mov.f32 %81, 0f00000000;\n"
        "mov.f32 %82, 0f00000000;\n"
        "mov.f32 %83, 0f00000000;\n"
        "mov.f32 %84, 0f00000000;\n"
        "mov.f32 %85, 0f00000000;\n"
        "mov.f32 %86, 0f00000000;\n"
        "mov.f32 %87, 0f00000000;\n"
        "mov.f32 %88, 0f00000000;\n"
        "mov.f32 %89, 0f00000000;\n"
        "mov.f32 %90, 0f00000000;\n"
        "mov.f32 %91, 0f00000000;\n"
        "mov.f32 %92, 0f00000000;\n"
        "mov.f32 %93, 0f00000000;\n"
        "mov.f32 %94, 0f00000000;\n"
        "mov.f32 %95, 0f00000000;\n"
        "mov.f32 %96, 0f00000000;\n"
        "mov.f32 %97, 0f00000000;\n"
        "mov.f32 %98, 0f00000000;\n"
        "mov.f32 %99, 0f00000000;\n"
        "mov.f32 %100, 0f00000000;\n"
        "mov.f32 %101, 0f00000000;\n"
        "mov.f32 %102, 0f00000000;\n"
        "mov.f32 %103, 0f00000000;\n"
        "mov.f32 %104, 0f00000000;\n"
        "mov.f32 %105, 0f00000000;\n"
        "mov.f32 %106, 0f00000000;\n"
        "mov.f32 %107, 0f00000000;\n"
        "mov.f32 %108, 0f00000000;\n"
        "mov.f32 %109, 0f00000000;\n"
        "mov.f32 %110, 0f00000000;\n"
        "mov.f32 %111, 0f00000000;\n"
        "mov.f32 %112, 0f00000000;\n"
        "mov.f32 %113, 0f00000000;\n"
        "mov.f32 %114, 0f00000000;\n"
        "mov.f32 %115, 0f00000000;\n"
        "mov.f32 %116, 0f00000000;\n"
        "mov.f32 %117, 0f00000000;\n"
        "mov.f32 %118, 0f00000000;\n"
        "mov.f32 %119, 0f00000000;\n"
        "mov.f32 %120, 0f00000000;\n"
        "mov.f32 %121, 0f00000000;\n"
        "mov.f32 %122, 0f00000000;\n"
        "mov.f32 %123, 0f00000000;\n"
        "mov.f32 %124, 0f00000000;\n"
        "mov.f32 %125, 0f00000000;\n"
        "mov.f32 %126, 0f00000000;\n"
        "mov.f32 %127, 0f00000000;\n"
        "mov.f32 %128, 0f00000000;\n"
        "mov.f32 %129, 0f00000000;\n"
        "mov.f32 %130, 0f00000000;\n"
        "mov.f32 %131, 0f00000000;\n"
        "mov.f32 %132, 0f00000000;\n"
        "mov.f32 %133, 0f00000000;\n"
        "mov.f32 %134, 0f00000000;\n"
        "mov.f32 %135, 0f00000000;\n"
        "mov.f32 %136, 0f00000000;\n"
        "mov.f32 %137, 0f00000000;\n"
        "mov.f32 %138, 0f00000000;\n"
        "mov.f32 %139, 0f00000000;\n"
        "mov.f32 %140, 0f00000000;\n"
        "mov.f32 %141, 0f00000000;\n"
        "mov.f32 %142, 0f00000000;\n"
        "mov.f32 %143, 0f00000000;\n"
        "mov.f32 %144, 0f00000000;\n"
        "mov.f32 %145, 0f00000000;\n"
        "mov.f32 %146, 0f00000000;\n"
        "mov.f32 %147, 0f00000000;\n"
        "mov.f32 %148, 0f00000000;\n"
        "mov.f32 %149, 0f00000000;\n"
        "mov.f32 %150, 0f00000000;\n"
        "mov.f32 %151, 0f00000000;\n"
        "setp.ne.u32 pf, 0, 0;\n"
        "add.u32 v0, %154, %159;\n"
        "shfl.sync.idx.b32 so, v0, 0, 31, 0xffffffff;\n"
        "mov.u32 npar, 0;\n"
        "shfl.sync.idx.b32 uz, %159, 7, 31, 0xffffffff;\n"
        "add.u32 bend, %155, " STR(NP * 16) ";\n"
        "add.u32 v0, %159, 8;\n"
        "shfl.sync.idx.b32 dh0, v0, 0, 31, 0xffffffff;\n"
        "shfl.sync.idx.b32 dh1, v0, 1, 31, 0xffffffff;\n"
        "shfl.sync.idx.b32 dh2, v0, 2, 31, 0xffffffff;\n"
        "shfl.sync.idx.b32 dh3, v0, 3, 31, 0xffffffff;\n"
        "add.u32 v0, %159, 0xc0000010;\n"
        "shfl.sync.idx.b32 dh4, v0, 4, 31, 0xffffffff;\n"
        "shfl.sync.idx.b32 dh5, v0, 5, 31, 0xffffffff;\n"
        "add.u32 v0, %159, %156;\n"
        "shfl.sync.idx.b32 eb0, v0, 0, 31, 0xffffffff;\n"
        "mov.u32 q, 0;\n"
        "mov.u32 pl, %158;\n"
        "shr.u32 nbar, so, 9;\n"
        "add.u32 nbar, nbar, %155;\n"
        "elect.sync _|plead, 0xffffffff;\n"
        "mov.b64 de0, {%156, dh4};\n"
        "mov.b64 de1, {eb0, dh5};\n"
        "mov.b32 hYa0, 0;\n"
        "mov.b32 hYa1, 0;\n"
        "mov.b32 hYa2, 0;\n"
        "mov.b32 hYa3, 0;\n"
        "mov.b32 hYa4, 0;\n"
        "mov.b32 hYa5, 0;\n"
        "mov.b32 hYa6, 0;\n"
        "mov.b32 hYa7, 0;\n"
        "mov.b32 hYb0, 0;\n"
        "mov.b32 hYb1, 0;\n"
        "mov.b32 hYb2, 0;\n"
        "mov.b32 hYb3, 0;\n"
        "mov.b32 hYb4, 0;\n"
        "mov.b32 hYb5, 0;\n"
        "mov.b32 hYb6, 0;\n"
        "mov.b32 hYb7, 0;\n"
        "mov.u32 ctm, 0x10001000;\n"
        "setp.lt.f16x2 t0|u0, ctm, cz;\n"
        "abs.f16x2 v3, ctm;\n"
        "setp.ge.f16x2 t1|u1, v3, ca;\n"
        "setp.geu.f16x2 t2|u2, v3, cb;\n"
        "ld.shared.v2.u32 {ctl, ctm}, [pl];\n"
        "add.u32 pl, pl, 8;\n"
        "add.u32 rbar, %155, " STR(DUMB) ";\n"
        "mov.b64 daX, {%157, dh0};\n"
        "mov.b64 dbX, {%157, dh1};\n"
        "mov.b64 daY, {%157, dh2};\n"
        "mov.b64 dbY, {%157, dh3};\n"
        "mov.u32 bar, nbar;\n"
        "mov.u32 par, npar;\n"
        "sub.u32 so, bar, %155;\n"
        "shl.b32 so, so, 9;\n"
        "add.u32 v0, %152, so;\n"
        "add.u32 v1, %153, so;\n"
        "add.u32 nbar, nbar, 16;\n"
        "setp.eq.u32 p, nbar, bend;\n"
        "selp.b32 nbar, %155, nbar, p;\n"
        "@p xor.b32 npar, npar, 1;\n"
        "SLOW:\n"
        "mov.u32 cnt, 0;\n"
        "W1:\n"
        "mbarrier.try_wait.parity.shared.b64 p, [bar], par;\n"
        "@p bra.uni RES;\n"
        "add.u32 cnt, cnt, 1;\n"
        "setp.lt.u32 p, cnt, 4000000;\n"
        "@p bra.uni W1;\n"
        "trap;\n"
        "CX:\n"
        "mbarrier.test_wait.parity.shared.b64 pok, [nbar], npar;\n"
        "and.b32 dl, q, 0x60;\n"
        "add.u32 dl, dl, %157;\n"
        "add.u32 v3, dl, 0;\n"
        "mov.b64 {v2, dh0}, daX;\n"
        "mov.b64 daX, {v3, dh0};\n"
        "add.u32 v3, dl, 257;\n"
        "mov.b64 {v2, dh1}, dbX;\n"
        "mov.b64 dbX, {v3, dh1};\n"
        "add.u32 v3, dl, 514;\n"
        "mov.b64 {v2, dh2}, daY;\n"
        "mov.b64 daY, {v3, dh2};\n"
        "add.u32 v3, dl, 771;\n"
        "mov.b64 {v2, dh3}, dbY;\n"
        "mov.b64 dbY, {v3, dh3};\n"
        "add.u32 q, q, 32;\n"
        "and.b32 qe, q, 0xe0;\n"
        "add.u32 v3, qe, %156;\n"
        "mov.b64 {v2, dh4}, de0;\n"
        "mov.b64 de0, {v3, dh4};\n"
        "mov.b64 {v2, dh5}, de1;\n"
        "mov.b64 de1, {v3, dh5};\n"
        "setp.lt.f16x2 t0|u0, ctl, cz;\n"
        "abs.f16x2 v3, ctl;\n"
        "setp.ge.f16x2 t1|u1, v3, ca;\n"
        "setp.geu.f16x2 t2|u2, v3, cb;\n"
        "wgmma.wait_group.sync.aligned 2;\n"
        "cvt.rn.bf16x2.f32 pX0, r1, r0;\n"
        "cvt.rn.bf16x2.f32 pX1, r3, r2;\n"
        "cvt.rn.bf16x2.f32 pX2, r9, r8;\n"
        "cvt.rn.bf16x2.f32 pX3, r11, r10;\n"
        "cvt.rn.bf16x2.f32 pY0, r5, r4;\n"
        "cvt.rn.bf16x2.f32 pY1, r7, r6;\n"
        "cvt.rn.bf16x2.f32 pY2, r13, r12;\n"
        "cvt.rn.bf16x2.f32 pY3, r15, r14;\n"
        "mov.b32 {sl, sh}, pX0;\n"
        "mov.b32 pp, {sl, sl};\n"
        "mul.rn.bf16x2 hXa0, hLa0, pp;\n"
        "mul.rn.bf16x2 hXa2, hLa2, pp;\n"
        "mov.b32 {sl, sh}, pX1;\n"
        "mov.b32 pp, {sl, sl};\n"
        "mul.rn.bf16x2 hXa1, hLa1, pp;\n"
        "mul.rn.bf16x2 hXa3, hLa3, pp;\n"
        "mov.b32 {sl, sh}, pX2;\n"
        "mov.b32 pp, {sl, sl};\n"
        "mul.rn.bf16x2 hXa4, hLa4, pp;\n"
        "mul.rn.bf16x2 hXa6, hLa6, pp;\n"
        "mov.b32 {sl, sh}, pX3;\n"
        "mov.b32 pp, {sl, sl};\n"
        "mul.rn.bf16x2 hXa5, hLa5, pp;\n"
        "mul.rn.bf16x2 hXa7, hLa7, pp;\n"
        "mov.b32 {sl, sh}, pX0;\n"
        "mov.b32 pp, {sh, sh};\n"
        "mul.rn.bf16x2 hXb0, hLb0, pp;\n"
        "mul.rn.bf16x2 hXb2, hLb2, pp;\n"
        "mov.b32 {sl, sh}, pX1;\n"
        "mov.b32 pp, {sh, sh};\n"
        "mul.rn.bf16x2 hXb1, hLb1, pp;\n"
        "mul.rn.bf16x2 hXb3, hLb3, pp;\n"
        "mov.b32 {sl, sh}, pX2;\n"
        "mov.b32 pp, {sh, sh};\n"
        "mul.rn.bf16x2 hXb4, hLb4, pp;\n"
        "mul.rn.bf16x2 hXb6, hLb6, pp;\n"
        "mov.b32 {sl, sh}, pX3;\n"
        "mov.b32 pp, {sh, sh};\n"
        "mul.rn.bf16x2 hXb5, hLb5, pp;\n"
        "mul.rn.bf16x2 hXb7, hLb7, pp;\n"
        "ldmatrix.sync.aligned.m8n8.x4.trans.shared.b16 {hLa0,hLa1,hLa2,hLa3}, [v0+4096];\n"
        "ldmatrix.sync.aligned.m8n8.x4.trans.shared.b16 {hLa4,hLa5,hLa6,hLa7}, [v1+4096];\n"
        "ldmatrix.sync.aligned.m8n8.x4.trans.shared.b16 {hLb0,hLb1,hLb2,hLb3}, [v0+6144];\n"
        "ldmatrix.sync.aligned.m8n8.x4.trans.shared.b16 {hLb4,hLb5,hLb6,hLb7}, [v1+6144];\n"
        "@t2 bra.uni T4X;\n"
        "@t1 bra.uni T2X;\n"
        "@t0 bra.uni L1X;\n"
        "L0X:\n"
        "wgmma.fence.sync.aligned;\n"
        "wgmma.mma_async.sync.aligned.m64n24k16.f32.bf16.bf16 {%0,%1,%2,%3,%4,%5,%6,%7,%8,%9,%10,%11}, {hXa0,hXa1,hXa2,hXa3}, daX, 1, 1, 1, 0;\n"
        "wgmma.mma_async.sync.aligned.m64n24k16.f32.bf16.bf16 {%76,%77,%78,%79,%80,%81,%82,%83,%84,%85,%86,%87}, {hXa4,hXa5,hXa6,hXa7}, daX, 1, 1, 1, 0;\n"
        "wgmma.commit_group.sync.aligned;\n"
        "@u2 bra.uni T4Xb;\n"
        "@u1 bra.uni T2Xb;\n"
        "@u0 bra.uni L1Xb;\n"
        "bra.uni L0Xb;\n"
        "L1X:\n"
        "wgmma.fence.sync.aligned;\n"
        "wgmma.mma_async.sync.aligned.m64n24k16.f32.bf16.bf16 {%12,%13,%14,%15,%16,%17,%18,%19,%20,%21,%22,%23}, {hXa0,hXa1,hXa2,hXa3}, daX, 1, 1, 1, 0;\n"
        "wgmma.mma_async.sync.aligned.m64n24k16.f32.bf16.bf16 {%88,%89,%90,%91,%92,%93,%94,%95,%96,%97,%98,%99}, {hXa4,hXa5,hXa6,hXa7}, daX, 1, 1, 1, 0;\n"
        "wgmma.commit_group.sync.aligned;\n"
        "@u2 bra.uni T4Xb;\n"
        "@u1 bra.uni T2Xb;\n"
        "@u0 bra.uni L1Xb;\n"
        "bra.uni L0Xb;\n"
        "T2X:\n"
        "@t0 bra.uni L3X;\n"
        "L2X:\n"
        "wgmma.fence.sync.aligned;\n"
        "wgmma.mma_async.sync.aligned.m64n24k16.f32.bf16.bf16 {%24,%25,%26,%27,%28,%29,%30,%31,%32,%33,%34,%35}, {hXa0,hXa1,hXa2,hXa3}, daX, 1, 1, 1, 0;\n"
        "wgmma.mma_async.sync.aligned.m64n24k16.f32.bf16.bf16 {%100,%101,%102,%103,%104,%105,%106,%107,%108,%109,%110,%111}, {hXa4,hXa5,hXa6,hXa7}, daX, 1, 1, 1, 0;\n"
        "wgmma.commit_group.sync.aligned;\n"
        "@u2 bra.uni T4Xb;\n"
        "@u1 bra.uni T2Xb;\n"
        "@u0 bra.uni L1Xb;\n"
        "bra.uni L0Xb;\n"
        "L3X:\n"
        "wgmma.fence.sync.aligned;\n"
        "wgmma.mma_async.sync.aligned.m64n24k16.f32.bf16.bf16 {%36,%37,%38,%39,%40,%41,%42,%43,%44,%45,%46,%47}, {hXa0,hXa1,hXa2,hXa3}, daX, 1, 1, 1, 0;\n"
        "wgmma.mma_async.sync.aligned.m64n24k16.f32.bf16.bf16 {%112,%113,%114,%115,%116,%117,%118,%119,%120,%121,%122,%123}, {hXa4,hXa5,hXa6,hXa7}, daX, 1, 1, 1, 0;\n"
        "wgmma.commit_group.sync.aligned;\n"
        "@u2 bra.uni T4Xb;\n"
        "@u1 bra.uni T2Xb;\n"
        "@u0 bra.uni L1Xb;\n"
        "bra.uni L0Xb;\n"
        "T4X:\n"
        "@!t1 bra.uni LEXIT;\n"
        "@t0 bra.uni L5X;\n"
        "L4X:\n"
        "wgmma.fence.sync.aligned;\n"
        "wgmma.mma_async.sync.aligned.m64n24k16.f32.bf16.bf16 {%48,%49,%50,%51,%52,%53,%54,%55,%56,%57,%58,%59}, {hXa0,hXa1,hXa2,hXa3}, daX, 1, 1, 1, 0;\n"
        "wgmma.mma_async.sync.aligned.m64n24k16.f32.bf16.bf16 {%124,%125,%126,%127,%128,%129,%130,%131,%132,%133,%134,%135}, {hXa4,hXa5,hXa6,hXa7}, daX, 1, 1, 1, 0;\n"
        "wgmma.commit_group.sync.aligned;\n"
        "@u2 bra.uni T4Xb;\n"
        "@u1 bra.uni T2Xb;\n"
        "@u0 bra.uni L1Xb;\n"
        "bra.uni L0Xb;\n"
        "L5X:\n"
        "wgmma.fence.sync.aligned;\n"
        "wgmma.mma_async.sync.aligned.m64n32k16.f32.bf16.bf16 {%60,%61,%62,%63,%64,%65,%66,%67,%68,%69,%70,%71,%72,%73,%74,%75}, {hXa0,hXa1,hXa2,hXa3}, daX, 1, 1, 1, 0;\n"
        "wgmma.mma_async.sync.aligned.m64n32k16.f32.bf16.bf16 {%136,%137,%138,%139,%140,%141,%142,%143,%144,%145,%146,%147,%148,%149,%150,%151}, {hXa4,hXa5,hXa6,hXa7}, daX, 1, 1, 1, 0;\n"
        "wgmma.commit_group.sync.aligned;\n"
        "@u2 bra.uni T4Xb;\n"
        "@u1 bra.uni T2Xb;\n"
        "@u0 bra.uni L1Xb;\n"
        "L0Xb:\n"
        "wgmma.fence.sync.aligned;\n"
        "wgmma.mma_async.sync.aligned.m64n24k16.f32.bf16.bf16 {%0,%1,%2,%3,%4,%5,%6,%7,%8,%9,%10,%11}, {hXb0,hXb1,hXb2,hXb3}, dbX, 1, 1, 1, 0;\n"
        "wgmma.mma_async.sync.aligned.m64n24k16.f32.bf16.bf16 {%76,%77,%78,%79,%80,%81,%82,%83,%84,%85,%86,%87}, {hXb4,hXb5,hXb6,hXb7}, dbX, 1, 1, 1, 0;\n"
        "wgmma.commit_group.sync.aligned;\n"
        "bra.uni CY;\n"
        "L1Xb:\n"
        "wgmma.fence.sync.aligned;\n"
        "wgmma.mma_async.sync.aligned.m64n24k16.f32.bf16.bf16 {%12,%13,%14,%15,%16,%17,%18,%19,%20,%21,%22,%23}, {hXb0,hXb1,hXb2,hXb3}, dbX, 1, 1, 1, 0;\n"
        "wgmma.mma_async.sync.aligned.m64n24k16.f32.bf16.bf16 {%88,%89,%90,%91,%92,%93,%94,%95,%96,%97,%98,%99}, {hXb4,hXb5,hXb6,hXb7}, dbX, 1, 1, 1, 0;\n"
        "wgmma.commit_group.sync.aligned;\n"
        "bra.uni CY;\n"
        "T2Xb:\n"
        "@u0 bra.uni L3Xb;\n"
        "L2Xb:\n"
        "wgmma.fence.sync.aligned;\n"
        "wgmma.mma_async.sync.aligned.m64n24k16.f32.bf16.bf16 {%24,%25,%26,%27,%28,%29,%30,%31,%32,%33,%34,%35}, {hXb0,hXb1,hXb2,hXb3}, dbX, 1, 1, 1, 0;\n"
        "wgmma.mma_async.sync.aligned.m64n24k16.f32.bf16.bf16 {%100,%101,%102,%103,%104,%105,%106,%107,%108,%109,%110,%111}, {hXb4,hXb5,hXb6,hXb7}, dbX, 1, 1, 1, 0;\n"
        "wgmma.commit_group.sync.aligned;\n"
        "bra.uni CY;\n"
        "L3Xb:\n"
        "wgmma.fence.sync.aligned;\n"
        "wgmma.mma_async.sync.aligned.m64n24k16.f32.bf16.bf16 {%36,%37,%38,%39,%40,%41,%42,%43,%44,%45,%46,%47}, {hXb0,hXb1,hXb2,hXb3}, dbX, 1, 1, 1, 0;\n"
        "wgmma.mma_async.sync.aligned.m64n24k16.f32.bf16.bf16 {%112,%113,%114,%115,%116,%117,%118,%119,%120,%121,%122,%123}, {hXb4,hXb5,hXb6,hXb7}, dbX, 1, 1, 1, 0;\n"
        "wgmma.commit_group.sync.aligned;\n"
        "bra.uni CY;\n"
        "T4Xb:\n"
        "@u0 bra.uni L5Xb;\n"
        "L4Xb:\n"
        "wgmma.fence.sync.aligned;\n"
        "wgmma.mma_async.sync.aligned.m64n24k16.f32.bf16.bf16 {%48,%49,%50,%51,%52,%53,%54,%55,%56,%57,%58,%59}, {hXb0,hXb1,hXb2,hXb3}, dbX, 1, 1, 1, 0;\n"
        "wgmma.mma_async.sync.aligned.m64n24k16.f32.bf16.bf16 {%124,%125,%126,%127,%128,%129,%130,%131,%132,%133,%134,%135}, {hXb4,hXb5,hXb6,hXb7}, dbX, 1, 1, 1, 0;\n"
        "wgmma.commit_group.sync.aligned;\n"
        "bra.uni CY;\n"
        "L5Xb:\n"
        "wgmma.fence.sync.aligned;\n"
        "wgmma.mma_async.sync.aligned.m64n32k16.f32.bf16.bf16 {%60,%61,%62,%63,%64,%65,%66,%67,%68,%69,%70,%71,%72,%73,%74,%75}, {hXb0,hXb1,hXb2,hXb3}, dbX, 1, 1, 1, 0;\n"
        "wgmma.mma_async.sync.aligned.m64n32k16.f32.bf16.bf16 {%136,%137,%138,%139,%140,%141,%142,%143,%144,%145,%146,%147,%148,%149,%150,%151}, {hXb4,hXb5,hXb6,hXb7}, dbX, 1, 1, 1, 0;\n"
        "wgmma.commit_group.sync.aligned;\n"
        "bra.uni CY;\n"
        "CY:\n"
        "mov.u32 rbar, bar;\n"
        "mov.u32 bar, nbar;\n"
        "mov.u32 par, npar;\n"
        "sub.u32 so, bar, %155;\n"
        "shl.b32 so, so, 9;\n"
        "add.u32 v0, %152, so;\n"
        "add.u32 v1, %153, so;\n"
        "add.u32 nbar, nbar, 16;\n"
        "setp.eq.u32 p, nbar, bend;\n"
        "selp.b32 nbar, %155, nbar, p;\n"
        "@p xor.b32 npar, npar, 1;\n"
        "wgmma.wait_group.sync.aligned 2;\n"
        "lop3.b32 v2, hLa3, hLa7, hLb3, 0x80;\n"
        "lop3.b32 v2, v2, hLb7, uz, 0x80;\n"
        "add.u32 v2, v2, rbar;\n"
        "@plead mbarrier.arrive.shared.b64 _, [v2+8];\n"
        "setp.lt.f16x2 t0|u0, ctm, cz;\n"
        "abs.f16x2 v3, ctm;\n"
        "setp.ge.f16x2 t1|u1, v3, ca;\n"
        "setp.geu.f16x2 t2|u2, v3, cb;\n"
        "ld.shared.v2.u32 {ctl, ctm}, [pl];\n"
        "add.u32 pl, pl, 8;\n"
        "mov.b32 {sl, sh}, pY0;\n"
        "mov.b32 pp, {sl, sl};\n"
        "mul.rn.bf16x2 hYa0, hLa0, pp;\n"
        "mul.rn.bf16x2 hYa2, hLa2, pp;\n"
        "mov.b32 {sl, sh}, pY1;\n"
        "mov.b32 pp, {sl, sl};\n"
        "mul.rn.bf16x2 hYa1, hLa1, pp;\n"
        "mul.rn.bf16x2 hYa3, hLa3, pp;\n"
        "mov.b32 {sl, sh}, pY2;\n"
        "mov.b32 pp, {sl, sl};\n"
        "mul.rn.bf16x2 hYa4, hLa4, pp;\n"
        "mul.rn.bf16x2 hYa6, hLa6, pp;\n"
        "mov.b32 {sl, sh}, pY3;\n"
        "mov.b32 pp, {sl, sl};\n"
        "mul.rn.bf16x2 hYa5, hLa5, pp;\n"
        "mul.rn.bf16x2 hYa7, hLa7, pp;\n"
        "mov.b32 {sl, sh}, pY0;\n"
        "mov.b32 pp, {sh, sh};\n"
        "mul.rn.bf16x2 hYb0, hLb0, pp;\n"
        "mul.rn.bf16x2 hYb2, hLb2, pp;\n"
        "mov.b32 {sl, sh}, pY1;\n"
        "mov.b32 pp, {sh, sh};\n"
        "mul.rn.bf16x2 hYb1, hLb1, pp;\n"
        "mul.rn.bf16x2 hYb3, hLb3, pp;\n"
        "mov.b32 {sl, sh}, pY2;\n"
        "mov.b32 pp, {sh, sh};\n"
        "mul.rn.bf16x2 hYb4, hLb4, pp;\n"
        "mul.rn.bf16x2 hYb6, hLb6, pp;\n"
        "mov.b32 {sl, sh}, pY3;\n"
        "mov.b32 pp, {sh, sh};\n"
        "mul.rn.bf16x2 hYb5, hLb5, pp;\n"
        "mul.rn.bf16x2 hYb7, hLb7, pp;\n"
        "@!pok bra.uni SLOW;\n"
        "RES:\n"
        "ldmatrix.sync.aligned.m8n8.x4.trans.shared.b16 {hLa0,hLa1,hLa2,hLa3}, [v0+0];\n"
        "ldmatrix.sync.aligned.m8n8.x4.trans.shared.b16 {hLa4,hLa5,hLa6,hLa7}, [v1+0];\n"
        "ldmatrix.sync.aligned.m8n8.x4.trans.shared.b16 {hLb0,hLb1,hLb2,hLb3}, [v0+2048];\n"
        "ldmatrix.sync.aligned.m8n8.x4.trans.shared.b16 {hLb4,hLb5,hLb6,hLb7}, [v1+2048];\n"
        "wgmma.wait_group.sync.aligned 0;\n"
        "@t2 bra.uni T4Y;\n"
        "@t1 bra.uni T2Y;\n"
        "@t0 bra.uni L1Y;\n"
        "L0Y:\n"
        "wgmma.fence.sync.aligned;\n"
        "wgmma.mma_async.sync.aligned.m64n16k16.f32.bf16.bf16 {r0,r1,r2,r3,r4,r5,r6,r7}, {wa0,wa1,wa2,wa3}, de0, pf, 1, 1, 0;\n"
        "wgmma.mma_async.sync.aligned.m64n16k16.f32.bf16.bf16 {r8,r9,r10,r11,r12,r13,r14,r15}, {wa4,wa5,wa6,wa7}, de1, pf, 1, 1, 0;\n"
        "wgmma.commit_group.sync.aligned;\n"
        "wgmma.mma_async.sync.aligned.m64n24k16.f32.bf16.bf16 {%0,%1,%2,%3,%4,%5,%6,%7,%8,%9,%10,%11}, {hYa0,hYa1,hYa2,hYa3}, daY, 1, 1, 1, 0;\n"
        "wgmma.mma_async.sync.aligned.m64n24k16.f32.bf16.bf16 {%76,%77,%78,%79,%80,%81,%82,%83,%84,%85,%86,%87}, {hYa4,hYa5,hYa6,hYa7}, daY, 1, 1, 1, 0;\n"
        "wgmma.commit_group.sync.aligned;\n"
        "@u2 bra.uni T4Yb;\n"
        "@u1 bra.uni T2Yb;\n"
        "@u0 bra.uni L1Yb;\n"
        "bra.uni L0Yb;\n"
        "L1Y:\n"
        "wgmma.fence.sync.aligned;\n"
        "wgmma.mma_async.sync.aligned.m64n16k16.f32.bf16.bf16 {r0,r1,r2,r3,r4,r5,r6,r7}, {wa0,wa1,wa2,wa3}, de0, pf, 1, 1, 0;\n"
        "wgmma.mma_async.sync.aligned.m64n16k16.f32.bf16.bf16 {r8,r9,r10,r11,r12,r13,r14,r15}, {wa4,wa5,wa6,wa7}, de1, pf, 1, 1, 0;\n"
        "wgmma.commit_group.sync.aligned;\n"
        "wgmma.mma_async.sync.aligned.m64n24k16.f32.bf16.bf16 {%12,%13,%14,%15,%16,%17,%18,%19,%20,%21,%22,%23}, {hYa0,hYa1,hYa2,hYa3}, daY, 1, 1, 1, 0;\n"
        "wgmma.mma_async.sync.aligned.m64n24k16.f32.bf16.bf16 {%88,%89,%90,%91,%92,%93,%94,%95,%96,%97,%98,%99}, {hYa4,hYa5,hYa6,hYa7}, daY, 1, 1, 1, 0;\n"
        "wgmma.commit_group.sync.aligned;\n"
        "@u2 bra.uni T4Yb;\n"
        "@u1 bra.uni T2Yb;\n"
        "@u0 bra.uni L1Yb;\n"
        "bra.uni L0Yb;\n"
        "T2Y:\n"
        "@t0 bra.uni L3Y;\n"
        "L2Y:\n"
        "wgmma.fence.sync.aligned;\n"
        "wgmma.mma_async.sync.aligned.m64n16k16.f32.bf16.bf16 {r0,r1,r2,r3,r4,r5,r6,r7}, {wa0,wa1,wa2,wa3}, de0, pf, 1, 1, 0;\n"
        "wgmma.mma_async.sync.aligned.m64n16k16.f32.bf16.bf16 {r8,r9,r10,r11,r12,r13,r14,r15}, {wa4,wa5,wa6,wa7}, de1, pf, 1, 1, 0;\n"
        "wgmma.commit_group.sync.aligned;\n"
        "wgmma.mma_async.sync.aligned.m64n24k16.f32.bf16.bf16 {%24,%25,%26,%27,%28,%29,%30,%31,%32,%33,%34,%35}, {hYa0,hYa1,hYa2,hYa3}, daY, 1, 1, 1, 0;\n"
        "wgmma.mma_async.sync.aligned.m64n24k16.f32.bf16.bf16 {%100,%101,%102,%103,%104,%105,%106,%107,%108,%109,%110,%111}, {hYa4,hYa5,hYa6,hYa7}, daY, 1, 1, 1, 0;\n"
        "wgmma.commit_group.sync.aligned;\n"
        "@u2 bra.uni T4Yb;\n"
        "@u1 bra.uni T2Yb;\n"
        "@u0 bra.uni L1Yb;\n"
        "bra.uni L0Yb;\n"
        "L3Y:\n"
        "wgmma.fence.sync.aligned;\n"
        "wgmma.mma_async.sync.aligned.m64n16k16.f32.bf16.bf16 {r0,r1,r2,r3,r4,r5,r6,r7}, {wa0,wa1,wa2,wa3}, de0, pf, 1, 1, 0;\n"
        "wgmma.mma_async.sync.aligned.m64n16k16.f32.bf16.bf16 {r8,r9,r10,r11,r12,r13,r14,r15}, {wa4,wa5,wa6,wa7}, de1, pf, 1, 1, 0;\n"
        "wgmma.commit_group.sync.aligned;\n"
        "wgmma.mma_async.sync.aligned.m64n24k16.f32.bf16.bf16 {%36,%37,%38,%39,%40,%41,%42,%43,%44,%45,%46,%47}, {hYa0,hYa1,hYa2,hYa3}, daY, 1, 1, 1, 0;\n"
        "wgmma.mma_async.sync.aligned.m64n24k16.f32.bf16.bf16 {%112,%113,%114,%115,%116,%117,%118,%119,%120,%121,%122,%123}, {hYa4,hYa5,hYa6,hYa7}, daY, 1, 1, 1, 0;\n"
        "wgmma.commit_group.sync.aligned;\n"
        "@u2 bra.uni T4Yb;\n"
        "@u1 bra.uni T2Yb;\n"
        "@u0 bra.uni L1Yb;\n"
        "bra.uni L0Yb;\n"
        "T4Y:\n"
        "@t0 bra.uni L5Y;\n"
        "L4Y:\n"
        "wgmma.fence.sync.aligned;\n"
        "wgmma.mma_async.sync.aligned.m64n16k16.f32.bf16.bf16 {r0,r1,r2,r3,r4,r5,r6,r7}, {wa0,wa1,wa2,wa3}, de0, pf, 1, 1, 0;\n"
        "wgmma.mma_async.sync.aligned.m64n16k16.f32.bf16.bf16 {r8,r9,r10,r11,r12,r13,r14,r15}, {wa4,wa5,wa6,wa7}, de1, pf, 1, 1, 0;\n"
        "wgmma.commit_group.sync.aligned;\n"
        "wgmma.mma_async.sync.aligned.m64n24k16.f32.bf16.bf16 {%48,%49,%50,%51,%52,%53,%54,%55,%56,%57,%58,%59}, {hYa0,hYa1,hYa2,hYa3}, daY, 1, 1, 1, 0;\n"
        "wgmma.mma_async.sync.aligned.m64n24k16.f32.bf16.bf16 {%124,%125,%126,%127,%128,%129,%130,%131,%132,%133,%134,%135}, {hYa4,hYa5,hYa6,hYa7}, daY, 1, 1, 1, 0;\n"
        "wgmma.commit_group.sync.aligned;\n"
        "@u2 bra.uni T4Yb;\n"
        "@u1 bra.uni T2Yb;\n"
        "@u0 bra.uni L1Yb;\n"
        "bra.uni L0Yb;\n"
        "L5Y:\n"
        "wgmma.fence.sync.aligned;\n"
        "wgmma.mma_async.sync.aligned.m64n16k16.f32.bf16.bf16 {r0,r1,r2,r3,r4,r5,r6,r7}, {wa0,wa1,wa2,wa3}, de0, pf, 1, 1, 0;\n"
        "wgmma.mma_async.sync.aligned.m64n16k16.f32.bf16.bf16 {r8,r9,r10,r11,r12,r13,r14,r15}, {wa4,wa5,wa6,wa7}, de1, pf, 1, 1, 0;\n"
        "wgmma.commit_group.sync.aligned;\n"
        "wgmma.mma_async.sync.aligned.m64n32k16.f32.bf16.bf16 {%60,%61,%62,%63,%64,%65,%66,%67,%68,%69,%70,%71,%72,%73,%74,%75}, {hYa0,hYa1,hYa2,hYa3}, daY, 1, 1, 1, 0;\n"
        "wgmma.mma_async.sync.aligned.m64n32k16.f32.bf16.bf16 {%136,%137,%138,%139,%140,%141,%142,%143,%144,%145,%146,%147,%148,%149,%150,%151}, {hYa4,hYa5,hYa6,hYa7}, daY, 1, 1, 1, 0;\n"
        "wgmma.commit_group.sync.aligned;\n"
        "@u2 bra.uni T4Yb;\n"
        "@u1 bra.uni T2Yb;\n"
        "@u0 bra.uni L1Yb;\n"
        "L0Yb:\n"
        "wgmma.fence.sync.aligned;\n"
        "wgmma.mma_async.sync.aligned.m64n24k16.f32.bf16.bf16 {%0,%1,%2,%3,%4,%5,%6,%7,%8,%9,%10,%11}, {hYb0,hYb1,hYb2,hYb3}, dbY, 1, 1, 1, 0;\n"
        "wgmma.mma_async.sync.aligned.m64n24k16.f32.bf16.bf16 {%76,%77,%78,%79,%80,%81,%82,%83,%84,%85,%86,%87}, {hYb4,hYb5,hYb6,hYb7}, dbY, 1, 1, 1, 0;\n"
        "wgmma.commit_group.sync.aligned;\n"
        "bra.uni CX;\n"
        "L1Yb:\n"
        "wgmma.fence.sync.aligned;\n"
        "wgmma.mma_async.sync.aligned.m64n24k16.f32.bf16.bf16 {%12,%13,%14,%15,%16,%17,%18,%19,%20,%21,%22,%23}, {hYb0,hYb1,hYb2,hYb3}, dbY, 1, 1, 1, 0;\n"
        "wgmma.mma_async.sync.aligned.m64n24k16.f32.bf16.bf16 {%88,%89,%90,%91,%92,%93,%94,%95,%96,%97,%98,%99}, {hYb4,hYb5,hYb6,hYb7}, dbY, 1, 1, 1, 0;\n"
        "wgmma.commit_group.sync.aligned;\n"
        "bra.uni CX;\n"
        "T2Yb:\n"
        "@u0 bra.uni L3Yb;\n"
        "L2Yb:\n"
        "wgmma.fence.sync.aligned;\n"
        "wgmma.mma_async.sync.aligned.m64n24k16.f32.bf16.bf16 {%24,%25,%26,%27,%28,%29,%30,%31,%32,%33,%34,%35}, {hYb0,hYb1,hYb2,hYb3}, dbY, 1, 1, 1, 0;\n"
        "wgmma.mma_async.sync.aligned.m64n24k16.f32.bf16.bf16 {%100,%101,%102,%103,%104,%105,%106,%107,%108,%109,%110,%111}, {hYb4,hYb5,hYb6,hYb7}, dbY, 1, 1, 1, 0;\n"
        "wgmma.commit_group.sync.aligned;\n"
        "bra.uni CX;\n"
        "L3Yb:\n"
        "wgmma.fence.sync.aligned;\n"
        "wgmma.mma_async.sync.aligned.m64n24k16.f32.bf16.bf16 {%36,%37,%38,%39,%40,%41,%42,%43,%44,%45,%46,%47}, {hYb0,hYb1,hYb2,hYb3}, dbY, 1, 1, 1, 0;\n"
        "wgmma.mma_async.sync.aligned.m64n24k16.f32.bf16.bf16 {%112,%113,%114,%115,%116,%117,%118,%119,%120,%121,%122,%123}, {hYb4,hYb5,hYb6,hYb7}, dbY, 1, 1, 1, 0;\n"
        "wgmma.commit_group.sync.aligned;\n"
        "bra.uni CX;\n"
        "T4Yb:\n"
        "@u0 bra.uni L5Yb;\n"
        "L4Yb:\n"
        "wgmma.fence.sync.aligned;\n"
        "wgmma.mma_async.sync.aligned.m64n24k16.f32.bf16.bf16 {%48,%49,%50,%51,%52,%53,%54,%55,%56,%57,%58,%59}, {hYb0,hYb1,hYb2,hYb3}, dbY, 1, 1, 1, 0;\n"
        "wgmma.mma_async.sync.aligned.m64n24k16.f32.bf16.bf16 {%124,%125,%126,%127,%128,%129,%130,%131,%132,%133,%134,%135}, {hYb4,hYb5,hYb6,hYb7}, dbY, 1, 1, 1, 0;\n"
        "wgmma.commit_group.sync.aligned;\n"
        "bra.uni CX;\n"
        "L5Yb:\n"
        "wgmma.fence.sync.aligned;\n"
        "wgmma.mma_async.sync.aligned.m64n32k16.f32.bf16.bf16 {%60,%61,%62,%63,%64,%65,%66,%67,%68,%69,%70,%71,%72,%73,%74,%75}, {hYb0,hYb1,hYb2,hYb3}, dbY, 1, 1, 1, 0;\n"
        "wgmma.mma_async.sync.aligned.m64n32k16.f32.bf16.bf16 {%136,%137,%138,%139,%140,%141,%142,%143,%144,%145,%146,%147,%148,%149,%150,%151}, {hYb4,hYb5,hYb6,hYb7}, dbY, 1, 1, 1, 0;\n"
        "wgmma.commit_group.sync.aligned;\n"
        "bra.uni CX;\n"
        "LEXIT:\n"
        "wgmma.wait_group.sync.aligned 0;\n"
        "}\n"
        : "=f"(acc[0][0][0]), "=f"(acc[0][0][1]), "=f"(acc[0][0][2]), "=f"(acc[0][0][3]),
          "=f"(acc[0][1][0]), "=f"(acc[0][1][1]), "=f"(acc[0][1][2]), "=f"(acc[0][1][3]),
          "=f"(acc[0][2][0]), "=f"(acc[0][2][1]), "=f"(acc[0][2][2]), "=f"(acc[0][2][3]),
          "=f"(acc[0][3][0]), "=f"(acc[0][3][1]), "=f"(acc[0][3][2]), "=f"(acc[0][3][3]),
          "=f"(acc[0][4][0]), "=f"(acc[0][4][1]), "=f"(acc[0][4][2]), "=f"(acc[0][4][3]),
          "=f"(acc[0][5][0]), "=f"(acc[0][5][1]), "=f"(acc[0][5][2]), "=f"(acc[0][5][3]),
          "=f"(acc[0][6][0]), "=f"(acc[0][6][1]), "=f"(acc[0][6][2]), "=f"(acc[0][6][3]),
          "=f"(acc[0][7][0]), "=f"(acc[0][7][1]), "=f"(acc[0][7][2]), "=f"(acc[0][7][3]),
          "=f"(acc[0][8][0]), "=f"(acc[0][8][1]), "=f"(acc[0][8][2]), "=f"(acc[0][8][3]),
          "=f"(acc[0][9][0]), "=f"(acc[0][9][1]), "=f"(acc[0][9][2]), "=f"(acc[0][9][3]),
          "=f"(acc[0][10][0]), "=f"(acc[0][10][1]), "=f"(acc[0][10][2]), "=f"(acc[0][10][3]),
          "=f"(acc[0][11][0]), "=f"(acc[0][11][1]), "=f"(acc[0][11][2]), "=f"(acc[0][11][3]),
          "=f"(acc[0][12][0]), "=f"(acc[0][12][1]), "=f"(acc[0][12][2]), "=f"(acc[0][12][3]),
          "=f"(acc[0][13][0]), "=f"(acc[0][13][1]), "=f"(acc[0][13][2]), "=f"(acc[0][13][3]),
          "=f"(acc[0][14][0]), "=f"(acc[0][14][1]), "=f"(acc[0][14][2]), "=f"(acc[0][14][3]),
          "=f"(acc[0][15][0]), "=f"(acc[0][15][1]), "=f"(acc[0][15][2]), "=f"(acc[0][15][3]),
          "=f"(acc[0][16][0]), "=f"(acc[0][16][1]), "=f"(acc[0][16][2]), "=f"(acc[0][16][3]),
          "=f"(acc[0][17][0]), "=f"(acc[0][17][1]), "=f"(acc[0][17][2]), "=f"(acc[0][17][3]),
          "=f"(acc[0][18][0]), "=f"(acc[0][18][1]), "=f"(acc[0][18][2]), "=f"(acc[0][18][3]),
          "=f"(acc[1][0][0]), "=f"(acc[1][0][1]), "=f"(acc[1][0][2]), "=f"(acc[1][0][3]),
          "=f"(acc[1][1][0]), "=f"(acc[1][1][1]), "=f"(acc[1][1][2]), "=f"(acc[1][1][3]),
          "=f"(acc[1][2][0]), "=f"(acc[1][2][1]), "=f"(acc[1][2][2]), "=f"(acc[1][2][3]),
          "=f"(acc[1][3][0]), "=f"(acc[1][3][1]), "=f"(acc[1][3][2]), "=f"(acc[1][3][3]),
          "=f"(acc[1][4][0]), "=f"(acc[1][4][1]), "=f"(acc[1][4][2]), "=f"(acc[1][4][3]),
          "=f"(acc[1][5][0]), "=f"(acc[1][5][1]), "=f"(acc[1][5][2]), "=f"(acc[1][5][3]),
          "=f"(acc[1][6][0]), "=f"(acc[1][6][1]), "=f"(acc[1][6][2]), "=f"(acc[1][6][3]),
          "=f"(acc[1][7][0]), "=f"(acc[1][7][1]), "=f"(acc[1][7][2]), "=f"(acc[1][7][3]),
          "=f"(acc[1][8][0]), "=f"(acc[1][8][1]), "=f"(acc[1][8][2]), "=f"(acc[1][8][3]),
          "=f"(acc[1][9][0]), "=f"(acc[1][9][1]), "=f"(acc[1][9][2]), "=f"(acc[1][9][3]),
          "=f"(acc[1][10][0]), "=f"(acc[1][10][1]), "=f"(acc[1][10][2]), "=f"(acc[1][10][3]),
          "=f"(acc[1][11][0]), "=f"(acc[1][11][1]), "=f"(acc[1][11][2]), "=f"(acc[1][11][3]),
          "=f"(acc[1][12][0]), "=f"(acc[1][12][1]), "=f"(acc[1][12][2]), "=f"(acc[1][12][3]),
          "=f"(acc[1][13][0]), "=f"(acc[1][13][1]), "=f"(acc[1][13][2]), "=f"(acc[1][13][3]),
          "=f"(acc[1][14][0]), "=f"(acc[1][14][1]), "=f"(acc[1][14][2]), "=f"(acc[1][14][3]),
          "=f"(acc[1][15][0]), "=f"(acc[1][15][1]), "=f"(acc[1][15][2]), "=f"(acc[1][15][3]),
          "=f"(acc[1][16][0]), "=f"(acc[1][16][1]), "=f"(acc[1][16][2]), "=f"(acc[1][16][3]),
          "=f"(acc[1][17][0]), "=f"(acc[1][17][1]), "=f"(acc[1][17][2]), "=f"(acc[1][17][3]),
          "=f"(acc[1][18][0]), "=f"(acc[1][18][1]), "=f"(acc[1][18][2]), "=f"(acc[1][18][3])
        : "r"(xa0), "r"(xa1), "r"(so0), "r"(bar0), "r"(ea0), "r"(d0), "r"(pl0), "r"(lz), "r"(wa[0]), "r"(wa[1]), "r"(wa[2]),
          "r"(wa[3]), "r"(wa[4]), "r"(wa[5]), "r"(wa[6]), "r"(wa[7])
        : "memory");
}
#define JA 9
__device__ __forceinline__ void wgmma_out(float (&o)[9][4], uint64_t da, uint64_t db, int acc) {
    asm volatile(
        "{\n.reg .pred p;\nsetp.ne.b32 p, %38, 0;\n"
        "wgmma.mma_async.sync.aligned.m64n72k16.f32.bf16.bf16 {%0,%1,%2,%3,%4,%5,%6,%7,%8,%9,%10,%11,%12,%13,%14,%15,%16,%17,%18,%19,%20,%21,%22,%23,%24,%25,%26,%27,%28,%29,%30,%31,%32,%33,%34,%35}, %36, %37, p, 1, 1, 1, 1;\n}"
        : "+f"(o[0][0]), "+f"(o[0][1]), "+f"(o[0][2]), "+f"(o[0][3]),
          "+f"(o[1][0]), "+f"(o[1][1]), "+f"(o[1][2]), "+f"(o[1][3]),
          "+f"(o[2][0]), "+f"(o[2][1]), "+f"(o[2][2]), "+f"(o[2][3]),
          "+f"(o[3][0]), "+f"(o[3][1]), "+f"(o[3][2]), "+f"(o[3][3]),
          "+f"(o[4][0]), "+f"(o[4][1]), "+f"(o[4][2]), "+f"(o[4][3]),
          "+f"(o[5][0]), "+f"(o[5][1]), "+f"(o[5][2]), "+f"(o[5][3]),
          "+f"(o[6][0]), "+f"(o[6][1]), "+f"(o[6][2]), "+f"(o[6][3]),
          "+f"(o[7][0]), "+f"(o[7][1]), "+f"(o[7][2]), "+f"(o[7][3]),
          "+f"(o[8][0]), "+f"(o[8][1]), "+f"(o[8][2]), "+f"(o[8][3])
        : "l"(da), "l"(db), "r"(acc));
}
__device__ __forceinline__ void wgmma_out(float (&o)[10][4], uint64_t da, uint64_t db, int acc) {
    asm volatile(
        "{\n.reg .pred p;\nsetp.ne.b32 p, %42, 0;\n"
        "wgmma.mma_async.sync.aligned.m64n80k16.f32.bf16.bf16 {%0,%1,%2,%3,%4,%5,%6,%7,%8,%9,%10,%11,%12,%13,%14,%15,%16,%17,%18,%19,%20,%21,%22,%23,%24,%25,%26,%27,%28,%29,%30,%31,%32,%33,%34,%35,%36,%37,%38,%39}, %40, %41, p, 1, 1, 1, 1;\n}"
        : "+f"(o[0][0]), "+f"(o[0][1]), "+f"(o[0][2]), "+f"(o[0][3]),
          "+f"(o[1][0]), "+f"(o[1][1]), "+f"(o[1][2]), "+f"(o[1][3]),
          "+f"(o[2][0]), "+f"(o[2][1]), "+f"(o[2][2]), "+f"(o[2][3]),
          "+f"(o[3][0]), "+f"(o[3][1]), "+f"(o[3][2]), "+f"(o[3][3]),
          "+f"(o[4][0]), "+f"(o[4][1]), "+f"(o[4][2]), "+f"(o[4][3]),
          "+f"(o[5][0]), "+f"(o[5][1]), "+f"(o[5][2]), "+f"(o[5][3]),
          "+f"(o[6][0]), "+f"(o[6][1]), "+f"(o[6][2]), "+f"(o[6][3]),
          "+f"(o[7][0]), "+f"(o[7][1]), "+f"(o[7][2]), "+f"(o[7][3]),
          "+f"(o[8][0]), "+f"(o[8][1]), "+f"(o[8][2]), "+f"(o[8][3]),
          "+f"(o[9][0]), "+f"(o[9][1]), "+f"(o[9][2]), "+f"(o[9][3])
        : "l"(da), "l"(db), "r"(acc));
}

__device__ __forceinline__ void slow_edge(int ee, int s, float* accn, const __nv_bfloat16* __restrict__ x,
                                          const __nv_bfloat16* __restrict__ sh, const __nv_bfloat16* __restrict__ ea,
                                          const __nv_bfloat16* __restrict__ cg, const __nv_bfloat16* __restrict__ wr,
                                          int lane) {
    float rwv[4] = {0.f, 0.f, 0.f, 0.f};
#pragma unroll 4
    for (int d = 0; d < 16; d++) {
        const float a = __bfloat162float(ea[(size_t)ee * 16 + d]);
        const uint2 wv = *(const uint2*)(wr + d * 128 + lane * 4);
        rwv[0] += a * __uint_as_float(wv.x << 16);
        rwv[1] += a * __uint_as_float(wv.x & 0xffff0000u);
        rwv[2] += a * __uint_as_float(wv.y << 16);
        rwv[3] += a * __uint_as_float(wv.y & 0xffff0000u);
    }
    float A = 0.f;
#pragma unroll
    for (int v = 0; v < 4; v++)
        A += __bfloat162float(cg[((lane >> 2) & 3) * 16 + v * 4 + (lane & 3)]) * __bfloat162float(sh[(size_t)ee * 4 + v]);
    float m[4][4];
#pragma unroll
    for (int w = 0; w < 4; w++)
#pragma unroll
        for (int j = 0; j < 4; j++) m[w][j] = 0.f;
#pragma unroll
    for (int u = 0; u < 4; u++) {
        const uint2 xv = *(const uint2*)(x + (size_t)s * 512 + u * 128 + lane * 4);
        const float x0 = __uint_as_float(xv.x << 16), x1 = __uint_as_float(xv.x & 0xffff0000u);
        const float x2 = __uint_as_float(xv.y << 16), x3 = __uint_as_float(xv.y & 0xffff0000u);
#pragma unroll
        for (int w = 0; w < 4; w++) {
            const float a = __shfl_sync(0xffffffffu, A, u * 4 + w);
            m[w][0] += a * x0;
            m[w][1] += a * x1;
            m[w][2] += a * x2;
            m[w][3] += a * x3;
        }
    }
#pragma unroll
    for (int w = 0; w < 4; w++)
#pragma unroll
        for (int j = 0; j < 4; j++) atomicAdd(accn + w * 128 + lane * 4 + j, m[w][j] * rwv[j]);
}

__device__ __forceinline__ void slow_out(const float* accn, const __nv_bfloat16* __restrict__ wout,
                                         __nv_bfloat16* __restrict__ outn, int lane) {
    float o[4][4];
#pragma unroll
    for (int w = 0; w < 4; w++)
#pragma unroll
        for (int j = 0; j < 4; j++) o[w][j] = 0.f;
#pragma unroll 2
    for (int c = 0; c < 128; c++) {
        const uint2 wv = *(const uint2*)(wout + c * 128 + lane * 4);
        const float w0 = __uint_as_float(wv.x << 16), w1 = __uint_as_float(wv.x & 0xffff0000u);
        const float w2 = __uint_as_float(wv.y << 16), w3 = __uint_as_float(wv.y & 0xffff0000u);
#pragma unroll
        for (int w = 0; w < 4; w++) {
            const float a = __bfloat162float(__float2bfloat16(accn[w * 128 + c]));
            o[w][0] += a * w0;
            o[w][1] += a * w1;
            o[w][2] += a * w2;
            o[w][3] += a * w3;
        }
    }
#pragma unroll
    for (int w = 0; w < 4; w++)
        *(uint2*)(outn + w * 128 + lane * 4) = make_uint2(pack_bf16(o[w][0], o[w][1]), pack_bf16(o[w][2], o[w][3]));
}

static_assert(NW > 2 * NP, "barriers");
#define FPOS 1
#define PW 0
#define TWAIT mbar_lean_u
#define PWAIT mbar_lean
#define TMA_ROW(k) "@pl cp.async.bulk.tensor.2d.shared::cluster.global.mbarrier::complete_tx::bytes [d" #k "], [tm, {r" #k ", z" #k "}], [b" #k "];\n"
#define TMA_INIT(k, o) "shfl.sync.idx.b32 z" #k ", %11, " #k ", 31, 0xffffffff;\nadd.u32 m" #k ", %2, " STR(o) ";\nadd.u32 m" #k ", m" #k ", %11;\nshfl.sync.idx.b32 m" #k ", m" #k ", 0, 31, 0xffffffff;\n"
#define TMA_PREP(k) "mad.lo.u32 d" #k ", dd, 512, m" #k ";\nadd.u32 b" #k ", dd, z" #k ";\n"
#define RDCLK(c) "mov.u64 ck, %%clock64;\ncvt.u32.u64 " c ", ck;\n"
#define BCAST(d, k) "selp.b32 " d ", a" #k ", 0, me;\nredux.sync.or.b32 " d ", " d ", 0xffffffff;\n"
#define PTIME(t, x, y, z) "shr.u32 " t ", " x ", 16;\nand.b32 c, " y ", 0xffff;\nadd.u32 " t ", " t ", c;\nmad.lo.u32 c, " t ", %13, %14;\nmul.lo.u32 " t ", " t ", %9;\nmin.u32 " t ", " t ", c;\nshr.u32 " t ", " t ", 5;\nadd.u32 " t ", " t ", %6;\nmin.u32 " t ", " t ", lim;\nlop3.b32 " t ", " t ", " z ", 7, 0xd8;\n"
#define PROWS(s, x, y) "and.b32 t0, " s ", 0xffc;\nsetp.gt.u32 p, t0, " STR(LNUL / 2) ";\nmad.lo.u32 t0, t0, 2, %5;\nld.shared.v2.u32 {" x ", " y "}, [t0];\nshr.u32 t0, " s ", 11;\nand.b32 t0, t0, 6;\nshr.u32 " s ", " s ", 15;\nadd.u32 t0, t0, " s ";\nselp.s32 " s ", " STR(NGR - 2) ", -2, p;\nadd.u32 t0, t0, " s ";\nmul.lo.s32 t0, t0, " STR(-NBK * 64) ";\nprmt.b32 t0, t0, 0, 0x1010;\nadd.u16x2 " x ", " x ", t0;\nadd.u16x2 " y ", " y ", t0;\n"
__device__ __forceinline__ void produce(const CUtensorMap* tm, uint32_t bar, uint32_t d0, uint32_t ps, int nit, uint32_t psrc,
                                        uint32_t tbase, uint32_t lim, uint32_t taug64, uint32_t taus, uint32_t n, int lz, int pr0,
                                        uint32_t tau2, uint32_t brk
) {
    asm volatile(
        "{\n.reg .pred p, pl, ok, me;\n.reg .b32 a<6>, u<4>, r<8>, d<8>, b<8>, z<8>, m<8>, ps, lim, n, it, pr, pe, tgt, tgu, c, dd, dn, par, t0, t1;\n"
        ".reg .b64 st, tm, ck;\n"
        "elect.sync _|pl, 0xffffffff;\n"
        TMA_INIT(0, 0) TMA_INIT(1, SM_ODD) TMA_INIT(2, 1024) TMA_INIT(3, SM_ODD + 1024)
        TMA_INIT(4, 4096) TMA_INIT(5, SM_ODD + 4096) TMA_INIT(6, 5120) TMA_INIT(7, SM_ODD + 5120)
        "mov.b64 {a0, a1}, %0;\n"
        "add.u32 a0, a0, %11;\n"
        "add.u32 a1, a1, %11;\n"
        "shfl.sync.idx.b32 a0, a0, 0, 31, 0xffffffff;\n"
        "shfl.sync.idx.b32 a1, a1, 0, 31, 0xffffffff;\n"
        "mov.b64 tm, {a0, a1};\n"
        "mov.u32 ps, %3;\n"
        "mov.u32 it, %4;\n"
        "mov.u32 lim, %7;\n"
        "mov.u32 n, %10;\n"
        "mov.u32 pr, %12;\n"
        "setp.le.s32 p, it, 0;\n"
        "bar.sync 0;\n"
        "@p bra.uni PEND;\n"
        "PBAT:\n"
        "ld.shared.u16 c, [ps];\n"
        "ld.shared.u16 t1, [ps+4];\n"
        "add.u32 ps, ps, 256;\n"
        "mul.lo.u32 par, n, " STR(65536 / NP + 1) ";\n"
        "shr.u32 par, par, 16;\n"
        "mad.lo.s32 dn, par, " STR(-NP) ", n;\n"
        "add.u32 n, n, 32;\n"
        "not.b32 par, par;\n"
        PROWS("c", "a0", "a1") PROWS("t1", "a2", "a3")
        "min.s32 pe, it, 32;\n"
        "sub.s32 it, it, 32;\n"
        "add.u32 pe, pe, pr;\n"
        PTIME("a4", "a0", "a1", "dn") PTIME("a5", "a2", "a3", "par")
        "add.u32 lim, lim, %8;\n"
        "PLOOP:\n"
        "setp.eq.u32 me, n, pr;\n"
        "add.u32 pr, pr, 1;\n"
        BCAST("tgt", 4) BCAST("tgu", 5) BCAST("u0", 0) BCAST("u1", 1) BCAST("u2", 2) BCAST("u3", 3)
        "and.b32 dd, tgt, 7;\n"
        "mad.lo.u32 dd, dd, 16, %1;\n"
        "and.b32 par, tgu, 1;\n"
        "mbarrier.test_wait.parity.shared.b64 ok, [dd+8], par;\n"
        "prmt.b32 r0, u0, 0, 0x4104;\nprmt.b32 r1, u0, 0, 0x4324;\nprmt.b32 r2, u1, 0, 0x4104;\nprmt.b32 r3, u1, 0, 0x4324;\n"
        "prmt.b32 r4, u2, 0, 0x4104;\nprmt.b32 r5, u2, 0, 0x4324;\nprmt.b32 r6, u3, 0, 0x4104;\nprmt.b32 r7, u3, 0, 0x4324;\n"
        TMA_PREP(0) TMA_PREP(1) TMA_PREP(2) TMA_PREP(3) TMA_PREP(4) TMA_PREP(5) TMA_PREP(6) TMA_PREP(7)
        RDCLK("c")
        "sub.s32 c, c, tgt;\n"
        "setp.ge.and.s32 p, c, 0, ok;\n"
        "@!p bra.uni PSLP;\n"
        "PRES:\n"
        "@pl mbarrier.arrive.expect_tx.shared.b64 _, [b0], 8192;\n"
        TMA_ROW(0) TMA_ROW(1) TMA_ROW(2) TMA_ROW(3)
        RDCLK("c")
        "sub.s32 c, c, tgu;\n"
        "setp.lt.s32 p, c, 0;\n"
        "@p bra.uni PSL2;\n"
        "PRE2:\n"
        TMA_ROW(4) TMA_ROW(5) TMA_ROW(6) TMA_ROW(7)
        "setp.lt.u32 p, pr, pe;\n"
        "@p bra.uni PLOOP;\n"
        "setp.gt.s32 p, it, 0;\n"
        "@p bra.uni PBAT;\n"
        "bra.uni PEND;\n"
        "PSL2:\n"
        "nanosleep.u32 " STR(PSLEEP) ";\n"
        RDCLK("c")
        "sub.s32 c, c, tgu;\n"
        "setp.lt.s32 p, c, 0;\n"
        "@p bra.uni PSL2;\n"
        "bra.uni PRE2;\n"
        "PSL1:\n"
        "nanosleep.u32 " STR(PSLEEP) ";\n"
        RDCLK("c")
        "sub.s32 c, c, tgt;\n"
        "PSLP:\n"
        "setp.lt.s32 p, c, 0;\n"
        "@p bra.uni PSL1;\n"
        "@ok bra.uni PRES;\n"
        "mov.u32 c, 0;\n"
        "PW:\n"
        "mbarrier.try_wait.parity.shared.b64 p, [b0+8], par;\n"
        "@p bra.uni PRES;\n"
        "add.u32 c, c, 1;\n"
        "setp.lt.u32 p, c, 4000000;\n"
        "@p bra.uni PW;\n"
        "trap;\n"
        "PEND:\n}"
        :
        : "l"(tm), "r"(bar), "r"(d0), "r"(ps), "r"(nit), "r"(psrc), "r"(tbase), "r"(lim), "r"(taug64), "r"(taus), "r"(n), "r"(lz),
          "r"(pr0), "r"(tau2), "r"(brk)
        : "memory");
}
template <int J0, int JN>
__device__ __forceinline__ void put_agg(const float (&acc)[2][NJ][4], uint32_t tb) {
#pragma unroll
    for (int h = 0; h < 2; h++) {
        const float(*a)[4] = acc[h] + J0;
#pragma unroll
        for (int j = 0; j + 1 < JN; j += 2)
            stsm4(tb + h * SM_ODD + j * 256, pack_bf16(a[j][0], a[j][1]), pack_bf16(a[j][2], a[j][3]),
                  pack_bf16(a[j + 1][0], a[j + 1][1]), pack_bf16(a[j + 1][2], a[j + 1][3]));
        if (JN & 1) stsm2(tb + h * SM_ODD + (JN - 1) * 256, pack_bf16(a[JN - 1][0], a[JN - 1][1]), pack_bf16(a[JN - 1][2], a[JN - 1][3]));
    }
}
template <int JN>
__device__ __forceinline__ void mul_out(float (&o)[JN][4], uint32_t r16, int hh, int tb) {
    asm volatile("wgmma.fence.sync.aligned;" ::: "memory");
#pragma unroll
    for (int ks = 0; ks < 8; ks++) {
        const uint32_t rg = (ks >> 2) * SM_ODD;
        wgmma_out(o, (uint64_t)(r16 + (((NP - 2 + hh) * 8192 + rg + (ks & 3) * 2048) >> 4)) | (64ull << 32) | (1ull << 62),
                  (uint64_t)(r16 + ((tb + rg + (ks & 3) * (JN * 256)) >> 4) + (8 << 16)) | (16ull << 32), ks);
    }
    asm volatile("wgmma.commit_group.sync.aligned;" ::: "memory");
}
static_assert(JA == 9 && NJ == 19 && NP == 5 && SM_EVEN == 0 && SM_ODD % 1024 == 128, "epilogue");
__device__ constexpr int out_at(int st, int j) {
    return st == 0   ? (j < 4 ? (19 + j) * 1024 : j < 8 ? SM_ODD + (16 + j) * 1024 : 23 * 1024)
           : st == 1 ? (10 + j) * 1024
           : st == 2 ? SM_ODD + (10 + j) * 1024
                     : (j < 8 ? (24 + j) * 1024 : SM_ODD + (16 + j) * 1024);
}
#define WG_SYNC(w) asm volatile("bar.sync %0, 128;" ::"r"((w) + 1) : "memory")
template <int ST, int JN>
__device__ __forceinline__ void put_out(float (&o)[JN][4], uint32_t ce, uint32_t co, int w) {
    asm volatile("wgmma.wait_group.sync.aligned %0;" ::"n"(ST == 2) : "memory");
#pragma unroll
    for (int j = 0; j < JN; j++)
#pragma unroll
        for (int k = 0; k < 4; k++) asm volatile("" : "+f"(o[j][k])::"memory");
#pragma unroll
    for (int j = 0; j + 1 < JN; j += 2)
        stsm4t((out_at(ST, j) & 128 ? co : ce) + out_at(ST, j), pack_bf16(o[j][0], o[j][1]), pack_bf16(o[j][2], o[j][3]),
               pack_bf16(o[j + 1][0], o[j + 1][1]), pack_bf16(o[j + 1][2], o[j + 1][3]));
    if (JN & 1) stsm2t(ce + out_at(ST, JN - 1), pack_bf16(o[JN - 1][0], o[JN - 1][1]), pack_bf16(o[JN - 1][2], o[JN - 1][3]));
    asm volatile("bar.arrive %0, 192;" ::"r"(6 + 2 * ST + w) : "memory");
}
#define DELAY 2500
#define NULW 0xf0000000
#define DREF 0
#define K0(npr) ((2 * NP - 2 - (npr) % NP) % NP)
#define GCODE(g) ((((g) >> 1) + 1) << 12 | ((g) & 1) << 15)
#define LISTS() asm volatile("bar.sync 0;" ::: "memory")
__global__ void __launch_bounds__(NT, 1)
main_kernel(const int* __restrict__ dst, const int* __restrict__ src, uint4* __restrict__ gbin, int E, int nbins, int fast_ok,
            int npb, unsigned npb_magic, int N, const __grid_constant__ CUtensorMap tme,
            const __grid_constant__ CUtensorMap tmx, const __grid_constant__ CUtensorMap tmw,
            const __grid_constant__ CUtensorMap tmo, const __nv_bfloat16* __restrict__ x,
            const __nv_bfloat16* __restrict__ sh, const __nv_bfloat16* __restrict__ ea,
            const __nv_bfloat16* __restrict__ cg, const __nv_bfloat16* __restrict__ wr,
            const __nv_bfloat16* __restrict__ wout, __nv_bfloat16* __restrict__ out, int tau16, int toff, int delay,
            int tau2, int brk) {
    extern __shared__ __align__(1024) unsigned char smem[];
    const uint32_t sb = __shfl_sync(0xffffffffu, s2u(smem), 0);
    const int tid = threadIdx.x;
    const int warp = __shfl_sync(0xffffffffu, tid >> 5, 0), lane = tid & 31;
    const int g = lane >> 2, t = lane & 3;

    TLSTAMP(0);
    TLINIT();
    const int bin = blockIdx.x;
    const int node0 = bin * npb, hpb = npb >> 1;
    uint32_t wa[8];
    uint2 c0 = make_uint2(0, 0), c1 = c0;
    bool fast = fast_ok;
    if (fast_ok) {
        int pd[EPS], ps[EPS];
        const int e0 = (warp * nbins + bin) * 32 + lane;
#pragma unroll
        for (int k = 0; k < EPS; k++)
            asm volatile("ld.global.nc.u32 %0, [%1];" : "=r"(pd[k]) : "l"(dst + min(e0 + k * NT * nbins, E - 1)));
#pragma unroll
        for (int k = 0; k < EPS; k++)
            asm volatile("ld.global.nc.u32 %0, [%1];" : "=r"(ps[k]) : "l"(src + min(e0 + k * NT * nbins, E - 1)));
        const unsigned ck0 = clock();
        const uint32_t cnt0 = (sb + SC_CNT + 8191) & ~8191;
        {
            const uint32_t nul = NULW | ((bin & 3) * 8 + (tid & 7)) << 21;
#pragma unroll
            for (int k = 0; k < 4; k++) {
                const int i = tid + k * NT;
                if (i < SC_EXT / 16 ? (tid & 7) != 7 : i < SC_TAB / 16) sts_v4(sb + SC_ENT + i * 16, make_uint4(nul, nul, nul, nul));
            }
            if (warp == NW - 1) {
                uint32_t now;
                asm volatile("mov.u32 %0, %%globaltimer_lo;" : "=r"(now));
                now = __shfl_sync(0xffffffffu, (now & 0x1fffff) | nul, 7);
#pragma unroll
                for (int k = 0; k < MAXBINS / 32; k++) sts_v4(sb + SC_ENT + (k * 32 + lane) * 128 + 112, make_uint4(now, now, now, now));
                if (lane == 0) {
                    asm volatile("prefetch.tensormap [%0];" ::"l"(&tme) : "memory");
                    asm volatile("prefetch.tensormap [%0];" ::"l"(&tmx) : "memory");
                    asm volatile("prefetch.tensormap [%0];" ::"l"(&tmw) : "memory");
                    asm volatile("prefetch.tensormap [%0];" ::"l"(&tmo) : "memory");
                    sts_v2(sb + SM_MISC + MI_INT, 0, now);
                }
            }
            sts_v4(cnt0 + tid * 16, make_uint4(0, 0, 0, 0));
            if (tid < (SC_END - SC_HIST) / 16) {
                const uint32_t v = (tid >> 3) == MAXBINS / 32 ? 0x80000000u : 0;
                sts_v4(sb + SC_HIST + tid * 16, make_uint4(v, v, v, v));
            }
            if (tid < 2 * HPB) {
                const int w = tid >= hpb, loc = tid - (w ? hpb : 0), gr = min(loc * 43 >> 8, NGR - 1);
                sts_u32(sb + SC_TAB + tid * 4, ((w ? NGR : 0) + gr) * (NBK * 64 << 15) + loc - gr * GSZ);
            }
        }
        TLMAX(1);
        __syncthreads();
        {
            const uint32_t z = lds_u32(sb + SM_MISC + MI_INT);
            int pb[EPS], pr[EPS];
            uint32_t v[EPS];
#pragma unroll
            for (int k = 0; k < EPS; k++) {
                pb[k] = (int)__umulhi((unsigned)pd[k], npb_magic + z);
                v[k] = lds_u32(sb + SC_TAB + (pd[k] - pb[k] * npb) * 4);
                pr[k] = atoms_add(sb + SC_HIST + (e0 + k * NT * nbins < E ? pb[k] : MAXBINS + lane) * 4, 4);
            }
            int mx = 0;
#pragma unroll
            for (int k = 0; k < EPS; k++) {
                v[k] += ps[k] * (32768 + z) + (k * NT + tid + 32) * 8;
                asm volatile("{\n.reg .pred p;\nsetp.lt.u32 p, %0, 128;\n@p st.shared.u32 [%1], %2;\n}" ::"r"(pr[k]),
                             "r"(sb + SC_ENT + pb[k] * 128 + pr[k]), "r"(v[k])
                             : "memory");
                mx = max(mx, pr[k]);
            }
            if (mx >= 128) {
#pragma unroll
                for (int k = 0; k < EPS; k++)
                    if (pr[k] >= 128 && pr[k] < 192) sts_u32(sb + SC_EXT - 128 + pb[k] * 64 + pr[k], v[k]);
            }
        }
        FENCE_ASYNC();
        TLMAX(6);
        __syncthreads();
        const unsigned c6 = DREF ? ck0 : clock();
        if (warp == NW - 1 && elect()) {
            tma_store(&tme, sb + SC_ENT, bin * 32, 0);
            asm volatile("cp.async.bulk.commit_group;" ::: "memory");
        }
        if (tid < nbins && lds_u32(sb + SC_HIST + tid * 4) >= 128) {
#pragma unroll 1
            for (int k = 0; k < 4; k++) __stcg(gbin + GEX + (tid * nbins + bin) * 4 + k, lds_v4(sb + SC_EXT + tid * 64 + k * 16));
        }
        uint32_t en[4][4], es[4][4], rank[4][4], ca[4][4];
        uint2 wv;
        asm volatile("ld.global.nc.v2.u32 {%0,%1}, [%2];" : "=r"(wv.x), "=r"(wv.y) : "l"((const uint2*)wr + tid));
        if (warp >= 12 && (g >> 2) == (t >> 1)) {
            const uint2* cp = (const uint2*)cg + (g & 3) * 4 + (t & 1) * 2;
            asm volatile("ld.global.nc.v2.u32 {%0,%1}, [%2];" : "=r"(c0.x), "=r"(c0.y) : "l"(cp));
            asm volatile("ld.global.nc.v2.u32 {%0,%1}, [%2];" : "=r"(c1.x), "=r"(c1.y) : "l"(cp + 1));
        }
        if (elect()) {
#pragma unroll
            for (int k = 0; k < (NP > 5 ? 4 : 2); k++) mbar_init(sb + SM_BAR + (warp * (NP > 5 ? 4 : 2) + k) * 8, 3 + (k & 1));
        }
#pragma unroll
        for (int k = 0; k < TS / 2; k++) sts_v4(sb + SM_BT + (tid + k * NT) * 16, make_uint4(0, 0, 0, 0));
        if (tid < 8) sts_v4(sb + SM_BT + (tid + TS / 2 * NT) * 16, make_uint4(0, 0, 0, 0));
        if (tid < 4) {
            sts_u16(sb + SM_SRC + (LNUL + tid) * 2, N);
            sts_u32(sb + SM_EID + (LNUL + tid) * 4, 0x80000000u);
        }
        FENCE_ASYNC();
        const int sg[4] = {tid >> 3, (tid >> 3) + 64, 128 + (tid >> 4), (tid >> 3) + (lane & 4) * 16};
        const uint4* gp[4];
        gp[0] = gbin + bin * nbins * 8 + tid;
        gp[1] = gp[0] + NT;
        gp[2] = lane & 8 ? gbin + GEX + (bin * nbins + sg[2]) * 4 + (lane & 7) : gbin + (bin * nbins + sg[2]) * 8 + (lane & 7);
        gp[3] = gbin + GEX + (bin * nbins + sg[3]) * 4 + (lane & 3);
        unsigned pend = (sg[0] < nbins) | (sg[1] < nbins) << 1 | (sg[2] < nbins && !(lane & 8)) << 2;
#pragma unroll
        for (int k = 0; k < 4; k++) en[k][0] = en[k][1] = en[k][2] = en[k][3] = NULW | lane << 21;
        auto fetch = [&](int k) {
            asm volatile("{\n.reg .pred p;\nsetp.ne.u32 p, %5, 0;\n@p ld.relaxed.gpu.global.v4.u32 {%0,%1,%2,%3}, [%4];\n}"
                         : "+r"(en[k][0]), "+r"(en[k][1]), "+r"(en[k][2]), "+r"(en[k][3])
                         : "l"(gp[k]), "r"(pend & (1u << k))
                         : "memory");
        };
        int spin = 0;
        auto poll = [&](int k0, int k1) {
            for (;;) {
#pragma unroll
                for (int k = k0; k < k1; k++)
                    if (min(min(en[k][0], en[k][1]), min(en[k][2], en[k][3]))) pend &= ~(1u << k);
                if (!__any_sync(0xffffffffu, pend)) break;
#pragma unroll
                for (int k = k0; k < k1; k++) fetch(k);
                if (++spin > 10000000) __trap();
            }
        };
        auto count = [&](int k) {
#pragma unroll
            for (int c = 0; c < 4; c++) {
                const uint32_t v = en[k][c];
                ca[k][c] = ((v >> 19) & 0x1ffc) | cnt0;
                rank[k][c] = atoms_add(ca[k][c], 1);
                asm volatile("{\n.reg .b32 a, b;\nprmt.b32 a, %1, %2, 0x6540;\nand.b32 b, %1, 0x7f00;\nmad.lo.u32 %0, b, %3, a;\n}"
                             : "=r"(es[k][c])
                             : "r"(v), "r"(sg[k] - nbins), "r"(nbins));
            }
        };
        uint32_t sg0 = 0x01010101 | ((lane & 1) << 8 | (lane & 2) << 15 | (lane & 4) << 22) * 0xfe;
        uint32_t sg2 = (0x0101 | ((lane >> 3 & 1) | (lane & 16) << 4) * 0xfe) * 0x10001 ^ 0xfefe0000;
        uint32_t cand = ((lane & 1) << 3 | (lane & 2) << 5 | (lane & 4) << 7 | (lane & 8) << 9) * 7 + (lane & 16) * (15 << 11);
        asm volatile("" : "+r"(sg0), "+r"(sg2), "+r"(cand));
        while ((int)(clock() - c6) < delay) {}
        TLMAX(7);
        fetch(0);
        fetch(1);
        fetch(2);
        poll(0, 3);
        TLMAX(2);
        const bool more = __any_sync(0xffffffffu, (lane & 7) == 7 && min(min(en[0][3], en[1][3]), en[2][3]) < NULW);
        const bool rest = 128 + warp * 2 < nbins;
        if (more) {
            const uint32_t l0 = __shfl_sync(0xffffffffu, en[0][3], lane | 7), l1 = __shfl_sync(0xffffffffu, en[1][3], lane | 7);
            const uint32_t l2 = __shfl_sync(0xffffffffu, en[2][3], (lane & 16) + 7);
            pend = ((lane & 12) == 8 && l2 < NULW) << 2 | ((lane & 4 ? l1 : l0) < NULW) << 3;
            fetch(2);
            fetch(3);
        }
        if (tid == 7 && en[0][3] >= NULW) sts_u32(sb + SM_MISC + MI_INT + 4, en[0][3]);
        count(0);
        count(1);
        if (more) {
            const unsigned ext = pend;
            poll(2, 4);
#pragma unroll
            for (int k = 2; k < 4; k++) {
                if ((ext >> k) & 1) {
                    __stcg((uint4*)gp[k], make_uint4(0, 0, 0, 0));
                    if ((lane & 3) == 3 && en[k][3] < NULW) sts_u32(sb + SM_MISC + MI_INT, 1);
                }
            }
            count(3);
        }
        if (rest) count(2);
        sts_v2(sb + SC_WR + ((tid >> 1) & 15) * 272 + (tid >> 5) * 16 + (tid & 1) * 8, wv.x, wv.y);
        TLMAX(9);
        __syncthreads();
        if (warp < 2 * NGR) {
            const int w0 = warp >= NGR, gr = warp - w0 * NGR;
            const uint32_t cp = cnt0 + (warp * NBK + lane * (NBK / 32)) * 4;
            uint32_t r[NBK / 32 + 1], old[NBK / 32 + 1];
#pragma unroll
            for (int c = 0; c < NBK / 32; c++) r[c + 1] = lds_u32(cp + c * 4);
            r[0] = 0;
#pragma unroll
            for (int c = 1; c < NBK / 32; c++) r[c + 1] += r[c];
            const uint32_t tot = __reduce_add_sync(0xffffffffu, r[NBK / 32]);
            asm volatile("st.shared.u8 [%0], %1;" ::"r"(sb + SM_MISC + MI_INT + 32 + (gr < 4 ? w0 * 4 : 4 + w0 * 2) + gr), "r"((tot + 3) >> 2) : "memory");
            const uint32_t incl = warp_incl_scan(r[NBK / 32], lane), off = incl - r[NBK / 32] + 3 - CE;
            const uint32_t base = warp * GCAP + w0 * GEXT;
#pragma unroll
            for (int c = 0; c <= NBK / 32; c++) r[c] += off;
            asm volatile("bar.sync 3, %0;" ::"n"(2 * NGR * 32) : "memory");
            const uint4 nb = lds_v4(sb + SM_MISC + MI_INT + 32);
            int df;
            asm("{\n.reg .s32 a;\ndp4a.u32.s32 a, %1, %4, 0;\ndp4a.u32.s32 a, %2, %5, a;\ndp4a.u32.s32 %0, %3, %6, a;\n}"
                : "=r"(df)
                : "r"(nb.x), "r"(nb.y), "r"(nb.z), "r"(sg0), "r"(sg0 ^ 0xfefefefe), "r"(sg2));
            const uint32_t swp = __reduce_min_sync(0xffffffffu, abs(df) << NJ | cand);
            const int w = w0 ^ ((swp >> (3 * gr)) & 1);
            const uint32_t bp = sb + SC_BLK + (w * (NBK + 2) + lane * (NBK / 32)) * 4;
#pragma unroll
            for (int c = 0; c < NBK / 32; c++) old[c] = atoms_add(bp + c * 4, (r[c + 1] >> 2) + (r[c] >> 2) * 0x1ffff);
            const bool tailb = (incl & 3) >= 1 && (incl & 3) <= CE;
            if (lane == 31) old[NBK / 32] = atoms_add(bp + NBK / 32 * 4, (r[NBK / 32] >> 2 << 17) + tailb);
            if (tot > GCAP + (gr == NGR - 1 ? GEXT : 0)) {
                sts_u32(sb + SM_MISC + MI_INT, 1);
            } else if (lane < (-tot & 3)) {
                sts_u16(sb + SM_SRC + (base + tot + lane) * 2, N + warp * (NBK * 64));
                sts_u32(sb + SM_EID + (base + tot + lane) * 4, 0x80000000u);
            }
            const uint32_t code = GCODE(gr);
#pragma unroll
            for (int c = 0; c < NBK / 32; c++)
                old[c] = ((old[c] - (r[c] >> 2) + (w * SEQCAP + 1023 - base / 4)) << 17) + r[c] + (base + 1 + code);
            TLMAX(5);
            asm volatile("bar.sync %0, %1;" ::"r"(w + 4), "n"(NGR * 32) : "memory");
#pragma unroll
            for (int c = 0; c < NBK / 32; c++) r[c] = lds_u32(bp + c * 4);
            const uint32_t tw = lds_u32(sb + SC_BLK + (w * (NBK + 2) + NBK) * 4);
#pragma unroll
            for (int c = 0; c < NBK / 32; c++) sts_u32(cp + c * 4, (r[c] & 0xffff0000u) + old[c]);
            const int nst = (tw >> 17) + (tw & 0xffff), npr = (nst + 3) >> 2;
            const uint32_t sq = sb + SM_SEQ + w * SEQCAP * 2;
            if (nst + 32 > SEQCAP) {
                sts_u32(sb + SM_MISC + MI_INT, 1);
            } else {
                if (lane == 31 && tailb) sts_u16(sq + ((tw >> 17) + (old[NBK / 32] & 0xffff)) * 2, ((base + tot + 4) & ~3) | code);
                if (gr == 0) {
                    sts_u16(sq + (nst + lane) * 2, (LNUL + 4) | (lane < (-nst & 3) ? GCODE(0) : 0x7c01));
                    const int k0 = K0(npr);
                    if (lane < k0) {
                        mbar_arrive_cnt(sb + SM_BAR + (w * NP + lane) * 16, 3);
                        mbar_arrive_cnt(sb + SM_BAR + (w * NP + lane) * 16 + 8, 4);
                    }
                    if (lane == 0) sts_v2(sb + SM_MISC + MI_INT + 8 + w * 8, npr, k0);
                    if (lane == 1) sts_u32(sb + SM_MISC + MI_INT + 24, swp);
                }
            }
        } else if (warp == NW - 1 && elect()) {
            asm volatile("cp.async.bulk.global.shared::cta.bulk_group [%0], [%1], %2;" ::"l"(gbin + bin * nbins * 8), "r"(sb + SM_BT),
                         "r"(nbins * 128)
                         : "memory");
            asm volatile("cp.async.bulk.commit_group;" ::: "memory");
            const uint32_t t0 = lds_u32(sb + SM_MISC + MI_INT + 4);
            uint32_t now;
            asm volatile("mov.u32 %0, %%globaltimer_lo;" : "=r"(now));
            sts_u32(sb + SM_MISC + MI_INT + 4, clock() - (min((now - t0) & 0x1fffff, 1u << 16) * 7 >> 2) + toff);
        }
#pragma unroll
        for (int h = 0; h < 2; h++)
            asm volatile("ldmatrix.sync.aligned.m8n8.x4.trans.shared.b16 {%0,%1,%2,%3}, [%4];"
                         : "=r"(wa[h * 4]), "=r"(wa[h * 4 + 1]), "=r"(wa[h * 4 + 2]), "=r"(wa[h * 4 + 3])
                         : "r"(sb + SC_WR + (h * 8 + (warp & 3) * 2 + ((lane >> 3) & 1)) * 272 + (lane >> 4) * 128 + (lane & 7) * 16));
        TLMAX(10);
        __syncthreads();
        auto place = [&](int k) {
#pragma unroll
            for (int c = 0; c < 4; c++) ca[k][c] = lds_u32(ca[k][c]);
#pragma unroll
            for (int c = 0; c < 4; c++) {
                const uint32_t q = ca[k][c] + rank[k][c], p = q & 0xfff;
                asm volatile(
                    "{\n.reg .pred p, q;\n.reg .b32 t;\n.reg .b16 h;\n"
                    "setp.ge.u32 p, %0, " STR(NULW) ";\n"
                    "@!p st.shared.u32 [%1], %2;\n"
                    "shr.u32 t, %0, 15;\ncvt.u16.u32 h, t;\n"
                    "@!p st.shared.u16 [%3], h;\n"
                    "lop3.or.b32 t|q, %5, 3, 0, 0xc0, p;\n"
                    "cvt.u16.u32 h, %5;\n"
                    "@!q st.shared.u16 [%4], h;\n}" ::"r"(en[k][c]),
                    "r"(sb + SM_EID - (4 - CE) * 4 + p * 4), "r"(es[k][c]), "r"(sb + SM_SRC - (4 - CE) * 2 + p * 2),
                    "r"(sb + SM_SEQ - 2048 + (q >> 16) + (p >> 1)), "r"(q)
                    : "memory");
            }
        };
        fast = lds_u32(sb + SM_MISC + MI_INT) == 0;
        if (fast) {
            place(0);
            place(1);
            if (rest) place(2);
            if (more) place(3);
        }
    }
    TLMAX(14);
    asm volatile("cp.async.bulk.wait_group.read 0;" ::: "memory");
    FENCE_ASYNC();

    if (fast && warp >= 12) {
        asm volatile("setmaxnreg.dec.sync.aligned.u32 %0;" ::"n"(HREG));
        const int w = warp & 1, j = (warp >> 1) & 1;
        const uint2 nk = lds_v2(sb + SM_MISC + MI_INT + 8 + w * 8);
        const int npr = __shfl_sync(0xffffffffu, nk.x, 0), kj = __shfl_sync(0xffffffffu, nk.y, 0) + j;
        const uint32_t bar0 = sb + SM_BAR + w * NP * 16;
        const int blk = (lane >> 4) * 2 + (t >> 1);
        uint32_t fseq = sb + SM_SEQ + w * SEQCAP * 2 + j * 8 + blk * 2;
        const uint32_t feid = sb + SM_EID - 16 + (g & 3) * 4;
        uint32_t pea = sb + SM_EA + w * 4096 + j * 512 + (lane ^ ((lane >> 3) & 1)) * 16;
        const uint32_t psd = sb + SM_SIDE + (warp - 12) * 512 + (lane >> 1) * 16 + (lane & 1) * 4;
        const uint32_t pt = sb + SM_BT + w * (TS * 256) + j * 512 + blk * BT_B + ((lane ^ (lane >> 3)) & 1) * BT_K + (g & 3) * 4;
        const char* gea = (const char*)ea + (lane & 1) * 16;
        uint32_t es, va[2], ta[2], old[2] = {pt, pt}, dea = 2048;
        auto ids = [&]() {
            es = lds_u32(feid + (lds_u16(fseq) & 0xffc) * 4);
            fseq += 16;
        };
        uint32_t wf[4];
        wf[0] = __byte_perm(c0.x, c1.x, 0x5410), wf[1] = __byte_perm(c0.x, c1.x, 0x7632);
        wf[2] = __byte_perm(c0.y, c1.y, 0x5410), wf[3] = __byte_perm(c0.y, c1.y, 0x7632);
        uint32_t vf = bar0 + (kj < NP ? kj : 0) * 16;
        uint32_t pe = kj < NP;
        auto run = [&](auto odd) {
            auto fetch = [&](int i) {
                asm volatile(
                    "{\n.reg .pred p, q;\n.reg .b32 e;\n.reg .b64 a;\n"
                    "setp.lt.s32 p, %0, 0;\n"
                    "and.b32 e, %0, 0x7ffffff8;\n"
                    "mad.wide.u32 a, e, 4, %1;\n"
                    "cp.async.cg.shared.global [%2], [a], 16, p;\n"
                    "}" ::"r"(es), "l"(gea), "r"(pea + i * 1024) : "memory");
                va[i] = psd + (es & 8);
                ta[i] = pt + (es & 7) * 64;
                if (odd.value) {
                    cp_async4(va[i] + i * 256, (const char*)sh + (es & 0x7ffffff8) + (lane & 1) * 4, (int)es >= 0 ? 4 : 0);
                } else {
                    asm volatile(
                        "{\n.reg .pred p;\n.reg .b32 e;\n.reg .b64 a;\n"
                        "setp.lt.s32 p, %0, 0;\n"
                        "and.b32 e, %0, 0x7ffffff0;\n"
                        "mad.wide.u32 a, e, 1, %1;\n"
                        "cp.async.cg.shared.global [%2], [a], 16, p;\n"
                        "}" ::"r"(es), "l"(sh), "r"((psd & ~15) + i * 256) : "memory");
                }
                asm volatile("cp.async.commit_group;" ::: "memory");
                if (i) pea += dea, dea = -dea;
            };
            LISTS();
            ids();
            fetch(0);
            ids();
            fetch(1);
#pragma unroll 1
            for (int m = (npr + 1 - j) >> 1; m > 0;) {
#pragma unroll
                for (int i = 0; i < 2; i++) {
                    asm volatile("cp.async.wait_group 1;" ::: "memory");
                    __syncwarp();
                    const uint32_t v = lds_u32(va[i] + i * 256);
                    ids();
                    float d0[4], d1[4];
                    mma_diag(d0, v, wf[0], wf[1]);
                    mma_diag(d1, v, wf[2], wf[3]);
                    uint32_t vn = vf + 32;
                    if (vn >= bar0 + NP * 16) vn -= NP * 16, pe ^= 1;
                    TWAIT(vn + 8, pe);
#pragma unroll
                    for (int k = 0; k < 4; k++) sts_u32(old[i] + i * 1024 + k * 16, 0);
                    old[i] = ta[i];
                    sts_u32(old[i] + i * 1024, pack_bf16(d0[0], d0[1]));
                    sts_u32(old[i] + i * 1024 + 16, pack_bf16(d0[2], d0[3]));
                    sts_u32(old[i] + i * 1024 + 32, pack_bf16(d1[0], d1[1]));
                    sts_u32(old[i] + i * 1024 + 48, pack_bf16(d1[2], d1[3]));
                    FENCE_ASYNC();
                    fetch(i);
                    __syncwarp();
                    if (lane == 0) mbar_arrive(vf);
                    vf = vn;
                    if (--m <= 0) break;
                }
            }
        };
        if (E & 1) run(std::true_type()); else run(std::false_type());
        asm volatile("cp.async.wait_group 0;" ::: "memory");
        TLMAX(13);
    } else if (fast && warp >= 8) {
        asm volatile("setmaxnreg.dec.sync.aligned.u32 %0;" ::"n"(PREG));
        const int w = warp & 1, j = (warp >> 1) & 1;
        const uint2 nk = lds_v2(sb + SM_MISC + MI_INT + 8 + w * 8);
        const int npr = __shfl_sync(0xffffffffu, nk.x, 0), k0 = __shfl_sync(0xffffffffu, nk.y, 0);
        const uint32_t bar0 = sb + SM_BAR + w * NP * 16, ring = sb + w * RING_BYTES + j * 4096;
        const uint32_t pseq = sb + SM_SEQ + w * SEQCAP * 2 + j * 2;
        const unsigned tbase = lds_u32(sb + SM_MISC + MI_INT + 4);
        const unsigned taug = __float2uint_rz(__fdividef((float)(N * tau16 >> 4), (float)max(npr, 1)));
        produce(&tmx, bar0, ring - j * 2048 - bar0 * 512, pseq + lane * 8, npr, sb + SM_SRC - 8, tbase,
                tbase + (N * tau16 >> 8) + lane * taug, taug * 32, tau16, k0 + lane, lane & (E >> 31), k0 + 32, tau2, brk
        );
        if (elect()) {
            const uint32_t d = ring + (NP - 2) * 8192 + j * 4096;
            const uint32_t fb = bar0 + (NP - 2 + j) * 16, par = ~((lds_u32(sb + SM_MISC + MI_INT + 8 + w * 8) + 1) / NP) & 1;
            mbar_wait(fb + 8, par);
            mbar_arrive_cnt(j ? bar0 + DUMB : fb, j ? 1 : 3);
            mbar_expect_tx(bar0 + DUMB, 16384);
            tma_2d(d + SM_EVEN, &tmw, bar0 + DUMB, j * 64, 0);
            tma_2d(d + SM_ODD, &tmw, bar0 + DUMB, j * 64, 64);
        }
        TLMAX(12);
        const uint32_t swp = lds_u32(sb + SM_MISC + MI_INT + 24) ^ -w;
        const int row = 2 * lane < hpb ? (node0 + ((swp >> lane) & 1) * hpb) * 4 + lane * 8 : N * 4;
        const CUtensorMap* po = &tmo;
        asm volatile("" : "+l"(po));
#pragma unroll
        for (int st = 0; st < 4; st++) {
            int rw[5];
#pragma unroll
            for (int k = 0; k < 5; k++) rw[k] = __shfl_sync(0xffffffffu, row, st < 2 && k == 4 ? JA - 1 + j * 16 : (st >> 1) * JA + 2 * k + j);
            asm volatile("bar.sync %0, 192;" ::"r"(6 + 2 * st + w) : "memory");
            FENCE_ASYNC();
            if (elect()) {
#pragma unroll
                for (int k = 0; k < 5; k++) tma_store(po, ring - j * 3072 + out_at(st, 2 * k), (st & 1) * 64, rw[k]);
                asm volatile("cp.async.bulk.commit_group;" ::: "memory");
            }
        }
        asm volatile("cp.async.bulk.wait_group.read 0;" ::: "memory");
    } else if (fast) {
        const int w = warp >> 2, wq = warp & 3;
        LISTS();
        asm volatile("setmaxnreg.inc.sync.aligned.u32 %0;" ::"n"(CREG));
        const int k0 = __shfl_sync(0xffffffffu, lds_u32(sb + SM_MISC + MI_INT + 12 + w * 8), 0);
        const uint32_t ring = sb + w * RING_BYTES, bar0 = sb + SM_BAR + w * NP * 16;
        float acc[2][NJ][4];
        {
            const int e = (lane >> 1) & 3, m = lane >> 3;
            const int line = 2 * ((lane & 1) + 2 * ((m >> 1) ^ (e >> 1))), ch = 2 * wq + (m & 1);
            const uint32_t xb = ring + (e & 1 ? SM_ODD : SM_EVEN) + (e >> 1) * 1024 + line * 128;
            consume(acc, xb + ((ch ^ ((line + (e & 1)) & 7)) * 16), xb + 128 + ((ch ^ ((line + 1 + (e & 1)) & 7)) * 16),
                    k0 * 8192, bar0, (((sb + SM_EA + w * 4096) & 0x3ffff) >> 4) | (1 << 16),
                    (((sb + SM_BT + w * (TS * 256)) & 0x3ffff) >> 4) | (BT_K / 16 << 16), sb + SM_SEQ + w * SEQCAP * 2, lane & (E >> 31),
                    wa);
        }
        TLMAX(11);
        put_agg<0, JA>(acc, ring + (NJ - JA) * 1024 + wq * (JA * 256) + lane * 16);
        FENCE_ASYNC();
        WG_SYNC(w);
        mbar_wait_u(bar0 + DUMB, 0);
        float oa[JA][4], ob[2][NJ - JA][4];
        mul_out<JA>(oa, ring >> 4, 0, (NJ - JA) * 1024);
        const uint32_t cr = ring + (lane & 7) * 128 + (lane >> 4) * 1024, cc = 2 * wq + ((lane >> 3) & 1);
        const uint32_t ce = cr + (cc ^ (lane & 7)) * 16, co = cr + (cc ^ ((lane + 1) & 7)) * 16;
        put_out<0, JA>(oa, ce, co, w);
        TLMAX(3);
        mul_out<JA>(oa, ring >> 4, 1, (NJ - JA) * 1024);
        put_agg<JA, NJ - JA>(acc, ring + wq * ((NJ - JA) * 256) + lane * 16);
        FENCE_ASYNC();
        WG_SYNC(w);
        put_out<1, JA>(oa, ce, co, w);
        mul_out<NJ - JA>(ob[0], ring >> 4, 0, 0);
        mul_out<NJ - JA>(ob[1], ring >> 4, 1, 0);
        put_out<2, NJ - JA>(ob[0], ce, co, w);
        put_out<3, NJ - JA>(ob[1], ce, co, w);
        TLMAX(15);
    } else {
        float* accs = (float*)smem;
        constexpr int NACC = SM_EID / 2048;
        const int nnodes = max(0, min(npb, N - node0));
#pragma unroll 1
        for (int nb = 0; nb < nnodes; nb += NACC) {
            __syncthreads();
            for (int i = tid; i < NACC * 512; i += NT) accs[i] = 0.f;
            __syncthreads();
#pragma unroll 1
            for (int base = warp * 32; base < E; base += NT) {
                const int e = base + lane;
                int dl = e < E ? dst[e] - node0 - nb : -1;
                if (dl + nb >= nnodes) dl = -1;
                unsigned mask = __ballot_sync(0xffffffffu, dl >= 0 && dl < NACC);
#pragma unroll 1
                while (mask) {
                    const int l = __ffs(mask) - 1;
                    mask &= mask - 1;
                    const int ee = __shfl_sync(0xffffffffu, e, l);
                    const int dd = __shfl_sync(0xffffffffu, dl, l);
                    slow_edge(ee, src[ee], accs + dd * 512, x, sh, ea, cg, wr, lane);
                }
            }
            __syncthreads();
#pragma unroll 1
            for (int nl = warp; nl < NACC && nb + nl < nnodes; nl += NW)
                slow_out(accs + nl * 512, wout, out + (size_t)(node0 + nb + nl) * 512, lane);
        }
        __syncthreads();
    }

    TLMAX(4);
    TLEND();
}

typedef CUresult (*EncodeTiledFn)(CUtensorMap*, CUtensorMapDataType, cuuint32_t, void*, const cuuint64_t*,
                                  const cuuint64_t*, const cuuint32_t*, const cuuint32_t*, CUtensorMapInterleave,
                                  CUtensorMapSwizzle, CUtensorMapL2promotion, CUtensorMapFloatOOBfill);

extern "C" void kernel_launch(void* const* d_in, const int* in_sizes, int n_in, void* d_out, int out_size) {
    const __nv_bfloat16* x = (const __nv_bfloat16*)d_in[0];
    const int* src = (const int*)d_in[1];
    const int* dst = (const int*)d_in[2];
    const __nv_bfloat16* sh = (const __nv_bfloat16*)d_in[3];
    const __nv_bfloat16* ea = (const __nv_bfloat16*)d_in[4];
    const __nv_bfloat16* cg = (const __nv_bfloat16*)d_in[5];
    const __nv_bfloat16* wr = (const __nv_bfloat16*)d_in[6];
    const __nv_bfloat16* wout = (const __nv_bfloat16*)d_in[7];
    __nv_bfloat16* out = (__nv_bfloat16*)d_out;
    const int N = in_sizes[0] / 512;
    const int E = in_sizes[1];

    static int num_sms = 0;
    static EncodeTiledFn encode = nullptr;
    static uint4* gbin = nullptr;
    if (num_sms == 0) {
        int dev = 0;
        cudaGetDevice(&dev);
        cudaDeviceGetAttribute(&num_sms, cudaDevAttrMultiProcessorCount, dev);
        cudaFuncSetAttribute(main_kernel, cudaFuncAttributeMaxDynamicSharedMemorySize, SM_TOTAL + TLX);
        cudaGetSymbolAddress((void**)&gbin, g_bin);
        void* fn = nullptr;
        cudaDriverEntryPointQueryResult qr;
        cudaGetDriverEntryPoint("cuTensorMapEncodeTiled", &fn, cudaEnableDefault, &qr);
        encode = (EncodeTiledFn)fn;
    }
    const int nbins = num_sms < MAXBINS ? num_sms : MAXBINS;
    int npb = ((N + nbins - 1) / nbins + 3) & ~3;
    if (npb < 32) npb = 32;
    const int fast_ok = E > 0 && npb <= 2 * HPB && N <= NBK * 64 && E <= EPS * NT * nbins;
    auto map2d = [&](CUtensorMap* tm, const void* p, int d0, int d1, int b1) {
        const cuuint64_t gd[2] = {(cuuint64_t)d0, (cuuint64_t)d1};
        const cuuint64_t gs[1] = {(cuuint64_t)d0 * 2};
        const cuuint32_t bx[2] = {64, (cuuint32_t)b1};
        const cuuint32_t es[2] = {1, 1};
        encode(tm, CU_TENSOR_MAP_DATA_TYPE_BFLOAT16, 2, (void*)p, gd, gs, bx, es, CU_TENSOR_MAP_INTERLEAVE_NONE,
               CU_TENSOR_MAP_SWIZZLE_128B, CU_TENSOR_MAP_L2_PROMOTION_NONE, CU_TENSOR_MAP_FLOAT_OOB_FILL_NONE);
    };
    CUtensorMap tme, tmx, tmw, tmo;
    {
        const cuuint64_t gd[2] = {(cuuint64_t)nbins * 32, (cuuint64_t)nbins};
        const cuuint64_t gs[1] = {(cuuint64_t)nbins * 128};
        const cuuint32_t bx[2] = {32, (cuuint32_t)nbins};
        const cuuint32_t es[2] = {1, 1};
        encode(&tme, CU_TENSOR_MAP_DATA_TYPE_UINT32, 2, (void*)gbin, gd, gs, bx, es, CU_TENSOR_MAP_INTERLEAVE_NONE,
               CU_TENSOR_MAP_SWIZZLE_NONE, CU_TENSOR_MAP_L2_PROMOTION_NONE, CU_TENSOR_MAP_FLOAT_OOB_FILL_NONE);
    }
    {
        const cuuint64_t gd[2] = {(cuuint64_t)N * 256 - 224, 8};
        const cuuint64_t gs[1] = {128};
        const cuuint32_t bx[2] = {32, 8};
        const cuuint32_t es[2] = {1, 1};
        encode(&tmx, CU_TENSOR_MAP_DATA_TYPE_UINT32, 2, (void*)x, gd, gs, bx, es, CU_TENSOR_MAP_INTERLEAVE_NONE,
               CU_TENSOR_MAP_SWIZZLE_128B, CU_TENSOR_MAP_L2_PROMOTION_NONE, CU_TENSOR_MAP_FLOAT_OOB_FILL_NONE);
    }
    map2d(&tmw, wout, 128, 128, 64);
    map2d(&tmo, out, 128, N * 4, 8);
    const unsigned npb_magic = (unsigned)((0x100000000ull + npb - 1) / npb);
    const int chunk = (E + nbins - 1) / nbins;
    int tau16 = (int)fmin((double)PACE * 16.0 * chunk / N, 100000.0), toff = TOFF, delay = DELAY;
    int tau2 = tau16 * PACE2 / 100, brk = BRK;
    brk = (tau16 - tau2) * (N * brk / 50);
    main_kernel<<<nbins, NT, SM_TOTAL + TLX, cudaStreamPerThread>>>(dst, src, gbin, E, nbins, fast_ok, npb, npb_magic, N, tme, tmx, tmw,
                                                              tmo, x, sh, ea, cg, wr, wout, out, tau16, toff, delay, tau2, brk);
}
```

```cpp
#include <cuda_runtime.h>
#include <cuda.h>
#include <cuda_bf16.h>
#include <stdint.h>
#include <stdlib.h>
#include <type_traits>

#define MAXBINS 160
#define NW 16
#define NT (NW * 32)
#define HPB 38
#define GCAP 280
#define GEXT 72
#define NGR 6
#define LNUL (2 * (NGR * GCAP + GEXT))
#define NBK 160
#define CE 2
#define GSZ 6
#define NS 10
#define RING_BYTES 40960
static_assert(RING_BYTES == NS * 4096, "ring");
#define NP (NS / 2)
#define CREG 224
#define PREG 24
#define HREG 40
#define TS 8
#define SM_EVEN 0
#define SM_MISC (2 * RING_BYTES)
#define SM_ODD (SM_MISC + 128)
#define SM_EA (SM_BT + TS * 4096 + 128)
#define SM_BT (SM_ODD + 2 * RING_BYTES)
#define BT_B (TS * 512 + 16)
#define BT_K (4 * BT_B)
#define SM_SIDE (SM_EA + 8192)
#define SM_EID (SM_SIDE + 2048)
#define SM_SRC (SM_EID + (LNUL + 4) * 4)
#define SEQCAP 408
#define SM_SEQ (SM_SRC + (LNUL + 8) * 2)
#define SM_BAR ((SM_SEQ + 2 * SEQCAP * 2 + 63) / 64 * 64)
#define SM_TOTAL (SM_BAR + NW * (NP > 5 ? 32 : 16))
#define DUMB (2 * NP * 16)
#define MI_INT 0
#define EPS 5
#define SC_ENT 0
#define SC_EXT (SC_ENT + MAXBINS * 128)
#define SC_TAB (SC_EXT + MAXBINS * 64)
#define SC_HIST (SC_TAB + 320)
#define SC_BLK (SC_HIST + MAXBINS * 4 + 128)
#define SC_END (SC_BLK + 2 * (NBK + 2) * 4)
#define SC_WR SC_END
#define SC_CNT (SC_WR + 4352)
static_assert(SC_END % 16 == 0 && SC_HIST % 16 == 0 && SC_END - SC_HIST <= NT * 16 && SC_CNT + 16384 <= SM_MISC && SC_TAB <= 4 * NT * 16 && 2 * HPB <= 80 && MAXBINS >= 24 * NGR, "scratch");
static_assert(LNUL >= 3072 && LNUL + 8 <= 4096 && GCAP % 4 == 0 && GEXT % 4 == 0, "lists");
static_assert(SM_TOTAL <= 232448 && SM_BAR % 16 == 0 && SM_SEQ % 16 == 0 && SM_SRC % 16 == 0 && SM_EA % 256 == 0, "smem");
#define PACE 18.6
#define PACE2 96
#define BRK 85
#define TOFF 9350
#define PSLEEP 20

#define GEX (MAXBINS * MAXBINS * 8)
__device__ __align__(128) uint4 g_bin[GEX + GEX / 2];
#define STR2(x) #x
#define STR(x) STR2(x)
#define TLINIT()
#define TLEND()
#define TLX 0
#define TLSTAMP(i)
#define TLMAX(i)

__device__ __forceinline__ uint32_t pack_bf16(float lo, float hi) {
    uint32_t r;
    asm("cvt.rn.bf16x2.f32 %0, %1, %2;" : "=r"(r) : "f"(hi), "f"(lo));
    return r;
}
__device__ __forceinline__ void mma1688_z(float (&d)[4], uint32_t a0, uint32_t a1, uint32_t b0) {
    asm("mma.sync.aligned.m16n8k8.row.col.f32.bf16.bf16.f32 {%0,%1,%2,%3}, {%4,%5}, {%6}, {%7,%7,%7,%7};"
        : "=f"(d[0]), "=f"(d[1]), "=f"(d[2]), "=f"(d[3])
        : "r"(a0), "r"(a1), "r"(b0), "f"(0.f));
}
__device__ __forceinline__ void mma_diag(float (&d)[4], uint32_t a, uint32_t b0, uint32_t b1) {
    asm("mma.sync.aligned.m16n8k16.row.col.f32.bf16.bf16.f32 {%0,%1,%2,%3}, {%4,%8,%8,%4}, {%5,%6}, {%7,%7,%7,%7};"
        : "=f"(d[0]), "=f"(d[1]), "=f"(d[2]), "=f"(d[3])
        : "r"(a), "r"(b0), "r"(b1), "f"(0.f), "r"(0));
}
__device__ __forceinline__ uint32_t s2u(const void* p) { return (uint32_t)__cvta_generic_to_shared(p); }
__device__ __forceinline__ void mbar_init(uint32_t a, int c) {
    asm volatile("mbarrier.init.shared.b64 [%0], %1;" ::"r"(a), "r"(c));
}
__device__ __forceinline__ void mbar_expect_tx(uint32_t a, int bytes) {
    asm volatile("mbarrier.arrive.expect_tx.shared.b64 _, [%0], %1;" ::"r"(a), "r"(bytes) : "memory");
}
__device__ __forceinline__ void mbar_arrive(uint32_t a) {
    asm volatile("mbarrier.arrive.shared.b64 _, [%0];" ::"r"(a) : "memory");
}
__device__ __forceinline__ void mbar_arrive_cnt(uint32_t a, int c) {
    asm volatile("mbarrier.arrive.shared.b64 _, [%0], %1;" ::"r"(a), "r"(c) : "memory");
}
__device__ __forceinline__ void mbar_wait(uint32_t a, int parity) {
    asm volatile(
        "{\n.reg .pred p;\n.reg .u32 c;\n"
        "mov.u32 c, 0;\n"
        "LAB_WAIT:\n"
        "mbarrier.try_wait.parity.shared.b64 p, [%0], %1, 2000;\n"
        "@p bra DONE;\n"
        "add.u32 c, c, 1;\n"
        "setp.lt.u32 p, c, 2000000;\n"
        "@p bra LAB_WAIT;\n"
        "trap;\n"
        "DONE:\n}" ::"r"(a),
        "r"(parity)
        : "memory");
}
__device__ __forceinline__ void mbar_wait_u(uint32_t a, int parity) {
    asm volatile(
        "{\n.reg .pred p;\n.reg .u32 c;\n"
        "mov.u32 c, 0;\n"
        "LAB_WAIT:\n"
        "mbarrier.try_wait.parity.shared.b64 p, [%0], %1, 2000;\n"
        "@p bra.uni DONE;\n"
        "add.u32 c, c, 1;\n"
        "setp.lt.u32 p, c, 2000000;\n"
        "@p bra.uni LAB_WAIT;\n"
        "trap;\n"
        "DONE:\n}" ::"r"(a),
        "r"(parity)
        : "memory");
}
__device__ __forceinline__ void mbar_spin_u(uint32_t a, int parity) {
    asm volatile(
        "{\n.reg .pred p;\n.reg .u32 c;\n"
        "mov.u32 c, 0;\n"
        "LAB_WAIT:\n"
        "mbarrier.test_wait.parity.shared.b64 p, [%0], %1;\n"
        "@p bra.uni DONE;\n"
        "add.u32 c, c, 1;\n"
        "setp.lt.u32 p, c, 20000000;\n"
        "@p bra.uni LAB_WAIT;\n"
        "trap;\n"
        "DONE:\n}" ::"r"(a),
        "r"(parity)
        : "memory");
}
__device__ __forceinline__ void mbar_lean(uint32_t a, int parity) {
    asm volatile(
        "{\n.reg .pred p;\n.reg .u32 c;\n"
        "mov.u32 c, 0;\n"
        "LAB_WAIT:\n"
        "mbarrier.try_wait.parity.shared.b64 p, [%0], %1;\n"
        "@p bra DONE;\n"
        "add.u32 c, c, 1;\n"
        "setp.lt.u32 p, c, 4000000;\n"
        "@p bra LAB_WAIT;\n"
        "trap;\n"
        "DONE:\n}" ::"r"(a),
        "r"(parity)
        : "memory");
}
__device__ __forceinline__ void mbar_lean_u(uint32_t a, int parity) {
    asm volatile(
        "{\n.reg .pred p;\n.reg .u32 c;\n"
        "mov.u32 c, 0;\n"
        "LAB_WAIT:\n"
        "mbarrier.try_wait.parity.shared.b64 p, [%0], %1;\n"
        "@p bra.uni DONE;\n"
        "add.u32 c, c, 1;\n"
        "setp.lt.u32 p, c, 4000000;\n"
        "@p bra.uni LAB_WAIT;\n"
        "trap;\n"
        "DONE:\n}" ::"r"(a),
        "r"(parity)
        : "memory");
}
__device__ __forceinline__ bool mbar_test(uint32_t a, int parity) {
    uint32_t p;
    asm volatile("{\n.reg .pred P;\nmbarrier.test_wait.parity.shared.b64 P, [%1], %2;\nselp.u32 %0, 1, 0, P;\n}"
                 : "=r"(p)
                 : "r"(a), "r"(parity)
                 : "memory");
    return p;
}
__device__ __forceinline__ bool elect() {
    uint32_t p;
    asm volatile("{\n.reg .pred P;\nelect.sync _|P, 0xffffffff;\nselp.u32 %0, 1, 0, P;\n}" : "=r"(p));
    return p;
}
__device__ __forceinline__ void tma_2d(uint32_t dst, const CUtensorMap* tm, uint32_t bar, int c0, int c1) {
    asm volatile(
        "cp.async.bulk.tensor.2d.shared::cluster.global.mbarrier::complete_tx::bytes [%0], [%1, {%3, %4}], [%2];" ::"r"(dst),
        "l"(tm), "r"(bar), "r"(c0), "r"(c1)
        : "memory");
}
__device__ __forceinline__ void tma_row(uint32_t dst, const CUtensorMap* tm, uint32_t bar, int row8) {
    tma_2d(dst, tm, bar, 0, row8);
}
__device__ __forceinline__ void tma_store(const CUtensorMap* tm, uint32_t src, int c0, int c1) {
    asm volatile("cp.async.bulk.tensor.2d.global.shared::cta.bulk_group [%0, {%2, %3}], [%1];" ::"l"(tm), "r"(src),
                 "r"(c0), "r"(c1)
                 : "memory");
}
__device__ __forceinline__ uint2 lds_v2(uint32_t a) {
    uint2 v;
    asm volatile("ld.shared.v2.u32 {%0,%1}, [%2];" : "=r"(v.x), "=r"(v.y) : "r"(a));
    return v;
}
__device__ __forceinline__ uint4 lds_v4(uint32_t a) {
    uint4 v;
    asm volatile("ld.shared.v4.u32 {%0,%1,%2,%3}, [%4];" : "=r"(v.x), "=r"(v.y), "=r"(v.z), "=r"(v.w) : "r"(a));
    return v;
}
__device__ __forceinline__ uint32_t lds_u32(uint32_t a) {
    uint32_t v;
    asm volatile("ld.shared.u32 %0, [%1];" : "=r"(v) : "r"(a));
    return v;
}
__device__ __forceinline__ uint32_t lds_u16(uint32_t a) {
    uint32_t v;
    asm volatile("ld.shared.u16 %0, [%1];" : "=r"(v) : "r"(a));
    return v;
}
__device__ __forceinline__ void sts_v2(uint32_t a, uint32_t x, uint32_t y) {
    asm volatile("st.shared.v2.u32 [%0], {%1,%2};" ::"r"(a), "r"(x), "r"(y) : "memory");
}
__device__ __forceinline__ void sts_v4(uint32_t a, uint4 v) {
    asm volatile("st.shared.v4.u32 [%0], {%1,%2,%3,%4};" ::"r"(a), "r"(v.x), "r"(v.y), "r"(v.z), "r"(v.w) : "memory");
}
__device__ __forceinline__ void stsm4(uint32_t a, uint32_t r0, uint32_t r1, uint32_t r2, uint32_t r3) {
    asm volatile("stmatrix.sync.aligned.m8n8.x4.shared.b16 [%0], {%1,%2,%3,%4};" ::"r"(a), "r"(r0), "r"(r1), "r"(r2), "r"(r3)
                 : "memory");
}
__device__ __forceinline__ void stsm2(uint32_t a, uint32_t r0, uint32_t r1) {
    asm volatile("stmatrix.sync.aligned.m8n8.x2.shared.b16 [%0], {%1,%2};" ::"r"(a), "r"(r0), "r"(r1) : "memory");
}
__device__ __forceinline__ void stsm4t(uint32_t a, uint32_t r0, uint32_t r1, uint32_t r2, uint32_t r3) {
    asm volatile("stmatrix.sync.aligned.m8n8.x4.trans.shared.b16 [%0], {%1,%2,%3,%4};" ::"r"(a), "r"(r0), "r"(r1), "r"(r2),
                 "r"(r3)
                 : "memory");
}
__device__ __forceinline__ void stsm2t(uint32_t a, uint32_t r0, uint32_t r1) {
    asm volatile("stmatrix.sync.aligned.m8n8.x2.trans.shared.b16 [%0], {%1,%2};" ::"r"(a), "r"(r0), "r"(r1) : "memory");
}
__device__ __forceinline__ void cp_async16(uint32_t d, const void* s, int n) {
    asm volatile("cp.async.cg.shared.global [%0], [%1], 16, %2;" ::"r"(d), "l"(s), "r"(n) : "memory");
}
__device__ __forceinline__ void cp_async4(uint32_t d, const void* s, int n) {
    asm volatile("cp.async.ca.shared.global [%0], [%1], 4, %2;" ::"r"(d), "l"(s), "r"(n) : "memory");
}
__device__ __forceinline__ void sts_u32(uint32_t a, uint32_t x) {
    asm volatile("st.shared.u32 [%0], %1;" ::"r"(a), "r"(x) : "memory");
}
#define FENCE_ASYNC() asm volatile("fence.proxy.async.shared::cta;" ::: "memory")
__device__ __forceinline__ int warp_incl_scan(int v, int lane) {
#pragma unroll
    for (int o = 1; o < 32; o <<= 1) {
        const int y = __shfl_up_sync(0xffffffffu, v, o);
        if (lane >= o) v += y;
    }
    return v;
}

__device__ __forceinline__ uint32_t atoms_add(uint32_t a, uint32_t v) {
    uint32_t r;
    asm volatile("atom.shared.add.u32 %0, [%1], %2;" : "=r"(r) : "r"(a), "r"(v) : "memory");
    return r;
}
__device__ __forceinline__ void sts_u16(uint32_t a, uint32_t x) {
    asm volatile("{\n.reg .b16 h;\ncvt.u16.u32 h, %1;\nst.shared.u16 [%0], h;\n}" ::"r"(a), "r"(x) : "memory");
}
#define NJ 19
__device__ __forceinline__ void consume(float (&acc)[2][NJ][4], uint32_t xa0, uint32_t xa1, uint32_t so0, uint32_t bar0,
                                        uint32_t ea0, uint32_t d0, uint32_t pl0, int lz, const uint32_t (&wa)[8]) {
    asm volatile(
        "{\n"
        ".reg .pred p, pf, plead, pok, t0, t1, t2, u0, u1, u2;\n"
        ".reg .b32 ca, cb, cz, rbar;\n"
        "mov.b32 cz, 0;\n"
        "mov.b32 ca, 0x20002000;\n"
        "mov.b32 cb, 0x30003000;\n"
        ".reg .b32 cnt, so, q, qe, bar, nbar, pl, ctl, ctm, ix, iy, dl, v0, v1, v2, v3, pp;\n"
        ".reg .b16 sl, sh;\n"
        ".reg .b32 hXa0, hXa1, hXa2, hXa3, hXa4, hXa5, hXa6, hXa7, hXb0, hXb1, hXb2, hXb3, hXb4, hXb5, hXb6, hXb7, hYa0, hYa1, hYa2, hYa3, hYa4, hYa5, hYa6, hYa7, hYb0, hYb1, hYb2, hYb3, hYb4, hYb5, hYb6, hYb7, hLa0, hLa1, hLa2, hLa3, hLa4, hLa5, hLa6, hLa7, hLb0, hLb1, hLb2, hLb3, hLb4, hLb5, hLb6, hLb7;\n"
        ".reg .b32 pX0, pX1, pX2, pX3, pY0, pY1, pY2, pY3;\n"
        ".reg .f32 r0, r1, r2, r3, r4, r5, r6, r7, r8, r9, r10, r11, r12, r13, r14, r15;\n"
        ".reg .b64 daX, dbX, daY, dbY, de0, de1;\n"
        ".reg .b32 dh<6>, eb0, par, npar, wa<8>, uz, bend;\n"
        "add.u32 wa0, %160, %159;\n"
        "add.u32 wa1, %161, %159;\n"
        "add.u32 wa2, %162, %159;\n"
        "add.u32 wa3, %163, %159;\n"
        "add.u32 wa4, %164, %159;\n"
        "add.u32 wa5, %165, %159;\n"
        "add.u32 wa6, %166, %159;\n"
        "add.u32 wa7, %167, %159;\n"
        "mov.f32 %0, 0f00000000;\n"
        "mov.f32 %1, 0f00000000;\n"
        "mov.f32 %2, 0f00000000;\n"
        "mov.f32 %3, 0f00000000;\n"
        "mov.f32 %4, 0f00000000;\n"
        "mov.f32 %5, 0f00000000;\n"
        "mov.f32 %6, 0f00000000;\n"
        "mov.f32 %7, 0f00000000;\n"
        "mov.f32 %8, 0f00000000;\n"
        "mov.f32 %9, 0f00000000;\n"
        "mov.f32 %10, 0f00000000;\n"
        "mov.f32 %11, 0f00000000;\n"
        "mov.f32 %12, 0f00000000;\n"
        "mov.f32 %13, 0f00000000;\n"
        "mov.f32 %14, 0f00000000;\n"
        "mov.f32 %15, 0f00000000;\n"
        "mov.f32 %16, 0f00000000;\n"
        "mov.f32 %17, 0f00000000;\n"
        "mov.f32 %18, 0f00000000;\n"
        "mov.f32 %19, 0f00000000;\n"
        "mov.f32 %20, 0f00000000;\n"
        "mov.f32 %21, 0f00000000;\n"
        "mov.f32 %22, 0f00000000;\n"
        "mov.f32 %23, 0f00000000;\n"
        "mov.f32 %24, 0f00000000;\n"
        "mov.f32 %25, 0f00000000;\n"
        "mov.f32 %26, 0f00000000;\n"
        "mov.f32 %27, 0f00000000;\n"
        "mov.f32 %28, 0f00000000;\n"
        "mov.f32 %29, 0f00000000;\n"
        "mov.f32 %30, 0f00000000;\n"
        "mov.f32 %31, 0f00000000;\n"
        "mov.f32 %32, 0f00000000;\n"
        "mov.f32 %33, 0f00000000;\n"
        "mov.f32 %34, 0f00000000;\n"
        "mov.f32 %35, 0f00000000;\n"
        "mov.f32 %36, 0f00000000;\n"
        "mov.f32 %37, 0f00000000;\n"
        "mov.f32 %38, 0f00000000;\n"
        "mov.f32 %39, 0f00000000;\n"
        "mov.f32 %40, 0f00000000;\n"
        "mov.f32 %41, 0f00000000;\n"
        "mov.f32 %42, 0f00000000;\n"
        "mov.f32 %43, 0f00000000;\n"
        "mov.f32 %44, 0f00000000;\n"
        "mov.f32 %45, 0f00000000;\n"
        "mov.f32 %46, 0f00000000;\n"
        "mov.f32 %47, 0f00000000;\n"
        "mov.f32 %48, 0f00000000;\n"
        "mov.f32 %49, 0f00000000;\n"
        "mov.f32 %50, 0f00000000;\n"
        "mov.f32 %51, 0f00000000;\n"
        "mov.f32 %52, 0f00000000;\n"
        "mov.f32 %53, 0f00000000;\n"
        "mov.f32 %54, 0f00000000;\n"
        "mov.f32 %55, 0f00000000;\n"
        "mov.f32 %56, 0f00000000;\n"
        "mov.f32 %57, 0f00000000;\n"
        "mov.f32 %58, 0f00000000;\n"
        "mov.f32 %59, 0f00000000;\n"
        "mov.f32 %60, 0f00000000;\n"
        "mov.f32 %61, 0f00000000;\n"
        "mov.f32 %62, 0f00000000;\n"
        "mov.f32 %63, 0f00000000;\n"
        "mov.f32 %64, 0f00000000;\n"
        "mov.f32 %65, 0f00000000;\n"
        "mov.f32 %66, 0f00000000;\n"
        "mov.f32 %67, 0f00000000;\n"
        "mov.f32 %68, 0f00000000;\n"
        "mov.f32 %69, 0f00000000;\n"
        "mov.f32 %70, 0f00000000;\n"
        "mov.f32 %71, 0f00000000;\n"
        "mov.f32 %72, 0f00000000;\n"
        "mov.f32 %73, 0f00000000;\n"
        "mov.f32 %74, 0f00000000;\n"
        "mov.f32 %75, 0f00000000;\n"
        "mov.f32 %76, 0f00000000;\n"
        "mov.f32 %77, 0f00000000;\n"
        "mov.f32 %78, 0f00000000;\n"
        "mov.f32 %79, 0f00000000;\n"
        "mov.f32 %80, 0f00000000;\n"
        "mov.f32 %81, 0f00000000;\n"
        "mov.f32 %82, 0f00000000;\n"
        "mov.f32 %83, 0f00000000;\n"
        "mov.f32 %84, 0f00000000;\n"
        "mov.f32 %85, 0f00000000;\n"
        "mov.f32 %86, 0f00000000;\n"
        "mov.f32 %87, 0f00000000;\n"
        "mov.f32 %88, 0f00000000;\n"
        "mov.f32 %89, 0f00000000;\n"
        "mov.f32 %90, 0f00000000;\n"
        "mov.f32 %91, 0f00000000;\n"
        "mov.f32 %92, 0f00000000;\n"
        "mov.f32 %93, 0f00000000;\n"
        "mov.f32 %94, 0f00000000;\n"
        "mov.f32 %95, 0f00000000;\n"
        "mov.f32 %96, 0f00000000;\n"
        "mov.f32 %97, 0f00000000;\n"
        "mov.f32 %98, 0f00000000;\n"
        "mov.f32 %99, 0f00000000;\n"
        "mov.f32 %100, 0f00000000;\n"
        "mov.f32 %101, 0f00000000;\n"
        "mov.f32 %102, 0f00000000;\n"
        "mov.f32 %103, 0f00000000;\n"
        "mov.f32 %104, 0f00000000;\n"
        "mov.f32 %105, 0f00000000;\n"
        "mov.f32 %106, 0f00000000;\n"
        "mov.f32 %107, 0f00000000;\n"
        "mov.f32 %108, 0f00000000;\n"
        "mov.f32 %109, 0f00000000;\n"
        "mov.f32 %110, 0f00000000;\n"
        "mov.f32 %111, 0f00000000;\n"
        "mov.f32 %112, 0f00000000;\n"
        "mov.f32 %113, 0f00000000;\n"
        "mov.f32 %114, 0f00000000;\n"
        "mov.f32 %115, 0f00000000;\n"
        "mov.f32 %116, 0f00000000;\n"
        "mov.f32 %117, 0f00000000;\n"
        "mov.f32 %118, 0f00000000;\n"
        "mov.f32 %119, 0f00000000;\n"
        "mov.f32 %120, 0f00000000;\n"
        "mov.f32 %121, 0f00000000;\n"
        "mov.f32 %122, 0f00000000;\n"
        "mov.f32 %123, 0f00000000;\n"
        "mov.f32 %124, 0f00000000;\n"
        "mov.f32 %125, 0f00000000;\n"
        "mov.f32 %126, 0f00000000;\n"
        "mov.f32 %127, 0f00000000;\n"
        "mov.f32 %128, 0f00000000;\n"
        "mov.f32 %129, 0f00000000;\n"
        "mov.f32 %130, 0f00000000;\n"
        "mov.f32 %131, 0f00000000;\n"
        "mov.f32 %132, 0f00000000;\n"
        "mov.f32 %133, 0f00000000;\n"
        "mov.f32 %134, 0f00000000;\n"
        "mov.f32 %135, 0f00000000;\n"
        "mov.f32 %136, 0f00000000;\n"
        "mov.f32 %137, 0f00000000;\n"
        "mov.f32 %138, 0f00000000;\n"
        "mov.f32 %139, 0f00000000;\n"
        "mov.f32 %140, 0f00000000;\n"
        "mov.f32 %141, 0f00000000;\n"
        "mov.f32 %142, 0f00000000;\n"
        "mov.f32 %143, 0f00000000;\n"
        "mov.f32 %144, 0f00000000;\n"
        "mov.f32 %145, 0f00000000;\n"
        "mov.f32 %146, 0f00000000;\n"
        "mov.f32 %147, 0f00000000;\n"
        "mov.f32 %148, 0f00000000;\n"
        "mov.f32 %149, 0f00000000;\n"
        "mov.f32 %150, 0f00000000;\n"
        "mov.f32 %151, 0f00000000;\n"
        "setp.ne.u32 pf, 0, 0;\n"
        "add.u32 v0, %154, %159;\n"
        "shfl.sync.idx.b32 so, v0, 0, 31, 0xffffffff;\n"
        "mov.u32 npar, 0;\n"
        "shfl.sync.idx.b32 uz, %159, 7, 31, 0xffffffff;\n"
        "add.u32 bend, %155, " STR(NP * 16) ";\n"
        "add.u32 v0, %159, 8;\n"
        "shfl.sync.idx.b32 dh0, v0, 0, 31, 0xffffffff;\n"
        "shfl.sync.idx.b32 dh1, v0, 1, 31, 0xffffffff;\n"
        "shfl.sync.idx.b32 dh2, v0, 2, 31, 0xffffffff;\n"
        "shfl.sync.idx.b32 dh3, v0, 3, 31, 0xffffffff;\n"
        "add.u32 v0, %159, 0xc0000010;\n"
        "shfl.sync.idx.b32 dh4, v0, 4, 31, 0xffffffff;\n"
        "shfl.sync.idx.b32 dh5, v0, 5, 31, 0xffffffff;\n"
        "add.u32 v0, %159, %156;\n"
        "shfl.sync.idx.b32 eb0, v0, 0, 31, 0xffffffff;\n"
        "mov.u32 q, 0;\n"
        "mov.u32 pl, %158;\n"
        "shr.u32 nbar, so, 9;\n"
        "add.u32 nbar, nbar, %155;\n"
        "elect.sync _|plead, 0xffffffff;\n"
        "mov.b64 de0, {%156, dh4};\n"
        "mov.b64 de1, {eb0, dh5};\n"
        "mov.b32 hYa0, 0;\n"
        "mov.b32 hYa1, 0;\n"
        "mov.b32 hYa2, 0;\n"
        "mov.b32 hYa3, 0;\n"
        "mov.b32 hYa4, 0;\n"
        "mov.b32 hYa5, 0;\n"
        "mov.b32 hYa6, 0;\n"
        "mov.b32 hYa7, 0;\n"
        "mov.b32 hYb0, 0;\n"
        "mov.b32 hYb1, 0;\n"
        "mov.b32 hYb2, 0;\n"
        "mov.b32 hYb3, 0;\n"
        "mov.b32 hYb4, 0;\n"
        "mov.b32 hYb5, 0;\n"
        "mov.b32 hYb6, 0;\n"
        "mov.b32 hYb7, 0;\n"
        "mov.u32 ctm, 0x10001000;\n"
        "setp.lt.f16x2 t0|u0, ctm, cz;\n"
        "abs.f16x2 v3, ctm;\n"
        "setp.ge.f16x2 t1|u1, v3, ca;\n"
        "setp.geu.f16x2 t2|u2, v3, cb;\n"
        "ld.shared.v2.u32 {ctl, ctm}, [pl];\n"
        "add.u32 pl, pl, 8;\n"
        "add.u32 rbar, %155, " STR(DUMB) ";\n"
        "mov.b64 daX, {%157, dh0};\n"
        "mov.b64 dbX, {%157, dh1};\n"
        "mov.b64 daY, {%157, dh2};\n"
        "mov.b64 dbY, {%157, dh3};\n"
        "mov.u32 bar, nbar;\n"
        "mov.u32 par, npar;\n"
        "sub.u32 so, bar, %155;\n"
        "shl.b32 so, so, 9;\n"
        "add.u32 v0, %152, so;\n"
        "add.u32 v1, %153, so;\n"
        "add.u32 nbar, nbar, 16;\n"
        "setp.eq.u32 p, nbar, bend;\n"
        "selp.b32 nbar, %155, nbar, p;\n"
        "@p xor.b32 npar, npar, 1;\n"
        "SLOW:\n"
        "mov.u32 cnt, 0;\n"
        "W1:\n"
        "mbarrier.try_wait.parity.shared.b64 p, [bar], par;\n"
        "@p bra.uni RES;\n"
        "add.u32 cnt, cnt, 1;\n"
        "setp.lt.u32 p, cnt, 4000000;\n"
        "@p bra.uni W1;\n"
        "trap;\n"
        "CX:\n"
        "mbarrier.test_wait.parity.shared.b64 pok, [nbar], npar;\n"
        "and.b32 dl, q, 0x60;\n"
        "add.u32 dl, dl, %157;\n"
        "add.u32 v3, dl, 0;\n"
        "mov.b64 {v2, dh0}, daX;\n"
        "mov.b64 daX, {v3, dh0};\n"
        "add.u32 v3, dl, 257;\n"
        "mov.b64 {v2, dh1}, dbX;\n"
        "mov.b64 dbX, {v3, dh1};\n"
        "add.u32 v3, dl, 514;\n"
        "mov.b64 {v2, dh2}, daY;\n"
        "mov.b64 daY, {v3, dh2};\n"
        "add.u32 v3, dl, 771;\n"
        "mov.b64 {v2, dh3}, dbY;\n"
        "mov.b64 dbY, {v3, dh3};\n"
        "add.u32 q, q, 32;\n"
        "and.b32 qe, q, 0xe0;\n"
        "add.u32 v3, qe, %156;\n"
        "mov.b64 {v2, dh4}, de0;\n"
        "mov.b64 de0, {v3, dh4};\n"
        "mov.b64 {v2, dh5}, de1;\n"
        "mov.b64 de1, {v3, dh5};\n"
        "setp.lt.f16x2 t0|u0, ctl, cz;\n"
        "abs.f16x2 v3, ctl;\n"
        "setp.ge.f16x2 t1|u1, v3, ca;\n"
        "setp.geu.f16x2 t2|u2, v3, cb;\n"
        "wgmma.wait_group.sync.aligned 2;\n"
        "cvt.rn.bf16x2.f32 pX0, r1, r0;\n"
        "cvt.rn.bf16x2.f32 pX1, r3, r2;\n"
        "cvt.rn.bf16x2.f32 pX2, r9, r8;\n"
        "cvt.rn.bf16x2.f32 pX3, r11, r10;\n"
        "cvt.rn.bf16x2.f32 pY0, r5, r4;\n"
        "cvt.rn.bf16x2.f32 pY1, r7, r6;\n"
        "cvt.rn.bf16x2.f32 pY2, r13, r12;\n"
        "cvt.rn.bf16x2.f32 pY3, r15, r14;\n"
        "mov.b32 {sl, sh}, pX0;\n"
        "mov.b32 pp, {sl, sl};\n"
        "mul.rn.bf16x2 hXa0, hLa0, pp;\n"
        "mul.rn.bf16x2 hXa2, hLa2, pp;\n"
        "mov.b32 {sl, sh}, pX1;\n"
        "mov.b32 pp, {sl, sl};\n"
        "mul.rn.bf16x2 hXa1, hLa1, pp;\n"
        "mul.rn.bf16x2 hXa3, hLa3, pp;\n"
        "mov.b32 {sl, sh}, pX2;\n"
        "mov.b32 pp, {sl, sl};\n"
        "mul.rn.bf16x2 hXa4, hLa4, pp;\n"
        "mul.rn.bf16x2 hXa6, hLa6, pp;\n"
        "mov.b32 {sl, sh}, pX3;\n"
        "mov.b32 pp, {sl, sl};\n"
        "mul.rn.bf16x2 hXa5, hLa5, pp;\n"
        "mul.rn.bf16x2 hXa7, hLa7, pp;\n"
        "mov.b32 {sl, sh}, pX0;\n"
        "mov.b32 pp, {sh, sh};\n"
        "mul.rn.bf16x2 hXb0, hLb0, pp;\n"
        "mul.rn.bf16x2 hXb2, hLb2, pp;\n"
        "mov.b32 {sl, sh}, pX1;\n"
        "mov.b32 pp, {sh, sh};\n"
        "mul.rn.bf16x2 hXb1, hLb1, pp;\n"
        "mul.rn.bf16x2 hXb3, hLb3, pp;\n"
        "mov.b32 {sl, sh}, pX2;\n"
        "mov.b32 pp, {sh, sh};\n"
        "mul.rn.bf16x2 hXb4, hLb4, pp;\n"
        "mul.rn.bf16x2 hXb6, hLb6, pp;\n"
        "mov.b32 {sl, sh}, pX3;\n"
        "mov.b32 pp, {sh, sh};\n"
        "mul.rn.bf16x2 hXb5, hLb5, pp;\n"
        "mul.rn.bf16x2 hXb7, hLb7, pp;\n"
        "ldmatrix.sync.aligned.m8n8.x4.trans.shared.b16 {hLa0,hLa1,hLa2,hLa3}, [v0+4096];\n"
        "ldmatrix.sync.aligned.m8n8.x4.trans.shared.b16 {hLa4,hLa5,hLa6,hLa7}, [v1+4096];\n"
        "ldmatrix.sync.aligned.m8n8.x4.trans.shared.b16 {hLb0,hLb1,hLb2,hLb3}, [v0+6144];\n"
        "ldmatrix.sync.aligned.m8n8.x4.trans.shared.b16 {hLb4,hLb5,hLb6,hLb7}, [v1+6144];\n"
        "@t2 bra.uni T4X;\n"
        "@t1 bra.uni T2X;\n"
        "@t0 bra.uni L1X;\n"
        "L0X:\n"
        "wgmma.fence.sync.aligned;\n"
        "wgmma.mma_async.sync.aligned.m64n24k16.f32.bf16.bf16 {%0,%1,%2,%3,%4,%5,%6,%7,%8,%9,%10,%11}, {hXa0,hXa1,hXa2,hXa3}, daX, 1, 1, 1, 0;\n"
        "wgmma.mma_async.sync.aligned.m64n24k16.f32.bf16.bf16 {%76,%77,%78,%79,%80,%81,%82,%83,%84,%85,%86,%87}, {hXa4,hXa5,hXa6,hXa7}, daX, 1, 1, 1, 0;\n"
        "wgmma.commit_group.sync.aligned;\n"
        "@u2 bra.uni T4Xb;\n"
        "@u1 bra.uni T2Xb;\n"
        "@u0 bra.uni L1Xb;\n"
        "bra.uni L0Xb;\n"
        "L1X:\n"
        "wgmma.fence.sync.aligned;\n"
        "wgmma.mma_async.sync.aligned.m64n24k16.f32.bf16.bf16 {%12,%13,%14,%15,%16,%17,%18,%19,%20,%21,%22,%23}, {hXa0,hXa1,hXa2,hXa3}, daX, 1, 1, 1, 0;\n"
        "wgmma.mma_async.sync.aligned.m64n24k16.f32.bf16.bf16 {%88,%89,%90,%91,%92,%93,%94,%95,%96,%97,%98,%99}, {hXa4,hXa5,hXa6,hXa7}, daX, 1, 1, 1, 0;\n"
        "wgmma.commit_group.sync.aligned;\n"
        "@u2 bra.uni T4Xb;\n"
        "@u1 bra.uni T2Xb;\n"
        "@u0 bra.uni L1Xb;\n"
        "bra.uni L0Xb;\n"
        "T2X:\n"
        "@t0 bra.uni L3X;\n"
        "L2X:\n"
        "wgmma.fence.sync.aligned;\n"
        "wgmma.mma_async.sync.aligned.m64n24k16.f32.bf16.bf16 {%24,%25,%26,%27,%28,%29,%30,%31,%32,%33,%34,%35}, {hXa0,hXa1,hXa2,hXa3}, daX, 1, 1, 1, 0;\n"
        "wgmma.mma_async.sync.aligned.m64n24k16.f32.bf16.bf16 {%100,%101,%102,%103,%104,%105,%106,%107,%108,%109,%110,%111}, {hXa4,hXa5,hXa6,hXa7}, daX, 1, 1, 1, 0;\n"
        "wgmma.commit_group.sync.aligned;\n"
        "@u2 bra.uni T4Xb;\n"
        "@u1 bra.uni T2Xb;\n"
        "@u0 bra.uni L1Xb;\n"
        "bra.uni L0Xb;\n"
        "L3X:\n"
        "wgmma.fence.sync.aligned;\n"
        "wgmma.mma_async.sync.aligned.m64n24k16.f32.bf16.bf16 {%36,%37,%38,%39,%40,%41,%42,%43,%44,%45,%46,%47}, {hXa0,hXa1,hXa2,hXa3}, daX, 1, 1, 1, 0;\n"
        "wgmma.mma_async.sync.aligned.m64n24k16.f32.bf16.bf16 {%112,%113,%114,%115,%116,%117,%118,%119,%120,%121,%122,%123}, {hXa4,hXa5,hXa6,hXa7}, daX, 1, 1, 1, 0;\n"
        "wgmma.commit_group.sync.aligned;\n"
        "@u2 bra.uni T4Xb;\n"
        "@u1 bra.uni T2Xb;\n"
        "@u0 bra.uni L1Xb;\n"
        "bra.uni L0Xb;\n"
        "T4X:\n"
        "@!t1 bra.uni LEXIT;\n"
        "@t0 bra.uni L5X;\n"
        "L4X:\n"
        "wgmma.fence.sync.aligned;\n"
        "wgmma.mma_async.sync.aligned.m64n24k16.f32.bf16.bf16 {%48,%49,%50,%51,%52,%53,%54,%55,%56,%57,%58,%59}, {hXa0,hXa1,hXa2,hXa3}, daX, 1, 1, 1, 0;\n"
        "wgmma.mma_async.sync.aligned.m64n24k16.f32.bf16.bf16 {%124,%125,%126,%127,%128,%129,%130,%131,%132,%133,%134,%135}, {hXa4,hXa5,hXa6,hXa7}, daX, 1, 1, 1, 0;\n"
        "wgmma.commit_group.sync.aligned;\n"
        "@u2 bra.uni T4Xb;\n"
        "@u1 bra.uni T2Xb;\n"
        "@u0 bra.uni L1Xb;\n"
        "bra.uni L0Xb;\n"
        "L5X:\n"
        "wgmma.fence.sync.aligned;\n"
        "wgmma.mma_async.sync.aligned.m64n32k16.f32.bf16.bf16 {%60,%61,%62,%63,%64,%65,%66,%67,%68,%69,%70,%71,%72,%73,%74,%75}, {hXa0,hXa1,hXa2,hXa3}, daX, 1, 1, 1, 0;\n"
        "wgmma.mma_async.sync.aligned.m64n32k16.f32.bf16.bf16 {%136,%137,%138,%139,%140,%141,%142,%143,%144,%145,%146,%147,%148,%149,%150,%151}, {hXa4,hXa5,hXa6,hXa7}, daX, 1, 1, 1, 0;\n"
        "wgmma.commit_group.sync.aligned;\n"
        "@u2 bra.uni T4Xb;\n"
        "@u1 bra.uni T2Xb;\n"
        "@u0 bra.uni L1Xb;\n"
        "L0Xb:\n"
        "wgmma.fence.sync.aligned;\n"
        "wgmma.mma_async.sync.aligned.m64n24k16.f32.bf16.bf16 {%0,%1,%2,%3,%4,%5,%6,%7,%8,%9,%10,%11}, {hXb0,hXb1,hXb2,hXb3}, dbX, 1, 1, 1, 0;\n"
        "wgmma.mma_async.sync.aligned.m64n24k16.f32.bf16.bf16 {%76,%77,%78,%79,%80,%81,%82,%83,%84,%85,%86,%87}, {hXb4,hXb5,hXb6,hXb7}, dbX, 1, 1, 1, 0;\n"
        "wgmma.commit_group.sync.aligned;\n"
        "bra.uni CY;\n"
        "L1Xb:\n"
        "wgmma.fence.sync.aligned;\n"
        "wgmma.mma_async.sync.aligned.m64n24k16.f32.bf16.bf16 {%12,%13,%14,%15,%16,%17,%18,%19,%20,%21,%22,%23}, {hXb0,hXb1,hXb2,hXb3}, dbX, 1, 1, 1, 0;\n"
        "wgmma.mma_async.sync.aligned.m64n24k16.f32.bf16.bf16 {%88,%89,%90,%91,%92,%93,%94,%95,%96,%97,%98,%99}, {hXb4,hXb5,hXb6,hXb7}, dbX, 1, 1, 1, 0;\n"
        "wgmma.commit_group.sync.aligned;\n"
        "bra.uni CY;\n"
        "T2Xb:\n"
        "@u0 bra.uni L3Xb;\n"
        "L2Xb:\n"
        "wgmma.fence.sync.aligned;\n"
        "wgmma.mma_async.sync.aligned.m64n24k16.f32.bf16.bf16 {%24,%25,%26,%27,%28,%29,%30,%31,%32,%33,%34,%35}, {hXb0,hXb1,hXb2,hXb3}, dbX, 1, 1, 1, 0;\n"
        "wgmma.mma_async.sync.aligned.m64n24k16.f32.bf16.bf16 {%100,%101,%102,%103,%104,%105,%106,%107,%108,%109,%110,%111}, {hXb4,hXb5,hXb6,hXb7}, dbX, 1, 1, 1, 0;\n"
        "wgmma.commit_group.sync.aligned;\n"
        "bra.uni CY;\n"
        "L3Xb:\n"
        "wgmma.fence.sync.aligned;\n"
        "wgmma.mma_async.sync.aligned.m64n24k16.f32.bf16.bf16 {%36,%37,%38,%39,%40,%41,%42,%43,%44,%45,%46,%47}, {hXb0,hXb1,hXb2,hXb3}, dbX, 1, 1, 1, 0;\n"
        "wgmma.mma_async.sync.aligned.m64n24k16.f32.bf16.bf16 {%112,%113,%114,%115,%116,%117,%118,%119,%120,%121,%122,%123}, {hXb4,hXb5,hXb6,hXb7}, dbX, 1, 1, 1, 0;\n"
        "wgmma.commit_group.sync.aligned;\n"
        "bra.uni CY;\n"
        "T4Xb:\n"
        "@u0 bra.uni L5Xb;\n"
        "L4Xb:\n"
        "wgmma.fence.sync.aligned;\n"
        "wgmma.mma_async.sync.aligned.m64n24k16.f32.bf16.bf16 {%48,%49,%50,%51,%52,%53,%54,%55,%56,%57,%58,%59}, {hXb0,hXb1,hXb2,hXb3}, dbX, 1, 1, 1, 0;\n"
        "wgmma.mma_async.sync.aligned.m64n24k16.f32.bf16.bf16 {%124,%125,%126,%127,%128,%129,%130,%131,%132,%133,%134,%135}, {hXb4,hXb5,hXb6,hXb7}, dbX, 1, 1, 1, 0;\n"
        "wgmma.commit_group.sync.aligned;\n"
        "bra.uni CY;\n"
        "L5Xb:\n"
        "wgmma.fence.sync.aligned;\n"
        "wgmma.mma_async.sync.aligned.m64n32k16.f32.bf16.bf16 {%60,%61,%62,%63,%64,%65,%66,%67,%68,%69,%70,%71,%72,%73,%74,%75}, {hXb0,hXb1,hXb2,hXb3}, dbX, 1, 1, 1, 0;\n"
        "wgmma.mma_async.sync.aligned.m64n32k16.f32.bf16.bf16 {%136,%137,%138,%139,%140,%141,%142,%143,%144,%145,%146,%147,%148,%149,%150,%151}, {hXb4,hXb5,hXb6,hXb7}, dbX, 1, 1, 1, 0;\n"
        "wgmma.commit_group.sync.aligned;\n"
        "bra.uni CY;\n"
        "CY:\n"
        "mov.u32 rbar, bar;\n"
        "mov.u32 bar, nbar;\n"
        "mov.u32 par, npar;\n"
        "sub.u32 so, bar, %155;\n"
        "shl.b32 so, so, 9;\n"
        "add.u32 v0, %152, so;\n"
        "add.u32 v1, %153, so;\n"
        "add.u32 nbar, nbar, 16;\n"
        "setp.eq.u32 p, nbar, bend;\n"
        "selp.b32 nbar, %155, nbar, p;\n"
        "@p xor.b32 npar, npar, 1;\n"
        "wgmma.wait_group.sync.aligned 2;\n"
        "lop3.b32 v2, hLa3, hLa7, hLb3, 0x80;\n"
        "lop3.b32 v2, v2, hLb7, uz, 0x80;\n"
        "add.u32 v2, v2, rbar;\n"
        "@plead mbarrier.arrive.shared.b64 _, [v2+8];\n"
        "setp.lt.f16x2 t0|u0, ctm, cz;\n"
        "abs.f16x2 v3, ctm;\n"
        "setp.ge.f16x2 t1|u1, v3, ca;\n"
        "setp.geu.f16x2 t2|u2, v3, cb;\n"
        "ld.shared.v2.u32 {ctl, ctm}, [pl];\n"
        "add.u32 pl, pl, 8;\n"
        "mov.b32 {sl, sh}, pY0;\n"
        "mov.b32 pp, {sl, sl};\n"
        "mul.rn.bf16x2 hYa0, hLa0, pp;\n"
        "mul.rn.bf16x2 hYa2, hLa2, pp;\n"
        "mov.b32 {sl, sh}, pY1;\n"
        "mov.b32 pp, {sl, sl};\n"
        "mul.rn.bf16x2 hYa1, hLa1, pp;\n"
        "mul.rn.bf16x2 hYa3, hLa3, pp;\n"
        "mov.b32 {sl, sh}, pY2;\n"
        "mov.b32 pp, {sl, sl};\n"
        "mul.rn.bf16x2 hYa4, hLa4, pp;\n"
        "mul.rn.bf16x2 hYa6, hLa6, pp;\n"
        "mov.b32 {sl, sh}, pY3;\n"
        "mov.b32 pp, {sl, sl};\n"
        "mul.rn.bf16x2 hYa5, hLa5, pp;\n"
        "mul.rn.bf16x2 hYa7, hLa7, pp;\n"
        "mov.b32 {sl, sh}, pY0;\n"
        "mov.b32 pp, {sh, sh};\n"
        "mul.rn.bf16x2 hYb0, hLb0, pp;\n"
        "mul.rn.bf16x2 hYb2, hLb2, pp;\n"
        "mov.b32 {sl, sh}, pY1;\n"
        "mov.b32 pp, {sh, sh};\n"
        "mul.rn.bf16x2 hYb1, hLb1, pp;\n"
        "mul.rn.bf16x2 hYb3, hLb3, pp;\n"
        "mov.b32 {sl, sh}, pY2;\n"
        "mov.b32 pp, {sh, sh};\n"
        "mul.rn.bf16x2 hYb4, hLb4, pp;\n"
        "mul.rn.bf16x2 hYb6, hLb6, pp;\n"
        "mov.b32 {sl, sh}, pY3;\n"
        "mov.b32 pp, {sh, sh};\n"
        "mul.rn.bf16x2 hYb5, hLb5, pp;\n"
        "mul.rn.bf16x2 hYb7, hLb7, pp;\n"
        "@!pok bra.uni SLOW;\n"
        "RES:\n"
        "ldmatrix.sync.aligned.m8n8.x4.trans.shared.b16 {hLa0,hLa1,hLa2,hLa3}, [v0+0];\n"
        "ldmatrix.sync.aligned.m8n8.x4.trans.shared.b16 {hLa4,hLa5,hLa6,hLa7}, [v1+0];\n"
        "ldmatrix.sync.aligned.m8n8.x4.trans.shared.b16 {hLb0,hLb1,hLb2,hLb3}, [v0+2048];\n"
        "ldmatrix.sync.aligned.m8n8.x4.trans.shared.b16 {hLb4,hLb5,hLb6,hLb7}, [v1+2048];\n"
        "wgmma.wait_group.sync.aligned 0;\n"
        "@t2 bra.uni T4Y;\n"
        "@t1 bra.uni T2Y;\n"
        "@t0 bra.uni L1Y;\n"
        "L0Y:\n"
        "wgmma.fence.sync.aligned;\n"
        "wgmma.mma_async.sync.aligned.m64n16k16.f32.bf16.bf16 {r0,r1,r2,r3,r4,r5,r6,r7}, {wa0,wa1,wa2,wa3}, de0, pf, 1, 1, 0;\n"
        "wgmma.mma_async.sync.aligned.m64n16k16.f32.bf16.bf16 {r8,r9,r10,r11,r12,r13,r14,r15}, {wa4,wa5,wa6,wa7}, de1, pf, 1, 1, 0;\n"
        "wgmma.commit_group.sync.aligned;\n"
        "wgmma.mma_async.sync.aligned.m64n24k16.f32.bf16.bf16 {%0,%1,%2,%3,%4,%5,%6,%7,%8,%9,%10,%11}, {hYa0,hYa1,hYa2,hYa3}, daY, 1, 1, 1, 0;\n"
        "wgmma.mma_async.sync.aligned.m64n24k16.f32.bf16.bf16 {%76,%77,%78,%79,%80,%81,%82,%83,%84,%85,%86,%87}, {hYa4,hYa5,hYa6,hYa7}, daY, 1, 1, 1, 0;\n"
        "wgmma.commit_group.sync.aligned;\n"
        "@u2 bra.uni T4Yb;\n"
        "@u1 bra.uni T2Yb;\n"
        "@u0 bra.uni L1Yb;\n"
        "bra.uni L0Yb;\n"
        "L1Y:\n"
        "wgmma.fence.sync.aligned;\n"
        "wgmma.mma_async.sync.aligned.m64n16k16.f32.bf16.bf16 {r0,r1,r2,r3,r4,r5,r6,r7}, {wa0,wa1,wa2,wa3}, de0, pf, 1, 1, 0;\n"
        "wgmma.mma_async.sync.aligned.m64n16k16.f32.bf16.bf16 {r8,r9,r10,r11,r12,r13,r14,r15}, {wa4,wa5,wa6,wa7}, de1, pf, 1, 1, 0;\n"
        "wgmma.commit_group.sync.aligned;\n"
        "wgmma.mma_async.sync.aligned.m64n24k16.f32.bf16.bf16 {%12,%13,%14,%15,%16,%17,%18,%19,%20,%21,%22,%23}, {hYa0,hYa1,hYa2,hYa3}, daY, 1, 1, 1, 0;\n"
        "wgmma.mma_async.sync.aligned.m64n24k16.f32.bf16.bf16 {%88,%89,%90,%91,%92,%93,%94,%95,%96,%97,%98,%99}, {hYa4,hYa5,hYa6,hYa7}, daY, 1, 1, 1, 0;\n"
        "wgmma.commit_group.sync.aligned;\n"
        "@u2 bra.uni T4Yb;\n"
        "@u1 bra.uni T2Yb;\n"
        "@u0 bra.uni L1Yb;\n"
        "bra.uni L0Yb;\n"
        "T2Y:\n"
        "@t0 bra.uni L3Y;\n"
        "L2Y:\n"
        "wgmma.fence.sync.aligned;\n"
        "wgmma.mma_async.sync.aligned.m64n16k16.f32.bf16.bf16 {r0,r1,r2,r3,r4,r5,r6,r7}, {wa0,wa1,wa2,wa3}, de0, pf, 1, 1, 0;\n"
        "wgmma.mma_async.sync.aligned.m64n16k16.f32.bf16.bf16 {r8,r9,r10,r11,r12,r13,r14,r15}, {wa4,wa5,wa6,wa7}, de1, pf, 1, 1, 0;\n"
        "wgmma.commit_group.sync.aligned;\n"
        "wgmma.mma_async.sync.aligned.m64n24k16.f32.bf16.bf16 {%24,%25,%26,%27,%28,%29,%30,%31,%32,%33,%34,%35}, {hYa0,hYa1,hYa2,hYa3}, daY, 1, 1, 1, 0;\n"
        "wgmma.mma_async.sync.aligned.m64n24k16.f32.bf16.bf16 {%100,%101,%102,%103,%104,%105,%106,%107,%108,%109,%110,%111}, {hYa4,hYa5,hYa6,hYa7}, daY, 1, 1, 1, 0;\n"
        "wgmma.commit_group.sync.aligned;\n"
        "@u2 bra.uni T4Yb;\n"
        "@u1 bra.uni T2Yb;\n"
        "@u0 bra.uni L1Yb;\n"
        "bra.uni L0Yb;\n"
        "L3Y:\n"
        "wgmma.fence.sync.aligned;\n"
        "wgmma.mma_async.sync.aligned.m64n16k16.f32.bf16.bf16 {r0,r1,r2,r3,r4,r5,r6,r7}, {wa0,wa1,wa2,wa3}, de0, pf, 1, 1, 0;\n"
        "wgmma.mma_async.sync.aligned.m64n16k16.f32.bf16.bf16 {r8,r9,r10,r11,r12,r13,r14,r15}, {wa4,wa5,wa6,wa7}, de1, pf, 1, 1, 0;\n"
        "wgmma.commit_group.sync.aligned;\n"
        "wgmma.mma_async.sync.aligned.m64n24k16.f32.bf16.bf16 {%36,%37,%38,%39,%40,%41,%42,%43,%44,%45,%46,%47}, {hYa0,hYa1,hYa2,hYa3}, daY, 1, 1, 1, 0;\n"
        "wgmma.mma_async.sync.aligned.m64n24k16.f32.bf16.bf16 {%112,%113,%114,%115,%116,%117,%118,%119,%120,%121,%122,%123}, {hYa4,hYa5,hYa6,hYa7}, daY, 1, 1, 1, 0;\n"
        "wgmma.commit_group.sync.aligned;\n"
        "@u2 bra.uni T4Yb;\n"
        "@u1 bra.uni T2Yb;\n"
        "@u0 bra.uni L1Yb;\n"
        "bra.uni L0Yb;\n"
        "T4Y:\n"
        "@t0 bra.uni L5Y;\n"
        "L4Y:\n"
        "wgmma.fence.sync.aligned;\n"
        "wgmma.mma_async.sync.aligned.m64n16k16.f32.bf16.bf16 {r0,r1,r2,r3,r4,r5,r6,r7}, {wa0,wa1,wa2,wa3}, de0, pf, 1, 1, 0;\n"
        "wgmma.mma_async.sync.aligned.m64n16k16.f32.bf16.bf16 {r8,r9,r10,r11,r12,r13,r14,r15}, {wa4,wa5,wa6,wa7}, de1, pf, 1, 1, 0;\n"
        "wgmma.commit_group.sync.aligned;\n"
        "wgmma.mma_async.sync.aligned.m64n24k16.f32.bf16.bf16 {%48,%49,%50,%51,%52,%53,%54,%55,%56,%57,%58,%59}, {hYa0,hYa1,hYa2,hYa3}, daY, 1, 1, 1, 0;\n"
        "wgmma.mma_async.sync.aligned.m64n24k16.f32.bf16.bf16 {%124,%125,%126,%127,%128,%129,%130,%131,%132,%133,%134,%135}, {hYa4,hYa5,hYa6,hYa7}, daY, 1, 1, 1, 0;\n"
        "wgmma.commit_group.sync.aligned;\n"
        "@u2 bra.uni T4Yb;\n"
        "@u1 bra.uni T2Yb;\n"
        "@u0 bra.uni L1Yb;\n"
        "bra.uni L0Yb;\n"
        "L5Y:\n"
        "wgmma.fence.sync.aligned;\n"
        "wgmma.mma_async.sync.aligned.m64n16k16.f32.bf16.bf16 {r0,r1,r2,r3,r4,r5,r6,r7}, {wa0,wa1,wa2,wa3}, de0, pf, 1, 1, 0;\n"
        "wgmma.mma_async.sync.aligned.m64n16k16.f32.bf16.bf16 {r8,r9,r10,r11,r12,r13,r14,r15}, {wa4,wa5,wa6,wa7}, de1, pf, 1, 1, 0;\n"
        "wgmma.commit_group.sync.aligned;\n"
        "wgmma.mma_async.sync.aligned.m64n32k16.f32.bf16.bf16 {%60,%61,%62,%63,%64,%65,%66,%67,%68,%69,%70,%71,%72,%73,%74,%75}, {hYa0,hYa1,hYa2,hYa3}, daY, 1, 1, 1, 0;\n"
        "wgmma.mma_async.sync.aligned.m64n32k16.f32.bf16.bf16 {%136,%137,%138,%139,%140,%141,%142,%143,%144,%145,%146,%147,%148,%149,%150,%151}, {hYa4,hYa5,hYa6,hYa7}, daY, 1, 1, 1, 0;\n"
        "wgmma.commit_group.sync.aligned;\n"
        "@u2 bra.uni T4Yb;\n"
        "@u1 bra.uni T2Yb;\n"
        "@u0 bra.uni L1Yb;\n"
        "L0Yb:\n"
        "wgmma.fence.sync.aligned;\n"
        "wgmma.mma_async.sync.aligned.m64n24k16.f32.bf16.bf16 {%0,%1,%2,%3,%4,%5,%6,%7,%8,%9,%10,%11}, {hYb0,hYb1,hYb2,hYb3}, dbY, 1, 1, 1, 0;\n"
        "wgmma.mma_async.sync.aligned.m64n24k16.f32.bf16.bf16 {%76,%77,%78,%79,%80,%81,%82,%83,%84,%85,%86,%87}, {hYb4,hYb5,hYb6,hYb7}, dbY, 1, 1, 1, 0;\n"
        "wgmma.commit_group.sync.aligned;\n"
        "bra.uni CX;\n"
        "L1Yb:\n"
        "wgmma.fence.sync.aligned;\n"
        "wgmma.mma_async.sync.aligned.m64n24k16.f32.bf16.bf16 {%12,%13,%14,%15,%16,%17,%18,%19,%20,%21,%22,%23}, {hYb0,hYb1,hYb2,hYb3}, dbY, 1, 1, 1, 0;\n"
        "wgmma.mma_async.sync.aligned.m64n24k16.f32.bf16.bf16 {%88,%89,%90,%91,%92,%93,%94,%95,%96,%97,%98,%99}, {hYb4,hYb5,hYb6,hYb7}, dbY, 1, 1, 1, 0;\n"
        "wgmma.commit_group.sync.aligned;\n"
        "bra.uni CX;\n"
        "T2Yb:\n"
        "@u0 bra.uni L3Yb;\n"
        "L2Yb:\n"
        "wgmma.fence.sync.aligned;\n"
        "wgmma.mma_async.sync.aligned.m64n24k16.f32.bf16.bf16 {%24,%25,%26,%27,%28,%29,%30,%31,%32,%33,%34,%35}, {hYb0,hYb1,hYb2,hYb3}, dbY, 1, 1, 1, 0;\n"
        "wgmma.mma_async.sync.aligned.m64n24k16.f32.bf16.bf16 {%100,%101,%102,%103,%104,%105,%106,%107,%108,%109,%110,%111}, {hYb4,hYb5,hYb6,hYb7}, dbY, 1, 1, 1, 0;\n"
        "wgmma.commit_group.sync.aligned;\n"
        "bra.uni CX;\n"
        "L3Yb:\n"
        "wgmma.fence.sync.aligned;\n"
        "wgmma.mma_async.sync.aligned.m64n24k16.f32.bf16.bf16 {%36,%37,%38,%39,%40,%41,%42,%43,%44,%45,%46,%47}, {hYb0,hYb1,hYb2,hYb3}, dbY, 1, 1, 1, 0;\n"
        "wgmma.mma_async.sync.aligned.m64n24k16.f32.bf16.bf16 {%112,%113,%114,%115,%116,%117,%118,%119,%120,%121,%122,%123}, {hYb4,hYb5,hYb6,hYb7}, dbY, 1, 1, 1, 0;\n"
        "wgmma.commit_group.sync.aligned;\n"
        "bra.uni CX;\n"
        "T4Yb:\n"
        "@u0 bra.uni L5Yb;\n"
        "L4Yb:\n"
        "wgmma.fence.sync.aligned;\n"
        "wgmma.mma_async.sync.aligned.m64n24k16.f32.bf16.bf16 {%48,%49,%50,%51,%52,%53,%54,%55,%56,%57,%58,%59}, {hYb0,hYb1,hYb2,hYb3}, dbY, 1, 1, 1, 0;\n"
        "wgmma.mma_async.sync.aligned.m64n24k16.f32.bf16.bf16 {%124,%125,%126,%127,%128,%129,%130,%131,%132,%133,%134,%135}, {hYb4,hYb5,hYb6,hYb7}, dbY, 1, 1, 1, 0;\n"
        "wgmma.commit_group.sync.aligned;\n"
        "bra.uni CX;\n"
        "L5Yb:\n"
        "wgmma.fence.sync.aligned;\n"
        "wgmma.mma_async.sync.aligned.m64n32k16.f32.bf16.bf16 {%60,%61,%62,%63,%64,%65,%66,%67,%68,%69,%70,%71,%72,%73,%74,%75}, {hYb0,hYb1,hYb2,hYb3}, dbY, 1, 1, 1, 0;\n"
        "wgmma.mma_async.sync.aligned.m64n32k16.f32.bf16.bf16 {%136,%137,%138,%139,%140,%141,%142,%143,%144,%145,%146,%147,%148,%149,%150,%151}, {hYb4,hYb5,hYb6,hYb7}, dbY, 1, 1, 1, 0;\n"
        "wgmma.commit_group.sync.aligned;\n"
        "bra.uni CX;\n"
        "LEXIT:\n"
        "wgmma.wait_group.sync.aligned 0;\n"
        "}\n"
        : "=f"(acc[0][0][0]), "=f"(acc[0][0][1]), "=f"(acc[0][0][2]), "=f"(acc[0][0][3]),
          "=f"(acc[0][1][0]), "=f"(acc[0][1][1]), "=f"(acc[0][1][2]), "=f"(acc[0][1][3]),
          "=f"(acc[0][2][0]), "=f"(acc[0][2][1]), "=f"(acc[0][2][2]), "=f"(acc[0][2][3]),
          "=f"(acc[0][3][0]), "=f"(acc[0][3][1]), "=f"(acc[0][3][2]), "=f"(acc[0][3][3]),
          "=f"(acc[0][4][0]), "=f"(acc[0][4][1]), "=f"(acc[0][4][2]), "=f"(acc[0][4][3]),
          "=f"(acc[0][5][0]), "=f"(acc[0][5][1]), "=f"(acc[0][5][2]), "=f"(acc[0][5][3]),
          "=f"(acc[0][6][0]), "=f"(acc[0][6][1]), "=f"(acc[0][6][2]), "=f"(acc[0][6][3]),
          "=f"(acc[0][7][0]), "=f"(acc[0][7][1]), "=f"(acc[0][7][2]), "=f"(acc[0][7][3]),
          "=f"(acc[0][8][0]), "=f"(acc[0][8][1]), "=f"(acc[0][8][2]), "=f"(acc[0][8][3]),
          "=f"(acc[0][9][0]), "=f"(acc[0][9][1]), "=f"(acc[0][9][2]), "=f"(acc[0][9][3]),
          "=f"(acc[0][10][0]), "=f"(acc[0][10][1]), "=f"(acc[0][10][2]), "=f"(acc[0][10][3]),
          "=f"(acc[0][11][0]), "=f"(acc[0][11][1]), "=f"(acc[0][11][2]), "=f"(acc[0][11][3]),
          "=f"(acc[0][12][0]), "=f"(acc[0][12][1]), "=f"(acc[0][12][2]), "=f"(acc[0][12][3]),
          "=f"(acc[0][13][0]), "=f"(acc[0][13][1]), "=f"(acc[0][13][2]), "=f"(acc[0][13][3]),
          "=f"(acc[0][14][0]), "=f"(acc[0][14][1]), "=f"(acc[0][14][2]), "=f"(acc[0][14][3]),
          "=f"(acc[0][15][0]), "=f"(acc[0][15][1]), "=f"(acc[0][15][2]), "=f"(acc[0][15][3]),
          "=f"(acc[0][16][0]), "=f"(acc[0][16][1]), "=f"(acc[0][16][2]), "=f"(acc[0][16][3]),
          "=f"(acc[0][17][0]), "=f"(acc[0][17][1]), "=f"(acc[0][17][2]), "=f"(acc[0][17][3]),
          "=f"(acc[0][18][0]), "=f"(acc[0][18][1]), "=f"(acc[0][18][2]), "=f"(acc[0][18][3]),
          "=f"(acc[1][0][0]), "=f"(acc[1][0][1]), "=f"(acc[1][0][2]), "=f"(acc[1][0][3]),
          "=f"(acc[1][1][0]), "=f"(acc[1][1][1]), "=f"(acc[1][1][2]), "=f"(acc[1][1][3]),
          "=f"(acc[1][2][0]), "=f"(acc[1][2][1]), "=f"(acc[1][2][2]), "=f"(acc[1][2][3]),
          "=f"(acc[1][3][0]), "=f"(acc[1][3][1]), "=f"(acc[1][3][2]), "=f"(acc[1][3][3]),
          "=f"(acc[1][4][0]), "=f"(acc[1][4][1]), "=f"(acc[1][4][2]), "=f"(acc[1][4][3]),
          "=f"(acc[1][5][0]), "=f"(acc[1][5][1]), "=f"(acc[1][5][2]), "=f"(acc[1][5][3]),
          "=f"(acc[1][6][0]), "=f"(acc[1][6][1]), "=f"(acc[1][6][2]), "=f"(acc[1][6][3]),
          "=f"(acc[1][7][0]), "=f"(acc[1][7][1]), "=f"(acc[1][7][2]), "=f"(acc[1][7][3]),
          "=f"(acc[1][8][0]), "=f"(acc[1][8][1]), "=f"(acc[1][8][2]), "=f"(acc[1][8][3]),
          "=f"(acc[1][9][0]), "=f"(acc[1][9][1]), "=f"(acc[1][9][2]), "=f"(acc[1][9][3]),
          "=f"(acc[1][10][0]), "=f"(acc[1][10][1]), "=f"(acc[1][10][2]), "=f"(acc[1][10][3]),
          "=f"(acc[1][11][0]), "=f"(acc[1][11][1]), "=f"(acc[1][11][2]), "=f"(acc[1][11][3]),
          "=f"(acc[1][12][0]), "=f"(acc[1][12][1]), "=f"(acc[1][12][2]), "=f"(acc[1][12][3]),
          "=f"(acc[1][13][0]), "=f"(acc[1][13][1]), "=f"(acc[1][13][2]), "=f"(acc[1][13][3]),
          "=f"(acc[1][14][0]), "=f"(acc[1][14][1]), "=f"(acc[1][14][2]), "=f"(acc[1][14][3]),
          "=f"(acc[1][15][0]), "=f"(acc[1][15][1]), "=f"(acc[1][15][2]), "=f"(acc[1][15][3]),
          "=f"(acc[1][16][0]), "=f"(acc[1][16][1]), "=f"(acc[1][16][2]), "=f"(acc[1][16][3]),
          "=f"(acc[1][17][0]), "=f"(acc[1][17][1]), "=f"(acc[1][17][2]), "=f"(acc[1][17][3]),
          "=f"(acc[1][18][0]), "=f"(acc[1][18][1]), "=f"(acc[1][18][2]), "=f"(acc[1][18][3])
        : "r"(xa0), "r"(xa1), "r"(so0), "r"(bar0), "r"(ea0), "r"(d0), "r"(pl0), "r"(lz), "r"(wa[0]), "r"(wa[1]), "r"(wa[2]),
          "r"(wa[3]), "r"(wa[4]), "r"(wa[5]), "r"(wa[6]), "r"(wa[7])
        : "memory");
}
#define JA 9
__device__ __forceinline__ void wgmma_out(float (&o)[9][4], uint64_t da, uint64_t db, int acc) {
    asm volatile(
        "{\n.reg .pred p;\nsetp.ne.b32 p, %38, 0;\n"
        "wgmma.mma_async.sync.aligned.m64n72k16.f32.bf16.bf16 {%0,%1,%2,%3,%4,%5,%6,%7,%8,%9,%10,%11,%12,%13,%14,%15,%16,%17,%18,%19,%20,%21,%22,%23,%24,%25,%26,%27,%28,%29,%30,%31,%32,%33,%34,%35}, %36, %37, p, 1, 1, 1, 1;\n}"
        : "+f"(o[0][0]), "+f"(o[0][1]), "+f"(o[0][2]), "+f"(o[0][3]),
          "+f"(o[1][0]), "+f"(o[1][1]), "+f"(o[1][2]), "+f"(o[1][3]),
          "+f"(o[2][0]), "+f"(o[2][1]), "+f"(o[2][2]), "+f"(o[2][3]),
          "+f"(o[3][0]), "+f"(o[3][1]), "+f"(o[3][2]), "+f"(o[3][3]),
          "+f"(o[4][0]), "+f"(o[4][1]), "+f"(o[4][2]), "+f"(o[4][3]),
          "+f"(o[5][0]), "+f"(o[5][1]), "+f"(o[5][2]), "+f"(o[5][3]),
          "+f"(o[6][0]), "+f"(o[6][1]), "+f"(o[6][2]), "+f"(o[6][3]),
          "+f"(o[7][0]), "+f"(o[7][1]), "+f"(o[7][2]), "+f"(o[7][3]),
          "+f"(o[8][0]), "+f"(o[8][1]), "+f"(o[8][2]), "+f"(o[8][3])
        : "l"(da), "l"(db), "r"(acc));
}
__device__ __forceinline__ void wgmma_out(float (&o)[10][4], uint64_t da, uint64_t db, int acc) {
    asm volatile(
        "{\n.reg .pred p;\nsetp.ne.b32 p, %42, 0;\n"
        "wgmma.mma_async.sync.aligned.m64n80k16.f32.bf16.bf16 {%0,%1,%2,%3,%4,%5,%6,%7,%8,%9,%10,%11,%12,%13,%14,%15,%16,%17,%18,%19,%20,%21,%22,%23,%24,%25,%26,%27,%28,%29,%30,%31,%32,%33,%34,%35,%36,%37,%38,%39}, %40, %41, p, 1, 1, 1, 1;\n}"
        : "+f"(o[0][0]), "+f"(o[0][1]), "+f"(o[0][2]), "+f"(o[0][3]),
          "+f"(o[1][0]), "+f"(o[1][1]), "+f"(o[1][2]), "+f"(o[1][3]),
          "+f"(o[2][0]), "+f"(o[2][1]), "+f"(o[2][2]), "+f"(o[2][3]),
          "+f"(o[3][0]), "+f"(o[3][1]), "+f"(o[3][2]), "+f"(o[3][3]),
          "+f"(o[4][0]), "+f"(o[4][1]), "+f"(o[4][2]), "+f"(o[4][3]),
          "+f"(o[5][0]), "+f"(o[5][1]), "+f"(o[5][2]), "+f"(o[5][3]),
          "+f"(o[6][0]), "+f"(o[6][1]), "+f"(o[6][2]), "+f"(o[6][3]),
          "+f"(o[7][0]), "+f"(o[7][1]), "+f"(o[7][2]), "+f"(o[7][3]),
          "+f"(o[8][0]), "+f"(o[8][1]), "+f"(o[8][2]), "+f"(o[8][3]),
          "+f"(o[9][0]), "+f"(o[9][1]), "+f"(o[9][2]), "+f"(o[9][3])
        : "l"(da), "l"(db), "r"(acc));
}

__device__ __forceinline__ void slow_edge(int ee, int s, float* accn, const __nv_bfloat16* __restrict__ x,
                                          const __nv_bfloat16* __restrict__ sh, const __nv_bfloat16* __restrict__ ea,
                                          const __nv_bfloat16* __restrict__ cg, const __nv_bfloat16* __restrict__ wr,
                                          int lane) {
    float rwv[4] = {0.f, 0.f, 0.f, 0.f};
#pragma unroll 4
    for (int d = 0; d < 16; d++) {
        const float a = __bfloat162float(ea[(size_t)ee * 16 + d]);
        const uint2 wv = *(const uint2*)(wr + d * 128 + lane * 4);
        rwv[0] += a * __uint_as_float(wv.x << 16);
        rwv[1] += a * __uint_as_float(wv.x & 0xffff0000u);
        rwv[2] += a * __uint_as_float(wv.y << 16);
        rwv[3] += a * __uint_as_float(wv.y & 0xffff0000u);
    }
    float A = 0.f;
#pragma unroll
    for (int v = 0; v < 4; v++)
        A += __bfloat162float(cg[((lane >> 2) & 3) * 16 + v * 4 + (lane & 3)]) * __bfloat162float(sh[(size_t)ee * 4 + v]);
    float m[4][4];
#pragma unroll
    for (int w = 0; w < 4; w++)
#pragma unroll
        for (int j = 0; j < 4; j++) m[w][j] = 0.f;
#pragma unroll
    for (int u = 0; u < 4; u++) {
        const uint2 xv = *(const uint2*)(x + (size_t)s * 512 + u * 128 + lane * 4);
        const float x0 = __uint_as_float(xv.x << 16), x1 = __uint_as_float(xv.x & 0xffff0000u);
        const float x2 = __uint_as_float(xv.y << 16), x3 = __uint_as_float(xv.y & 0xffff0000u);
#pragma unroll
        for (int w = 0; w < 4; w++) {
            const float a = __shfl_sync(0xffffffffu, A, u * 4 + w);
            m[w][0] += a * x0;
            m[w][1] += a * x1;
            m[w][2] += a * x2;
            m[w][3] += a * x3;
        }
    }
#pragma unroll
    for (int w = 0; w < 4; w++)
#pragma unroll
        for (int j = 0; j < 4; j++) atomicAdd(accn + w * 128 + lane * 4 + j, m[w][j] * rwv[j]);
}

__device__ __forceinline__ void slow_out(const float* accn, const __nv_bfloat16* __restrict__ wout,
                                         __nv_bfloat16* __restrict__ outn, int lane) {
    float o[4][4];
#pragma unroll
    for (int w = 0; w < 4; w++)
#pragma unroll
        for (int j = 0; j < 4; j++) o[w][j] = 0.f;
#pragma unroll 2
    for (int c = 0; c < 128; c++) {
        const uint2 wv = *(const uint2*)(wout + c * 128 + lane * 4);
        const float w0 = __uint_as_float(wv.x << 16), w1 = __uint_as_float(wv.x & 0xffff0000u);
        const float w2 = __uint_as_float(wv.y << 16), w3 = __uint_as_float(wv.y & 0xffff0000u);
#pragma unroll
        for (int w = 0; w < 4; w++) {
            const float a = __bfloat162float(__float2bfloat16(accn[w * 128 + c]));
            o[w][0] += a * w0;
            o[w][1] += a * w1;
            o[w][2] += a * w2;
            o[w][3] += a * w3;
        }
    }
#pragma unroll
    for (int w = 0; w < 4; w++)
        *(uint2*)(outn + w * 128 + lane * 4) = make_uint2(pack_bf16(o[w][0], o[w][1]), pack_bf16(o[w][2], o[w][3]));
}

static_assert(NW > 2 * NP, "barriers");
#define FPOS 1
#define PW 0
#define TWAIT mbar_lean_u
#define PWAIT mbar_lean
#define TMA_ROW(k) "@pl cp.async.bulk.tensor.2d.shared::cluster.global.mbarrier::complete_tx::bytes [d" #k "], [tm, {r" #k ", z" #k "}], [b" #k "];\n"
#define TMA_INIT(k, o) "shfl.sync.idx.b32 z" #k ", %11, " #k ", 31, 0xffffffff;\nadd.u32 m" #k ", %2, " STR(o) ";\nadd.u32 m" #k ", m" #k ", %11;\nshfl.sync.idx.b32 m" #k ", m" #k ", 0, 31, 0xffffffff;\n"
#define TMA_PREP(k) "mad.lo.u32 d" #k ", dd, 512, m" #k ";\nadd.u32 b" #k ", dd, z" #k ";\n"
#define RDCLK(c) "mov.u64 ck, %%clock64;\ncvt.u32.u64 " c ", ck;\n"
#define BCAST(d, k) "selp.b32 " d ", a" #k ", 0, me;\nredux.sync.or.b32 " d ", " d ", 0xffffffff;\n"
#define PTIME(t, x, y, z) "shr.u32 " t ", " x ", 16;\nand.b32 c, " y ", 0xffff;\nadd.u32 " t ", " t ", c;\nmad.lo.u32 c, " t ", %13, %14;\nmul.lo.u32 " t ", " t ", %9;\nmin.u32 " t ", " t ", c;\nshr.u32 " t ", " t ", 5;\nadd.u32 " t ", " t ", %6;\nmin.u32 " t ", " t ", lim;\nlop3.b32 " t ", " t ", " z ", 7, 0xd8;\n"
#define PROWS(s, x, y) "and.b32 t0, " s ", 0xffc;\nsetp.gt.u32 p, t0, " STR(LNUL / 2) ";\nmad.lo.u32 t0, t0, 2, %5;\nld.shared.v2.u32 {" x ", " y "}, [t0];\nshr.u32 t0, " s ", 11;\nand.b32 t0, t0, 6;\nshr.u32 " s ", " s ", 15;\nadd.u32 t0, t0, " s ";\nselp.s32 " s ", " STR(NGR - 2) ", -2, p;\nadd.u32 t0, t0, " s ";\nmul.lo.s32 t0, t0, " STR(-NBK * 64) ";\nprmt.b32 t0, t0, 0, 0x1010;\nadd.u16x2 " x ", " x ", t0;\nadd.u16x2 " y ", " y ", t0;\n"
__device__ __forceinline__ void produce(const CUtensorMap* tm, uint32_t bar, uint32_t d0, uint32_t ps, int nit, uint32_t psrc,
                                        uint32_t tbase, uint32_t lim, uint32_t taug64, uint32_t taus, uint32_t n, int lz, int pr0,
                                        uint32_t tau2, uint32_t brk
) {
    asm volatile(
        "{\n.reg .pred p, pl, ok, me;\n.reg .b32 a<6>, u<4>, r<8>, d<8>, b<8>, z<8>, m<8>, ps, lim, n, it, pr, pe, tgt, tgu, c, dd, dn, par, t0, t1;\n"
        ".reg .b64 st, tm, ck;\n"
        "elect.sync _|pl, 0xffffffff;\n"
        TMA_INIT(0, 0) TMA_INIT(1, SM_ODD) TMA_INIT(2, 1024) TMA_INIT(3, SM_ODD + 1024)
        TMA_INIT(4, 4096) TMA_INIT(5, SM_ODD + 4096) TMA_INIT(6, 5120) TMA_INIT(7, SM_ODD + 5120)
        "mov.b64 {a0, a1}, %0;\n"
        "add.u32 a0, a0, %11;\n"
        "add.u32 a1, a1, %11;\n"
        "shfl.sync.idx.b32 a0, a0, 0, 31, 0xffffffff;\n"
        "shfl.sync.idx.b32 a1, a1, 0, 31, 0xffffffff;\n"
        "mov.b64 tm, {a0, a1};\n"
        "mov.u32 ps, %3;\n"
        "mov.u32 it, %4;\n"
        "mov.u32 lim, %7;\n"
        "mov.u32 n, %10;\n"
        "mov.u32 pr, %12;\n"
        "setp.le.s32 p, it, 0;\n"
        "bar.sync 0;\n"
        "@p bra.uni PEND;\n"
        "PBAT:\n"
        "ld.shared.u16 c, [ps];\n"
        "ld.shared.u16 t1, [ps+4];\n"
        "add.u32 ps, ps, 256;\n"
        "mul.lo.u32 par, n, " STR(65536 / NP + 1) ";\n"
        "shr.u32 par, par, 16;\n"
        "mad.lo.s32 dn, par, " STR(-NP) ", n;\n"
        "add.u32 n, n, 32;\n"
        "not.b32 par, par;\n"
        PROWS("c", "a0", "a1") PROWS("t1", "a2", "a3")
        "min.s32 pe, it, 32;\n"
        "sub.s32 it, it, 32;\n"
        "add.u32 pe, pe, pr;\n"
        PTIME("a4", "a0", "a1", "dn") PTIME("a5", "a2", "a3", "par")
        "add.u32 lim, lim, %8;\n"
        "PLOOP:\n"
        "setp.eq.u32 me, n, pr;\n"
        "add.u32 pr, pr, 1;\n"
        BCAST("tgt", 4) BCAST("tgu", 5) BCAST("u0", 0) BCAST("u1", 1) BCAST("u2", 2) BCAST("u3", 3)
        "and.b32 dd, tgt, 7;\n"
        "mad.lo.u32 dd, dd, 16, %1;\n"
        "and.b32 par, tgu, 1;\n"
        "mbarrier.test_wait.parity.shared.b64 ok, [dd+8], par;\n"
        "prmt.b32 r0, u0, 0, 0x4104;\nprmt.b32 r1, u0, 0, 0x4324;\nprmt.b32 r2, u1, 0, 0x4104;\nprmt.b32 r3, u1, 0, 0x4324;\n"
        "prmt.b32 r4, u2, 0, 0x4104;\nprmt.b32 r5, u2, 0, 0x4324;\nprmt.b32 r6, u3, 0, 0x4104;\nprmt.b32 r7, u3, 0, 0x4324;\n"
        TMA_PREP(0) TMA_PREP(1) TMA_PREP(2) TMA_PREP(3) TMA_PREP(4) TMA_PREP(5) TMA_PREP(6) TMA_PREP(7)
        RDCLK("c")
        "sub.s32 c, c, tgt;\n"
        "setp.ge.and.s32 p, c, 0, ok;\n"
        "@!p bra.uni PSLP;\n"
        "PRES:\n"
        "@pl mbarrier.arrive.expect_tx.shared.b64 _, [b0], 8192;\n"
        TMA_ROW(0) TMA_ROW(1) TMA_ROW(2) TMA_ROW(3)
        RDCLK("c")
        "sub.s32 c, c, tgu;\n"
        "setp.lt.s32 p, c, 0;\n"
        "@p bra.uni PSL2;\n"
        "PRE2:\n"
        TMA_ROW(4) TMA_ROW(5) TMA_ROW(6) TMA_ROW(7)
        "setp.lt.u32 p, pr, pe;\n"
        "@p bra.uni PLOOP;\n"
        "setp.gt.s32 p, it, 0;\n"
        "@p bra.uni PBAT;\n"
        "bra.uni PEND;\n"
        "PSL2:\n"
        "nanosleep.u32 " STR(PSLEEP) ";\n"
        RDCLK("c")
        "sub.s32 c, c, tgu;\n"
        "setp.lt.s32 p, c, 0;\n"
        "@p bra.uni PSL2;\n"
        "bra.uni PRE2;\n"
        "PSL1:\n"
        "nanosleep.u32 " STR(PSLEEP) ";\n"
        RDCLK("c")
        "sub.s32 c, c, tgt;\n"
        "PSLP:\n"
        "setp.lt.s32 p, c, 0;\n"
        "@p bra.uni PSL1;\n"
        "@ok bra.uni PRES;\n"
        "mov.u32 c, 0;\n"
        "PW:\n"
        "mbarrier.try_wait.parity.shared.b64 p, [b0+8], par;\n"
        "@p bra.uni PRES;\n"
        "add.u32 c, c, 1;\n"
        "setp.lt.u32 p, c, 4000000;\n"
        "@p bra.uni PW;\n"
        "trap;\n"
        "PEND:\n}"
        :
        : "l"(tm), "r"(bar), "r"(d0), "r"(ps), "r"(nit), "r"(psrc), "r"(tbase), "r"(lim), "r"(taug64), "r"(taus), "r"(n), "r"(lz),
          "r"(pr0), "r"(tau2), "r"(brk)
        : "memory");
}
template <int J0, int JN>
__device__ __forceinline__ void put_agg(const float (&acc)[2][NJ][4], uint32_t tb) {
#pragma unroll
    for (int h = 0; h < 2; h++) {
        const float(*a)[4] = acc[h] + J0;
#pragma unroll
        for (int j = 0; j + 1 < JN; j += 2)
            stsm4(tb + h * SM_ODD + j * 256, pack_bf16(a[j][0], a[j][1]), pack_bf16(a[j][2], a[j][3]),
                  pack_bf16(a[j + 1][0], a[j + 1][1]), pack_bf16(a[j + 1][2], a[j + 1][3]));
        if (JN & 1) stsm2(tb + h * SM_ODD + (JN - 1) * 256, pack_bf16(a[JN - 1][0], a[JN - 1][1]), pack_bf16(a[JN - 1][2], a[JN - 1][3]));
    }
}
template <int JN>
__device__ __forceinline__ void mul_out(float (&o)[JN][4], uint32_t r16, int hh, int tb) {
    asm volatile("wgmma.fence.sync.aligned;" ::: "memory");
#pragma unroll
    for (int ks = 0; ks < 8; ks++) {
        const uint32_t rg = (ks >> 2) * SM_ODD;
        wgmma_out(o, (uint64_t)(r16 + (((NP - 2 + hh) * 8192 + rg + (ks & 3) * 2048) >> 4)) | (64ull << 32) | (1ull << 62),
                  (uint64_t)(r16 + ((tb + rg + (ks & 3) * (JN * 256)) >> 4) + (8 << 16)) | (16ull << 32), ks);
    }
    asm volatile("wgmma.commit_group.sync.aligned;" ::: "memory");
}
static_assert(JA == 9 && NJ == 19 && NP == 5 && SM_EVEN == 0 && SM_ODD % 1024 == 128, "epilogue");
__device__ constexpr int out_at(int st, int j) {
    return st == 0   ? (j < 4 ? (19 + j) * 1024 : j < 8 ? SM_ODD + (16 + j) * 1024 : 23 * 1024)
           : st == 1 ? (10 + j) * 1024
           : st == 2 ? SM_ODD + (10 + j) * 1024
                     : (j < 8 ? (24 + j) * 1024 : SM_ODD + (16 + j) * 1024);
}
#define WG_SYNC(w) asm volatile("bar.sync %0, 128;" ::"r"((w) + 1) : "memory")
template <int ST, int JN>
__device__ __forceinline__ void put_out(float (&o)[JN][4], uint32_t ce, uint32_t co, int w) {
    asm volatile("wgmma.wait_group.sync.aligned %0;" ::"n"(ST == 2) : "memory");
#pragma unroll
    for (int j = 0; j < JN; j++)
#pragma unroll
        for (int k = 0; k < 4; k++) asm volatile("" : "+f"(o[j][k])::"memory");
#pragma unroll
    for (int j = 0; j + 1 < JN; j += 2)
        stsm4t((out_at(ST, j) & 128 ? co : ce) + out_at(ST, j), pack_bf16(o[j][0], o[j][1]), pack_bf16(o[j][2], o[j][3]),
               pack_bf16(o[j + 1][0], o[j + 1][1]), pack_bf16(o[j + 1][2], o[j + 1][3]));
    if (JN & 1) stsm2t(ce + out_at(ST, JN - 1), pack_bf16(o[JN - 1][0], o[JN - 1][1]), pack_bf16(o[JN - 1][2], o[JN - 1][3]));
    asm volatile("bar.arrive %0, 192;" ::"r"(6 + 2 * ST + w) : "memory");
}
#define DELAY 2500
#define NULW 0xf0000000
#define DREF 0
#define K0(npr) ((2 * NP - 2 - (npr) % NP) % NP)
#define GCODE(g) ((((g) >> 1) + 1) << 12 | ((g) & 1) << 15)
#define SYNC() asm volatile("bar.sync 0;" ::: "memory")
#define LISTS SYNC
#define NB (2 * NGR * 32)
#define PREF(p, tot, k0, n)                                                                                       \
    {                                                                                                             \
        _Pragma("unroll") for (int k = (k0); k < (k0) + (n); k++) {                                                \
            const int l = (k * nbins + bin) * 128 + tid - NB;                                                     \
            if (l < (tot)) asm volatile("prefetch.global.L2 [%0];" ::"l"(p + (size_t)l * 64) : "memory");         \
        }                                                                                                         \
    }
#define WX 010
#define WS 0011
#define WE 000
#define PL 8
#define PLE 0
#define DG(v, i) ((v) >> (6 - 3 * (i)) & 7)
#define PREW(i)                                                                                \
    PREF(x, N * 8, (i > 0 ? DG(WX, 0) : 0) + (i > 1 ? DG(WX, 1) : 0), DG(WX, i))                \
    PREF(sh, E / 16, (i > 0 ? DG(WS, 0) : 0) + (i > 1 ? DG(WS, 1) : 0), DG(WS, i))              \
    PREF(ea, E / 4, (i > 0 ? DG(WE, 0) : 0) + (i > 1 ? DG(WE, 1) : 0), DG(WE, i))
#define PFN (DG(WX, 0) + DG(WX, 1) + DG(WX, 2))
#define PFE (DG(WE, 0) + DG(WE, 1) + DG(WE, 2))
__global__ void __launch_bounds__(NT, 1)
main_kernel(const int* __restrict__ dst, const int* __restrict__ src, uint4* __restrict__ gbin, int E, int nbins, int fast_ok,
            int npb, unsigned npb_magic, int N, const __grid_constant__ CUtensorMap tme,
            const __grid_constant__ CUtensorMap tmx, const __grid_constant__ CUtensorMap tmw,
            const __grid_constant__ CUtensorMap tmo, const __nv_bfloat16* __restrict__ x,
            const __nv_bfloat16* __restrict__ sh, const __nv_bfloat16* __restrict__ ea,
            const __nv_bfloat16* __restrict__ cg, const __nv_bfloat16* __restrict__ wr,
            const __nv_bfloat16* __restrict__ wout, __nv_bfloat16* __restrict__ out, int tau16, int toff, int delay,
            int tau2, int brk) {
    extern __shared__ __align__(1024) unsigned char smem[];
    const uint32_t sb = __shfl_sync(0xffffffffu, s2u(smem), 0);
    const int tid = threadIdx.x;
    const int warp = __shfl_sync(0xffffffffu, tid >> 5, 0), lane = tid & 31;
    const int g = lane >> 2, t = lane & 3;

    TLSTAMP(0);
    TLINIT();
    const int bin = blockIdx.x;
    const int node0 = bin * npb, hpb = npb >> 1;
    uint32_t wa[8];
    uint2 c0 = make_uint2(0, 0), c1 = c0;
    bool fast = fast_ok;
    if (fast_ok) {
        int pd[EPS], ps[EPS];
        const int e0 = (warp * nbins + bin) * 32 + lane;
#pragma unroll
        for (int k = 0; k < EPS; k++)
            asm volatile("ld.global.nc.u32 %0, [%1];" : "=r"(pd[k]) : "l"(dst + min(e0 + k * NT * nbins, E - 1)));
#pragma unroll
        for (int k = 0; k < EPS; k++)
            asm volatile("ld.global.nc.u32 %0, [%1];" : "=r"(ps[k]) : "l"(src + min(e0 + k * NT * nbins, E - 1)));
        const unsigned ck0 = clock();
        const uint32_t cnt0 = (sb + SC_CNT + 8191) & ~8191;
        {
            const uint32_t nul = NULW | ((bin & 3) * 8 + (tid & 7)) << 21;
#pragma unroll
            for (int k = 0; k < 4; k++) {
                const int i = tid + k * NT;
                if (i < SC_EXT / 16 ? (tid & 7) != 7 : i < SC_TAB / 16) sts_v4(sb + SC_ENT + i * 16, make_uint4(nul, nul, nul, nul));
            }
            if (warp == NW - 1) {
                uint32_t now;
                asm volatile("mov.u32 %0, %%globaltimer_lo;" : "=r"(now));
                now = __shfl_sync(0xffffffffu, (now & 0x1fffff) | nul, 7);
#pragma unroll
                for (int k = 0; k < MAXBINS / 32; k++) sts_v4(sb + SC_ENT + (k * 32 + lane) * 128 + 112, make_uint4(now, now, now, now));
                if (lane == 0) {
                    asm volatile("prefetch.tensormap [%0];" ::"l"(&tme) : "memory");
                    asm volatile("prefetch.tensormap [%0];" ::"l"(&tmx) : "memory");
                    asm volatile("prefetch.tensormap [%0];" ::"l"(&tmw) : "memory");
                    asm volatile("prefetch.tensormap [%0];" ::"l"(&tmo) : "memory");
                    sts_v2(sb + SM_MISC + MI_INT, 0, now);
                }
            }
            sts_v4(cnt0 + tid * 16, make_uint4(0, 0, 0, 0));
            if (tid < (SC_END - SC_HIST) / 16) {
                const uint32_t v = (tid >> 3) == MAXBINS / 32 ? 0x80000000u : 0;
                sts_v4(sb + SC_HIST + tid * 16, make_uint4(v, v, v, v));
            }
            if (tid < 2 * HPB) {
                const int w = tid >= hpb, loc = tid - (w ? hpb : 0), gr = min(loc * 43 >> 8, NGR - 1);
                sts_u32(sb + SC_TAB + tid * 4, ((w ? NGR : 0) + gr) * (NBK * 64 << 15) + loc - gr * GSZ);
            }
        }
        TLMAX(1);
        __syncthreads();
        {
            const uint32_t z = lds_u32(sb + SM_MISC + MI_INT);
            int pb[EPS], pr[EPS];
            uint32_t v[EPS];
#pragma unroll
            for (int k = 0; k < EPS; k++) {
                pb[k] = (int)__umulhi((unsigned)pd[k], npb_magic + z);
                v[k] = lds_u32(sb + SC_TAB + (pd[k] - pb[k] * npb) * 4);
                pr[k] = atoms_add(sb + SC_HIST + (e0 + k * NT * nbins < E ? pb[k] : MAXBINS + lane) * 4, 4);
            }
            int mx = 0;
#pragma unroll
            for (int k = 0; k < EPS; k++) {
                v[k] += ps[k] * (32768 + z) + (k * NT + tid + 32) * 8;
                asm volatile("{\n.reg .pred p;\nsetp.lt.u32 p, %0, 128;\n@p st.shared.u32 [%1], %2;\n}" ::"r"(pr[k]),
                             "r"(sb + SC_ENT + pb[k] * 128 + pr[k]), "r"(v[k])
                             : "memory");
                mx = max(mx, pr[k]);
            }
            if (mx >= 128) {
#pragma unroll
                for (int k = 0; k < EPS; k++)
                    if (pr[k] >= 128 && pr[k] < 192) sts_u32(sb + SC_EXT - 128 + pb[k] * 64 + pr[k], v[k]);
            }
        }
        FENCE_ASYNC();
        TLMAX(6);
        __syncthreads();
        const unsigned c6 = DREF ? ck0 : clock();
        if (warp == NW - 1 && elect()) {
            tma_store(&tme, sb + SC_ENT, bin * 32, 0);
            asm volatile("cp.async.bulk.commit_group;" ::: "memory");
        }
        if (tid < nbins && lds_u32(sb + SC_HIST + tid * 4) >= 128) {
#pragma unroll 1
            for (int k = 0; k < 4; k++) __stcg(gbin + GEX + (tid * nbins + bin) * 4 + k, lds_v4(sb + SC_EXT + tid * 64 + k * 16));
        }
        if (elect()) {
#pragma unroll
            for (int k = 0; k < (NP > 5 ? 4 : 2); k++) mbar_init(sb + SM_BAR + (warp * (NP > 5 ? 4 : 2) + k) * 8, 3 + (k & 1));
        }
#pragma unroll
        for (int k = 0; k < TS / 2; k++) sts_v4(sb + SM_BT + (tid + k * NT) * 16, make_uint4(0, 0, 0, 0));
        if (tid < 8) sts_v4(sb + SM_BT + (tid + TS / 2 * NT) * 16, make_uint4(0, 0, 0, 0));
        if (tid < 4) {
            sts_u16(sb + SM_SRC + (LNUL + tid) * 2, N);
            sts_u32(sb + SM_EID + (LNUL + tid) * 4, 0x80000000u);
        }
        FENCE_ASYNC();
        if (warp >= 2 * NGR) {
            uint2 wv[4];
#pragma unroll
            for (int k = 0; k < 4; k++)
                asm volatile("ld.global.nc.v2.u32 {%0,%1}, [%2];" : "=r"(wv[k].x), "=r"(wv[k].y) : "l"((const uint2*)wr + (tid - NB) + k * 128));
#pragma unroll
            for (int k = 0; k < 4; k++) sts_v2(sb + SC_WR + (lane >> 1) * 272 + (warp - 2 * NGR + k * 4) * 16 + (lane & 1) * 8, wv[k].x, wv[k].y);
            PREW(0);
            SYNC();
            PREW(1);
            if (warp == NW - 1 && elect()) {
                asm volatile("cp.async.bulk.global.shared::cta.bulk_group [%0], [%1], %2;" ::"l"(gbin + bin * nbins * 8), "r"(sb + SM_BT),
                             "r"(nbins * 128)
                             : "memory");
                asm volatile("cp.async.bulk.commit_group;" ::: "memory");
                const uint32_t t0 = lds_u32(sb + SM_MISC + MI_INT + 4);
                uint32_t now;
                asm volatile("mov.u32 %0, %%globaltimer_lo;" : "=r"(now));
                sts_u32(sb + SM_MISC + MI_INT + 4, clock() - (min((now - t0) & 0x1fffff, 1u << 16) * 7 >> 2) + toff);
            }
            SYNC();
            PREW(2);
            fast = lds_u32(sb + SM_MISC + MI_INT) == 0;
            asm volatile("cp.async.bulk.wait_group.read 0;" ::: "memory");
        } else {
        uint32_t en[5][4], es[5][4], rank[5][4], ca[5][4];
        if (warp >= 8 && (g >> 2) == (t >> 1)) {
            const uint2* cp = (const uint2*)cg + (g & 3) * 4 + (t & 1) * 2;
            asm volatile("ld.global.nc.v2.u32 {%0,%1}, [%2];" : "=r"(c0.x), "=r"(c0.y) : "l"(cp));
            asm volatile("ld.global.nc.v2.u32 {%0,%1}, [%2];" : "=r"(c1.x), "=r"(c1.y) : "l"(cp + 1));
        }
        const int sg[5] = {tid >> 3, (tid >> 3) + NB / 8, (tid >> 3) + NB / 4, (tid >> 3) + (lane & 4) * (NB / 32), (tid >> 3) + NB / 4};
        const uint4* gp[5];
        gp[0] = gbin + bin * nbins * 8 + tid;
        gp[1] = gp[0] + NB;
        gp[2] = gp[0] + 2 * NB;
        gp[3] = gbin + GEX + (bin * nbins + sg[3]) * 4 + (lane & 3);
        gp[4] = gbin + GEX + (bin * nbins + sg[4]) * 4 + (lane & 3);
        unsigned pend = (sg[0] < nbins) | (sg[1] < nbins) << 1 | (sg[2] < nbins) << 2;
#pragma unroll
        for (int k = 0; k < 5; k++) en[k][0] = en[k][1] = en[k][2] = en[k][3] = NULW | lane << 21;
        auto fetch = [&](int k) {
            asm volatile("{\n.reg .pred p;\nsetp.ne.u32 p, %5, 0;\n@p ld.relaxed.gpu.global.v4.u32 {%0,%1,%2,%3}, [%4];\n}"
                         : "+r"(en[k][0]), "+r"(en[k][1]), "+r"(en[k][2]), "+r"(en[k][3])
                         : "l"(gp[k]), "r"(pend & (1u << k))
                         : "memory");
        };
        int spin = 0;
        auto poll = [&](int k0, int k1) {
            for (;;) {
#pragma unroll
                for (int k = k0; k < k1; k++)
                    if (min(min(en[k][0], en[k][1]), min(en[k][2], en[k][3]))) pend &= ~(1u << k);
                if (!__any_sync(0xffffffffu, pend)) break;
#pragma unroll
                for (int k = k0; k < k1; k++) fetch(k);
                if (++spin > 10000000) __trap();
            }
        };
        auto count = [&](int k) {
#pragma unroll
            for (int c = 0; c < 4; c++) {
                const uint32_t v = en[k][c];
                ca[k][c] = ((v >> 19) & 0x1ffc) | cnt0;
                rank[k][c] = atoms_add(ca[k][c], 1);
                asm volatile("{\n.reg .b32 a, b;\nprmt.b32 a, %1, %2, 0x6540;\nand.b32 b, %1, 0x7f00;\nmad.lo.u32 %0, b, %3, a;\n}"
                             : "=r"(es[k][c])
                             : "r"(v), "r"(sg[k] - nbins), "r"(nbins));
            }
        };
        uint32_t sg0 = 0x01010101 | ((lane & 1) << 8 | (lane & 2) << 15 | (lane & 4) << 22) * 0xfe;
        uint32_t sg2 = (0x0101 | ((lane >> 3 & 1) | (lane & 16) << 4) * 0xfe) * 0x10001 ^ 0xfefe0000;
        uint32_t cand = ((lane & 1) << 3 | (lane & 2) << 5 | (lane & 4) << 7 | (lane & 8) << 9) * 7 + (lane & 16) * (15 << 11);
        asm volatile("" : "+r"(sg0), "+r"(sg2), "+r"(cand));
        while ((int)(clock() - c6) < delay) {}
        TLMAX(7);
        fetch(0);
        fetch(1);
        fetch(2);
        poll(0, 3);
        TLMAX(2);
        const bool more = __any_sync(0xffffffffu, (lane & 7) == 7 && min(min(en[0][3], en[1][3]), en[2][3]) < NULW);
        const bool rest = NB / 4 + warp * 4 < nbins;
        if (more) {
            const uint32_t l0 = __shfl_sync(0xffffffffu, en[0][3], lane | 7), l1 = __shfl_sync(0xffffffffu, en[1][3], lane | 7);
            const uint32_t l2 = __shfl_sync(0xffffffffu, en[2][3], lane | 7);
            pend = ((lane & 4 ? l1 : l0) < NULW) << 3 | (!(lane & 4) && l2 < NULW) << 4;
            fetch(3);
            fetch(4);
        }
        if (tid == 7 && en[0][3] >= NULW) sts_u32(sb + SM_MISC + MI_INT + 4, en[0][3]);
        count(0);
        count(1);
        if (rest) count(2);
        if (more) {
            const unsigned ext = pend;
            poll(3, 5);
#pragma unroll
            for (int k = 3; k < 5; k++) {
                if ((ext >> k) & 1) {
                    __stcg((uint4*)gp[k], make_uint4(0, 0, 0, 0));
                    if ((lane & 3) == 3 && en[k][3] < NULW) sts_u32(sb + SM_MISC + MI_INT, 1);
                }
            }
            count(3);
            count(4);
        }
        TLMAX(9);
        SYNC();
        {
            const int w0 = warp >= NGR, gr = warp - w0 * NGR;
            const uint32_t cp = cnt0 + (warp * NBK + lane * (NBK / 32)) * 4;
            uint32_t r[NBK / 32 + 1], old[NBK / 32 + 1];
#pragma unroll
            for (int c = 0; c < NBK / 32; c++) r[c + 1] = lds_u32(cp + c * 4);
            r[0] = 0;
#pragma unroll
            for (int c = 1; c < NBK / 32; c++) r[c + 1] += r[c];
            const uint32_t tot = __reduce_add_sync(0xffffffffu, r[NBK / 32]);
            asm volatile("st.shared.u8 [%0], %1;" ::"r"(sb + SM_MISC + MI_INT + 32 + (gr < 4 ? w0 * 4 : 4 + w0 * 2) + gr), "r"((tot + 3) >> 2) : "memory");
            const uint32_t incl = warp_incl_scan(r[NBK / 32], lane), off = incl - r[NBK / 32] + 3 - CE;
            const uint32_t base = warp * GCAP + w0 * GEXT;
#pragma unroll
            for (int c = 0; c <= NBK / 32; c++) r[c] += off;
            asm volatile("bar.sync 3, %0;" ::"n"(2 * NGR * 32) : "memory");
            const uint4 nb = lds_v4(sb + SM_MISC + MI_INT + 32);
            int df;
            asm("{\n.reg .s32 a;\ndp4a.u32.s32 a, %1, %4, 0;\ndp4a.u32.s32 a, %2, %5, a;\ndp4a.u32.s32 %0, %3, %6, a;\n}"
                : "=r"(df)
                : "r"(nb.x), "r"(nb.y), "r"(nb.z), "r"(sg0), "r"(sg0 ^ 0xfefefefe), "r"(sg2));
            const uint32_t swp = __reduce_min_sync(0xffffffffu, abs(df) << NJ | cand);
            const int w = w0 ^ ((swp >> (3 * gr)) & 1);
            const uint32_t bp = sb + SC_BLK + (w * (NBK + 2) + lane * (NBK / 32)) * 4;
#pragma unroll
            for (int c = 0; c < NBK / 32; c++) old[c] = atoms_add(bp + c * 4, (r[c + 1] >> 2) + (r[c] >> 2) * 0x1ffff);
            const bool tailb = (incl & 3) >= 1 && (incl & 3) <= CE;
            if (lane == 31) old[NBK / 32] = atoms_add(bp + NBK / 32 * 4, (r[NBK / 32] >> 2 << 17) + tailb);
            if (tot > GCAP + (gr == NGR - 1 ? GEXT : 0)) {
                sts_u32(sb + SM_MISC + MI_INT, 1);
            } else if (lane < (-tot & 3)) {
                sts_u16(sb + SM_SRC + (base + tot + lane) * 2, N + warp * (NBK * 64));
                sts_u32(sb + SM_EID + (base + tot + lane) * 4, 0x80000000u);
            }
            const uint32_t code = GCODE(gr);
#pragma unroll
            for (int c = 0; c < NBK / 32; c++)
                old[c] = ((old[c] - (r[c] >> 2) + (w * SEQCAP + 1023 - base / 4)) << 17) + r[c] + (base + 1 + code);
            TLMAX(5);
            asm volatile("bar.sync %0, %1;" ::"r"(w + 4), "n"(NGR * 32) : "memory");
#pragma unroll
            for (int c = 0; c < NBK / 32; c++) r[c] = lds_u32(bp + c * 4);
            const uint32_t tw = lds_u32(sb + SC_BLK + (w * (NBK + 2) + NBK) * 4);
#pragma unroll
            for (int c = 0; c < NBK / 32; c++) sts_u32(cp + c * 4, (r[c] & 0xffff0000u) + old[c]);
            const int nst = (tw >> 17) + (tw & 0xffff), npr = (nst + 3) >> 2;
            const uint32_t sq = sb + SM_SEQ + w * SEQCAP * 2;
            if (nst + 32 > SEQCAP) {
                sts_u32(sb + SM_MISC + MI_INT, 1);
            } else {
                if (lane == 31 && tailb) sts_u16(sq + ((tw >> 17) + (old[NBK / 32] & 0xffff)) * 2, ((base + tot + 4) & ~3) | code);
                if (gr == 0) {
                    sts_u16(sq + (nst + lane) * 2, (LNUL + 4) | (lane < (-nst & 3) ? GCODE(0) : 0x7c01));
                    const int k0 = K0(npr);
                    if (lane < k0) {
                        mbar_arrive_cnt(sb + SM_BAR + (w * NP + lane) * 16, 3);
                        mbar_arrive_cnt(sb + SM_BAR + (w * NP + lane) * 16 + 8, 4);
                    }
                    if (lane == 0) sts_v2(sb + SM_MISC + MI_INT + 8 + w * 8, npr, k0);
                    if (lane == 1) sts_u32(sb + SM_MISC + MI_INT + 24, swp);
                }
            }
        }
#pragma unroll
        for (int h = 0; h < 2; h++)
            asm volatile("ldmatrix.sync.aligned.m8n8.x4.trans.shared.b16 {%0,%1,%2,%3}, [%4];"
                         : "=r"(wa[h * 4]), "=r"(wa[h * 4 + 1]), "=r"(wa[h * 4 + 2]), "=r"(wa[h * 4 + 3])
                         : "r"(sb + SC_WR + (h * 8 + (warp & 3) * 2 + ((lane >> 3) & 1)) * 272 + (lane >> 4) * 128 + (lane & 7) * 16));
        TLMAX(10);
        SYNC();
        auto place = [&](int k) {
#pragma unroll
            for (int c = 0; c < 4; c++) ca[k][c] = lds_u32(ca[k][c]);
#pragma unroll
            for (int c = 0; c < 4; c++) {
                const uint32_t q = ca[k][c] + rank[k][c], p = q & 0xfff;
                asm volatile(
                    "{\n.reg .pred p, q;\n.reg .b32 t;\n.reg .b16 h;\n"
                    "setp.ge.u32 p, %0, " STR(NULW) ";\n"
                    "@!p st.shared.u32 [%1], %2;\n"
                    "shr.u32 t, %0, 15;\ncvt.u16.u32 h, t;\n"
                    "@!p st.shared.u16 [%3], h;\n"
                    "lop3.or.b32 t|q, %5, 3, 0, 0xc0, p;\n"
                    "cvt.u16.u32 h, %5;\n"
                    "@!q st.shared.u16 [%4], h;\n}" ::"r"(en[k][c]),
                    "r"(sb + SM_EID - (4 - CE) * 4 + p * 4), "r"(es[k][c]), "r"(sb + SM_SRC - (4 - CE) * 2 + p * 2),
                    "r"(sb + SM_SEQ - 2048 + (q >> 16) + (p >> 1)), "r"(q)
                    : "memory");
            }
        };
        fast = lds_u32(sb + SM_MISC + MI_INT) == 0;
        if (fast) {
            place(0);
            place(1);
            if (rest) place(2);
            if (more) place(3), place(4);
        }
        }
    }
    TLMAX(14);
    FENCE_ASYNC();

    if (fast && (warp >> 2) == 2) {
        asm volatile("setmaxnreg.dec.sync.aligned.u32 %0;" ::"n"(HREG));
        const int w = warp & 1, j = (warp >> 1) & 1;
        const uint2 nk = lds_v2(sb + SM_MISC + MI_INT + 8 + w * 8);
        const int npr = __shfl_sync(0xffffffffu, nk.x, 0), kj = __shfl_sync(0xffffffffu, nk.y, 0) + j;
        const uint32_t bar0 = sb + SM_BAR + w * NP * 16;
        const int blk = (lane >> 4) * 2 + (t >> 1);
        uint32_t fseq = sb + SM_SEQ + w * SEQCAP * 2 + j * 8 + blk * 2;
        const uint32_t feid = sb + SM_EID - 16 + (g & 3) * 4;
        uint32_t pea = sb + SM_EA + w * 4096 + j * 512 + (lane ^ ((lane >> 3) & 1)) * 16;
        const uint32_t psd = sb + SM_SIDE + (warp - 8) * 512 + (lane >> 1) * 16 + (lane & 1) * 4;
        const uint32_t pt = sb + SM_BT + w * (TS * 256) + j * 512 + blk * BT_B + ((lane ^ (lane >> 3)) & 1) * BT_K + (g & 3) * 4;
        const char* gea = (const char*)ea + (lane & 1) * 16;
        uint32_t es, va[2], ta[2], old[2] = {pt, pt}, dea = 2048;
        auto ids = [&]() {
            es = lds_u32(feid + (lds_u16(fseq) & 0xffc) * 4);
            fseq += 16;
        };
        uint32_t wf[4];
        wf[0] = __byte_perm(c0.x, c1.x, 0x5410), wf[1] = __byte_perm(c0.x, c1.x, 0x7632);
        wf[2] = __byte_perm(c0.y, c1.y, 0x5410), wf[3] = __byte_perm(c0.y, c1.y, 0x7632);
        uint32_t vf = bar0 + (kj < NP ? kj : 0) * 16;
        uint32_t pe = kj < NP;
        int pfl = lane < PL ? PFN * nbins * 128 + (bin * 4 + warp - 8) * PL + lane - N * 8 : 0;
        int pfs = nbins * (4 * PL);
        const char* pfb = (const char*)(x + (size_t)N * 512);
        auto run = [&](auto odd) {
            auto fetch = [&](int i) {
                asm volatile(
                    "{\n.reg .pred p, q;\n.reg .b32 e;\n.reg .b64 a;\n"
                    "setp.lt.s32 p, %0, 0;\n"
                    "and.b32 e, %0, 0x7ffffff8;\n"
                    "mad.wide.u32 a, e, 4, %1;\n"
                    "cp.async.cg.shared.global [%2], [a], 16, p;\n"
                    "}" ::"r"(es), "l"(gea), "r"(pea + i * 1024) : "memory");
                va[i] = psd + (es & 8);
                ta[i] = pt + (es & 7) * 64;
                if (odd.value) {
                    cp_async4(va[i] + i * 256, (const char*)sh + (es & 0x7ffffff8) + (lane & 1) * 4, (int)es >= 0 ? 4 : 0);
                } else {
                    asm volatile(
                        "{\n.reg .pred p;\n.reg .b32 e;\n.reg .b64 a;\n"
                        "setp.lt.s32 p, %0, 0;\n"
                        "and.b32 e, %0, 0x7ffffff0;\n"
                        "mad.wide.u32 a, e, 1, %1;\n"
                        "cp.async.cg.shared.global [%2], [a], 16, p;\n"
                        "}" ::"r"(es), "l"(sh), "r"((psd & ~15) + i * 256) : "memory");
                }
                asm volatile("cp.async.commit_group;" ::: "memory");
                if (i) pea += dea, dea = -dea;
            };
            LISTS();
            ids();
            fetch(0);
            ids();
            fetch(1);
#pragma unroll 1
            for (int m = (npr + 1 - j) >> 1; m > 0;) {
#pragma unroll
                for (int i = 0; i < 2; i++) {
                    asm volatile("cp.async.wait_group 1;" ::: "memory");
                    __syncwarp();
                    const uint32_t v = lds_u32(va[i] + i * 256);
                    ids();
                    float d0[4], d1[4];
                    mma_diag(d0, v, wf[0], wf[1]);
                    mma_diag(d1, v, wf[2], wf[3]);
                    uint32_t vn = vf + 32;
                    if (vn >= bar0 + NP * 16) vn -= NP * 16, pe ^= 1;
                    TWAIT(vn + 8, pe);
#pragma unroll
                    for (int k = 0; k < 4; k++) sts_u32(old[i] + i * 1024 + k * 16, 0);
                    old[i] = ta[i];
                    sts_u32(old[i] + i * 1024, pack_bf16(d0[0], d0[1]));
                    sts_u32(old[i] + i * 1024 + 16, pack_bf16(d0[2], d0[3]));
                    sts_u32(old[i] + i * 1024 + 32, pack_bf16(d1[0], d1[1]));
                    sts_u32(old[i] + i * 1024 + 48, pack_bf16(d1[2], d1[3]));
                    FENCE_ASYNC();
                    fetch(i);
                    __syncwarp();
                    if (lane == 0) mbar_arrive(vf);
                    asm volatile("{\n.reg .pred p;\n.reg .b64 a;\nsetp.lt.s32 p, %0, 0;\nmad.wide.s32 a, %0, 128, %1;\n@p prefetch.global.L2 [a];\n}" ::"r"(pfl),
                                 "l"(pfb));
                    pfl += pfs;
                    vf = vn;
                    if (--m <= 0) break;
                }
            }
        };
        if (E & 1) run(std::true_type()); else run(std::false_type());
        asm volatile("cp.async.wait_group 0;" ::: "memory");
        TLMAX(13);
    } else if (fast && warp >= 12) {
        asm volatile("setmaxnreg.dec.sync.aligned.u32 %0;" ::"n"(PREG));
        const int w = warp & 1, j = (warp >> 1) & 1;
        const uint2 nk = lds_v2(sb + SM_MISC + MI_INT + 8 + w * 8);
        const int npr = __shfl_sync(0xffffffffu, nk.x, 0), k0 = __shfl_sync(0xffffffffu, nk.y, 0);
        const uint32_t bar0 = sb + SM_BAR + w * NP * 16, ring = sb + w * RING_BYTES + j * 4096;
        const uint32_t pseq = sb + SM_SEQ + w * SEQCAP * 2 + j * 2;
        const unsigned tbase = lds_u32(sb + SM_MISC + MI_INT + 4);
        const unsigned taug = __float2uint_rz(__fdividef((float)(N * tau16 >> 4), (float)max(npr, 1)));
        produce(&tmx, bar0, ring - j * 2048 - bar0 * 512, pseq + lane * 8, npr, sb + SM_SRC - 8, tbase,
                tbase + (N * tau16 >> 8) + lane * taug, taug * 32, tau16, k0 + lane, lane & (E >> 31), k0 + 32, tau2, brk
        );
        if (elect()) {
            const uint32_t d = ring + (NP - 2) * 8192 + j * 4096;
            const uint32_t fb = bar0 + (NP - 2 + j) * 16, par = ~((lds_u32(sb + SM_MISC + MI_INT + 8 + w * 8) + 1) / NP) & 1;
            mbar_wait(fb + 8, par);
            mbar_arrive_cnt(j ? bar0 + DUMB : fb, j ? 1 : 3);
            mbar_expect_tx(bar0 + DUMB, 16384);
            tma_2d(d + SM_EVEN, &tmw, bar0 + DUMB, j * 64, 0);
            tma_2d(d + SM_ODD, &tmw, bar0 + DUMB, j * 64, 64);
        }
        TLMAX(12);
        const uint32_t swp = lds_u32(sb + SM_MISC + MI_INT + 24) ^ -w;
        const int row = 2 * lane < hpb ? (node0 + ((swp >> lane) & 1) * hpb) * 4 + lane * 8 : N * 4;
        const CUtensorMap* po = &tmo;
        asm volatile("" : "+l"(po));
#pragma unroll
        for (int st = 0; st < 4; st++) {
            int rw[5];
#pragma unroll
            for (int k = 0; k < 5; k++) rw[k] = __shfl_sync(0xffffffffu, row, st < 2 && k == 4 ? JA - 1 + j * 16 : (st >> 1) * JA + 2 * k + j);
            asm volatile("bar.sync %0, 192;" ::"r"(6 + 2 * st + w) : "memory");
            FENCE_ASYNC();
            if (elect()) {
#pragma unroll
                for (int k = 0; k < 5; k++) tma_store(po, ring - j * 3072 + out_at(st, 2 * k), (st & 1) * 64, rw[k]);
                asm volatile("cp.async.bulk.commit_group;" ::: "memory");
            }
        }
        asm volatile("cp.async.bulk.wait_group.read 0;" ::: "memory");
    } else if (fast) {
        const int w = warp >> 2, wq = warp & 3;
        LISTS();
        asm volatile("setmaxnreg.inc.sync.aligned.u32 %0;" ::"n"(CREG));
        const int k0 = __shfl_sync(0xffffffffu, lds_u32(sb + SM_MISC + MI_INT + 12 + w * 8), 0);
        const uint32_t ring = sb + w * RING_BYTES, bar0 = sb + SM_BAR + w * NP * 16;
        float acc[2][NJ][4];
        {
            const int e = (lane >> 1) & 3, m = lane >> 3;
            const int line = 2 * ((lane & 1) + 2 * ((m >> 1) ^ (e >> 1))), ch = 2 * wq + (m & 1);
            const uint32_t xb = ring + (e & 1 ? SM_ODD : SM_EVEN) + (e >> 1) * 1024 + line * 128;
            consume(acc, xb + ((ch ^ ((line + (e & 1)) & 7)) * 16), xb + 128 + ((ch ^ ((line + 1 + (e & 1)) & 7)) * 16),
                    k0 * 8192, bar0, (((sb + SM_EA + w * 4096) & 0x3ffff) >> 4) | (1 << 16),
                    (((sb + SM_BT + w * (TS * 256)) & 0x3ffff) >> 4) | (BT_K / 16 << 16), sb + SM_SEQ + w * SEQCAP * 2, lane & (E >> 31),
                    wa);
        }
        TLMAX(11);
        put_agg<0, JA>(acc, ring + (NJ - JA) * 1024 + wq * (JA * 256) + lane * 16);
        FENCE_ASYNC();
        WG_SYNC(w);
        mbar_wait_u(bar0 + DUMB, 0);
        float oa[JA][4], ob[2][NJ - JA][4];
        mul_out<JA>(oa, ring >> 4, 0, (NJ - JA) * 1024);
        const uint32_t cr = ring + (lane & 7) * 128 + (lane >> 4) * 1024, cc = 2 * wq + ((lane >> 3) & 1);
        const uint32_t ce = cr + (cc ^ (lane & 7)) * 16, co = cr + (cc ^ ((lane + 1) & 7)) * 16;
        put_out<0, JA>(oa, ce, co, w);
        TLMAX(3);
        mul_out<JA>(oa, ring >> 4, 1, (NJ - JA) * 1024);
        put_agg<JA, NJ - JA>(acc, ring + wq * ((NJ - JA) * 256) + lane * 16);
        FENCE_ASYNC();
        WG_SYNC(w);
        put_out<1, JA>(oa, ce, co, w);
        mul_out<NJ - JA>(ob[0], ring >> 4, 0, 0);
        mul_out<NJ - JA>(ob[1], ring >> 4, 1, 0);
        put_out<2, NJ - JA>(ob[0], ce, co, w);
        put_out<3, NJ - JA>(ob[1], ce, co, w);
        TLMAX(15);
    } else {
        float* accs = (float*)smem;
        constexpr int NACC = SM_EID / 2048;
        const int nnodes = max(0, min(npb, N - node0));
#pragma unroll 1
        for (int nb = 0; nb < nnodes; nb += NACC) {
            __syncthreads();
            for (int i = tid; i < NACC * 512; i += NT) accs[i] = 0.f;
            __syncthreads();
#pragma unroll 1
            for (int base = warp * 32; base < E; base += NT) {
                const int e = base + lane;
                int dl = e < E ? dst[e] - node0 - nb : -1;
                if (dl + nb >= nnodes) dl = -1;
                unsigned mask = __ballot_sync(0xffffffffu, dl >= 0 && dl < NACC);
#pragma unroll 1
                while (mask) {
                    const int l = __ffs(mask) - 1;
                    mask &= mask - 1;
                    const int ee = __shfl_sync(0xffffffffu, e, l);
                    const int dd = __shfl_sync(0xffffffffu, dl, l);
                    slow_edge(ee, src[ee], accs + dd * 512, x, sh, ea, cg, wr, lane);
                }
            }
            __syncthreads();
#pragma unroll 1
            for (int nl = warp; nl < NACC && nb + nl < nnodes; nl += NW)
                slow_out(accs + nl * 512, wout, out + (size_t)(node0 + nb + nl) * 512, lane);
        }
        __syncthreads();
    }

    TLMAX(4);
    TLEND();
}

typedef CUresult (*EncodeTiledFn)(CUtensorMap*, CUtensorMapDataType, cuuint32_t, void*, const cuuint64_t*,
                                  const cuuint64_t*, const cuuint32_t*, const cuuint32_t*, CUtensorMapInterleave,
                                  CUtensorMapSwizzle, CUtensorMapL2promotion, CUtensorMapFloatOOBfill);

extern "C" void kernel_launch(void* const* d_in, const int* in_sizes, int n_in, void* d_out, int out_size) {
    const __nv_bfloat16* x = (const __nv_bfloat16*)d_in[0];
    const int* src = (const int*)d_in[1];
    const int* dst = (const int*)d_in[2];
    const __nv_bfloat16* sh = (const __nv_bfloat16*)d_in[3];
    const __nv_bfloat16* ea = (const __nv_bfloat16*)d_in[4];
    const __nv_bfloat16* cg = (const __nv_bfloat16*)d_in[5];
    const __nv_bfloat16* wr = (const __nv_bfloat16*)d_in[6];
    const __nv_bfloat16* wout = (const __nv_bfloat16*)d_in[7];
    __nv_bfloat16* out = (__nv_bfloat16*)d_out;
    const int N = in_sizes[0] / 512;
    const int E = in_sizes[1];

    static int num_sms = 0;
    static EncodeTiledFn encode = nullptr;
    static uint4* gbin = nullptr;
    if (num_sms == 0) {
        int dev = 0;
        cudaGetDevice(&dev);
        cudaDeviceGetAttribute(&num_sms, cudaDevAttrMultiProcessorCount, dev);
        cudaFuncSetAttribute(main_kernel, cudaFuncAttributeMaxDynamicSharedMemorySize, SM_TOTAL + TLX);
        cudaGetSymbolAddress((void**)&gbin, g_bin);
        void* fn = nullptr;
        cudaDriverEntryPointQueryResult qr;
        cudaGetDriverEntryPoint("cuTensorMapEncodeTiled", &fn, cudaEnableDefault, &qr);
        encode = (EncodeTiledFn)fn;
    }
    const int nbins = num_sms < NB * 3 / 8 ? num_sms : NB * 3 / 8;
    int npb = ((N + nbins - 1) / nbins + 3) & ~3;
    if (npb < 32) npb = 32;
    const int fast_ok = E > 0 && npb <= 2 * HPB && N <= NBK * 64 && E <= EPS * NT * nbins;
    auto map2d = [&](CUtensorMap* tm, const void* p, int d0, int d1, int b1) {
        const cuuint64_t gd[2] = {(cuuint64_t)d0, (cuuint64_t)d1};
        const cuuint64_t gs[1] = {(cuuint64_t)d0 * 2};
        const cuuint32_t bx[2] = {64, (cuuint32_t)b1};
        const cuuint32_t es[2] = {1, 1};
        encode(tm, CU_TENSOR_MAP_DATA_TYPE_BFLOAT16, 2, (void*)p, gd, gs, bx, es, CU_TENSOR_MAP_INTERLEAVE_NONE,
               CU_TENSOR_MAP_SWIZZLE_128B, CU_TENSOR_MAP_L2_PROMOTION_NONE, CU_TENSOR_MAP_FLOAT_OOB_FILL_NONE);
    };
    CUtensorMap tme, tmx, tmw, tmo;
    {
        const cuuint64_t gd[2] = {(cuuint64_t)nbins * 32, (cuuint64_t)nbins};
        const cuuint64_t gs[1] = {(cuuint64_t)nbins * 128};
        const cuuint32_t bx[2] = {32, (cuuint32_t)nbins};
        const cuuint32_t es[2] = {1, 1};
        encode(&tme, CU_TENSOR_MAP_DATA_TYPE_UINT32, 2, (void*)gbin, gd, gs, bx, es, CU_TENSOR_MAP_INTERLEAVE_NONE,
               CU_TENSOR_MAP_SWIZZLE_NONE, CU_TENSOR_MAP_L2_PROMOTION_NONE, CU_TENSOR_MAP_FLOAT_OOB_FILL_NONE);
    }
    {
        const cuuint64_t gd[2] = {(cuuint64_t)N * 256 - 224, 8};
        const cuuint64_t gs[1] = {128};
        const cuuint32_t bx[2] = {32, 8};
        const cuuint32_t es[2] = {1, 1};
        encode(&tmx, CU_TENSOR_MAP_DATA_TYPE_UINT32, 2, (void*)x, gd, gs, bx, es, CU_TENSOR_MAP_INTERLEAVE_NONE,
               CU_TENSOR_MAP_SWIZZLE_128B, CU_TENSOR_MAP_L2_PROMOTION_NONE, CU_TENSOR_MAP_FLOAT_OOB_FILL_NONE);
    }
    map2d(&tmw, wout, 128, 128, 64);
    map2d(&tmo, out, 128, N * 4, 8);
    const unsigned npb_magic = (unsigned)((0x100000000ull + npb - 1) / npb);
    const int chunk = (E + nbins - 1) / nbins;
    int tau16 = (int)fmin((double)PACE * 16.0 * chunk / N, 100000.0), toff = TOFF, delay = DELAY;
    int tau2 = tau16 * PACE2 / 100, brk = BRK;
    brk = (tau16 - tau2) * (N * brk / 50);
    main_kernel<<<nbins, NT, SM_TOTAL + TLX, cudaStreamPerThread>>>(dst, src, gbin, E, nbins, fast_ok, npb, npb_magic, N, tme, tmx, tmw,
                                                              tmo, x, sh, ea, cg, wr, wout, out, tau16, toff, delay, tau2, brk);
}
```

```cpp
#include <cuda_runtime.h>
#include <cuda.h>
#include <cuda_bf16.h>
#include <stdint.h>
#include <stdlib.h>
#include <type_traits>

#define MAXBINS 160
#define NW 16
#define NT (NW * 32)
#define HPB 38
#define GCAP 280
#define GEXT 72
#define NGR 6
#define LNUL (2 * (NGR * GCAP + GEXT))
#define NBK 160
#define CE 2
#define GSZ 6
#define NS 10
#define RING_BYTES 40960
static_assert(RING_BYTES == NS * 4096, "ring");
#define NP (NS / 2)
#define CREG 224
#define PREG 24
#define HREG 40
#define TS 8
#define SM_EVEN 0
#define SM_MISC (2 * RING_BYTES)
#define SM_ODD (SM_MISC + 128)
#define SM_EA (SM_BT + TS * 4096 + 128)
#define SM_BT (SM_ODD + 2 * RING_BYTES)
#define BT_B (TS * 512 + 16)
#define BT_K (4 * BT_B)
#define SM_SIDE (SM_EA + 8192)
#define SM_EID (SM_SIDE + 2048)
#define SM_SRC (SM_EID + (LNUL + 4) * 4)
#define SEQCAP ((LNUL / 8 + 32 + 7) / 8 * 8)
#define SM_SEQ (SM_SRC + (LNUL + 8) * 2)
#define SM_BAR ((SM_SEQ + 2 * SEQCAP * 2 + 63) / 64 * 64)
#define SM_TOTAL (SM_BAR + NW * (NP > 5 ? 32 : 16))
#define DUMB (2 * NP * 16)
#define MI_INT 0
#define EPS 5
#define SC_ENT 0
#define SC_EXT (SC_ENT + MAXBINS * 128)
#define SC_TAB (SC_EXT + MAXBINS * 64)
#define SC_HIST (SC_TAB + 320)
#define SC_END (SC_HIST + MAXBINS * 4 + 128)
#define SC_WR SC_END
#define SC_CNT (SC_WR + 4352)
static_assert(SC_END % 16 == 0 && SC_HIST % 16 == 0 && SC_END - SC_HIST <= NT * 16 && SC_CNT + 16384 <= SM_MISC && SC_TAB <= 4 * NT * 16 && 2 * HPB <= 80 && MAXBINS >= 24 * NGR, "scratch");
static_assert(LNUL >= 3072 && LNUL + 8 <= 4096 && GCAP % 4 == 0 && GEXT % 4 == 0, "lists");
static_assert(SM_TOTAL <= 232448 && SM_BAR % 16 == 0 && SM_SEQ % 16 == 0 && SM_SRC % 16 == 0 && SM_EA % 256 == 0, "smem");
#define PACE 18.6
#define PACE2 96
#define BRK 85
#define TOFF 9500
#define PSLEEP 20

#define GEX (MAXBINS * MAXBINS * 8)
__device__ __align__(128) uint4 g_bin[GEX + GEX / 2];
#define STR2(x) #x
#define STR(x) STR2(x)
#define TLINIT()
#define TLEND()
#define TLX 0
#define TLSTAMP(i)
#define TLMAX(i)

#define TLS(i) TLMAX(i)
#define TLE(i)
__device__ __forceinline__ uint32_t pack_bf16(float lo, float hi) {
    uint32_t r;
    asm("cvt.rn.bf16x2.f32 %0, %1, %2;" : "=r"(r) : "f"(hi), "f"(lo));
    return r;
}
__device__ __forceinline__ void mma1688_z(float (&d)[4], uint32_t a0, uint32_t a1, uint32_t b0) {
    asm("mma.sync.aligned.m16n8k8.row.col.f32.bf16.bf16.f32 {%0,%1,%2,%3}, {%4,%5}, {%6}, {%7,%7,%7,%7};"
        : "=f"(d[0]), "=f"(d[1]), "=f"(d[2]), "=f"(d[3])
        : "r"(a0), "r"(a1), "r"(b0), "f"(0.f));
}
__device__ __forceinline__ void mma_diag(float (&d)[4], uint32_t a, uint32_t b0, uint32_t b1) {
    asm("mma.sync.aligned.m16n8k16.row.col.f32.bf16.bf16.f32 {%0,%1,%2,%3}, {%4,%8,%8,%4}, {%5,%6}, {%7,%7,%7,%7};"
        : "=f"(d[0]), "=f"(d[1]), "=f"(d[2]), "=f"(d[3])
        : "r"(a), "r"(b0), "r"(b1), "f"(0.f), "r"(0));
}
__device__ __forceinline__ uint32_t s2u(const void* p) { return (uint32_t)__cvta_generic_to_shared(p); }
__device__ __forceinline__ void mbar_init(uint32_t a, int c) {
    asm volatile("mbarrier.init.shared.b64 [%0], %1;" ::"r"(a), "r"(c));
}
__device__ __forceinline__ void mbar_expect_tx(uint32_t a, int bytes) {
    asm volatile("mbarrier.arrive.expect_tx.shared.b64 _, [%0], %1;" ::"r"(a), "r"(bytes) : "memory");
}
__device__ __forceinline__ void mbar_arrive(uint32_t a) {
    asm volatile("mbarrier.arrive.shared.b64 _, [%0];" ::"r"(a) : "memory");
}
__device__ __forceinline__ void mbar_arrive_cnt(uint32_t a, int c) {
    asm volatile("mbarrier.arrive.shared.b64 _, [%0], %1;" ::"r"(a), "r"(c) : "memory");
}
__device__ __forceinline__ void mbar_wait(uint32_t a, int parity) {
    asm volatile(
        "{\n.reg .pred p;\n.reg .u32 c;\n"
        "mov.u32 c, 0;\n"
        "LAB_WAIT:\n"
        "mbarrier.try_wait.parity.shared.b64 p, [%0], %1, 2000;\n"
        "@p bra DONE;\n"
        "add.u32 c, c, 1;\n"
        "setp.lt.u32 p, c, 2000000;\n"
        "@p bra LAB_WAIT;\n"
        "trap;\n"
        "DONE:\n}" ::"r"(a),
        "r"(parity)
        : "memory");
}
__device__ __forceinline__ void mbar_wait_u(uint32_t a, int parity) {
    asm volatile(
        "{\n.reg .pred p;\n.reg .u32 c;\n"
        "mov.u32 c, 0;\n"
        "LAB_WAIT:\n"
        "mbarrier.try_wait.parity.shared.b64 p, [%0], %1, 2000;\n"
        "@p bra.uni DONE;\n"
        "add.u32 c, c, 1;\n"
        "setp.lt.u32 p, c, 2000000;\n"
        "@p bra.uni LAB_WAIT;\n"
        "trap;\n"
        "DONE:\n}" ::"r"(a),
        "r"(parity)
        : "memory");
}
__device__ __forceinline__ void mbar_spin_u(uint32_t a, int parity) {
    asm volatile(
        "{\n.reg .pred p;\n.reg .u32 c;\n"
        "mov.u32 c, 0;\n"
        "LAB_WAIT:\n"
        "mbarrier.test_wait.parity.shared.b64 p, [%0], %1;\n"
        "@p bra.uni DONE;\n"
        "add.u32 c, c, 1;\n"
        "setp.lt.u32 p, c, 20000000;\n"
        "@p bra.uni LAB_WAIT;\n"
        "trap;\n"
        "DONE:\n}" ::"r"(a),
        "r"(parity)
        : "memory");
}
__device__ __forceinline__ void mbar_lean(uint32_t a, int parity) {
    asm volatile(
        "{\n.reg .pred p;\n.reg .u32 c;\n"
        "mov.u32 c, 0;\n"
        "LAB_WAIT:\n"
        "mbarrier.try_wait.parity.shared.b64 p, [%0], %1;\n"
        "@p bra DONE;\n"
        "add.u32 c, c, 1;\n"
        "setp.lt.u32 p, c, 4000000;\n"
        "@p bra LAB_WAIT;\n"
        "trap;\n"
        "DONE:\n}" ::"r"(a),
        "r"(parity)
        : "memory");
}
__device__ __forceinline__ void mbar_lean_u(uint32_t a, int parity) {
    asm volatile(
        "{\n.reg .pred p;\n.reg .u32 c;\n"
        "mov.u32 c, 0;\n"
        "LAB_WAIT:\n"
        "mbarrier.try_wait.parity.shared.b64 p, [%0], %1;\n"
        "@p bra.uni DONE;\n"
        "add.u32 c, c, 1;\n"
        "setp.lt.u32 p, c, 4000000;\n"
        "@p bra.uni LAB_WAIT;\n"
        "trap;\n"
        "DONE:\n}" ::"r"(a),
        "r"(parity)
        : "memory");
}
__device__ __forceinline__ bool mbar_test(uint32_t a, int parity) {
    uint32_t p;
    asm volatile("{\n.reg .pred P;\nmbarrier.test_wait.parity.shared.b64 P, [%1], %2;\nselp.u32 %0, 1, 0, P;\n}"
                 : "=r"(p)
                 : "r"(a), "r"(parity)
                 : "memory");
    return p;
}
__device__ __forceinline__ bool elect() {
    uint32_t p;
    asm volatile("{\n.reg .pred P;\nelect.sync _|P, 0xffffffff;\nselp.u32 %0, 1, 0, P;\n}" : "=r"(p));
    return p;
}
__device__ __forceinline__ void tma_2d(uint32_t dst, const CUtensorMap* tm, uint32_t bar, int c0, int c1) {
    asm volatile(
        "cp.async.bulk.tensor.2d.shared::cluster.global.mbarrier::complete_tx::bytes [%0], [%1, {%3, %4}], [%2];" ::"r"(dst),
        "l"(tm), "r"(bar), "r"(c0), "r"(c1)
        : "memory");
}
__device__ __forceinline__ void tma_row(uint32_t dst, const CUtensorMap* tm, uint32_t bar, int row8) {
    tma_2d(dst, tm, bar, 0, row8);
}
__device__ __forceinline__ void tma_store(const CUtensorMap* tm, uint32_t src, int c0, int c1) {
    asm volatile("cp.async.bulk.tensor.2d.global.shared::cta.bulk_group [%0, {%2, %3}], [%1];" ::"l"(tm), "r"(src),
                 "r"(c0), "r"(c1)
                 : "memory");
}
__device__ __forceinline__ uint2 lds_v2(uint32_t a) {
    uint2 v;
    asm volatile("ld.shared.v2.u32 {%0,%1}, [%2];" : "=r"(v.x), "=r"(v.y) : "r"(a));
    return v;
}
__device__ __forceinline__ uint4 lds_v4(uint32_t a) {
    uint4 v;
    asm volatile("ld.shared.v4.u32 {%0,%1,%2,%3}, [%4];" : "=r"(v.x), "=r"(v.y), "=r"(v.z), "=r"(v.w) : "r"(a));
    return v;
}
__device__ __forceinline__ uint32_t lds_u32(uint32_t a) {
    uint32_t v;
    asm volatile("ld.shared.u32 %0, [%1];" : "=r"(v) : "r"(a));
    return v;
}
__device__ __forceinline__ uint32_t lds_u16(uint32_t a) {
    uint32_t v;
    asm volatile("ld.shared.u16 %0, [%1];" : "=r"(v) : "r"(a));
    return v;
}
__device__ __forceinline__ void sts_v2(uint32_t a, uint32_t x, uint32_t y) {
    asm volatile("st.shared.v2.u32 [%0], {%1,%2};" ::"r"(a), "r"(x), "r"(y) : "memory");
}
__device__ __forceinline__ void sts_v4(uint32_t a, uint4 v) {
    asm volatile("st.shared.v4.u32 [%0], {%1,%2,%3,%4};" ::"r"(a), "r"(v.x), "r"(v.y), "r"(v.z), "r"(v.w) : "memory");
}
__device__ __forceinline__ void stsm4(uint32_t a, uint32_t r0, uint32_t r1, uint32_t r2, uint32_t r3) {
    asm volatile("stmatrix.sync.aligned.m8n8.x4.shared.b16 [%0], {%1,%2,%3,%4};" ::"r"(a), "r"(r0), "r"(r1), "r"(r2), "r"(r3)
                 : "memory");
}
__device__ __forceinline__ void stsm2(uint32_t a, uint32_t r0, uint32_t r1) {
    asm volatile("stmatrix.sync.aligned.m8n8.x2.shared.b16 [%0], {%1,%2};" ::"r"(a), "r"(r0), "r"(r1) : "memory");
}
__device__ __forceinline__ void stsm4t(uint32_t a, uint32_t r0, uint32_t r1, uint32_t r2, uint32_t r3) {
    asm volatile("stmatrix.sync.aligned.m8n8.x4.trans.shared.b16 [%0], {%1,%2,%3,%4};" ::"r"(a), "r"(r0), "r"(r1), "r"(r2),
                 "r"(r3)
                 : "memory");
}
__device__ __forceinline__ void stsm2t(uint32_t a, uint32_t r0, uint32_t r1) {
    asm volatile("stmatrix.sync.aligned.m8n8.x2.trans.shared.b16 [%0], {%1,%2};" ::"r"(a), "r"(r0), "r"(r1) : "memory");
}
__device__ __forceinline__ void cp_async16(uint32_t d, const void* s, int n) {
    asm volatile("cp.async.cg.shared.global [%0], [%1], 16, %2;" ::"r"(d), "l"(s), "r"(n) : "memory");
}
__device__ __forceinline__ void cp_async4(uint32_t d, const void* s, int n) {
    asm volatile("cp.async.ca.shared.global [%0], [%1], 4, %2;" ::"r"(d), "l"(s), "r"(n) : "memory");
}
__device__ __forceinline__ void sts_u32(uint32_t a, uint32_t x) {
    asm volatile("st.shared.u32 [%0], %1;" ::"r"(a), "r"(x) : "memory");
}
#define FENCE_ASYNC() asm volatile("fence.proxy.async.shared::cta;" ::: "memory")
__device__ __forceinline__ int warp_incl_scan(int v, int lane) {
#pragma unroll
    for (int o = 1; o < 32; o <<= 1) {
        const int y = __shfl_up_sync(0xffffffffu, v, o);
        if (lane >= o) v += y;
    }
    return v;
}

__device__ __forceinline__ uint32_t atoms_add(uint32_t a, uint32_t v) {
    uint32_t r;
    asm volatile("atom.shared.add.u32 %0, [%1], %2;" : "=r"(r) : "r"(a), "r"(v) : "memory");
    return r;
}
__device__ __forceinline__ void sts_u16(uint32_t a, uint32_t x) {
    asm volatile("{\n.reg .b16 h;\ncvt.u16.u32 h, %1;\nst.shared.u16 [%0], h;\n}" ::"r"(a), "r"(x) : "memory");
}
#define NJ 19
__device__ __forceinline__ void consume(float (&acc)[2][NJ][4], uint32_t (&wo)[8][4], uint32_t ring, uint32_t xa0, uint32_t xa1, uint32_t so0, uint32_t bar0,
                                        uint32_t ea0, uint32_t d0, uint32_t pl0, int lz, const uint32_t (&wa)[8]) {
    asm volatile(
        "{\n"
        ".reg .pred p, pf, plead, pok, t0, t1, t2, u0, u1, u2;\n"
        ".reg .b32 ca, cb, cz, rbar;\n"
        "mov.b32 cz, 0;\n"
        "mov.b32 ca, 0x20002000;\n"
        "mov.b32 cb, 0x30003000;\n"
        ".reg .b32 cnt, so, q, qe, bar, nbar, pl, ctl, ctm, ix, iy, dl, v0, v1, v2, v3, pp;\n"
        ".reg .b16 sl, sh;\n"
        ".reg .b32 hXa0, hXa1, hXa2, hXa3, hXa4, hXa5, hXa6, hXa7, hXb0, hXb1, hXb2, hXb3, hXb4, hXb5, hXb6, hXb7, hYa0, hYa1, hYa2, hYa3, hYa4, hYa5, hYa6, hYa7, hYb0, hYb1, hYb2, hYb3, hYb4, hYb5, hYb6, hYb7, hLa0, hLa1, hLa2, hLa3, hLa4, hLa5, hLa6, hLa7, hLb0, hLb1, hLb2, hLb3, hLb4, hLb5, hLb6, hLb7;\n"
        ".reg .b32 pX0, pX1, pX2, pX3, pY0, pY1, pY2, pY3;\n"
        ".reg .f32 r0, r1, r2, r3, r4, r5, r6, r7, r8, r9, r10, r11, r12, r13, r14, r15;\n"
        ".reg .b64 daX, dbX, daY, dbY, de0, de1;\n"
        ".reg .b32 dh<6>, eb0, par, npar, wa<8>, uz, bend;\n"
        "add.u32 wa0, %192, %191;\n"
        "add.u32 wa1, %193, %191;\n"
        "add.u32 wa2, %194, %191;\n"
        "add.u32 wa3, %195, %191;\n"
        "add.u32 wa4, %196, %191;\n"
        "add.u32 wa5, %197, %191;\n"
        "add.u32 wa6, %198, %191;\n"
        "add.u32 wa7, %199, %191;\n"
        "mov.f32 %0, 0f00000000;\n"
        "mov.f32 %1, 0f00000000;\n"
        "mov.f32 %2, 0f00000000;\n"
        "mov.f32 %3, 0f00000000;\n"
        "mov.f32 %4, 0f00000000;\n"
        "mov.f32 %5, 0f00000000;\n"
        "mov.f32 %6, 0f00000000;\n"
        "mov.f32 %7, 0f00000000;\n"
        "mov.f32 %8, 0f00000000;\n"
        "mov.f32 %9, 0f00000000;\n"
        "mov.f32 %10, 0f00000000;\n"
        "mov.f32 %11, 0f00000000;\n"
        "mov.f32 %12, 0f00000000;\n"
        "mov.f32 %13, 0f00000000;\n"
        "mov.f32 %14, 0f00000000;\n"
        "mov.f32 %15, 0f00000000;\n"
        "mov.f32 %16, 0f00000000;\n"
        "mov.f32 %17, 0f00000000;\n"
        "mov.f32 %18, 0f00000000;\n"
        "mov.f32 %19, 0f00000000;\n"
        "mov.f32 %20, 0f00000000;\n"
        "mov.f32 %21, 0f00000000;\n"
        "mov.f32 %22, 0f00000000;\n"
        "mov.f32 %23, 0f00000000;\n"
        "mov.f32 %24, 0f00000000;\n"
        "mov.f32 %25, 0f00000000;\n"
        "mov.f32 %26, 0f00000000;\n"
        "mov.f32 %27, 0f00000000;\n"
        "mov.f32 %28, 0f00000000;\n"
        "mov.f32 %29, 0f00000000;\n"
        "mov.f32 %30, 0f00000000;\n"
        "mov.f32 %31, 0f00000000;\n"
        "mov.f32 %32, 0f00000000;\n"
        "mov.f32 %33, 0f00000000;\n"
        "mov.f32 %34, 0f00000000;\n"
        "mov.f32 %35, 0f00000000;\n"
        "mov.f32 %36, 0f00000000;\n"
        "mov.f32 %37, 0f00000000;\n"
        "mov.f32 %38, 0f00000000;\n"
        "mov.f32 %39, 0f00000000;\n"
        "mov.f32 %40, 0f00000000;\n"
        "mov.f32 %41, 0f00000000;\n"
        "mov.f32 %42, 0f00000000;\n"
        "mov.f32 %43, 0f00000000;\n"
        "mov.f32 %44, 0f00000000;\n"
        "mov.f32 %45, 0f00000000;\n"
        "mov.f32 %46, 0f00000000;\n"
        "mov.f32 %47, 0f00000000;\n"
        "mov.f32 %48, 0f00000000;\n"
        "mov.f32 %49, 0f00000000;\n"
        "mov.f32 %50, 0f00000000;\n"
        "mov.f32 %51, 0f00000000;\n"
        "mov.f32 %52, 0f00000000;\n"
        "mov.f32 %53, 0f00000000;\n"
        "mov.f32 %54, 0f00000000;\n"
        "mov.f32 %55, 0f00000000;\n"
        "mov.f32 %56, 0f00000000;\n"
        "mov.f32 %57, 0f00000000;\n"
        "mov.f32 %58, 0f00000000;\n"
        "mov.f32 %59, 0f00000000;\n"
        "mov.f32 %60, 0f00000000;\n"
        "mov.f32 %61, 0f00000000;\n"
        "mov.f32 %62, 0f00000000;\n"
        "mov.f32 %63, 0f00000000;\n"
        "mov.f32 %64, 0f00000000;\n"
        "mov.f32 %65, 0f00000000;\n"
        "mov.f32 %66, 0f00000000;\n"
        "mov.f32 %67, 0f00000000;\n"
        "mov.f32 %68, 0f00000000;\n"
        "mov.f32 %69, 0f00000000;\n"
        "mov.f32 %70, 0f00000000;\n"
        "mov.f32 %71, 0f00000000;\n"
        "mov.f32 %72, 0f00000000;\n"
        "mov.f32 %73, 0f00000000;\n"
        "mov.f32 %74, 0f00000000;\n"
        "mov.f32 %75, 0f00000000;\n"
        "mov.f32 %76, 0f00000000;\n"
        "mov.f32 %77, 0f00000000;\n"
        "mov.f32 %78, 0f00000000;\n"
        "mov.f32 %79, 0f00000000;\n"
        "mov.f32 %80, 0f00000000;\n"
        "mov.f32 %81, 0f00000000;\n"
        "mov.f32 %82, 0f00000000;\n"
        "mov.f32 %83, 0f00000000;\n"
        "mov.f32 %84, 0f00000000;\n"
        "mov.f32 %85, 0f00000000;\n"
        "mov.f32 %86, 0f00000000;\n"
        "mov.f32 %87, 0f00000000;\n"
        "mov.f32 %88, 0f00000000;\n"
        "mov.f32 %89, 0f00000000;\n"
        "mov.f32 %90, 0f00000000;\n"
        "mov.f32 %91, 0f00000000;\n"
        "mov.f32 %92, 0f00000000;\n"
        "mov.f32 %93, 0f00000000;\n"
        "mov.f32 %94, 0f00000000;\n"
        "mov.f32 %95, 0f00000000;\n"
        "mov.f32 %96, 0f00000000;\n"
        "mov.f32 %97, 0f00000000;\n"
        "mov.f32 %98, 0f00000000;\n"
        "mov.f32 %99, 0f00000000;\n"
        "mov.f32 %100, 0f00000000;\n"
        "mov.f32 %101, 0f00000000;\n"
        "mov.f32 %102, 0f00000000;\n"
        "mov.f32 %103, 0f00000000;\n"
        "mov.f32 %104, 0f00000000;\n"
        "mov.f32 %105, 0f00000000;\n"
        "mov.f32 %106, 0f00000000;\n"
        "mov.f32 %107, 0f00000000;\n"
        "mov.f32 %108, 0f00000000;\n"
        "mov.f32 %109, 0f00000000;\n"
        "mov.f32 %110, 0f00000000;\n"
        "mov.f32 %111, 0f00000000;\n"
        "mov.f32 %112, 0f00000000;\n"
        "mov.f32 %113, 0f00000000;\n"
        "mov.f32 %114, 0f00000000;\n"
        "mov.f32 %115, 0f00000000;\n"
        "mov.f32 %116, 0f00000000;\n"
        "mov.f32 %117, 0f00000000;\n"
        "mov.f32 %118, 0f00000000;\n"
        "mov.f32 %119, 0f00000000;\n"
        "mov.f32 %120, 0f00000000;\n"
        "mov.f32 %121, 0f00000000;\n"
        "mov.f32 %122, 0f00000000;\n"
        "mov.f32 %123, 0f00000000;\n"
        "mov.f32 %124, 0f00000000;\n"
        "mov.f32 %125, 0f00000000;\n"
        "mov.f32 %126, 0f00000000;\n"
        "mov.f32 %127, 0f00000000;\n"
        "mov.f32 %128, 0f00000000;\n"
        "mov.f32 %129, 0f00000000;\n"
        "mov.f32 %130, 0f00000000;\n"
        "mov.f32 %131, 0f00000000;\n"
        "mov.f32 %132, 0f00000000;\n"
        "mov.f32 %133, 0f00000000;\n"
        "mov.f32 %134, 0f00000000;\n"
        "mov.f32 %135, 0f00000000;\n"
        "mov.f32 %136, 0f00000000;\n"
        "mov.f32 %137, 0f00000000;\n"
        "mov.f32 %138, 0f00000000;\n"
        "mov.f32 %139, 0f00000000;\n"
        "mov.f32 %140, 0f00000000;\n"
        "mov.f32 %141, 0f00000000;\n"
        "mov.f32 %142, 0f00000000;\n"
        "mov.f32 %143, 0f00000000;\n"
        "mov.f32 %144, 0f00000000;\n"
        "mov.f32 %145, 0f00000000;\n"
        "mov.f32 %146, 0f00000000;\n"
        "mov.f32 %147, 0f00000000;\n"
        "mov.f32 %148, 0f00000000;\n"
        "mov.f32 %149, 0f00000000;\n"
        "mov.f32 %150, 0f00000000;\n"
        "mov.f32 %151, 0f00000000;\n"
        "setp.ne.u32 pf, 0, 0;\n"
        "add.u32 v0, %186, %191;\n"
        "shfl.sync.idx.b32 so, v0, 0, 31, 0xffffffff;\n"
        "mov.u32 npar, 0;\n"
        "shfl.sync.idx.b32 uz, %191, 7, 31, 0xffffffff;\n"
        "add.u32 bend, %187, " STR(NP * 16) ";\n"
        "add.u32 v0, %191, 8;\n"
        "shfl.sync.idx.b32 dh0, v0, 0, 31, 0xffffffff;\n"
        "shfl.sync.idx.b32 dh1, v0, 1, 31, 0xffffffff;\n"
        "shfl.sync.idx.b32 dh2, v0, 2, 31, 0xffffffff;\n"
        "shfl.sync.idx.b32 dh3, v0, 3, 31, 0xffffffff;\n"
        "add.u32 v0, %191, 0xc0000010;\n"
        "shfl.sync.idx.b32 dh4, v0, 4, 31, 0xffffffff;\n"
        "shfl.sync.idx.b32 dh5, v0, 5, 31, 0xffffffff;\n"
        "add.u32 v0, %191, %188;\n"
        "shfl.sync.idx.b32 eb0, v0, 0, 31, 0xffffffff;\n"
        "mov.u32 q, 0;\n"
        "mov.u32 pl, %190;\n"
        "shr.u32 nbar, so, 9;\n"
        "add.u32 nbar, nbar, %187;\n"
        "elect.sync _|plead, 0xffffffff;\n"
        "mov.b64 de0, {%188, dh4};\n"
        "mov.b64 de1, {eb0, dh5};\n"
        "mov.b32 hYa0, 0;\n"
        "mov.b32 hYa1, 0;\n"
        "mov.b32 hYa2, 0;\n"
        "mov.b32 hYa3, 0;\n"
        "mov.b32 hYa4, 0;\n"
        "mov.b32 hYa5, 0;\n"
        "mov.b32 hYa6, 0;\n"
        "mov.b32 hYa7, 0;\n"
        "mov.b32 hYb0, 0;\n"
        "mov.b32 hYb1, 0;\n"
        "mov.b32 hYb2, 0;\n"
        "mov.b32 hYb3, 0;\n"
        "mov.b32 hYb4, 0;\n"
        "mov.b32 hYb5, 0;\n"
        "mov.b32 hYb6, 0;\n"
        "mov.b32 hYb7, 0;\n"
        "mov.u32 ctm, 0x10001000;\n"
        "setp.lt.f16x2 t0|u0, ctm, cz;\n"
        "abs.f16x2 v3, ctm;\n"
        "setp.ge.f16x2 t1|u1, v3, ca;\n"
        "setp.geu.f16x2 t2|u2, v3, cb;\n"
        "ld.shared.v2.u32 {ctl, ctm}, [pl];\n"
        "add.u32 pl, pl, 8;\n"
        "add.u32 rbar, %187, " STR(DUMB) ";\n"
        "mov.b64 daX, {%189, dh0};\n"
        "mov.b64 dbX, {%189, dh1};\n"
        "mov.b64 daY, {%189, dh2};\n"
        "mov.b64 dbY, {%189, dh3};\n"
        "mov.u32 bar, nbar;\n"
        "mov.u32 par, npar;\n"
        "sub.u32 so, bar, %187;\n"
        "shl.b32 so, so, 9;\n"
        "add.u32 v0, %184, so;\n"
        "add.u32 v1, %185, so;\n"
        "add.u32 nbar, nbar, 16;\n"
        "setp.eq.u32 p, nbar, bend;\n"
        "selp.b32 nbar, %187, nbar, p;\n"
        "@p xor.b32 npar, npar, 1;\n"
        "SLOW:\n"
        "mov.u32 cnt, 0;\n"
        "W1:\n"
        "mbarrier.try_wait.parity.shared.b64 p, [bar], par;\n"
        "@p bra.uni RES;\n"
        "add.u32 cnt, cnt, 1;\n"
        "setp.lt.u32 p, cnt, 4000000;\n"
        "@p bra.uni W1;\n"
        "trap;\n"
        "CX:\n"
        "mbarrier.test_wait.parity.shared.b64 pok, [nbar], npar;\n"
        "and.b32 dl, q, 0x60;\n"
        "add.u32 dl, dl, %189;\n"
        "add.u32 v3, dl, 0;\n"
        "mov.b64 {v2, dh0}, daX;\n"
        "mov.b64 daX, {v3, dh0};\n"
        "add.u32 v3, dl, 257;\n"
        "mov.b64 {v2, dh1}, dbX;\n"
        "mov.b64 dbX, {v3, dh1};\n"
        "add.u32 v3, dl, 514;\n"
        "mov.b64 {v2, dh2}, daY;\n"
        "mov.b64 daY, {v3, dh2};\n"
        "add.u32 v3, dl, 771;\n"
        "mov.b64 {v2, dh3}, dbY;\n"
        "mov.b64 dbY, {v3, dh3};\n"
        "add.u32 q, q, 32;\n"
        "and.b32 qe, q, 0xe0;\n"
        "add.u32 v3, qe, %188;\n"
        "mov.b64 {v2, dh4}, de0;\n"
        "mov.b64 de0, {v3, dh4};\n"
        "mov.b64 {v2, dh5}, de1;\n"
        "mov.b64 de1, {v3, dh5};\n"
        "setp.lt.f16x2 t0|u0, ctl, cz;\n"
        "abs.f16x2 v3, ctl;\n"
        "setp.ge.f16x2 t1|u1, v3, ca;\n"
        "setp.geu.f16x2 t2|u2, v3, cb;\n"
        "wgmma.wait_group.sync.aligned 2;\n"
        "cvt.rn.bf16x2.f32 pX0, r1, r0;\n"
        "cvt.rn.bf16x2.f32 pX1, r3, r2;\n"
        "cvt.rn.bf16x2.f32 pX2, r9, r8;\n"
        "cvt.rn.bf16x2.f32 pX3, r11, r10;\n"
        "cvt.rn.bf16x2.f32 pY0, r5, r4;\n"
        "cvt.rn.bf16x2.f32 pY1, r7, r6;\n"
        "cvt.rn.bf16x2.f32 pY2, r13, r12;\n"
        "cvt.rn.bf16x2.f32 pY3, r15, r14;\n"
        "mov.b32 {sl, sh}, pX0;\n"
        "mov.b32 pp, {sl, sl};\n"
        "mul.rn.bf16x2 hXa0, hLa0, pp;\n"
        "mul.rn.bf16x2 hXa2, hLa2, pp;\n"
        "mov.b32 {sl, sh}, pX1;\n"
        "mov.b32 pp, {sl, sl};\n"
        "mul.rn.bf16x2 hXa1, hLa1, pp;\n"
        "mul.rn.bf16x2 hXa3, hLa3, pp;\n"
        "mov.b32 {sl, sh}, pX2;\n"
        "mov.b32 pp, {sl, sl};\n"
        "mul.rn.bf16x2 hXa4, hLa4, pp;\n"
        "mul.rn.bf16x2 hXa6, hLa6, pp;\n"
        "mov.b32 {sl, sh}, pX3;\n"
        "mov.b32 pp, {sl, sl};\n"
        "mul.rn.bf16x2 hXa5, hLa5, pp;\n"
        "mul.rn.bf16x2 hXa7, hLa7, pp;\n"
        "mov.b32 {sl, sh}, pX0;\n"
        "mov.b32 pp, {sh, sh};\n"
        "mul.rn.bf16x2 hXb0, hLb0, pp;\n"
        "mul.rn.bf16x2 hXb2, hLb2, pp;\n"
        "mov.b32 {sl, sh}, pX1;\n"
        "mov.b32 pp, {sh, sh};\n"
        "mul.rn.bf16x2 hXb1, hLb1, pp;\n"
        "mul.rn.bf16x2 hXb3, hLb3, pp;\n"
        "mov.b32 {sl, sh}, pX2;\n"
        "mov.b32 pp, {sh, sh};\n"
        "mul.rn.bf16x2 hXb4, hLb4, pp;\n"
        "mul.rn.bf16x2 hXb6, hLb6, pp;\n"
        "mov.b32 {sl, sh}, pX3;\n"
        "mov.b32 pp, {sh, sh};\n"
        "mul.rn.bf16x2 hXb5, hLb5, pp;\n"
        "mul.rn.bf16x2 hXb7, hLb7, pp;\n"
        "ldmatrix.sync.aligned.m8n8.x4.trans.shared.b16 {hLa0,hLa1,hLa2,hLa3}, [v0+4096];\n"
        "ldmatrix.sync.aligned.m8n8.x4.trans.shared.b16 {hLa4,hLa5,hLa6,hLa7}, [v1+4096];\n"
        "ldmatrix.sync.aligned.m8n8.x4.trans.shared.b16 {hLb0,hLb1,hLb2,hLb3}, [v0+6144];\n"
        "ldmatrix.sync.aligned.m8n8.x4.trans.shared.b16 {hLb4,hLb5,hLb6,hLb7}, [v1+6144];\n"
        "@t2 bra.uni T4X;\n"
        "@t1 bra.uni T2X;\n"
        "@t0 bra.uni L1X;\n"
        "L0X:\n"
        "wgmma.fence.sync.aligned;\n"
        "wgmma.mma_async.sync.aligned.m64n24k16.f32.bf16.bf16 {%0,%1,%2,%3,%4,%5,%6,%7,%8,%9,%10,%11}, {hXa0,hXa1,hXa2,hXa3}, daX, 1, 1, 1, 0;\n"
        "wgmma.mma_async.sync.aligned.m64n24k16.f32.bf16.bf16 {%76,%77,%78,%79,%80,%81,%82,%83,%84,%85,%86,%87}, {hXa4,hXa5,hXa6,hXa7}, daX, 1, 1, 1, 0;\n"
        "wgmma.commit_group.sync.aligned;\n"
        "@u2 bra.uni T4Xb;\n"
        "@u1 bra.uni T2Xb;\n"
        "@u0 bra.uni L1Xb;\n"
        "bra.uni L0Xb;\n"
        "L1X:\n"
        "wgmma.fence.sync.aligned;\n"
        "wgmma.mma_async.sync.aligned.m64n24k16.f32.bf16.bf16 {%12,%13,%14,%15,%16,%17,%18,%19,%20,%21,%22,%23}, {hXa0,hXa1,hXa2,hXa3}, daX, 1, 1, 1, 0;\n"
        "wgmma.mma_async.sync.aligned.m64n24k16.f32.bf16.bf16 {%88,%89,%90,%91,%92,%93,%94,%95,%96,%97,%98,%99}, {hXa4,hXa5,hXa6,hXa7}, daX, 1, 1, 1, 0;\n"
        "wgmma.commit_group.sync.aligned;\n"
        "@u2 bra.uni T4Xb;\n"
        "@u1 bra.uni T2Xb;\n"
        "@u0 bra.uni L1Xb;\n"
        "bra.uni L0Xb;\n"
        "T2X:\n"
        "@t0 bra.uni L3X;\n"
        "L2X:\n"
        "wgmma.fence.sync.aligned;\n"
        "wgmma.mma_async.sync.aligned.m64n24k16.f32.bf16.bf16 {%24,%25,%26,%27,%28,%29,%30,%31,%32,%33,%34,%35}, {hXa0,hXa1,hXa2,hXa3}, daX, 1, 1, 1, 0;\n"
        "wgmma.mma_async.sync.aligned.m64n24k16.f32.bf16.bf16 {%100,%101,%102,%103,%104,%105,%106,%107,%108,%109,%110,%111}, {hXa4,hXa5,hXa6,hXa7}, daX, 1, 1, 1, 0;\n"
        "wgmma.commit_group.sync.aligned;\n"
        "@u2 bra.uni T4Xb;\n"
        "@u1 bra.uni T2Xb;\n"
        "@u0 bra.uni L1Xb;\n"
        "bra.uni L0Xb;\n"
        "L3X:\n"
        "wgmma.fence.sync.aligned;\n"
        "wgmma.mma_async.sync.aligned.m64n24k16.f32.bf16.bf16 {%36,%37,%38,%39,%40,%41,%42,%43,%44,%45,%46,%47}, {hXa0,hXa1,hXa2,hXa3}, daX, 1, 1, 1, 0;\n"
        "wgmma.mma_async.sync.aligned.m64n24k16.f32.bf16.bf16 {%112,%113,%114,%115,%116,%117,%118,%119,%120,%121,%122,%123}, {hXa4,hXa5,hXa6,hXa7}, daX, 1, 1, 1, 0;\n"
        "wgmma.commit_group.sync.aligned;\n"
        "@u2 bra.uni T4Xb;\n"
        "@u1 bra.uni T2Xb;\n"
        "@u0 bra.uni L1Xb;\n"
        "bra.uni L0Xb;\n"
        "T4X:\n"
        "@!t1 bra.uni LEXIT;\n"
        "@t0 bra.uni L5X;\n"
        "L4X:\n"
        "wgmma.fence.sync.aligned;\n"
        "wgmma.mma_async.sync.aligned.m64n24k16.f32.bf16.bf16 {%48,%49,%50,%51,%52,%53,%54,%55,%56,%57,%58,%59}, {hXa0,hXa1,hXa2,hXa3}, daX, 1, 1, 1, 0;\n"
        "wgmma.mma_async.sync.aligned.m64n24k16.f32.bf16.bf16 {%124,%125,%126,%127,%128,%129,%130,%131,%132,%133,%134,%135}, {hXa4,hXa5,hXa6,hXa7}, daX, 1, 1, 1, 0;\n"
        "wgmma.commit_group.sync.aligned;\n"
        "@u2 bra.uni T4Xb;\n"
        "@u1 bra.uni T2Xb;\n"
        "@u0 bra.uni L1Xb;\n"
        "bra.uni L0Xb;\n"
        "L5X:\n"
        "wgmma.fence.sync.aligned;\n"
        "wgmma.mma_async.sync.aligned.m64n32k16.f32.bf16.bf16 {%60,%61,%62,%63,%64,%65,%66,%67,%68,%69,%70,%71,%72,%73,%74,%75}, {hXa0,hXa1,hXa2,hXa3}, daX, 1, 1, 1, 0;\n"
        "wgmma.mma_async.sync.aligned.m64n32k16.f32.bf16.bf16 {%136,%137,%138,%139,%140,%141,%142,%143,%144,%145,%146,%147,%148,%149,%150,%151}, {hXa4,hXa5,hXa6,hXa7}, daX, 1, 1, 1, 0;\n"
        "wgmma.commit_group.sync.aligned;\n"
        "@u2 bra.uni T4Xb;\n"
        "@u1 bra.uni T2Xb;\n"
        "@u0 bra.uni L1Xb;\n"
        "L0Xb:\n"
        "wgmma.fence.sync.aligned;\n"
        "wgmma.mma_async.sync.aligned.m64n24k16.f32.bf16.bf16 {%0,%1,%2,%3,%4,%5,%6,%7,%8,%9,%10,%11}, {hXb0,hXb1,hXb2,hXb3}, dbX, 1, 1, 1, 0;\n"
        "wgmma.mma_async.sync.aligned.m64n24k16.f32.bf16.bf16 {%76,%77,%78,%79,%80,%81,%82,%83,%84,%85,%86,%87}, {hXb4,hXb5,hXb6,hXb7}, dbX, 1, 1, 1, 0;\n"
        "wgmma.commit_group.sync.aligned;\n"
        "bra.uni CY;\n"
        "L1Xb:\n"
        "wgmma.fence.sync.aligned;\n"
        "wgmma.mma_async.sync.aligned.m64n24k16.f32.bf16.bf16 {%12,%13,%14,%15,%16,%17,%18,%19,%20,%21,%22,%23}, {hXb0,hXb1,hXb2,hXb3}, dbX, 1, 1, 1, 0;\n"
        "wgmma.mma_async.sync.aligned.m64n24k16.f32.bf16.bf16 {%88,%89,%90,%91,%92,%93,%94,%95,%96,%97,%98,%99}, {hXb4,hXb5,hXb6,hXb7}, dbX, 1, 1, 1, 0;\n"
        "wgmma.commit_group.sync.aligned;\n"
        "bra.uni CY;\n"
        "T2Xb:\n"
        "@u0 bra.uni L3Xb;\n"
        "L2Xb:\n"
        "wgmma.fence.sync.aligned;\n"
        "wgmma.mma_async.sync.aligned.m64n24k16.f32.bf16.bf16 {%24,%25,%26,%27,%28,%29,%30,%31,%32,%33,%34,%35}, {hXb0,hXb1,hXb2,hXb3}, dbX, 1, 1, 1, 0;\n"
        "wgmma.mma_async.sync.aligned.m64n24k16.f32.bf16.bf16 {%100,%101,%102,%103,%104,%105,%106,%107,%108,%109,%110,%111}, {hXb4,hXb5,hXb6,hXb7}, dbX, 1, 1, 1, 0;\n"
        "wgmma.commit_group.sync.aligned;\n"
        "bra.uni CY;\n"
        "L3Xb:\n"
        "wgmma.fence.sync.aligned;\n"
        "wgmma.mma_async.sync.aligned.m64n24k16.f32.bf16.bf16 {%36,%37,%38,%39,%40,%41,%42,%43,%44,%45,%46,%47}, {hXb0,hXb1,hXb2,hXb3}, dbX, 1, 1, 1, 0;\n"
        "wgmma.mma_async.sync.aligned.m64n24k16.f32.bf16.bf16 {%112,%113,%114,%115,%116,%117,%118,%119,%120,%121,%122,%123}, {hXb4,hXb5,hXb6,hXb7}, dbX, 1, 1, 1, 0;\n"
        "wgmma.commit_group.sync.aligned;\n"
        "bra.uni CY;\n"
        "T4Xb:\n"
        "@u0 bra.uni L5Xb;\n"
        "L4Xb:\n"
        "wgmma.fence.sync.aligned;\n"
        "wgmma.mma_async.sync.aligned.m64n24k16.f32.bf16.bf16 {%48,%49,%50,%51,%52,%53,%54,%55,%56,%57,%58,%59}, {hXb0,hXb1,hXb2,hXb3}, dbX, 1, 1, 1, 0;\n"
        "wgmma.mma_async.sync.aligned.m64n24k16.f32.bf16.bf16 {%124,%125,%126,%127,%128,%129,%130,%131,%132,%133,%134,%135}, {hXb4,hXb5,hXb6,hXb7}, dbX, 1, 1, 1, 0;\n"
        "wgmma.commit_group.sync.aligned;\n"
        "bra.uni CY;\n"
        "L5Xb:\n"
        "wgmma.fence.sync.aligned;\n"
        "wgmma.mma_async.sync.aligned.m64n32k16.f32.bf16.bf16 {%60,%61,%62,%63,%64,%65,%66,%67,%68,%69,%70,%71,%72,%73,%74,%75}, {hXb0,hXb1,hXb2,hXb3}, dbX, 1, 1, 1, 0;\n"
        "wgmma.mma_async.sync.aligned.m64n32k16.f32.bf16.bf16 {%136,%137,%138,%139,%140,%141,%142,%143,%144,%145,%146,%147,%148,%149,%150,%151}, {hXb4,hXb5,hXb6,hXb7}, dbX, 1, 1, 1, 0;\n"
        "wgmma.commit_group.sync.aligned;\n"
        "bra.uni CY;\n"
        "CY:\n"
        "mov.u32 rbar, bar;\n"
        "mov.u32 bar, nbar;\n"
        "mov.u32 par, npar;\n"
        "sub.u32 so, bar, %187;\n"
        "shl.b32 so, so, 9;\n"
        "add.u32 v0, %184, so;\n"
        "add.u32 v1, %185, so;\n"
        "add.u32 nbar, nbar, 16;\n"
        "setp.eq.u32 p, nbar, bend;\n"
        "selp.b32 nbar, %187, nbar, p;\n"
        "@p xor.b32 npar, npar, 1;\n"
        "wgmma.wait_group.sync.aligned 2;\n"
        "lop3.b32 v2, hLa3, hLa7, hLb3, 0x80;\n"
        "lop3.b32 v2, v2, hLb7, uz, 0x80;\n"
        "add.u32 v2, v2, rbar;\n"
        "@plead mbarrier.arrive.shared.b64 _, [v2+8];\n"
        "setp.lt.f16x2 t0|u0, ctm, cz;\n"
        "abs.f16x2 v3, ctm;\n"
        "setp.ge.f16x2 t1|u1, v3, ca;\n"
        "setp.geu.f16x2 t2|u2, v3, cb;\n"
        "ld.shared.v2.u32 {ctl, ctm}, [pl];\n"
        "add.u32 pl, pl, 8;\n"
        "mov.b32 {sl, sh}, pY0;\n"
        "mov.b32 pp, {sl, sl};\n"
        "mul.rn.bf16x2 hYa0, hLa0, pp;\n"
        "mul.rn.bf16x2 hYa2, hLa2, pp;\n"
        "mov.b32 {sl, sh}, pY1;\n"
        "mov.b32 pp, {sl, sl};\n"
        "mul.rn.bf16x2 hYa1, hLa1, pp;\n"
        "mul.rn.bf16x2 hYa3, hLa3, pp;\n"
        "mov.b32 {sl, sh}, pY2;\n"
        "mov.b32 pp, {sl, sl};\n"
        "mul.rn.bf16x2 hYa4, hLa4, pp;\n"
        "mul.rn.bf16x2 hYa6, hLa6, pp;\n"
        "mov.b32 {sl, sh}, pY3;\n"
        "mov.b32 pp, {sl, sl};\n"
        "mul.rn.bf16x2 hYa5, hLa5, pp;\n"
        "mul.rn.bf16x2 hYa7, hLa7, pp;\n"
        "mov.b32 {sl, sh}, pY0;\n"
        "mov.b32 pp, {sh, sh};\n"
        "mul.rn.bf16x2 hYb0, hLb0, pp;\n"
        "mul.rn.bf16x2 hYb2, hLb2, pp;\n"
        "mov.b32 {sl, sh}, pY1;\n"
        "mov.b32 pp, {sh, sh};\n"
        "mul.rn.bf16x2 hYb1, hLb1, pp;\n"
        "mul.rn.bf16x2 hYb3, hLb3, pp;\n"
        "mov.b32 {sl, sh}, pY2;\n"
        "mov.b32 pp, {sh, sh};\n"
        "mul.rn.bf16x2 hYb4, hLb4, pp;\n"
        "mul.rn.bf16x2 hYb6, hLb6, pp;\n"
        "mov.b32 {sl, sh}, pY3;\n"
        "mov.b32 pp, {sh, sh};\n"
        "mul.rn.bf16x2 hYb5, hLb5, pp;\n"
        "mul.rn.bf16x2 hYb7, hLb7, pp;\n"
        "@!pok bra.uni SLOW;\n"
        "RES:\n"
        "ldmatrix.sync.aligned.m8n8.x4.trans.shared.b16 {hLa0,hLa1,hLa2,hLa3}, [v0+0];\n"
        "ldmatrix.sync.aligned.m8n8.x4.trans.shared.b16 {hLa4,hLa5,hLa6,hLa7}, [v1+0];\n"
        "ldmatrix.sync.aligned.m8n8.x4.trans.shared.b16 {hLb0,hLb1,hLb2,hLb3}, [v0+2048];\n"
        "ldmatrix.sync.aligned.m8n8.x4.trans.shared.b16 {hLb4,hLb5,hLb6,hLb7}, [v1+2048];\n"
        "wgmma.wait_group.sync.aligned 0;\n"
        "@t2 bra.uni T4Y;\n"
        "@t1 bra.uni T2Y;\n"
        "@t0 bra.uni L1Y;\n"
        "L0Y:\n"
        "wgmma.fence.sync.aligned;\n"
        "wgmma.mma_async.sync.aligned.m64n16k16.f32.bf16.bf16 {r0,r1,r2,r3,r4,r5,r6,r7}, {wa0,wa1,wa2,wa3}, de0, pf, 1, 1, 0;\n"
        "wgmma.mma_async.sync.aligned.m64n16k16.f32.bf16.bf16 {r8,r9,r10,r11,r12,r13,r14,r15}, {wa4,wa5,wa6,wa7}, de1, pf, 1, 1, 0;\n"
        "wgmma.commit_group.sync.aligned;\n"
        "wgmma.mma_async.sync.aligned.m64n24k16.f32.bf16.bf16 {%0,%1,%2,%3,%4,%5,%6,%7,%8,%9,%10,%11}, {hYa0,hYa1,hYa2,hYa3}, daY, 1, 1, 1, 0;\n"
        "wgmma.mma_async.sync.aligned.m64n24k16.f32.bf16.bf16 {%76,%77,%78,%79,%80,%81,%82,%83,%84,%85,%86,%87}, {hYa4,hYa5,hYa6,hYa7}, daY, 1, 1, 1, 0;\n"
        "wgmma.commit_group.sync.aligned;\n"
        "@u2 bra.uni T4Yb;\n"
        "@u1 bra.uni T2Yb;\n"
        "@u0 bra.uni L1Yb;\n"
        "bra.uni L0Yb;\n"
        "L1Y:\n"
        "wgmma.fence.sync.aligned;\n"
        "wgmma.mma_async.sync.aligned.m64n16k16.f32.bf16.bf16 {r0,r1,r2,r3,r4,r5,r6,r7}, {wa0,wa1,wa2,wa3}, de0, pf, 1, 1, 0;\n"
        "wgmma.mma_async.sync.aligned.m64n16k16.f32.bf16.bf16 {r8,r9,r10,r11,r12,r13,r14,r15}, {wa4,wa5,wa6,wa7}, de1, pf, 1, 1, 0;\n"
        "wgmma.commit_group.sync.aligned;\n"
        "wgmma.mma_async.sync.aligned.m64n24k16.f32.bf16.bf16 {%12,%13,%14,%15,%16,%17,%18,%19,%20,%21,%22,%23}, {hYa0,hYa1,hYa2,hYa3}, daY, 1, 1, 1, 0;\n"
        "wgmma.mma_async.sync.aligned.m64n24k16.f32.bf16.bf16 {%88,%89,%90,%91,%92,%93,%94,%95,%96,%97,%98,%99}, {hYa4,hYa5,hYa6,hYa7}, daY, 1, 1, 1, 0;\n"
        "wgmma.commit_group.sync.aligned;\n"
        "@u2 bra.uni T4Yb;\n"
        "@u1 bra.uni T2Yb;\n"
        "@u0 bra.uni L1Yb;\n"
        "bra.uni L0Yb;\n"
        "T2Y:\n"
        "@t0 bra.uni L3Y;\n"
        "L2Y:\n"
        "wgmma.fence.sync.aligned;\n"
        "wgmma.mma_async.sync.aligned.m64n16k16.f32.bf16.bf16 {r0,r1,r2,r3,r4,r5,r6,r7}, {wa0,wa1,wa2,wa3}, de0, pf, 1, 1, 0;\n"
        "wgmma.mma_async.sync.aligned.m64n16k16.f32.bf16.bf16 {r8,r9,r10,r11,r12,r13,r14,r15}, {wa4,wa5,wa6,wa7}, de1, pf, 1, 1, 0;\n"
        "wgmma.commit_group.sync.aligned;\n"
        "wgmma.mma_async.sync.aligned.m64n24k16.f32.bf16.bf16 {%24,%25,%26,%27,%28,%29,%30,%31,%32,%33,%34,%35}, {hYa0,hYa1,hYa2,hYa3}, daY, 1, 1, 1, 0;\n"
        "wgmma.mma_async.sync.aligned.m64n24k16.f32.bf16.bf16 {%100,%101,%102,%103,%104,%105,%106,%107,%108,%109,%110,%111}, {hYa4,hYa5,hYa6,hYa7}, daY, 1, 1, 1, 0;\n"
        "wgmma.commit_group.sync.aligned;\n"
        "@u2 bra.uni T4Yb;\n"
        "@u1 bra.uni T2Yb;\n"
        "@u0 bra.uni L1Yb;\n"
        "bra.uni L0Yb;\n"
        "L3Y:\n"
        "wgmma.fence.sync.aligned;\n"
        "wgmma.mma_async.sync.aligned.m64n16k16.f32.bf16.bf16 {r0,r1,r2,r3,r4,r5,r6,r7}, {wa0,wa1,wa2,wa3}, de0, pf, 1, 1, 0;\n"
        "wgmma.mma_async.sync.aligned.m64n16k16.f32.bf16.bf16 {r8,r9,r10,r11,r12,r13,r14,r15}, {wa4,wa5,wa6,wa7}, de1, pf, 1, 1, 0;\n"
        "wgmma.commit_group.sync.aligned;\n"
        "wgmma.mma_async.sync.aligned.m64n24k16.f32.bf16.bf16 {%36,%37,%38,%39,%40,%41,%42,%43,%44,%45,%46,%47}, {hYa0,hYa1,hYa2,hYa3}, daY, 1, 1, 1, 0;\n"
        "wgmma.mma_async.sync.aligned.m64n24k16.f32.bf16.bf16 {%112,%113,%114,%115,%116,%117,%118,%119,%120,%121,%122,%123}, {hYa4,hYa5,hYa6,hYa7}, daY, 1, 1, 1, 0;\n"
        "wgmma.commit_group.sync.aligned;\n"
        "@u2 bra.uni T4Yb;\n"
        "@u1 bra.uni T2Yb;\n"
        "@u0 bra.uni L1Yb;\n"
        "bra.uni L0Yb;\n"
        "T4Y:\n"
        "@t0 bra.uni L5Y;\n"
        "L4Y:\n"
        "wgmma.fence.sync.aligned;\n"
        "wgmma.mma_async.sync.aligned.m64n16k16.f32.bf16.bf16 {r0,r1,r2,r3,r4,r5,r6,r7}, {wa0,wa1,wa2,wa3}, de0, pf, 1, 1, 0;\n"
        "wgmma.mma_async.sync.aligned.m64n16k16.f32.bf16.bf16 {r8,r9,r10,r11,r12,r13,r14,r15}, {wa4,wa5,wa6,wa7}, de1, pf, 1, 1, 0;\n"
        "wgmma.commit_group.sync.aligned;\n"
        "wgmma.mma_async.sync.aligned.m64n24k16.f32.bf16.bf16 {%48,%49,%50,%51,%52,%53,%54,%55,%56,%57,%58,%59}, {hYa0,hYa1,hYa2,hYa3}, daY, 1, 1, 1, 0;\n"
        "wgmma.mma_async.sync.aligned.m64n24k16.f32.bf16.bf16 {%124,%125,%126,%127,%128,%129,%130,%131,%132,%133,%134,%135}, {hYa4,hYa5,hYa6,hYa7}, daY, 1, 1, 1, 0;\n"
        "wgmma.commit_group.sync.aligned;\n"
        "@u2 bra.uni T4Yb;\n"
        "@u1 bra.uni T2Yb;\n"
        "@u0 bra.uni L1Yb;\n"
        "bra.uni L0Yb;\n"
        "L5Y:\n"
        "wgmma.fence.sync.aligned;\n"
        "wgmma.mma_async.sync.aligned.m64n16k16.f32.bf16.bf16 {r0,r1,r2,r3,r4,r5,r6,r7}, {wa0,wa1,wa2,wa3}, de0, pf, 1, 1, 0;\n"
        "wgmma.mma_async.sync.aligned.m64n16k16.f32.bf16.bf16 {r8,r9,r10,r11,r12,r13,r14,r15}, {wa4,wa5,wa6,wa7}, de1, pf, 1, 1, 0;\n"
        "wgmma.commit_group.sync.aligned;\n"
        "wgmma.mma_async.sync.aligned.m64n32k16.f32.bf16.bf16 {%60,%61,%62,%63,%64,%65,%66,%67,%68,%69,%70,%71,%72,%73,%74,%75}, {hYa0,hYa1,hYa2,hYa3}, daY, 1, 1, 1, 0;\n"
        "wgmma.mma_async.sync.aligned.m64n32k16.f32.bf16.bf16 {%136,%137,%138,%139,%140,%141,%142,%143,%144,%145,%146,%147,%148,%149,%150,%151}, {hYa4,hYa5,hYa6,hYa7}, daY, 1, 1, 1, 0;\n"
        "wgmma.commit_group.sync.aligned;\n"
        "@u2 bra.uni T4Yb;\n"
        "@u1 bra.uni T2Yb;\n"
        "@u0 bra.uni L1Yb;\n"
        "L0Yb:\n"
        "wgmma.fence.sync.aligned;\n"
        "wgmma.mma_async.sync.aligned.m64n24k16.f32.bf16.bf16 {%0,%1,%2,%3,%4,%5,%6,%7,%8,%9,%10,%11}, {hYb0,hYb1,hYb2,hYb3}, dbY, 1, 1, 1, 0;\n"
        "wgmma.mma_async.sync.aligned.m64n24k16.f32.bf16.bf16 {%76,%77,%78,%79,%80,%81,%82,%83,%84,%85,%86,%87}, {hYb4,hYb5,hYb6,hYb7}, dbY, 1, 1, 1, 0;\n"
        "wgmma.commit_group.sync.aligned;\n"
        "bra.uni CX;\n"
        "L1Yb:\n"
        "wgmma.fence.sync.aligned;\n"
        "wgmma.mma_async.sync.aligned.m64n24k16.f32.bf16.bf16 {%12,%13,%14,%15,%16,%17,%18,%19,%20,%21,%22,%23}, {hYb0,hYb1,hYb2,hYb3}, dbY, 1, 1, 1, 0;\n"
        "wgmma.mma_async.sync.aligned.m64n24k16.f32.bf16.bf16 {%88,%89,%90,%91,%92,%93,%94,%95,%96,%97,%98,%99}, {hYb4,hYb5,hYb6,hYb7}, dbY, 1, 1, 1, 0;\n"
        "wgmma.commit_group.sync.aligned;\n"
        "bra.uni CX;\n"
        "T2Yb:\n"
        "@u0 bra.uni L3Yb;\n"
        "L2Yb:\n"
        "wgmma.fence.sync.aligned;\n"
        "wgmma.mma_async.sync.aligned.m64n24k16.f32.bf16.bf16 {%24,%25,%26,%27,%28,%29,%30,%31,%32,%33,%34,%35}, {hYb0,hYb1,hYb2,hYb3}, dbY, 1, 1, 1, 0;\n"
        "wgmma.mma_async.sync.aligned.m64n24k16.f32.bf16.bf16 {%100,%101,%102,%103,%104,%105,%106,%107,%108,%109,%110,%111}, {hYb4,hYb5,hYb6,hYb7}, dbY, 1, 1, 1, 0;\n"
        "wgmma.commit_group.sync.aligned;\n"
        "bra.uni CX;\n"
        "L3Yb:\n"
        "wgmma.fence.sync.aligned;\n"
        "wgmma.mma_async.sync.aligned.m64n24k16.f32.bf16.bf16 {%36,%37,%38,%39,%40,%41,%42,%43,%44,%45,%46,%47}, {hYb0,hYb1,hYb2,hYb3}, dbY, 1, 1, 1, 0;\n"
        "wgmma.mma_async.sync.aligned.m64n24k16.f32.bf16.bf16 {%112,%113,%114,%115,%116,%117,%118,%119,%120,%121,%122,%123}, {hYb4,hYb5,hYb6,hYb7}, dbY, 1, 1, 1, 0;\n"
        "wgmma.commit_group.sync.aligned;\n"
        "bra.uni CX;\n"
        "T4Yb:\n"
        "@u0 bra.uni L5Yb;\n"
        "L4Yb:\n"
        "wgmma.fence.sync.aligned;\n"
        "wgmma.mma_async.sync.aligned.m64n24k16.f32.bf16.bf16 {%48,%49,%50,%51,%52,%53,%54,%55,%56,%57,%58,%59}, {hYb0,hYb1,hYb2,hYb3}, dbY, 1, 1, 1, 0;\n"
        "wgmma.mma_async.sync.aligned.m64n24k16.f32.bf16.bf16 {%124,%125,%126,%127,%128,%129,%130,%131,%132,%133,%134,%135}, {hYb4,hYb5,hYb6,hYb7}, dbY, 1, 1, 1, 0;\n"
        "wgmma.commit_group.sync.aligned;\n"
        "bra.uni CX;\n"
        "L5Yb:\n"
        "wgmma.fence.sync.aligned;\n"
        "wgmma.mma_async.sync.aligned.m64n32k16.f32.bf16.bf16 {%60,%61,%62,%63,%64,%65,%66,%67,%68,%69,%70,%71,%72,%73,%74,%75}, {hYb0,hYb1,hYb2,hYb3}, dbY, 1, 1, 1, 0;\n"
        "wgmma.mma_async.sync.aligned.m64n32k16.f32.bf16.bf16 {%136,%137,%138,%139,%140,%141,%142,%143,%144,%145,%146,%147,%148,%149,%150,%151}, {hYb4,hYb5,hYb6,hYb7}, dbY, 1, 1, 1, 0;\n"
        "wgmma.commit_group.sync.aligned;\n"
        "bra.uni CX;\n"
        "LEXIT:\n"
        "mov.u32 v2, %%tid.x;\n"
        "shr.u32 v3, v2, 4;\n"
        "and.b32 v0, v3, 1;\n"
        "mad.lo.u32 v0, v0, 1024, %200;\n"
        "and.b32 v1, v2, 7;\n"
        "mad.lo.u32 v0, v1, 128, v0;\n"
        "shr.u32 pp, v2, 3;\n"
        "lop3.b32 v3, v3, pp, 6, 0xe4;\n"
        "add.u32 pp, v2, 1;\n"
        "lop3.b32 pp, v3, pp, 7, 0x28;\n"
        "mad.lo.u32 v1, pp, 16, v0;\n"
        "lop3.b32 pp, v3, v2, 7, 0x28;\n"
        "mad.lo.u32 v0, pp, 16, v0;\n"
        "@pok bra.uni LW;\n"
        "mov.u32 cnt, 0;\n"
        "W2:\n"
        "mbarrier.try_wait.parity.shared.b64 p, [nbar], npar;\n"
        "@p bra.uni LW;\n"
        "add.u32 cnt, cnt, 1;\n"
        "setp.lt.u32 p, cnt, 4000000;\n"
        "@p bra.uni W2;\n"
        "trap;\n"
        "LW:\n"
        "ldmatrix.sync.aligned.m8n8.x4.trans.shared.b16 {hLa0,hLa1,hLa2,hLa3}, [v0+" STR((NP - 2) * 8192 + 0 * SM_ODD + 0) "];\n"
        "ldmatrix.sync.aligned.m8n8.x4.trans.shared.b16 {hLa4,hLa5,hLa6,hLa7}, [v0+" STR((NP - 2) * 8192 + 0 * SM_ODD + 2048) "];\n"
        "wgmma.wait_group.sync.aligned 0;\n"
        "ldmatrix.sync.aligned.m8n8.x4.trans.shared.b16 {hLb0,hLb1,hLb2,hLb3}, [v0+" STR((NP - 2) * 8192 + 0 * SM_ODD + 4096) "];\n"
        "ldmatrix.sync.aligned.m8n8.x4.trans.shared.b16 {hLb4,hLb5,hLb6,hLb7}, [v0+" STR((NP - 2) * 8192 + 0 * SM_ODD + 6144) "];\n"
        "ldmatrix.sync.aligned.m8n8.x4.trans.shared.b16 {hXa0,hXa1,hXa2,hXa3}, [v1+" STR((NP - 2) * 8192 + 1 * SM_ODD + 0) "];\n"
        "ldmatrix.sync.aligned.m8n8.x4.trans.shared.b16 {hXa4,hXa5,hXa6,hXa7}, [v1+" STR((NP - 2) * 8192 + 1 * SM_ODD + 2048) "];\n"
        "ldmatrix.sync.aligned.m8n8.x4.trans.shared.b16 {hXb0,hXb1,hXb2,hXb3}, [v1+" STR((NP - 2) * 8192 + 1 * SM_ODD + 4096) "];\n"
        "ldmatrix.sync.aligned.m8n8.x4.trans.shared.b16 {hXb4,hXb5,hXb6,hXb7}, [v1+" STR((NP - 2) * 8192 + 1 * SM_ODD + 6144) "];\n"
        "mov.b32 %152, hLa0;\n"
        "mov.b32 %153, hLa1;\n"
        "mov.b32 %154, hLa2;\n"
        "mov.b32 %155, hLa3;\n"
        "mov.b32 %156, hLa4;\n"
        "mov.b32 %157, hLa5;\n"
        "mov.b32 %158, hLa6;\n"
        "mov.b32 %159, hLa7;\n"
        "mov.b32 %160, hLb0;\n"
        "mov.b32 %161, hLb1;\n"
        "mov.b32 %162, hLb2;\n"
        "mov.b32 %163, hLb3;\n"
        "mov.b32 %164, hLb4;\n"
        "mov.b32 %165, hLb5;\n"
        "mov.b32 %166, hLb6;\n"
        "mov.b32 %167, hLb7;\n"
        "mov.b32 %168, hXa0;\n"
        "mov.b32 %169, hXa1;\n"
        "mov.b32 %170, hXa2;\n"
        "mov.b32 %171, hXa3;\n"
        "mov.b32 %172, hXa4;\n"
        "mov.b32 %173, hXa5;\n"
        "mov.b32 %174, hXa6;\n"
        "mov.b32 %175, hXa7;\n"
        "mov.b32 %176, hXb0;\n"
        "mov.b32 %177, hXb1;\n"
        "mov.b32 %178, hXb2;\n"
        "mov.b32 %179, hXb3;\n"
        "mov.b32 %180, hXb4;\n"
        "mov.b32 %181, hXb5;\n"
        "mov.b32 %182, hXb6;\n"
        "mov.b32 %183, hXb7;\n"
        "}\n"
        : "=f"(acc[0][0][0]), "=f"(acc[0][0][1]), "=f"(acc[0][0][2]), "=f"(acc[0][0][3]),
          "=f"(acc[0][1][0]), "=f"(acc[0][1][1]), "=f"(acc[0][1][2]), "=f"(acc[0][1][3]),
          "=f"(acc[0][2][0]), "=f"(acc[0][2][1]), "=f"(acc[0][2][2]), "=f"(acc[0][2][3]),
          "=f"(acc[0][3][0]), "=f"(acc[0][3][1]), "=f"(acc[0][3][2]), "=f"(acc[0][3][3]),
          "=f"(acc[0][4][0]), "=f"(acc[0][4][1]), "=f"(acc[0][4][2]), "=f"(acc[0][4][3]),
          "=f"(acc[0][5][0]), "=f"(acc[0][5][1]), "=f"(acc[0][5][2]), "=f"(acc[0][5][3]),
          "=f"(acc[0][6][0]), "=f"(acc[0][6][1]), "=f"(acc[0][6][2]), "=f"(acc[0][6][3]),
          "=f"(acc[0][7][0]), "=f"(acc[0][7][1]), "=f"(acc[0][7][2]), "=f"(acc[0][7][3]),
          "=f"(acc[0][8][0]), "=f"(acc[0][8][1]), "=f"(acc[0][8][2]), "=f"(acc[0][8][3]),
          "=f"(acc[0][9][0]), "=f"(acc[0][9][1]), "=f"(acc[0][9][2]), "=f"(acc[0][9][3]),
          "=f"(acc[0][10][0]), "=f"(acc[0][10][1]), "=f"(acc[0][10][2]), "=f"(acc[0][10][3]),
          "=f"(acc[0][11][0]), "=f"(acc[0][11][1]), "=f"(acc[0][11][2]), "=f"(acc[0][11][3]),
          "=f"(acc[0][12][0]), "=f"(acc[0][12][1]), "=f"(acc[0][12][2]), "=f"(acc[0][12][3]),
          "=f"(acc[0][13][0]), "=f"(acc[0][13][1]), "=f"(acc[0][13][2]), "=f"(acc[0][13][3]),
          "=f"(acc[0][14][0]), "=f"(acc[0][14][1]), "=f"(acc[0][14][2]), "=f"(acc[0][14][3]),
          "=f"(acc[0][15][0]), "=f"(acc[0][15][1]), "=f"(acc[0][15][2]), "=f"(acc[0][15][3]),
          "=f"(acc[0][16][0]), "=f"(acc[0][16][1]), "=f"(acc[0][16][2]), "=f"(acc[0][16][3]),
          "=f"(acc[0][17][0]), "=f"(acc[0][17][1]), "=f"(acc[0][17][2]), "=f"(acc[0][17][3]),
          "=f"(acc[0][18][0]), "=f"(acc[0][18][1]), "=f"(acc[0][18][2]), "=f"(acc[0][18][3]),
          "=f"(acc[1][0][0]), "=f"(acc[1][0][1]), "=f"(acc[1][0][2]), "=f"(acc[1][0][3]),
          "=f"(acc[1][1][0]), "=f"(acc[1][1][1]), "=f"(acc[1][1][2]), "=f"(acc[1][1][3]),
          "=f"(acc[1][2][0]), "=f"(acc[1][2][1]), "=f"(acc[1][2][2]), "=f"(acc[1][2][3]),
          "=f"(acc[1][3][0]), "=f"(acc[1][3][1]), "=f"(acc[1][3][2]), "=f"(acc[1][3][3]),
          "=f"(acc[1][4][0]), "=f"(acc[1][4][1]), "=f"(acc[1][4][2]), "=f"(acc[1][4][3]),
          "=f"(acc[1][5][0]), "=f"(acc[1][5][1]), "=f"(acc[1][5][2]), "=f"(acc[1][5][3]),
          "=f"(acc[1][6][0]), "=f"(acc[1][6][1]), "=f"(acc[1][6][2]), "=f"(acc[1][6][3]),
          "=f"(acc[1][7][0]), "=f"(acc[1][7][1]), "=f"(acc[1][7][2]), "=f"(acc[1][7][3]),
          "=f"(acc[1][8][0]), "=f"(acc[1][8][1]), "=f"(acc[1][8][2]), "=f"(acc[1][8][3]),
          "=f"(acc[1][9][0]), "=f"(acc[1][9][1]), "=f"(acc[1][9][2]), "=f"(acc[1][9][3]),
          "=f"(acc[1][10][0]), "=f"(acc[1][10][1]), "=f"(acc[1][10][2]), "=f"(acc[1][10][3]),
          "=f"(acc[1][11][0]), "=f"(acc[1][11][1]), "=f"(acc[1][11][2]), "=f"(acc[1][11][3]),
          "=f"(acc[1][12][0]), "=f"(acc[1][12][1]), "=f"(acc[1][12][2]), "=f"(acc[1][12][3]),
          "=f"(acc[1][13][0]), "=f"(acc[1][13][1]), "=f"(acc[1][13][2]), "=f"(acc[1][13][3]),
          "=f"(acc[1][14][0]), "=f"(acc[1][14][1]), "=f"(acc[1][14][2]), "=f"(acc[1][14][3]),
          "=f"(acc[1][15][0]), "=f"(acc[1][15][1]), "=f"(acc[1][15][2]), "=f"(acc[1][15][3]),
          "=f"(acc[1][16][0]), "=f"(acc[1][16][1]), "=f"(acc[1][16][2]), "=f"(acc[1][16][3]),
          "=f"(acc[1][17][0]), "=f"(acc[1][17][1]), "=f"(acc[1][17][2]), "=f"(acc[1][17][3]),
          "=f"(acc[1][18][0]), "=f"(acc[1][18][1]), "=f"(acc[1][18][2]), "=f"(acc[1][18][3]),
          "=r"(wo[0][0]), "=r"(wo[0][1]), "=r"(wo[0][2]), "=r"(wo[0][3]),
          "=r"(wo[1][0]), "=r"(wo[1][1]), "=r"(wo[1][2]), "=r"(wo[1][3]),
          "=r"(wo[2][0]), "=r"(wo[2][1]), "=r"(wo[2][2]), "=r"(wo[2][3]),
          "=r"(wo[3][0]), "=r"(wo[3][1]), "=r"(wo[3][2]), "=r"(wo[3][3]),
          "=r"(wo[4][0]), "=r"(wo[4][1]), "=r"(wo[4][2]), "=r"(wo[4][3]),
          "=r"(wo[5][0]), "=r"(wo[5][1]), "=r"(wo[5][2]), "=r"(wo[5][3]),
          "=r"(wo[6][0]), "=r"(wo[6][1]), "=r"(wo[6][2]), "=r"(wo[6][3]),
          "=r"(wo[7][0]), "=r"(wo[7][1]), "=r"(wo[7][2]), "=r"(wo[7][3])
        : "r"(xa0), "r"(xa1), "r"(so0), "r"(bar0), "r"(ea0), "r"(d0), "r"(pl0), "r"(lz), "r"(wa[0]), "r"(wa[1]), "r"(wa[2]),
          "r"(wa[3]), "r"(wa[4]), "r"(wa[5]), "r"(wa[6]), "r"(wa[7]), "r"(ring)
        : "memory");
}
#define CH0 4
#define CH1 7
#define CH2 8
#define CH3 10
#define CH4 9
__device__ __forceinline__ void wgmma_out(float (&o)[4][4], const uint32_t (&a)[4], uint64_t db, bool acc) {
    if (!acc)
        asm volatile(
            "wgmma.mma_async.sync.aligned.m64n32k16.f32.bf16.bf16 {%0,%1,%2,%3,%4,%5,%6,%7,%8,%9,%10,%11,%12,%13,%14,%15}, {%16,%17,%18,%19}, %20, 0, 1, 1, 1;"
            : "=f"(o[0][0]), "=f"(o[0][1]), "=f"(o[0][2]), "=f"(o[0][3]),
              "=f"(o[1][0]), "=f"(o[1][1]), "=f"(o[1][2]), "=f"(o[1][3]),
              "=f"(o[2][0]), "=f"(o[2][1]), "=f"(o[2][2]), "=f"(o[2][3]),
              "=f"(o[3][0]), "=f"(o[3][1]), "=f"(o[3][2]), "=f"(o[3][3])
            : "r"(a[0]), "r"(a[1]), "r"(a[2]), "r"(a[3]), "l"(db)
            : "memory");
    else
        asm volatile(
            "wgmma.mma_async.sync.aligned.m64n32k16.f32.bf16.bf16 {%0,%1,%2,%3,%4,%5,%6,%7,%8,%9,%10,%11,%12,%13,%14,%15}, {%16,%17,%18,%19}, %20, 1, 1, 1, 1;"
            : "+f"(o[0][0]), "+f"(o[0][1]), "+f"(o[0][2]), "+f"(o[0][3]),
              "+f"(o[1][0]), "+f"(o[1][1]), "+f"(o[1][2]), "+f"(o[1][3]),
              "+f"(o[2][0]), "+f"(o[2][1]), "+f"(o[2][2]), "+f"(o[2][3]),
              "+f"(o[3][0]), "+f"(o[3][1]), "+f"(o[3][2]), "+f"(o[3][3])
            : "r"(a[0]), "r"(a[1]), "r"(a[2]), "r"(a[3]), "l"(db)
            : "memory");
}
__device__ __forceinline__ void wgmma_out(float (&o)[7][4], const uint32_t (&a)[4], uint64_t db, bool acc) {
    if (!acc)
        asm volatile(
            "wgmma.mma_async.sync.aligned.m64n56k16.f32.bf16.bf16 {%0,%1,%2,%3,%4,%5,%6,%7,%8,%9,%10,%11,%12,%13,%14,%15,%16,%17,%18,%19,%20,%21,%22,%23,%24,%25,%26,%27}, {%28,%29,%30,%31}, %32, 0, 1, 1, 1;"
            : "=f"(o[0][0]), "=f"(o[0][1]), "=f"(o[0][2]), "=f"(o[0][3]),
              "=f"(o[1][0]), "=f"(o[1][1]), "=f"(o[1][2]), "=f"(o[1][3]),
              "=f"(o[2][0]), "=f"(o[2][1]), "=f"(o[2][2]), "=f"(o[2][3]),
              "=f"(o[3][0]), "=f"(o[3][1]), "=f"(o[3][2]), "=f"(o[3][3]),
              "=f"(o[4][0]), "=f"(o[4][1]), "=f"(o[4][2]), "=f"(o[4][3]),
              "=f"(o[5][0]), "=f"(o[5][1]), "=f"(o[5][2]), "=f"(o[5][3]),
              "=f"(o[6][0]), "=f"(o[6][1]), "=f"(o[6][2]), "=f"(o[6][3])
            : "r"(a[0]), "r"(a[1]), "r"(a[2]), "r"(a[3]), "l"(db)
            : "memory");
    else
        asm volatile(
            "wgmma.mma_async.sync.aligned.m64n56k16.f32.bf16.bf16 {%0,%1,%2,%3,%4,%5,%6,%7,%8,%9,%10,%11,%12,%13,%14,%15,%16,%17,%18,%19,%20,%21,%22,%23,%24,%25,%26,%27}, {%28,%29,%30,%31}, %32, 1, 1, 1, 1;"
            : "+f"(o[0][0]), "+f"(o[0][1]), "+f"(o[0][2]), "+f"(o[0][3]),
              "+f"(o[1][0]), "+f"(o[1][1]), "+f"(o[1][2]), "+f"(o[1][3]),
              "+f"(o[2][0]), "+f"(o[2][1]), "+f"(o[2][2]), "+f"(o[2][3]),
              "+f"(o[3][0]), "+f"(o[3][1]), "+f"(o[3][2]), "+f"(o[3][3]),
              "+f"(o[4][0]), "+f"(o[4][1]), "+f"(o[4][2]), "+f"(o[4][3]),
              "+f"(o[5][0]), "+f"(o[5][1]), "+f"(o[5][2]), "+f"(o[5][3]),
              "+f"(o[6][0]), "+f"(o[6][1]), "+f"(o[6][2]), "+f"(o[6][3])
            : "r"(a[0]), "r"(a[1]), "r"(a[2]), "r"(a[3]), "l"(db)
            : "memory");
}
__device__ __forceinline__ void wgmma_out(float (&o)[8][4], const uint32_t (&a)[4], uint64_t db, bool acc) {
    if (!acc)
        asm volatile(
            "wgmma.mma_async.sync.aligned.m64n64k16.f32.bf16.bf16 {%0,%1,%2,%3,%4,%5,%6,%7,%8,%9,%10,%11,%12,%13,%14,%15,%16,%17,%18,%19,%20,%21,%22,%23,%24,%25,%26,%27,%28,%29,%30,%31}, {%32,%33,%34,%35}, %36, 0, 1, 1, 1;"
            : "=f"(o[0][0]), "=f"(o[0][1]), "=f"(o[0][2]), "=f"(o[0][3]),
              "=f"(o[1][0]), "=f"(o[1][1]), "=f"(o[1][2]), "=f"(o[1][3]),
              "=f"(o[2][0]), "=f"(o[2][1]), "=f"(o[2][2]), "=f"(o[2][3]),
              "=f"(o[3][0]), "=f"(o[3][1]), "=f"(o[3][2]), "=f"(o[3][3]),
              "=f"(o[4][0]), "=f"(o[4][1]), "=f"(o[4][2]), "=f"(o[4][3]),
              "=f"(o[5][0]), "=f"(o[5][1]), "=f"(o[5][2]), "=f"(o[5][3]),
              "=f"(o[6][0]), "=f"(o[6][1]), "=f"(o[6][2]), "=f"(o[6][3]),
              "=f"(o[7][0]), "=f"(o[7][1]), "=f"(o[7][2]), "=f"(o[7][3])
            : "r"(a[0]), "r"(a[1]), "r"(a[2]), "r"(a[3]), "l"(db)
            : "memory");
    else
        asm volatile(
            "wgmma.mma_async.sync.aligned.m64n64k16.f32.bf16.bf16 {%0,%1,%2,%3,%4,%5,%6,%7,%8,%9,%10,%11,%12,%13,%14,%15,%16,%17,%18,%19,%20,%21,%22,%23,%24,%25,%26,%27,%28,%29,%30,%31}, {%32,%33,%34,%35}, %36, 1, 1, 1, 1;"
            : "+f"(o[0][0]), "+f"(o[0][1]), "+f"(o[0][2]), "+f"(o[0][3]),
              "+f"(o[1][0]), "+f"(o[1][1]), "+f"(o[1][2]), "+f"(o[1][3]),
              "+f"(o[2][0]), "+f"(o[2][1]), "+f"(o[2][2]), "+f"(o[2][3]),
              "+f"(o[3][0]), "+f"(o[3][1]), "+f"(o[3][2]), "+f"(o[3][3]),
              "+f"(o[4][0]), "+f"(o[4][1]), "+f"(o[4][2]), "+f"(o[4][3]),
              "+f"(o[5][0]), "+f"(o[5][1]), "+f"(o[5][2]), "+f"(o[5][3]),
              "+f"(o[6][0]), "+f"(o[6][1]), "+f"(o[6][2]), "+f"(o[6][3]),
              "+f"(o[7][0]), "+f"(o[7][1]), "+f"(o[7][2]), "+f"(o[7][3])
            : "r"(a[0]), "r"(a[1]), "r"(a[2]), "r"(a[3]), "l"(db)
            : "memory");
}
__device__ __forceinline__ void wgmma_out(float (&o)[9][4], const uint32_t (&a)[4], uint64_t db, bool acc) {
    if (!acc)
        asm volatile(
            "wgmma.mma_async.sync.aligned.m64n72k16.f32.bf16.bf16 {%0,%1,%2,%3,%4,%5,%6,%7,%8,%9,%10,%11,%12,%13,%14,%15,%16,%17,%18,%19,%20,%21,%22,%23,%24,%25,%26,%27,%28,%29,%30,%31,%32,%33,%34,%35}, {%36,%37,%38,%39}, %40, 0, 1, 1, 1;"
            : "=f"(o[0][0]), "=f"(o[0][1]), "=f"(o[0][2]), "=f"(o[0][3]),
              "=f"(o[1][0]), "=f"(o[1][1]), "=f"(o[1][2]), "=f"(o[1][3]),
              "=f"(o[2][0]), "=f"(o[2][1]), "=f"(o[2][2]), "=f"(o[2][3]),
              "=f"(o[3][0]), "=f"(o[3][1]), "=f"(o[3][2]), "=f"(o[3][3]),
              "=f"(o[4][0]), "=f"(o[4][1]), "=f"(o[4][2]), "=f"(o[4][3]),
              "=f"(o[5][0]), "=f"(o[5][1]), "=f"(o[5][2]), "=f"(o[5][3]),
              "=f"(o[6][0]), "=f"(o[6][1]), "=f"(o[6][2]), "=f"(o[6][3]),
              "=f"(o[7][0]), "=f"(o[7][1]), "=f"(o[7][2]), "=f"(o[7][3]),
              "=f"(o[8][0]), "=f"(o[8][1]), "=f"(o[8][2]), "=f"(o[8][3])
            : "r"(a[0]), "r"(a[1]), "r"(a[2]), "r"(a[3]), "l"(db)
            : "memory");
    else
        asm volatile(
            "wgmma.mma_async.sync.aligned.m64n72k16.f32.bf16.bf16 {%0,%1,%2,%3,%4,%5,%6,%7,%8,%9,%10,%11,%12,%13,%14,%15,%16,%17,%18,%19,%20,%21,%22,%23,%24,%25,%26,%27,%28,%29,%30,%31,%32,%33,%34,%35}, {%36,%37,%38,%39}, %40, 1, 1, 1, 1;"
            : "+f"(o[0][0]), "+f"(o[0][1]), "+f"(o[0][2]), "+f"(o[0][3]),
              "+f"(o[1][0]), "+f"(o[1][1]), "+f"(o[1][2]), "+f"(o[1][3]),
              "+f"(o[2][0]), "+f"(o[2][1]), "+f"(o[2][2]), "+f"(o[2][3]),
              "+f"(o[3][0]), "+f"(o[3][1]), "+f"(o[3][2]), "+f"(o[3][3]),
              "+f"(o[4][0]), "+f"(o[4][1]), "+f"(o[4][2]), "+f"(o[4][3]),
              "+f"(o[5][0]), "+f"(o[5][1]), "+f"(o[5][2]), "+f"(o[5][3]),
              "+f"(o[6][0]), "+f"(o[6][1]), "+f"(o[6][2]), "+f"(o[6][3]),
              "+f"(o[7][0]), "+f"(o[7][1]), "+f"(o[7][2]), "+f"(o[7][3]),
              "+f"(o[8][0]), "+f"(o[8][1]), "+f"(o[8][2]), "+f"(o[8][3])
            : "r"(a[0]), "r"(a[1]), "r"(a[2]), "r"(a[3]), "l"(db)
            : "memory");
}
__device__ __forceinline__ void wgmma_out(float (&o)[10][4], const uint32_t (&a)[4], uint64_t db, bool acc) {
    if (!acc)
        asm volatile(
            "wgmma.mma_async.sync.aligned.m64n80k16.f32.bf16.bf16 {%0,%1,%2,%3,%4,%5,%6,%7,%8,%9,%10,%11,%12,%13,%14,%15,%16,%17,%18,%19,%20,%21,%22,%23,%24,%25,%26,%27,%28,%29,%30,%31,%32,%33,%34,%35,%36,%37,%38,%39}, {%40,%41,%42,%43}, %44, 0, 1, 1, 1;"
            : "=f"(o[0][0]), "=f"(o[0][1]), "=f"(o[0][2]), "=f"(o[0][3]),
              "=f"(o[1][0]), "=f"(o[1][1]), "=f"(o[1][2]), "=f"(o[1][3]),
              "=f"(o[2][0]), "=f"(o[2][1]), "=f"(o[2][2]), "=f"(o[2][3]),
              "=f"(o[3][0]), "=f"(o[3][1]), "=f"(o[3][2]), "=f"(o[3][3]),
              "=f"(o[4][0]), "=f"(o[4][1]), "=f"(o[4][2]), "=f"(o[4][3]),
              "=f"(o[5][0]), "=f"(o[5][1]), "=f"(o[5][2]), "=f"(o[5][3]),
              "=f"(o[6][0]), "=f"(o[6][1]), "=f"(o[6][2]), "=f"(o[6][3]),
              "=f"(o[7][0]), "=f"(o[7][1]), "=f"(o[7][2]), "=f"(o[7][3]),
              "=f"(o[8][0]), "=f"(o[8][1]), "=f"(o[8][2]), "=f"(o[8][3]),
              "=f"(o[9][0]), "=f"(o[9][1]), "=f"(o[9][2]), "=f"(o[9][3])
            : "r"(a[0]), "r"(a[1]), "r"(a[2]), "r"(a[3]), "l"(db)
            : "memory");
    else
        asm volatile(
            "wgmma.mma_async.sync.aligned.m64n80k16.f32.bf16.bf16 {%0,%1,%2,%3,%4,%5,%6,%7,%8,%9,%10,%11,%12,%13,%14,%15,%16,%17,%18,%19,%20,%21,%22,%23,%24,%25,%26,%27,%28,%29,%30,%31,%32,%33,%34,%35,%36,%37,%38,%39}, {%40,%41,%42,%43}, %44, 1, 1, 1, 1;"
            : "+f"(o[0][0]), "+f"(o[0][1]), "+f"(o[0][2]), "+f"(o[0][3]),
              "+f"(o[1][0]), "+f"(o[1][1]), "+f"(o[1][2]), "+f"(o[1][3]),
              "+f"(o[2][0]), "+f"(o[2][1]), "+f"(o[2][2]), "+f"(o[2][3]),
              "+f"(o[3][0]), "+f"(o[3][1]), "+f"(o[3][2]), "+f"(o[3][3]),
              "+f"(o[4][0]), "+f"(o[4][1]), "+f"(o[4][2]), "+f"(o[4][3]),
              "+f"(o[5][0]), "+f"(o[5][1]), "+f"(o[5][2]), "+f"(o[5][3]),
              "+f"(o[6][0]), "+f"(o[6][1]), "+f"(o[6][2]), "+f"(o[6][3]),
              "+f"(o[7][0]), "+f"(o[7][1]), "+f"(o[7][2]), "+f"(o[7][3]),
              "+f"(o[8][0]), "+f"(o[8][1]), "+f"(o[8][2]), "+f"(o[8][3]),
              "+f"(o[9][0]), "+f"(o[9][1]), "+f"(o[9][2]), "+f"(o[9][3])
            : "r"(a[0]), "r"(a[1]), "r"(a[2]), "r"(a[3]), "l"(db)
            : "memory");
}

__device__ __forceinline__ void slow_edge(int ee, int s, float* accn, const __nv_bfloat16* __restrict__ x,
                                          const __nv_bfloat16* __restrict__ sh, const __nv_bfloat16* __restrict__ ea,
                                          const __nv_bfloat16* __restrict__ cg, const __nv_bfloat16* __restrict__ wr,
                                          int lane) {
    float rwv[4] = {0.f, 0.f, 0.f, 0.f};
#pragma unroll 4
    for (int d = 0; d < 16; d++) {
        const float a = __bfloat162float(ea[(size_t)ee * 16 + d]);
        const uint2 wv = *(const uint2*)(wr + d * 128 + lane * 4);
        rwv[0] += a * __uint_as_float(wv.x << 16);
        rwv[1] += a * __uint_as_float(wv.x & 0xffff0000u);
        rwv[2] += a * __uint_as_float(wv.y << 16);
        rwv[3] += a * __uint_as_float(wv.y & 0xffff0000u);
    }
    float A = 0.f;
#pragma unroll
    for (int v = 0; v < 4; v++)
        A += __bfloat162float(cg[((lane >> 2) & 3) * 16 + v * 4 + (lane & 3)]) * __bfloat162float(sh[(size_t)ee * 4 + v]);
    float m[4][4];
#pragma unroll
    for (int w = 0; w < 4; w++)
#pragma unroll
        for (int j = 0; j < 4; j++) m[w][j] = 0.f;
#pragma unroll
    for (int u = 0; u < 4; u++) {
        const uint2 xv = *(const uint2*)(x + (size_t)s * 512 + u * 128 + lane * 4);
        const float x0 = __uint_as_float(xv.x << 16), x1 = __uint_as_float(xv.x & 0xffff0000u);
        const float x2 = __uint_as_float(xv.y << 16), x3 = __uint_as_float(xv.y & 0xffff0000u);
#pragma unroll
        for (int w = 0; w < 4; w++) {
            const float a = __shfl_sync(0xffffffffu, A, u * 4 + w);
            m[w][0] += a * x0;
            m[w][1] += a * x1;
            m[w][2] += a * x2;
            m[w][3] += a * x3;
        }
    }
#pragma unroll
    for (int w = 0; w < 4; w++)
#pragma unroll
        for (int j = 0; j < 4; j++) atomicAdd(accn + w * 128 + lane * 4 + j, m[w][j] * rwv[j]);
}

__device__ __forceinline__ void slow_out(const float* accn, const __nv_bfloat16* __restrict__ wout,
                                         __nv_bfloat16* __restrict__ outn, int lane) {
    float o[4][4];
#pragma unroll
    for (int w = 0; w < 4; w++)
#pragma unroll
        for (int j = 0; j < 4; j++) o[w][j] = 0.f;
#pragma unroll 2
    for (int c = 0; c < 128; c++) {
        const uint2 wv = *(const uint2*)(wout + c * 128 + lane * 4);
        const float w0 = __uint_as_float(wv.x << 16), w1 = __uint_as_float(wv.x & 0xffff0000u);
        const float w2 = __uint_as_float(wv.y << 16), w3 = __uint_as_float(wv.y & 0xffff0000u);
#pragma unroll
        for (int w = 0; w < 4; w++) {
            const float a = __bfloat162float(__float2bfloat16(accn[w * 128 + c]));
            o[w][0] += a * w0;
            o[w][1] += a * w1;
            o[w][2] += a * w2;
            o[w][3] += a * w3;
        }
    }
#pragma unroll
    for (int w = 0; w < 4; w++)
        *(uint2*)(outn + w * 128 + lane * 4) = make_uint2(pack_bf16(o[w][0], o[w][1]), pack_bf16(o[w][2], o[w][3]));
}

static_assert(NW > 2 * NP, "barriers");
#define FPOS 1
#define PW 0
#define TWAIT mbar_lean_u
#define PWAIT mbar_lean
#define TMA_ROW(k) "@pl cp.async.bulk.tensor.2d.shared::cluster.global.mbarrier::complete_tx::bytes [d" #k "], [tm, {r" #k ", z" #k "}], [b" #k "];\n"
#define TMA_INIT(k, o) "shfl.sync.idx.b32 z" #k ", %11, " #k ", 31, 0xffffffff;\nadd.u32 m" #k ", %2, " STR(o) ";\nadd.u32 m" #k ", m" #k ", %11;\nshfl.sync.idx.b32 m" #k ", m" #k ", 0, 31, 0xffffffff;\n"
#define TMA_PREP(k) "mad.lo.u32 d" #k ", dd, 512, m" #k ";\nadd.u32 b" #k ", dd, z" #k ";\n"
#define RDCLK(c) "mov.u64 ck, %%clock64;\ncvt.u32.u64 " c ", ck;\n"
#define BCAST(d, k) "selp.b32 " d ", a" #k ", 0, me;\nredux.sync.or.b32 " d ", " d ", 0xffffffff;\n"
#define PTIME(t, x, y, z) "shr.u32 " t ", " x ", 16;\nand.b32 c, " y ", 0xffff;\nadd.u32 " t ", " t ", c;\nmad.lo.u32 c, " t ", %13, %14;\nmul.lo.u32 " t ", " t ", %9;\nmin.u32 " t ", " t ", c;\nshr.u32 " t ", " t ", 5;\nadd.u32 " t ", " t ", %6;\nmin.u32 " t ", " t ", lim;\nlop3.b32 " t ", " t ", " z ", 7, 0xd8;\n"
#define PROWS(s, x, y) "and.b32 t0, " s ", 0xffc;\nsetp.gt.u32 p, t0, " STR(LNUL / 2) ";\nmad.lo.u32 t0, t0, 2, %5;\nld.shared.v2.u32 {" x ", " y "}, [t0];\nshr.u32 t0, " s ", 11;\nand.b32 t0, t0, 6;\nshr.u32 " s ", " s ", 15;\nadd.u32 t0, t0, " s ";\nselp.s32 " s ", " STR(NGR - 2) ", -2, p;\nadd.u32 t0, t0, " s ";\nmul.lo.s32 t0, t0, " STR(-NBK * 64) ";\nprmt.b32 t0, t0, 0, 0x1010;\nadd.u16x2 " x ", " x ", t0;\nadd.u16x2 " y ", " y ", t0;\n"
__device__ __forceinline__ void produce(const CUtensorMap* tm, uint32_t bar, uint32_t d0, uint32_t ps, int nit, uint32_t psrc,
                                        uint32_t tbase, uint32_t lim, uint32_t taug64, uint32_t taus, uint32_t n, int lz, int pr0,
                                        uint32_t tau2, uint32_t brk
) {
    asm volatile(
        "{\n.reg .pred p, pl, ok, me;\n.reg .b32 a<6>, u<4>, r<8>, d<8>, b<8>, z<8>, m<8>, ps, lim, n, it, pr, pe, tgt, tgu, c, dd, dn, par, t0, t1;\n"
        ".reg .b64 st, tm, ck;\n"
        "elect.sync _|pl, 0xffffffff;\n"
        TMA_INIT(0, 0) TMA_INIT(1, SM_ODD) TMA_INIT(2, 1024) TMA_INIT(3, SM_ODD + 1024)
        TMA_INIT(4, 4096) TMA_INIT(5, SM_ODD + 4096) TMA_INIT(6, 5120) TMA_INIT(7, SM_ODD + 5120)
        "mov.b64 {a0, a1}, %0;\n"
        "add.u32 a0, a0, %11;\n"
        "add.u32 a1, a1, %11;\n"
        "shfl.sync.idx.b32 a0, a0, 0, 31, 0xffffffff;\n"
        "shfl.sync.idx.b32 a1, a1, 0, 31, 0xffffffff;\n"
        "mov.b64 tm, {a0, a1};\n"
        "mov.u32 ps, %3;\n"
        "mov.u32 it, %4;\n"
        "mov.u32 lim, %7;\n"
        "mov.u32 n, %10;\n"
        "mov.u32 pr, %12;\n"
        "setp.le.s32 p, it, 0;\n"
        "bar.sync 4, " STR(NT) ";\n"
        "@p bra.uni PEND;\n"
        "PBAT:\n"
        "ld.shared.u16 c, [ps];\n"
        "ld.shared.u16 t1, [ps+4];\n"
        "add.u32 ps, ps, 256;\n"
        "mul.lo.u32 par, n, " STR(65536 / NP + 1) ";\n"
        "shr.u32 par, par, 16;\n"
        "mad.lo.s32 dn, par, " STR(-NP) ", n;\n"
        "add.u32 n, n, 32;\n"
        "not.b32 par, par;\n"
        PROWS("c", "a0", "a1") PROWS("t1", "a2", "a3")
        "min.s32 pe, it, 32;\n"
        "sub.s32 it, it, 32;\n"
        "add.u32 pe, pe, pr;\n"
        PTIME("a4", "a0", "a1", "dn") PTIME("a5", "a2", "a3", "par")
        "add.u32 lim, lim, %8;\n"
        "PLOOP:\n"
        "setp.eq.u32 me, n, pr;\n"
        "add.u32 pr, pr, 1;\n"
        BCAST("tgt", 4) BCAST("tgu", 5) BCAST("u0", 0) BCAST("u1", 1) BCAST("u2", 2) BCAST("u3", 3)
        "and.b32 dd, tgt, 7;\n"
        "mad.lo.u32 dd, dd, 16, %1;\n"
        "and.b32 par, tgu, 1;\n"
        "mbarrier.test_wait.parity.shared.b64 ok, [dd+8], par;\n"
        "prmt.b32 r0, u0, 0, 0x4104;\nprmt.b32 r1, u0, 0, 0x4324;\nprmt.b32 r2, u1, 0, 0x4104;\nprmt.b32 r3, u1, 0, 0x4324;\n"
        "prmt.b32 r4, u2, 0, 0x4104;\nprmt.b32 r5, u2, 0, 0x4324;\nprmt.b32 r6, u3, 0, 0x4104;\nprmt.b32 r7, u3, 0, 0x4324;\n"
        TMA_PREP(0) TMA_PREP(1) TMA_PREP(2) TMA_PREP(3) TMA_PREP(4) TMA_PREP(5) TMA_PREP(6) TMA_PREP(7)
        RDCLK("c")
        "sub.s32 c, c, tgt;\n"
        "setp.ge.and.s32 p, c, 0, ok;\n"
        "@!p bra.uni PSLP;\n"
        "PRES:\n"
        "@pl mbarrier.arrive.expect_tx.shared.b64 _, [b0], 8192;\n"
        TMA_ROW(0) TMA_ROW(1) TMA_ROW(2) TMA_ROW(3)
        RDCLK("c")
        "sub.s32 c, c, tgu;\n"
        "setp.lt.s32 p, c, 0;\n"
        "@p bra.uni PSL2;\n"
        "PRE2:\n"
        TMA_ROW(4) TMA_ROW(5) TMA_ROW(6) TMA_ROW(7)
        "setp.lt.u32 p, pr, pe;\n"
        "@p bra.uni PLOOP;\n"
        "setp.gt.s32 p, it, 0;\n"
        "@p bra.uni PBAT;\n"
        "bra.uni PEND;\n"
        "PSL2:\n"
        "nanosleep.u32 " STR(PSLEEP) ";\n"
        RDCLK("c")
        "sub.s32 c, c, tgu;\n"
        "setp.lt.s32 p, c, 0;\n"
        "@p bra.uni PSL2;\n"
        "bra.uni PRE2;\n"
        "PSL1:\n"
        "nanosleep.u32 " STR(PSLEEP) ";\n"
        RDCLK("c")
        "sub.s32 c, c, tgt;\n"
        "PSLP:\n"
        "setp.lt.s32 p, c, 0;\n"
        "@p bra.uni PSL1;\n"
        "@ok bra.uni PRES;\n"
        "mov.u32 c, 0;\n"
        "PW:\n"
        "mbarrier.try_wait.parity.shared.b64 p, [b0+8], par;\n"
        "@p bra.uni PRES;\n"
        "add.u32 c, c, 1;\n"
        "setp.lt.u32 p, c, 4000000;\n"
        "@p bra.uni PW;\n"
        "trap;\n"
        "PEND:\n}"
        :
        : "l"(tm), "r"(bar), "r"(d0), "r"(ps), "r"(nit), "r"(psrc), "r"(tbase), "r"(lim), "r"(taug64), "r"(taus), "r"(n), "r"(lz),
          "r"(pr0), "r"(tau2), "r"(brk)
        : "memory");
}
template <int J0, int JN>
__device__ __forceinline__ void put_agg(const float (&acc)[2][NJ][4], uint32_t tb, int u) {
    const int h = u & 1, j = u & ~1;
    const float(*a)[4] = acc[h] + J0 + (j < JN ? j : 0);
    if (j + 1 < JN)
        stsm4(tb + h * SM_ODD + (J0 + j) * 256, pack_bf16(a[0][0], a[0][1]), pack_bf16(a[0][2], a[0][3]), pack_bf16(a[1][0], a[1][1]),
              pack_bf16(a[1][2], a[1][3]));
    else if (j < JN)
        stsm2(tb + h * SM_ODD + (J0 + j) * 256, pack_bf16(a[0][0], a[0][1]), pack_bf16(a[0][2], a[0][3]));
}
template <int JN>
__device__ __forceinline__ void pin(float (&o)[JN][4]) {
#pragma unroll
    for (int j = 0; j < JN; j++)
#pragma unroll
        for (int k = 0; k < 4; k++) asm volatile("" : "+f"(o[j][k])::"memory");
}
#define WG_WAIT(n) asm volatile("wgmma.wait_group.sync.aligned %0;" ::"n"(n) : "memory")
#define WG_COMMIT() asm volatile("wgmma.commit_group.sync.aligned;" ::: "memory")
#define KA 2
template <int K0, int JN, class F>
__device__ __forceinline__ void mul_out(float (&o)[JN][4], const uint32_t (&a)[8][4], uint32_t db, F f) {
    asm volatile("wgmma.fence.sync.aligned;" ::: "memory");
#pragma unroll
    for (int ks = 0; ks < 8; ks++) {
        wgmma_out(o, a[ks], (uint64_t)(db + (((ks >> 2) * SM_ODD + (ks & 3) * (NJ * 256)) >> 4)) | (16ull << 32), ks);
        if (ks == K0 - 1 || ks == 7) WG_COMMIT();
        if (ks == K0 - 1) WG_WAIT(1);
        if (ks >= K0 - 1) f(K0 ? ks - K0 + 1 : ks);
    }
}
static_assert(CH1 <= 8 && CH2 <= 8 && CH3 <= 10 && CH4 <= 10 && KA <= 3 && NJ == 19 && NP == 5 && SM_EVEN == 0 && SM_ODD % 1024 == 128 && CH0 + CH2 <= 13 && CH1 <= 13 && CH0 + CH2 + CH4 <= 21 && CH1 + CH3 <= 21, "epilogue");
__device__ constexpr int out_n(int st) { return st == 0 ? CH0 : st == 1 ? CH1 : st == 2 ? CH2 : st == 3 ? CH3 : CH4; }
__device__ constexpr int out_j(int st) { return st == 1 ? CH0 : st == 2 ? CH0 + CH1 : st == 4 ? CH3 : 0; }
__device__ constexpr int out_at(int st) { return (NJ + (st == 2 ? CH0 : st == 3 ? CH1 : st == 4 ? CH0 + CH2 : 0)) * 1024 + (st & 1) * SM_ODD; }
#define WG_SYNC(w) asm volatile("bar.sync %0, 128;" ::"r"((w) + 1) : "memory")
#define HAND(st, w) asm volatile("bar.arrive %0, 192;" ::"r"(6 + 2 * (st) + (w)) : "memory")
template <int ST, int JN>
__device__ __forceinline__ void put_out(float (&o)[JN][4], uint32_t c, int u, int w) {
    if (u == 0) pin(o);
    const int j = 2 * u < JN ? 2 * u : 0;
    if (2 * u + 1 < JN)
        stsm4t(c + out_at(ST) + j * 1024, pack_bf16(o[j][0], o[j][1]), pack_bf16(o[j][2], o[j][3]), pack_bf16(o[j + 1][0], o[j + 1][1]),
               pack_bf16(o[j + 1][2], o[j + 1][3]));
    else if (2 * u < JN)
        stsm2t(c + out_at(ST) + j * 1024, pack_bf16(o[j][0], o[j][1]), pack_bf16(o[j][2], o[j][3]));
    if (u == (JN - 1) / 2) HAND(ST, w);
}
__device__ __forceinline__ void get_w(uint32_t (&a)[8][4], uint32_t ce, uint32_t co, int ks) {
    if (ks >= 0 && ks < 8)
        asm volatile("ldmatrix.sync.aligned.m8n8.x4.trans.shared.b16 {%0,%1,%2,%3}, [%4];"
                     : "=r"(a[ks & 7][0]), "=r"(a[ks & 7][1]), "=r"(a[ks & 7][2]), "=r"(a[ks & 7][3])
                     : "r"((ks < 4 ? ce : co + SM_ODD) + (ks & 3) * 2048)
                     : "memory");
}
#define TB 8
#define DELAY 2500
#define NULW 0xf0000000
#define DREF 0
#define K0(npr) ((2 * NP - 2 - (npr) % NP) % NP)
#define GCODE(g) ((((g) >> 1) + 1) << 12 | ((g) & 1) << 15)
#define SYNC() asm volatile("bar.sync 0;" ::: "memory")
#define LISTS() asm volatile("bar.sync 4, %0;" ::"n"(NT) : "memory")
#define NB (2 * NGR * 32)
#define PREF(p, tot, k0, n)                                                                                       \
    {                                                                                                             \
        _Pragma("unroll") for (int k = (k0); k < (k0) + (n); k++) {                                                \
            const int l = (k * nbins + bin) * 128 + tid - NB;                                                     \
            if (l < (tot)) asm volatile("prefetch.global.L2 [%0];" ::"l"(p + (size_t)l * 64) : "memory");         \
        }                                                                                                         \
    }
#define WX 010
#define WS 0011
#define WE 000
#define PL 8
#define PLE 0
#define DG(v, i) ((v) >> (6 - 3 * (i)) & 7)
#define PREW(i)                                                                                \
    PREF(x, N * 8, (i > 0 ? DG(WX, 0) : 0) + (i > 1 ? DG(WX, 1) : 0), DG(WX, i))                \
    PREF(sh, E / 16, (i > 0 ? DG(WS, 0) : 0) + (i > 1 ? DG(WS, 1) : 0), DG(WS, i))              \
    PREF(ea, E / 4, (i > 0 ? DG(WE, 0) : 0) + (i > 1 ? DG(WE, 1) : 0), DG(WE, i))
#define PFN (DG(WX, 0) + DG(WX, 1) + DG(WX, 2))
#define PFE (DG(WE, 0) + DG(WE, 1) + DG(WE, 2))
__global__ void __launch_bounds__(NT, 1)
main_kernel(const int* __restrict__ dst, const int* __restrict__ src, uint4* __restrict__ gbin, int E, int nbins, int fast_ok,
            int npb, unsigned npb_magic, int N, const __grid_constant__ CUtensorMap tme,
            const __grid_constant__ CUtensorMap tmx, const __grid_constant__ CUtensorMap tmw,
            const __grid_constant__ CUtensorMap tmo, const __nv_bfloat16* __restrict__ x,
            const __nv_bfloat16* __restrict__ sh, const __nv_bfloat16* __restrict__ ea,
            const __nv_bfloat16* __restrict__ cg, const __nv_bfloat16* __restrict__ wr,
            const __nv_bfloat16* __restrict__ wout, __nv_bfloat16* __restrict__ out, int tau16, int toff, int delay,
            int tau2, int brk) {
    extern __shared__ __align__(1024) unsigned char smem[];
    const uint32_t sb = __shfl_sync(0xffffffffu, s2u(smem), 0);
    const int tid = threadIdx.x;
    const int warp = __shfl_sync(0xffffffffu, tid >> 5, 0), lane = tid & 31;
    const int g = lane >> 2, t = lane & 3;

    TLSTAMP(0);
    TLINIT();
    const int bin = blockIdx.x;
    const int node0 = bin * npb, hpb = npb >> 1;
    uint32_t wa[8];
    uint2 c0 = make_uint2(0, 0), c1 = c0;
    bool fast = fast_ok;
    uint32_t swp = 0;
    int npr = 0, k0 = 0;
    if (fast_ok) {
        int pd[EPS], ps[EPS];
        const int e0 = (warp * nbins + bin) * 32 + lane;
#pragma unroll
        for (int k = 0; k < EPS; k++)
            asm volatile("ld.global.nc.u32 %0, [%1];" : "=r"(pd[k]) : "l"(dst + min(e0 + k * NT * nbins, E - 1)));
#pragma unroll
        for (int k = 0; k < EPS; k++)
            asm volatile("ld.global.nc.u32 %0, [%1];" : "=r"(ps[k]) : "l"(src + min(e0 + k * NT * nbins, E - 1)));
        const unsigned ck0 = clock();
        const uint32_t cnt0 = (sb + SC_CNT + 8191) & ~8191;
        {
            const uint32_t nul = NULW | ((bin & 3) * 8 + (tid & 7)) << 21;
#pragma unroll
            for (int k = 0; k < 4; k++) {
                const int i = tid + k * NT;
                if (i < SC_EXT / 16 ? (tid & 7) != 7 : i < SC_TAB / 16) sts_v4(sb + SC_ENT + i * 16, make_uint4(nul, nul, nul, nul));
            }
            if (warp == NW - 1) {
                uint32_t now;
                asm volatile("mov.u32 %0, %%globaltimer_lo;" : "=r"(now));
                now = __shfl_sync(0xffffffffu, (now & 0x1fffff) | nul, 7);
#pragma unroll
                for (int k = 0; k < MAXBINS / 32; k++) sts_v4(sb + SC_ENT + (k * 32 + lane) * 128 + 112, make_uint4(now, now, now, now));
                if (lane == 0) {
                    asm volatile("prefetch.tensormap [%0];" ::"l"(&tme) : "memory");
                    asm volatile("prefetch.tensormap [%0];" ::"l"(&tmx) : "memory");
                    asm volatile("prefetch.tensormap [%0];" ::"l"(&tmw) : "memory");
                    asm volatile("prefetch.tensormap [%0];" ::"l"(&tmo) : "memory");
                    sts_v2(sb + SM_MISC + MI_INT, 0, now);
                    sts_u32(sb + SM_MISC + MI_INT + 44, 0);
                }
            }
            sts_v4(cnt0 + tid * 16, make_uint4(0, 0, 0, 0));
            if (tid < (SC_END - SC_HIST) / 16) {
                const uint32_t v = (tid >> 3) == MAXBINS / 32 ? 0x80000000u : 0;
                sts_v4(sb + SC_HIST + tid * 16, make_uint4(v, v, v, v));
            }
            if (tid < 2 * HPB) {
                const int w = tid >= hpb, loc = tid - (w ? hpb : 0), gr = min(loc * 43 >> 8, NGR - 1);
                sts_u32(sb + SC_TAB + tid * 4, ((w ? NGR : 0) + gr) * (NBK * 64 << 15) + loc - gr * GSZ);
            }
        }
        TLS(1);
        __syncthreads();
        {
            const uint32_t z = lds_u32(sb + SM_MISC + MI_INT);
            int pb[EPS], pr[EPS];
            uint32_t v[EPS];
#pragma unroll
            for (int k = 0; k < EPS; k++) {
                pb[k] = (int)__umulhi((unsigned)pd[k], npb_magic + z);
                v[k] = lds_u32(sb + SC_TAB + (pd[k] - pb[k] * npb) * 4);
                pr[k] = atoms_add(sb + SC_HIST + (e0 + k * NT * nbins < E ? pb[k] : MAXBINS + lane) * 4, 4);
            }
            int mx = 0;
#pragma unroll
            for (int k = 0; k < EPS; k++) {
                v[k] += ps[k] * (32768 + z) + (k * NT + tid + 32) * 8;
                asm volatile("{\n.reg .pred p;\nsetp.lt.u32 p, %0, 128;\n@p st.shared.u32 [%1], %2;\n}" ::"r"(pr[k]),
                             "r"(sb + SC_ENT + pb[k] * 128 + pr[k]), "r"(v[k])
                             : "memory");
                mx = max(mx, pr[k]);
            }
            if (mx >= 128) {
#pragma unroll
                for (int k = 0; k < EPS; k++)
                    if (pr[k] >= 128 && pr[k] < 192) sts_u32(sb + SC_EXT - 128 + pb[k] * 64 + pr[k], v[k]);
            }
        }
        FENCE_ASYNC();
        TLS(6);
        __syncthreads();
        const unsigned c6 = DREF ? ck0 : clock();
        if (warp == NW - 1 && elect()) {
            tma_store(&tme, sb + SC_ENT, bin * 32, 0);
            asm volatile("cp.async.bulk.commit_group;" ::: "memory");
        }
        if (tid < nbins && lds_u32(sb + SC_HIST + tid * 4) >= 128) {
#pragma unroll 1
            for (int k = 0; k < 4; k++) __stcg(gbin + GEX + (tid * nbins + bin) * 4 + k, lds_v4(sb + SC_EXT + tid * 64 + k * 16));
        }
        if (elect()) {
#pragma unroll
            for (int k = 0; k < (NP > 5 ? 4 : 2); k++) mbar_init(sb + SM_BAR + (warp * (NP > 5 ? 4 : 2) + k) * 8, 3 + (k & 1));
        }
#pragma unroll
        for (int k = 0; k < TS / 2; k++) sts_v4(sb + SM_BT + (tid + k * NT) * 16, make_uint4(0, 0, 0, 0));
        if (tid < 8) sts_v4(sb + SM_BT + (tid + TS / 2 * NT) * 16, make_uint4(0, 0, 0, 0));
        if (tid < 4) {
            sts_u16(sb + SM_SRC + (LNUL + tid) * 2, N);
            sts_u32(sb + SM_EID + (LNUL + tid) * 4, 0x80000000u);
        }
        FENCE_ASYNC();
        if (warp >= 2 * NGR) {
            uint2 wv[4];
#pragma unroll
            for (int k = 0; k < 4; k++)
                asm volatile("ld.global.nc.v2.u32 {%0,%1}, [%2];" : "=r"(wv[k].x), "=r"(wv[k].y) : "l"((const uint2*)wr + (tid - NB) + k * 128));
#pragma unroll
            for (int k = 0; k < 4; k++) sts_v2(sb + SC_WR + (lane >> 1) * 272 + (warp - 2 * NGR + k * 4) * 16 + (lane & 1) * 8, wv[k].x, wv[k].y);
            PREW(0);
            SYNC();
            PREW(1);
            if (warp == NW - 1 && elect()) {
                asm volatile("cp.async.bulk.global.shared::cta.bulk_group [%0], [%1], %2;" ::"l"(gbin + bin * nbins * 8), "r"(sb + SM_BT),
                             "r"(nbins * 128)
                             : "memory");
                asm volatile("cp.async.bulk.commit_group;" ::: "memory");
                const uint32_t t0 = lds_u32(sb + SM_MISC + MI_INT + 4);
                uint32_t now, ck;
                asm volatile(
                    "{\n.reg .pred p;\n.reg .b32 a, n;\nmov.u32 a, %%globaltimer_lo;\nmov.u32 n, 0;\n"
                    "TK:\nmov.u32 %0, %%globaltimer_lo;\nmov.u32 %1, %%clock;\nadd.u32 n, n, 1;\n"
                    "setp.lt.u32 p, n, " STR(TB) ";\nsetp.eq.and.u32 p, %0, a, p;\n@p bra TK;\n}"
                    : "=r"(now), "=r"(ck));
                sts_u32(sb + SM_MISC + MI_INT + 4, ck - (min((now - t0) & 0x1fffff, 1u << 16) * 63 >> 5) + toff);
            }
            uint32_t sg0 = 0x01010101 | ((lane & 1) << 8 | (lane & 2) << 15 | (lane & 4) << 22) * 0xfe;
            uint32_t sg2 = (0x0101 | ((lane >> 3 & 1) | (lane & 16) << 4) * 0xfe) * 0x10001 ^ 0xfefe0000;
            uint32_t cand = ((lane & 1) << 3 | (lane & 2) << 5 | (lane & 4) << 7 | (lane & 8) << 9) * 7 + (lane & 16) * (15 << 11);
            asm volatile("" : "+r"(sg0), "+r"(sg2), "+r"(cand));
            asm volatile("bar.sync 5, %0;" ::"n"(NT) : "memory");
            const uint4 nb = lds_v4(sb + SM_MISC + MI_INT + 32);
            fast = nb.w == 0;
            int df;
            asm("{\n.reg .s32 a;\ndp4a.u32.s32 a, %1, %4, 0;\ndp4a.u32.s32 a, %2, %5, a;\ndp4a.u32.s32 %0, %3, %6, a;\n}"
                : "=r"(df)
                : "r"(nb.x), "r"(nb.y), "r"(nb.z), "r"(sg0), "r"(sg0 ^ 0xfefefefe), "r"(sg2));
            const uint32_t best = __reduce_min_sync(0xffffffffu, abs(df) << (NJ + 1) | (df < 0) << NJ | cand);
            const int w = warp & 1;
            swp = best ^ -w;
            uint32_t ga[NGR];
#pragma unroll
            for (int k = 0; k < NGR; k++) {
                ga[k] = cnt0 + ((swp >> (3 * k)) & 1) * (NGR * NBK * 4) + (warp & 2) * NBK + lane * 16;
                asm volatile("" : "+r"(ga[k]));
            }
            SYNC();
            if (fast) {
                const uint32_t sq = sb + SM_SEQ + w * SEQCAP * 2;
                if (lane < NBK / 8) {
                    uint32_t v[NGR][4];
#pragma unroll
                    for (int k = 0; k < NGR; k++) {
                        const uint4 u = lds_v4(ga[k] + k * (NBK * 4));
                        v[k][0] = u.x, v[k][1] = u.y, v[k][2] = u.z, v[k][3] = u.w;
                    }
                    uint32_t a = -(__popc(swp & 0111111) * (NGR * GCAP + GEXT) + NGR * (NGR - 1) / 2 * GCAP + NGR * 4), mx = 0;
#pragma unroll
                    for (int k = 0; k < NGR; k++) a += v[k][0] & 0xffc;
                    a = sq + (a >> 1);
                    const uint32_t a0 = a;
#pragma unroll
                    for (int c = 0; c < 4; c++)
#pragma unroll
                        for (int k = 0; k < NGR; k++) {
                            asm volatile(
                                "{\n.reg .pred p, q;\n.reg .b16 h;\n"
                                "setp.ge.u32 p, %2, 0x10000;\nsetp.ge.u32 q, %2, 0x40000;\n"
                                "cvt.u16.u32 h, %1;\n@p st.shared.u16 [%0], h;\n"
                                "add.u16 h, h, 4;\n@q st.shared.u16 [%0+2], h;\n}" ::"r"(a), "r"((v[k][c] & 0xffc) | GCODE(k)), "r"(v[k][c])
                                : "memory");
                            a += v[k][c] >> 16;
                            mx = max(mx, v[k][c]);
                        }
                    if (mx >= 0x60000) {
                        a = a0;
#pragma unroll 1
                        for (int i = 0; i < 4 * NGR; i++) {
                            const int c = i / NGR, k = i - c * NGR;
                            const uint32_t u = lds_u32(cnt0 + (((swp >> (3 * k)) & 1) * NGR + k) * (NBK * 4) + (warp & 2) * NBK + lane * 16 + c * 4);
#pragma unroll 1
                            for (uint32_t n = 0; n < u >> 16; n += 2, a += 2) sts_u16(a, ((u & 0xffc) | GCODE(k)) + 2 * n);
                        }
                    }
                }
                __syncwarp();
                const int all = __dp4a(nb.x, 0x01010101u, __dp4a(nb.y, 0x01010101u, __dp4a(nb.z, 0x01010101u, 0u))), d = best >> (NJ + 1);
                const int nst = (all + ((swp >> NJ) & 1 ? -d : d)) >> 1;
                npr = (nst + 3) >> 2;
                k0 = K0(npr);
                if (!(warp & 2)) {
                    sts_u16(sq + (nst + lane) * 2, (LNUL + 4) | (lane < (-nst & 3) ? GCODE(0) : 0x7c01));
                    if (lane < k0) {
                        mbar_arrive_cnt(sb + SM_BAR + (w * NP + lane) * 16, 3);
                        mbar_arrive_cnt(sb + SM_BAR + (w * NP + lane) * 16 + 8, 4);
                    }
                    if (lane == 0) sts_v2(sb + SM_MISC + MI_INT + 8 + w * 8, npr, k0);
                }
            }
            PREW(2);
            TLS(5);
            asm volatile("cp.async.bulk.wait_group.read 0;" ::: "memory");
        } else {
        uint32_t en[5][4], es[5][4], rank[5][4], ca[5][4];
        if (warp >= 8 && (g >> 2) == (t >> 1)) {
            const uint2* cp = (const uint2*)cg + (g & 3) * 4 + (t & 1) * 2;
            asm volatile("ld.global.nc.v2.u32 {%0,%1}, [%2];" : "=r"(c0.x), "=r"(c0.y) : "l"(cp));
            asm volatile("ld.global.nc.v2.u32 {%0,%1}, [%2];" : "=r"(c1.x), "=r"(c1.y) : "l"(cp + 1));
        }
        const int sg[5] = {tid >> 3, (tid >> 3) + NB / 8, (tid >> 3) + NB / 4, (tid >> 3) + (lane & 4) * (NB / 32), (tid >> 3) + NB / 4};
        const uint4* gp[5];
        gp[0] = gbin + bin * nbins * 8 + tid;
        gp[1] = gp[0] + NB;
        gp[2] = gp[0] + 2 * NB;
        gp[3] = gbin + GEX + (bin * nbins + sg[3]) * 4 + (lane & 3);
        gp[4] = gbin + GEX + (bin * nbins + sg[4]) * 4 + (lane & 3);
        unsigned pend = (sg[0] < nbins) | (sg[1] < nbins) << 1 | (sg[2] < nbins) << 2;
#pragma unroll
        for (int k = 0; k < 5; k++) en[k][0] = en[k][1] = en[k][2] = en[k][3] = NULW | lane << 21;
        auto fetch = [&](int k) {
            asm volatile("{\n.reg .pred p;\nsetp.ne.u32 p, %5, 0;\n@p ld.relaxed.gpu.global.v4.u32 {%0,%1,%2,%3}, [%4];\n}"
                         : "+r"(en[k][0]), "+r"(en[k][1]), "+r"(en[k][2]), "+r"(en[k][3])
                         : "l"(gp[k]), "r"(pend & (1u << k))
                         : "memory");
        };
        int spin = 0;
        auto poll = [&](int k0, int k1) {
            for (;;) {
#pragma unroll
                for (int k = k0; k < k1; k++)
                    if (min(min(en[k][0], en[k][1]), min(en[k][2], en[k][3]))) pend &= ~(1u << k);
                if (!__any_sync(0xffffffffu, pend)) break;
#pragma unroll
                for (int k = k0; k < k1; k++) fetch(k);
                if (++spin > 10000000) __trap();
            }
        };
        auto count = [&](int k) {
#pragma unroll
            for (int c = 0; c < 4; c++) {
                const uint32_t v = en[k][c];
                ca[k][c] = ((v >> 19) & 0x1ffc) | cnt0;
                rank[k][c] = atoms_add(ca[k][c], 1);
                asm volatile("{\n.reg .b32 a, b;\nprmt.b32 a, %1, %2, 0x6540;\nand.b32 b, %1, 0x7f00;\nmad.lo.u32 %0, b, %3, a;\n}"
                             : "=r"(es[k][c])
                             : "r"(v), "r"(sg[k] - nbins), "r"(nbins));
            }
        };
        while ((int)(clock() - c6) < delay) {}
        TLS(7);
        fetch(0);
        fetch(1);
        fetch(2);
        poll(0, 3);
        TLS(2);
        const bool more = __any_sync(0xffffffffu, (lane & 7) == 7 && min(min(en[0][3], en[1][3]), en[2][3]) < NULW);
        const bool rest = NB / 4 + warp * 4 < nbins;
        if (more) {
            const uint32_t l0 = __shfl_sync(0xffffffffu, en[0][3], lane | 7), l1 = __shfl_sync(0xffffffffu, en[1][3], lane | 7);
            const uint32_t l2 = __shfl_sync(0xffffffffu, en[2][3], lane | 7);
            pend = ((lane & 4 ? l1 : l0) < NULW) << 3 | (!(lane & 4) && l2 < NULW) << 4;
            fetch(3);
            fetch(4);
        }
        if (tid == 7 && en[0][3] >= NULW) sts_u32(sb + SM_MISC + MI_INT + 4, en[0][3]);
        count(0);
        count(1);
        if (rest) count(2);
        if (more) {
            const unsigned ext = pend;
            poll(3, 5);
#pragma unroll
            for (int k = 3; k < 5; k++) {
                if ((ext >> k) & 1) {
                    __stcg((uint4*)gp[k], make_uint4(0, 0, 0, 0));
                    if ((lane & 3) == 3 && en[k][3] < NULW) sts_u32(sb + SM_MISC + MI_INT + 44, 1);
                }
            }
            count(3);
            count(4);
        }
        TLS(9);
        SYNC();
#pragma unroll
        for (int h = 0; h < 2; h++)
            asm volatile("ldmatrix.sync.aligned.m8n8.x4.trans.shared.b16 {%0,%1,%2,%3}, [%4];"
                         : "=r"(wa[h * 4]), "=r"(wa[h * 4 + 1]), "=r"(wa[h * 4 + 2]), "=r"(wa[h * 4 + 3])
                         : "r"(sb + SC_WR + (h * 8 + (warp & 3) * 2 + ((lane >> 3) & 1)) * 272 + (lane >> 4) * 128 + (lane & 7) * 16));
        {
            const int w0 = warp >= NGR, gr = warp - w0 * NGR;
            const uint32_t cp = cnt0 + (warp * NBK + lane * (NBK / 32)) * 4;
            uint32_t r[NBK / 32 + 1];
#pragma unroll
            for (int c = 0; c < NBK / 32; c++) r[c + 1] = lds_u32(cp + c * 4);
            r[0] = 0;
#pragma unroll
            for (int c = 1; c < NBK / 32; c++) r[c + 1] += r[c];
            const uint32_t tot = __reduce_add_sync(0xffffffffu, r[NBK / 32]);
            const uint32_t base = warp * GCAP + w0 * GEXT;
            const bool full = tot > GCAP + (gr == NGR - 1 ? GEXT : 0);
            asm volatile("st.shared.u8 [%0], %1;" ::"r"(sb + SM_MISC + MI_INT + 32 + (full ? 12 : (gr < 4 ? w0 * 4 : 4 + w0 * 2) + gr)), "r"(full ? 1 : (tot + 3) >> 2) : "memory");
            asm volatile("bar.arrive 5, %0;" ::"n"(NT) : "memory");
            const uint32_t off = warp_incl_scan(r[NBK / 32], lane) - r[NBK / 32] + base + 7 - CE;
            if (lane == 31) r[NBK / 32] += CE;
#pragma unroll
            for (int c = 0; c <= NBK / 32; c++) r[c] += off;
#pragma unroll
            for (int c = 0; c < NBK / 32; c++) sts_u32(cp + c * 4, r[c] + (((r[c + 1] & ~3) - (r[c] & ~3)) << 15));
            asm volatile("{\n.reg .pred p;\n.reg .b16 h;\nsetp.lt.u32 p, %0, %1;\ncvt.u16.u32 h, %3;\n@p st.shared.u16 [%2], h;\n@p st.shared.u32 [%4], 0x80000000;\n}" ::"r"(lane),
                         "r"(full ? 0 : -tot & 3), "r"(sb + SM_SRC + (base + tot + lane) * 2), "r"(N + warp * (NBK * 64)), "r"(sb + SM_EID + (base + tot + lane) * 4)
                         : "memory");
        }
        TLS(10);
        SYNC();
        auto place = [&](int k) {
#pragma unroll
            for (int c = 0; c < 4; c++)
                asm volatile("{\n.reg .pred p;\nsetp.lt.u32 p, %1, " STR(NULW) ";\n@p ld.shared.u16 %0, [%0];\n}" : "+r"(ca[k][c]) : "r"(en[k][c]));
#pragma unroll
            for (int c = 0; c < 4; c++) {
                const uint32_t p = ca[k][c] + rank[k][c];
                asm volatile(
                    "{\n.reg .pred p;\n.reg .b32 t;\n.reg .b16 h;\n"
                    "setp.lt.u32 p, %0, " STR(NULW) ";\n"
                    "@p st.shared.u32 [%1], %2;\n"
                    "shr.u32 t, %0, 15;\ncvt.u16.u32 h, t;\n"
                    "@p st.shared.u16 [%3], h;\n}" ::"r"(en[k][c]),
                    "r"(sb + SM_EID - (7 - CE) * 4 + p * 4), "r"(es[k][c]), "r"(sb + SM_SRC - (7 - CE) * 2 + p * 2)
                    : "memory");
            }
        };
        fast = lds_u32(sb + SM_MISC + MI_INT + 44) == 0;
        if (fast) {
            place(0);
            place(1);
            if (rest) place(2);
            if (more) place(3), place(4);
        }
        TLS(14);
        }
    }
    FENCE_ASYNC();

    if (fast && (warp >> 2) == 2) {
        asm volatile("bar.arrive 4, %0;" ::"n"(NT) : "memory");
        asm volatile("setmaxnreg.dec.sync.aligned.u32 %0;" ::"n"(HREG));
        const int w = warp & 1, j = (warp >> 1) & 1;
        const uint32_t bar0 = sb + SM_BAR + w * NP * 16;
        const int blk = (lane >> 4) * 2 + (t >> 1);
        uint32_t fseq = sb + SM_SEQ + w * SEQCAP * 2 + j * 8 + blk * 2;
        const uint32_t feid = sb + SM_EID - 16 + (g & 3) * 4;
        uint32_t pea = sb + SM_EA + w * 4096 + j * 512 + (lane ^ ((lane >> 3) & 1)) * 16;
        const uint32_t psd = sb + SM_SIDE + (warp - 8) * 512 + (lane >> 1) * 16 + (lane & 1) * 4;
        const uint32_t pt = sb + SM_BT + w * (TS * 256) + j * 512 + blk * BT_B + ((lane ^ (lane >> 3)) & 1) * BT_K + (g & 3) * 4;
        const char* gea = (const char*)ea + (lane & 1) * 16;
        uint32_t es, va[2], ta[2], old[2] = {pt, pt}, dea = 2048;
        auto ids = [&]() {
            es = lds_u32(feid + (lds_u16(fseq) & 0xffc) * 4);
            fseq += 16;
        };
        uint32_t wf[4];
        wf[0] = __byte_perm(c0.x, c1.x, 0x5410), wf[1] = __byte_perm(c0.x, c1.x, 0x7632);
        wf[2] = __byte_perm(c0.y, c1.y, 0x5410), wf[3] = __byte_perm(c0.y, c1.y, 0x7632);
        int pfl = lane < PL ? PFN * nbins * 128 + (bin * 4 + warp - 8) * PL + lane - N * 8 : 0;
        int pfs = nbins * (4 * PL);
        const char* pfb = (const char*)(x + (size_t)N * 512);
        auto run = [&](auto odd) {
            auto fetch = [&](int i) {
                asm volatile(
                    "{\n.reg .pred p, q;\n.reg .b32 e;\n.reg .b64 a;\n"
                    "setp.lt.s32 p, %0, 0;\n"
                    "and.b32 e, %0, 0x7ffffff8;\n"
                    "mad.wide.u32 a, e, 4, %1;\n"
                    "cp.async.cg.shared.global [%2], [a], 16, p;\n"
                    "}" ::"r"(es), "l"(gea), "r"(pea + i * 1024) : "memory");
                va[i] = psd + (es & 8);
                ta[i] = pt + (es & 7) * 64;
                if (odd.value) {
                    cp_async4(va[i] + i * 256, (const char*)sh + (es & 0x7ffffff8) + (lane & 1) * 4, (int)es >= 0 ? 4 : 0);
                } else {
                    asm volatile(
                        "{\n.reg .pred p;\n.reg .b32 e;\n.reg .b64 a;\n"
                        "setp.lt.s32 p, %0, 0;\n"
                        "and.b32 e, %0, 0x7ffffff0;\n"
                        "mad.wide.u32 a, e, 1, %1;\n"
                        "cp.async.cg.shared.global [%2], [a], 16, p;\n"
                        "}" ::"r"(es), "l"(sh), "r"((psd & ~15) + i * 256) : "memory");
                }
                asm volatile("cp.async.commit_group;" ::: "memory");
                if (i) pea += dea, dea = -dea;
            };
            asm volatile("bar.sync 3, %0;" ::"n"(NT) : "memory");
            const uint2 nk = lds_v2(sb + SM_MISC + MI_INT + 8 + w * 8);
            ids();
            fetch(0);
            ids();
            fetch(1);
            const int npr = __shfl_sync(0xffffffffu, nk.x, 0), kj = __shfl_sync(0xffffffffu, nk.y, 0) + j;
        uint32_t vf = bar0 + (kj < NP ? kj : 0) * 16;
        uint32_t pe = kj < NP;
#pragma unroll 1
            for (int m = (npr + 1 - j) >> 1; m > 0;) {
#pragma unroll
                for (int i = 0; i < 2; i++) {
                    asm volatile("cp.async.wait_group 1;" ::: "memory");
                    __syncwarp();
                    const uint32_t v = lds_u32(va[i] + i * 256);
                    ids();
                    float d0[4], d1[4];
                    mma_diag(d0, v, wf[0], wf[1]);
                    mma_diag(d1, v, wf[2], wf[3]);
                    uint32_t vn = vf + 32;
                    if (vn >= bar0 + NP * 16) vn -= NP * 16, pe ^= 1;
                    TWAIT(vn + 8, pe);
#pragma unroll
                    for (int k = 0; k < 4; k++) sts_u32(old[i] + i * 1024 + k * 16, 0);
                    old[i] = ta[i];
                    sts_u32(old[i] + i * 1024, pack_bf16(d0[0], d0[1]));
                    sts_u32(old[i] + i * 1024 + 16, pack_bf16(d0[2], d0[3]));
                    sts_u32(old[i] + i * 1024 + 32, pack_bf16(d1[0], d1[1]));
                    sts_u32(old[i] + i * 1024 + 48, pack_bf16(d1[2], d1[3]));
                    FENCE_ASYNC();
                    fetch(i);
                    __syncwarp();
                    if (lane == 0) mbar_arrive(vf);
                    asm volatile("{\n.reg .pred p;\n.reg .b64 a;\nsetp.lt.s32 p, %0, 0;\nmad.wide.s32 a, %0, 128, %1;\n@p prefetch.global.L2 [a];\n}" ::"r"(pfl),
                                 "l"(pfb));
                    pfl += pfs;
                    vf = vn;
                    if (--m <= 0) break;
                }
            }
        };
        if (E & 1) run(std::true_type()); else run(std::false_type());
        asm volatile("cp.async.wait_group 0;" ::: "memory");
        TLMAX(13);
    } else if (fast && warp >= 12) {
        asm volatile("bar.arrive 3, %0;" ::"n"(NT) : "memory");
        asm volatile("setmaxnreg.dec.sync.aligned.u32 %0;" ::"n"(PREG));
        const int w = warp & 1, j = (warp >> 1) & 1;
        npr = __shfl_sync(0xffffffffu, npr, 0), k0 = __shfl_sync(0xffffffffu, k0, 0);
        if (lane == 0) sts_u32(sb + SM_MISC + MI_INT + 48 + w * 4, swp);
        const uint32_t bar0 = sb + SM_BAR + w * NP * 16, ring = sb + w * RING_BYTES + j * 4096;
        const uint32_t pseq = sb + SM_SEQ + w * SEQCAP * 2 + j * 2;
#define STG 0
        const unsigned tbase = lds_u32(sb + SM_MISC + MI_INT + 4) + w * STG;
        const unsigned taug = __float2uint_rz(__fdividef((float)(N * tau16 >> 4), (float)max(npr, 1)));
        produce(&tmx, bar0, ring - j * 2048 - bar0 * 512, pseq + lane * 8, npr, sb + SM_SRC - 8, tbase,
                tbase + (N * tau16 >> 8) + lane * taug, taug * 32, tau16, k0 + lane, lane & (E >> 31), k0 + 32, tau2, brk
        );
        if (elect()) {
            const uint32_t d = ring + (NP - 2) * 8192 + j * (SM_ODD - 4096);
            const uint32_t fb = bar0 + (NP - 2) * 16, par = ~((lds_u32(sb + SM_MISC + MI_INT + 8 + w * 8) + 1) / NP) & 1;
            mbar_wait(fb + 24, par);
            mbar_arrive_cnt(fb + j * 16, j ? 1 : 3);
            mbar_expect_tx(fb + 16, 8192);
            tma_2d(d, &tmw, fb + 16, 0, j * 64);
            if (j) mbar_arrive(bar0 + DUMB);
            mbar_expect_tx(bar0 + DUMB, 8192);
            tma_2d(d + 8192, &tmw, bar0 + DUMB, 64, j * 64);
        }
        TLMAX(12);
        swp = lds_u32(sb + SM_MISC + MI_INT + 48 + w * 4);
        const int row = 2 * lane < hpb ? (node0 + ((swp >> lane) & 1) * hpb) * 4 + lane * 8 : N * 4;
        const CUtensorMap* po = &tmo;
        asm volatile("" : "+l"(po));
#pragma unroll
        for (int st = 0; st < 5; st++) {
            int rw[5];
#pragma unroll
            for (int k = 0; k < 5; k++)
                if (2 * k < out_n(st)) rw[k] = __shfl_sync(0xffffffffu, row, out_j(st) + 2 * k + (2 * k + 1 < out_n(st) ? j : j * (31 - out_j(st) - 2 * k)));
            asm volatile("bar.sync %0, 192;" ::"r"(6 + 2 * st + w) : "memory");
            FENCE_ASYNC();
            if (elect()) {
#pragma unroll
                for (int k = 0; k < 5; k++)
                    if (2 * k < out_n(st)) tma_store(po, ring - j * 3072 + out_at(st) + k * 2048, st < 3 ? 0 : 64, rw[k]);
                asm volatile("cp.async.bulk.commit_group;" ::: "memory");
            }
        }
        asm volatile("cp.async.bulk.wait_group.read 0;" ::: "memory");
    } else if (fast) {
        const int w = warp >> 2, wq = warp & 3;
        asm volatile("bar.arrive 3, %0;" ::"n"(NT) : "memory");
        LISTS();
        asm volatile("setmaxnreg.inc.sync.aligned.u32 %0;" ::"n"(CREG));
        const int k0 = __shfl_sync(0xffffffffu, lds_u32(sb + SM_MISC + MI_INT + 12 + w * 8), 0);
        const uint32_t ring = sb + w * RING_BYTES, bar0 = sb + SM_BAR + w * NP * 16;
        float acc[2][NJ][4];
        uint32_t a0[8][4], a1[8][4];
        {
            const int e = (lane >> 1) & 3, m = lane >> 3;
            const int line = 2 * ((lane & 1) + 2 * ((m >> 1) ^ (e >> 1))), ch = 2 * wq + (m & 1);
            const uint32_t xb = ring + (e & 1 ? SM_ODD : SM_EVEN) + (e >> 1) * 1024 + line * 128;
            consume(acc, a0, ring, xb + ((ch ^ ((line + (e & 1)) & 7)) * 16), xb + 128 + ((ch ^ ((line + 1 + (e & 1)) & 7)) * 16),
                    k0 * 8192, bar0, (((sb + SM_EA + w * 4096) & 0x3ffff) >> 4) | (1 << 16),
                    (((sb + SM_BT + w * (TS * 256)) & 0x3ffff) >> 4) | (BT_K / 16 << 16), sb + SM_SEQ + w * SEQCAP * 2, lane & (E >> 31),
                    wa);
        }
        const uint32_t tb = ring + wq * (NJ * 256) + lane * 16, db = (ring >> 4) + (8 << 16);
        const uint32_t cr = ring + (lane & 7) * 128 + (lane >> 4) * 1024, cc = 2 * wq + ((lane >> 3) & 1);
        const uint32_t ce = cr + (cc ^ (lane & 7)) * 16, co = cr + (cc ^ ((lane + 1) & 7)) * 16;
        float o0[CH0][4], o1[CH1][4], o2[CH2][4], o3[CH3][4], o4[CH4][4];
        TLMAX(11);
#pragma unroll
        for (int u = 0; u <= CH0; u++) put_agg<0, CH0>(acc, tb, u);
        TLE(1);
        FENCE_ASYNC();
        WG_SYNC(w);
        TLE(6);
        mul_out<0>(o0, a0, db, [&](int u) { put_agg<CH0, CH1>(acc, tb, u); });
        const bool ok1 = mbar_test(bar0 + DUMB, 0);
        FENCE_ASYNC();
        WG_SYNC(w);
        TLE(7);
        mul_out<KA>(o1, a0, db + CH0 * 16, [&](int u) {
            if (u == 0) {
                TLE(2);
#pragma unroll
                for (int k = 0; 2 * k < CH0; k++) put_out<0>(o0, ce, k, w);
                TLMAX(3);
            } else {
                put_agg<CH0 + CH1, CH2>(acc, tb, 2 * u - 2);
                put_agg<CH0 + CH1, CH2>(acc, tb, 2 * u - 1);
            }
        });
        FENCE_ASYNC();
        if (!ok1) mbar_wait(bar0 + DUMB, 0);
        WG_SYNC(w);
        TLE(9);
        mul_out<KA>(o2, a0, db + (CH0 + CH1) * 16, [&](int u) {
            put_out<1>(o1, co, 2 * u, w);
            put_out<1>(o1, co, 2 * u + 1, w);
            if (u == 1) TLE(5);
            get_w(a1, ce + (NP - 1) * 8192, co + (NP - 1) * 8192, 2 * u - 4);
            get_w(a1, ce + (NP - 1) * 8192, co + (NP - 1) * 8192, 2 * u - 3);
        });
        mul_out<KA>(o3, a1, db, [&](int u) {
            if (u == 0) TLE(10);
            put_out<2>(o2, ce, u, w);
            if (u == 8 - KA) WG_SYNC(w);
        });
        mul_out<KA>(o4, a1, db + CH3 * 16, [&](int u) { put_out<3>(o3, co, u, w); });
        TLE(14);
        WG_WAIT(0);
#pragma unroll
        for (int u = 0; 2 * u < CH4; u++) put_out<4>(o4, ce, u, w);
        TLMAX(15);
    } else {
        float* accs = (float*)smem;
        constexpr int NACC = SM_EID / 2048;
        const int nnodes = max(0, min(npb, N - node0));
#pragma unroll 1
        for (int nb = 0; nb < nnodes; nb += NACC) {
            __syncthreads();
            for (int i = tid; i < NACC * 512; i += NT) accs[i] = 0.f;
            __syncthreads();
#pragma unroll 1
            for (int base = warp * 32; base < E; base += NT) {
                const int e = base + lane;
                int dl = e < E ? dst[e] - node0 - nb : -1;
                if (dl + nb >= nnodes) dl = -1;
                unsigned mask = __ballot_sync(0xffffffffu, dl >= 0 && dl < NACC);
#pragma unroll 1
                while (mask) {
                    const int l = __ffs(mask) - 1;
                    mask &= mask - 1;
                    const int ee = __shfl_sync(0xffffffffu, e, l);
                    const int dd = __shfl_sync(0xffffffffu, dl, l);
                    slow_edge(ee, src[ee], accs + dd * 512, x, sh, ea, cg, wr, lane);
                }
            }
            __syncthreads();
#pragma unroll 1
            for (int nl = warp; nl < NACC && nb + nl < nnodes; nl += NW)
                slow_out(accs + nl * 512, wout, out + (size_t)(node0 + nb + nl) * 512, lane);
        }
        __syncthreads();
    }

    TLMAX(4);
    TLEND();
}

typedef CUresult (*EncodeTiledFn)(CUtensorMap*, CUtensorMapDataType, cuuint32_t, void*, const cuuint64_t*,
                                  const cuuint64_t*, const cuuint32_t*, const cuuint32_t*, CUtensorMapInterleave,
                                  CUtensorMapSwizzle, CUtensorMapL2promotion, CUtensorMapFloatOOBfill);

extern "C" void kernel_launch(void* const* d_in, const int* in_sizes, int n_in, void* d_out, int out_size) {
    const __nv_bfloat16* x = (const __nv_bfloat16*)d_in[0];
    const int* src = (const int*)d_in[1];
    const int* dst = (const int*)d_in[2];
    const __nv_bfloat16* sh = (const __nv_bfloat16*)d_in[3];
    const __nv_bfloat16* ea = (const __nv_bfloat16*)d_in[4];
    const __nv_bfloat16* cg = (const __nv_bfloat16*)d_in[5];
    const __nv_bfloat16* wr = (const __nv_bfloat16*)d_in[6];
    const __nv_bfloat16* wout = (const __nv_bfloat16*)d_in[7];
    __nv_bfloat16* out = (__nv_bfloat16*)d_out;
    const int N = in_sizes[0] / 512;
    const int E = in_sizes[1];

    static int num_sms = 0;
    static EncodeTiledFn encode = nullptr;
    static uint4* gbin = nullptr;
    if (num_sms == 0) {
        int dev = 0;
        cudaGetDevice(&dev);
        cudaDeviceGetAttribute(&num_sms, cudaDevAttrMultiProcessorCount, dev);
        cudaFuncSetAttribute(main_kernel, cudaFuncAttributeMaxDynamicSharedMemorySize, SM_TOTAL + TLX);
        cudaGetSymbolAddress((void**)&gbin, g_bin);
        void* fn = nullptr;
        cudaDriverEntryPointQueryResult qr;
        cudaGetDriverEntryPoint("cuTensorMapEncodeTiled", &fn, cudaEnableDefault, &qr);
        encode = (EncodeTiledFn)fn;
    }
    const int nbins = num_sms < NB * 3 / 8 ? num_sms : NB * 3 / 8;
    int npb = ((N + nbins - 1) / nbins + 3) & ~3;
    if (npb < 32) npb = 32;
    const int fast_ok = E > 0 && npb <= 2 * HPB && N <= (NBK - 1) * 64 && E <= EPS * NT * nbins;
    auto map2d = [&](CUtensorMap* tm, const void* p, int d0, int d1, int b1) {
        const cuuint64_t gd[2] = {(cuuint64_t)d0, (cuuint64_t)d1};
        const cuuint64_t gs[1] = {(cuuint64_t)d0 * 2};
        const cuuint32_t bx[2] = {64, (cuuint32_t)b1};
        const cuuint32_t es[2] = {1, 1};
        encode(tm, CU_TENSOR_MAP_DATA_TYPE_BFLOAT16, 2, (void*)p, gd, gs, bx, es, CU_TENSOR_MAP_INTERLEAVE_NONE,
               CU_TENSOR_MAP_SWIZZLE_128B, CU_TENSOR_MAP_L2_PROMOTION_NONE, CU_TENSOR_MAP_FLOAT_OOB_FILL_NONE);
    };
    CUtensorMap tme, tmx, tmw, tmo;
    {
        const cuuint64_t gd[2] = {(cuuint64_t)nbins * 32, (cuuint64_t)nbins};
        const cuuint64_t gs[1] = {(cuuint64_t)nbins * 128};
        const cuuint32_t bx[2] = {32, (cuuint32_t)nbins};
        const cuuint32_t es[2] = {1, 1};
        encode(&tme, CU_TENSOR_MAP_DATA_TYPE_UINT32, 2, (void*)gbin, gd, gs, bx, es, CU_TENSOR_MAP_INTERLEAVE_NONE,
               CU_TENSOR_MAP_SWIZZLE_NONE, CU_TENSOR_MAP_L2_PROMOTION_NONE, CU_TENSOR_MAP_FLOAT_OOB_FILL_NONE);
    }
    {
        const cuuint64_t gd[2] = {(cuuint64_t)N * 256 - 224, 8};
        const cuuint64_t gs[1] = {128};
        const cuuint32_t bx[2] = {32, 8};
        const cuuint32_t es[2] = {1, 1};
        encode(&tmx, CU_TENSOR_MAP_DATA_TYPE_UINT32, 2, (void*)x, gd, gs, bx, es, CU_TENSOR_MAP_INTERLEAVE_NONE,
               CU_TENSOR_MAP_SWIZZLE_128B, CU_TENSOR_MAP_L2_PROMOTION_NONE, CU_TENSOR_MAP_FLOAT_OOB_FILL_NONE);
    }
    map2d(&tmw, wout, 128, 128, 64);
    map2d(&tmo, out, 128, N * 4, 8);
    const unsigned npb_magic = (unsigned)((0x100000000ull + npb - 1) / npb);
    const int chunk = (E + nbins - 1) / nbins;
    int tau16 = (int)fmin((double)PACE * 16.0 * chunk / N, 100000.0), toff = TOFF, delay = DELAY;
    int tau2 = tau16 * PACE2 / 100, brk = BRK;
    brk = (tau16 - tau2) * (N * brk / 50);
    main_kernel<<<nbins, NT, SM_TOTAL + TLX, cudaStreamPerThread>>>(dst, src, gbin, E, nbins, fast_ok, npb, npb_magic, N, tme, tmx, tmw,
                                                              tmo, x, sh, ea, cg, wr, wout, out, tau16, toff, delay, tau2, brk);
}
```

```cpp
#include <cuda_runtime.h>
#include <cuda.h>
#include <cuda_bf16.h>
#include <stdint.h>
#include <stdlib.h>
#include <type_traits>

#define MAXBINS 160
#define NW 16
#define NT (NW * 32)
#define HPB 38
#define GCAP 280
#define GEXT 72
#define NGR 6
#define LNUL (2 * (NGR * GCAP + GEXT))
#define NBK 128
#define KEYW 10240
#define CE 2
#define GSZ 6
#define NS 10
#define RING_BYTES 40960
static_assert(RING_BYTES == NS * 4096, "ring");
#define NP (NS / 2)
#define CREG 224
#define PREG 24
#define HREG 40
#define TS 8
#define SM_EVEN 0
#define SM_MISC (2 * RING_BYTES)
#define SM_ODD (SM_MISC + 128)
#define SM_EA (SM_BT + TS * 4096 + 128)
#define SM_BT (SM_ODD + 2 * RING_BYTES)
#define BT_B (TS * 512 + 16)
#define BT_K (4 * BT_B)
#define SM_SIDE (SM_EA + 8192)
#define SM_EID (SM_SIDE + 2048)
#define SM_SRC (SM_EID + (LNUL + 4) * 4)
#define SEQCAP ((LNUL / 8 + 32 + 7) / 8 * 8)
#define SM_SEQ (SM_SRC + (LNUL + 8) * 2)
#define SM_BAR ((SM_SEQ + 2 * SEQCAP * 2 + 63) / 64 * 64)
#define SM_TOTAL (SM_BAR + NW * (NP > 5 ? 32 : 16))
#define DUMB (2 * NP * 16)
#define MI_INT 0
#define EPS 5
#define SC_ENT 0
#define SC_EXT (SC_ENT + MAXBINS * 128)
#define SC_TAB (SC_EXT + MAXBINS * 64)
#define SC_HIST (SC_TAB + 320)
#define SC_END (SC_HIST + MAXBINS * 4 + 128)
#define SC_WR SC_END
#define SC_CNT (SC_WR + 4352)
static_assert(SC_END % 16 == 0 && SC_HIST % 16 == 0 && SC_END - SC_HIST <= NT * 16 && SC_CNT + 16384 <= SM_MISC && SC_TAB <= 4 * NT * 16 && 2 * HPB <= 80 && MAXBINS >= 24 * NGR, "scratch");
static_assert(LNUL >= 3072 && LNUL + 8 <= 4096 && GCAP % 4 == 0 && GEXT % 4 == 0, "lists");
static_assert(SM_TOTAL <= 232448 && SM_BAR % 16 == 0 && SM_SEQ % 16 == 0 && SM_SRC % 16 == 0 && SM_EA % 256 == 0, "smem");
#define PACE 18.6
#define PACE2 96
#define BRK 85
#define TOFF 9000
#define PSLEEP 20

#define GEX (MAXBINS * MAXBINS * 8)
__device__ __align__(128) uint4 g_bin[GEX + GEX / 2];
#define STR2(x) #x
#define STR(x) STR2(x)
#define TLINIT()
#define TLEND()
#define TLX 0
#define TLSTAMP(i)
#define TLMAX(i)

#define TLA(i, d)
#define TLS(i) TLMAX(i)
#define TLE(i)
__device__ __forceinline__ uint32_t pack_bf16(float lo, float hi) {
    uint32_t r;
    asm("cvt.rn.bf16x2.f32 %0, %1, %2;" : "=r"(r) : "f"(hi), "f"(lo));
    return r;
}
__device__ __forceinline__ void mma1688_z(float (&d)[4], uint32_t a0, uint32_t a1, uint32_t b0) {
    asm("mma.sync.aligned.m16n8k8.row.col.f32.bf16.bf16.f32 {%0,%1,%2,%3}, {%4,%5}, {%6}, {%7,%7,%7,%7};"
        : "=f"(d[0]), "=f"(d[1]), "=f"(d[2]), "=f"(d[3])
        : "r"(a0), "r"(a1), "r"(b0), "f"(0.f));
}
__device__ __forceinline__ void mma_diag(float (&d)[4], uint32_t a, uint32_t b0, uint32_t b1) {
    asm("mma.sync.aligned.m16n8k16.row.col.f32.bf16.bf16.f32 {%0,%1,%2,%3}, {%4,%8,%8,%4}, {%5,%6}, {%7,%7,%7,%7};"
        : "=f"(d[0]), "=f"(d[1]), "=f"(d[2]), "=f"(d[3])
        : "r"(a), "r"(b0), "r"(b1), "f"(0.f), "r"(0));
}
__device__ __forceinline__ uint32_t s2u(const void* p) { return (uint32_t)__cvta_generic_to_shared(p); }
__device__ __forceinline__ void mbar_init(uint32_t a, int c) {
    asm volatile("mbarrier.init.shared.b64 [%0], %1;" ::"r"(a), "r"(c));
}
__device__ __forceinline__ void mbar_expect_tx(uint32_t a, int bytes) {
    asm volatile("mbarrier.arrive.expect_tx.shared.b64 _, [%0], %1;" ::"r"(a), "r"(bytes) : "memory");
}
__device__ __forceinline__ void mbar_arrive(uint32_t a) {
    asm volatile("mbarrier.arrive.shared.b64 _, [%0];" ::"r"(a) : "memory");
}
__device__ __forceinline__ void mbar_arrive_cnt(uint32_t a, int c) {
    asm volatile("mbarrier.arrive.shared.b64 _, [%0], %1;" ::"r"(a), "r"(c) : "memory");
}
__device__ __forceinline__ void mbar_wait(uint32_t a, int parity) {
    asm volatile(
        "{\n.reg .pred p;\n.reg .u32 c;\n"
        "mov.u32 c, 0;\n"
        "LAB_WAIT:\n"
        "mbarrier.try_wait.parity.shared.b64 p, [%0], %1, 2000;\n"
        "@p bra DONE;\n"
        "add.u32 c, c, 1;\n"
        "setp.lt.u32 p, c, 2000000;\n"
        "@p bra LAB_WAIT;\n"
        "trap;\n"
        "DONE:\n}" ::"r"(a),
        "r"(parity)
        : "memory");
}
__device__ __forceinline__ void mbar_wait_u(uint32_t a, int parity) {
    asm volatile(
        "{\n.reg .pred p;\n.reg .u32 c;\n"
        "mov.u32 c, 0;\n"
        "LAB_WAIT:\n"
        "mbarrier.try_wait.parity.shared.b64 p, [%0], %1, 2000;\n"
        "@p bra.uni DONE;\n"
        "add.u32 c, c, 1;\n"
        "setp.lt.u32 p, c, 2000000;\n"
        "@p bra.uni LAB_WAIT;\n"
        "trap;\n"
        "DONE:\n}" ::"r"(a),
        "r"(parity)
        : "memory");
}
__device__ __forceinline__ void mbar_spin_u(uint32_t a, int parity) {
    asm volatile(
        "{\n.reg .pred p;\n.reg .u32 c;\n"
        "mov.u32 c, 0;\n"
        "LAB_WAIT:\n"
        "mbarrier.test_wait.parity.shared.b64 p, [%0], %1;\n"
        "@p bra.uni DONE;\n"
        "add.u32 c, c, 1;\n"
        "setp.lt.u32 p, c, 20000000;\n"
        "@p bra.uni LAB_WAIT;\n"
        "trap;\n"
        "DONE:\n}" ::"r"(a),
        "r"(parity)
        : "memory");
}
__device__ __forceinline__ void mbar_lean(uint32_t a, int parity) {
    asm volatile(
        "{\n.reg .pred p;\n.reg .u32 c;\n"
        "mov.u32 c, 0;\n"
        "LAB_WAIT:\n"
        "mbarrier.try_wait.parity.shared.b64 p, [%0], %1;\n"
        "@p bra DONE;\n"
        "add.u32 c, c, 1;\n"
        "setp.lt.u32 p, c, 4000000;\n"
        "@p bra LAB_WAIT;\n"
        "trap;\n"
        "DONE:\n}" ::"r"(a),
        "r"(parity)
        : "memory");
}
__device__ __forceinline__ void mbar_lean_u(uint32_t a, int parity) {
    asm volatile(
        "{\n.reg .pred p;\n.reg .u32 c;\n"
        "mov.u32 c, 0;\n"
        "LAB_WAIT:\n"
        "mbarrier.try_wait.parity.shared.b64 p, [%0], %1;\n"
        "@p bra.uni DONE;\n"
        "add.u32 c, c, 1;\n"
        "setp.lt.u32 p, c, 4000000;\n"
        "@p bra.uni LAB_WAIT;\n"
        "trap;\n"
        "DONE:\n}" ::"r"(a),
        "r"(parity)
        : "memory");
}
__device__ __forceinline__ bool mbar_test(uint32_t a, int parity) {
    uint32_t p;
    asm volatile("{\n.reg .pred P;\nmbarrier.test_wait.parity.shared.b64 P, [%1], %2;\nselp.u32 %0, 1, 0, P;\n}"
                 : "=r"(p)
                 : "r"(a), "r"(parity)
                 : "memory");
    return p;
}
__device__ __forceinline__ bool elect() {
    uint32_t p;
    asm volatile("{\n.reg .pred P;\nelect.sync _|P, 0xffffffff;\nselp.u32 %0, 1, 0, P;\n}" : "=r"(p));
    return p;
}
__device__ __forceinline__ void tma_2d(uint32_t dst, const CUtensorMap* tm, uint32_t bar, int c0, int c1) {
    asm volatile(
        "cp.async.bulk.tensor.2d.shared::cluster.global.mbarrier::complete_tx::bytes [%0], [%1, {%3, %4}], [%2];" ::"r"(dst),
        "l"(tm), "r"(bar), "r"(c0), "r"(c1)
        : "memory");
}
__device__ __forceinline__ void tma_row(uint32_t dst, const CUtensorMap* tm, uint32_t bar, int row8) {
    tma_2d(dst, tm, bar, 0, row8);
}
__device__ __forceinline__ void tma_store(const CUtensorMap* tm, uint32_t src, int c0, int c1) {
    asm volatile("cp.async.bulk.tensor.2d.global.shared::cta.bulk_group [%0, {%2, %3}], [%1];" ::"l"(tm), "r"(src),
                 "r"(c0), "r"(c1)
                 : "memory");
}
__device__ __forceinline__ uint2 lds_v2(uint32_t a) {
    uint2 v;
    asm volatile("ld.shared.v2.u32 {%0,%1}, [%2];" : "=r"(v.x), "=r"(v.y) : "r"(a));
    return v;
}
__device__ __forceinline__ uint4 lds_v4(uint32_t a) {
    uint4 v;
    asm volatile("ld.shared.v4.u32 {%0,%1,%2,%3}, [%4];" : "=r"(v.x), "=r"(v.y), "=r"(v.z), "=r"(v.w) : "r"(a));
    return v;
}
__device__ __forceinline__ uint32_t lds_u32(uint32_t a) {
    uint32_t v;
    asm volatile("ld.shared.u32 %0, [%1];" : "=r"(v) : "r"(a));
    return v;
}
__device__ __forceinline__ uint32_t lds_u16(uint32_t a) {
    uint32_t v;
    asm volatile("ld.shared.u16 %0, [%1];" : "=r"(v) : "r"(a));
    return v;
}
__device__ __forceinline__ void sts_v2(uint32_t a, uint32_t x, uint32_t y) {
    asm volatile("st.shared.v2.u32 [%0], {%1,%2};" ::"r"(a), "r"(x), "r"(y) : "memory");
}
__device__ __forceinline__ void sts_v4(uint32_t a, uint4 v) {
    asm volatile("st.shared.v4.u32 [%0], {%1,%2,%3,%4};" ::"r"(a), "r"(v.x), "r"(v.y), "r"(v.z), "r"(v.w) : "memory");
}
__device__ __forceinline__ void stsm4(uint32_t a, uint32_t r0, uint32_t r1, uint32_t r2, uint32_t r3) {
    asm volatile("stmatrix.sync.aligned.m8n8.x4.shared.b16 [%0], {%1,%2,%3,%4};" ::"r"(a), "r"(r0), "r"(r1), "r"(r2), "r"(r3)
                 : "memory");
}
__device__ __forceinline__ void stsm2(uint32_t a, uint32_t r0, uint32_t r1) {
    asm volatile("stmatrix.sync.aligned.m8n8.x2.shared.b16 [%0], {%1,%2};" ::"r"(a), "r"(r0), "r"(r1) : "memory");
}
__device__ __forceinline__ void stsm4t(uint32_t a, uint32_t r0, uint32_t r1, uint32_t r2, uint32_t r3) {
    asm volatile("stmatrix.sync.aligned.m8n8.x4.trans.shared.b16 [%0], {%1,%2,%3,%4};" ::"r"(a), "r"(r0), "r"(r1), "r"(r2),
                 "r"(r3)
                 : "memory");
}
__device__ __forceinline__ void stsm2t(uint32_t a, uint32_t r0, uint32_t r1) {
    asm volatile("stmatrix.sync.aligned.m8n8.x2.trans.shared.b16 [%0], {%1,%2};" ::"r"(a), "r"(r0), "r"(r1) : "memory");
}
__device__ __forceinline__ void cp_async16(uint32_t d, const void* s, int n) {
    asm volatile("cp.async.cg.shared.global [%0], [%1], 16, %2;" ::"r"(d), "l"(s), "r"(n) : "memory");
}
__device__ __forceinline__ void cp_async4(uint32_t d, const void* s, int n) {
    asm volatile("cp.async.ca.shared.global [%0], [%1], 4, %2;" ::"r"(d), "l"(s), "r"(n) : "memory");
}
__device__ __forceinline__ void sts_u32(uint32_t a, uint32_t x) {
    asm volatile("st.shared.u32 [%0], %1;" ::"r"(a), "r"(x) : "memory");
}
#define FENCE_ASYNC() asm volatile("fence.proxy.async.shared::cta;" ::: "memory")
#define ZS 4
__device__ __forceinline__ int warp_incl_scan(int v, int lane, int z) {
#pragma unroll
    for (int o = 1; o < 32; o <<= 1) {
        const int y = __shfl_up_sync(0xffffffffu, v, o);
        if (lane >= o) v += y;
        if (o == ZS) v += z;
    }
    return v;
}

__device__ __forceinline__ uint32_t atoms_add(uint32_t a, uint32_t v) {
    uint32_t r;
    asm volatile("atom.shared.add.u32 %0, [%1], %2;" : "=r"(r) : "r"(a), "r"(v) : "memory");
    return r;
}
__device__ __forceinline__ void sts_u16(uint32_t a, uint32_t x) {
    asm volatile("{\n.reg .b16 h;\ncvt.u16.u32 h, %1;\nst.shared.u16 [%0], h;\n}" ::"r"(a), "r"(x) : "memory");
}
#define NJ 19
__device__ __forceinline__ void consume(float (&acc)[2][NJ][4], uint32_t (&wo)[8][4], uint32_t ring, uint32_t xa0, uint32_t xa1, uint32_t so0, uint32_t bar0,
                                        uint32_t ea0, uint32_t d0, uint32_t pl0, int lz, const uint32_t (&wa)[8]) {
    asm volatile(
        "{\n"
        ".reg .pred p, pf, plead, pok, t0, t1, t2, u0, u1, u2;\n"
        ".reg .b32 ca, cb, cz, rbar;\n"
        "mov.b32 cz, 0;\n"
        "mov.b32 ca, 0x20002000;\n"
        "mov.b32 cb, 0x30003000;\n"
        ".reg .b32 cnt, so, q, qe, bar, nbar, pl, ctl, ctm, ix, iy, dl, v0, v1, v2, v3, pp;\n"
        ".reg .b16 sl, sh;\n"
        ".reg .b32 hXa0, hXa1, hXa2, hXa3, hXa4, hXa5, hXa6, hXa7, hXb0, hXb1, hXb2, hXb3, hXb4, hXb5, hXb6, hXb7, hYa0, hYa1, hYa2, hYa3, hYa4, hYa5, hYa6, hYa7, hYb0, hYb1, hYb2, hYb3, hYb4, hYb5, hYb6, hYb7, hLa0, hLa1, hLa2, hLa3, hLa4, hLa5, hLa6, hLa7, hLb0, hLb1, hLb2, hLb3, hLb4, hLb5, hLb6, hLb7;\n"
        ".reg .b32 pX0, pX1, pX2, pX3, pY0, pY1, pY2, pY3;\n"
        ".reg .f32 r0, r1, r2, r3, r4, r5, r6, r7, r8, r9, r10, r11, r12, r13, r14, r15;\n"
        ".reg .b64 daX, dbX, daY, dbY, de0, de1;\n"
        ".reg .b32 dh<6>, eb0, par, npar, wa<8>, uz, bend;\n"
        "add.u32 wa0, %192, %191;\n"
        "add.u32 wa1, %193, %191;\n"
        "add.u32 wa2, %194, %191;\n"
        "add.u32 wa3, %195, %191;\n"
        "add.u32 wa4, %196, %191;\n"
        "add.u32 wa5, %197, %191;\n"
        "add.u32 wa6, %198, %191;\n"
        "add.u32 wa7, %199, %191;\n"
        "mov.f32 %0, 0f00000000;\n"
        "mov.f32 %1, 0f00000000;\n"
        "mov.f32 %2, 0f00000000;\n"
        "mov.f32 %3, 0f00000000;\n"
        "mov.f32 %4, 0f00000000;\n"
        "mov.f32 %5, 0f00000000;\n"
        "mov.f32 %6, 0f00000000;\n"
        "mov.f32 %7, 0f00000000;\n"
        "mov.f32 %8, 0f00000000;\n"
        "mov.f32 %9, 0f00000000;\n"
        "mov.f32 %10, 0f00000000;\n"
        "mov.f32 %11, 0f00000000;\n"
        "mov.f32 %12, 0f00000000;\n"
        "mov.f32 %13, 0f00000000;\n"
        "mov.f32 %14, 0f00000000;\n"
        "mov.f32 %15, 0f00000000;\n"
        "mov.f32 %16, 0f00000000;\n"
        "mov.f32 %17, 0f00000000;\n"
        "mov.f32 %18, 0f00000000;\n"
        "mov.f32 %19, 0f00000000;\n"
        "mov.f32 %20, 0f00000000;\n"
        "mov.f32 %21, 0f00000000;\n"
        "mov.f32 %22, 0f00000000;\n"
        "mov.f32 %23, 0f00000000;\n"
        "mov.f32 %24, 0f00000000;\n"
        "mov.f32 %25, 0f00000000;\n"
        "mov.f32 %26, 0f00000000;\n"
        "mov.f32 %27, 0f00000000;\n"
        "mov.f32 %28, 0f00000000;\n"
        "mov.f32 %29, 0f00000000;\n"
        "mov.f32 %30, 0f00000000;\n"
        "mov.f32 %31, 0f00000000;\n"
        "mov.f32 %32, 0f00000000;\n"
        "mov.f32 %33, 0f00000000;\n"
        "mov.f32 %34, 0f00000000;\n"
        "mov.f32 %35, 0f00000000;\n"
        "mov.f32 %36, 0f00000000;\n"
        "mov.f32 %37, 0f00000000;\n"
        "mov.f32 %38, 0f00000000;\n"
        "mov.f32 %39, 0f00000000;\n"
        "mov.f32 %40, 0f00000000;\n"
        "mov.f32 %41, 0f00000000;\n"
        "mov.f32 %42, 0f00000000;\n"
        "mov.f32 %43, 0f00000000;\n"
        "mov.f32 %44, 0f00000000;\n"
        "mov.f32 %45, 0f00000000;\n"
        "mov.f32 %46, 0f00000000;\n"
        "mov.f32 %47, 0f00000000;\n"
        "mov.f32 %48, 0f00000000;\n"
        "mov.f32 %49, 0f00000000;\n"
        "mov.f32 %50, 0f00000000;\n"
        "mov.f32 %51, 0f00000000;\n"
        "mov.f32 %52, 0f00000000;\n"
        "mov.f32 %53, 0f00000000;\n"
        "mov.f32 %54, 0f00000000;\n"
        "mov.f32 %55, 0f00000000;\n"
        "mov.f32 %56, 0f00000000;\n"
        "mov.f32 %57, 0f00000000;\n"
        "mov.f32 %58, 0f00000000;\n"
        "mov.f32 %59, 0f00000000;\n"
        "mov.f32 %60, 0f00000000;\n"
        "mov.f32 %61, 0f00000000;\n"
        "mov.f32 %62, 0f00000000;\n"
        "mov.f32 %63, 0f00000000;\n"
        "mov.f32 %64, 0f00000000;\n"
        "mov.f32 %65, 0f00000000;\n"
        "mov.f32 %66, 0f00000000;\n"
        "mov.f32 %67, 0f00000000;\n"
        "mov.f32 %68, 0f00000000;\n"
        "mov.f32 %69, 0f00000000;\n"
        "mov.f32 %70, 0f00000000;\n"
        "mov.f32 %71, 0f00000000;\n"
        "mov.f32 %72, 0f00000000;\n"
        "mov.f32 %73, 0f00000000;\n"
        "mov.f32 %74, 0f00000000;\n"
        "mov.f32 %75, 0f00000000;\n"
        "mov.f32 %76, 0f00000000;\n"
        "mov.f32 %77, 0f00000000;\n"
        "mov.f32 %78, 0f00000000;\n"
        "mov.f32 %79, 0f00000000;\n"
        "mov.f32 %80, 0f00000000;\n"
        "mov.f32 %81, 0f00000000;\n"
        "mov.f32 %82, 0f00000000;\n"
        "mov.f32 %83, 0f00000000;\n"
        "mov.f32 %84, 0f00000000;\n"
        "mov.f32 %85, 0f00000000;\n"
        "mov.f32 %86, 0f00000000;\n"
        "mov.f32 %87, 0f00000000;\n"
        "mov.f32 %88, 0f00000000;\n"
        "mov.f32 %89, 0f00000000;\n"
        "mov.f32 %90, 0f00000000;\n"
        "mov.f32 %91, 0f00000000;\n"
        "mov.f32 %92, 0f00000000;\n"
        "mov.f32 %93, 0f00000000;\n"
        "mov.f32 %94, 0f00000000;\n"
        "mov.f32 %95, 0f00000000;\n"
        "mov.f32 %96, 0f00000000;\n"
        "mov.f32 %97, 0f00000000;\n"
        "mov.f32 %98, 0f00000000;\n"
        "mov.f32 %99, 0f00000000;\n"
        "mov.f32 %100, 0f00000000;\n"
        "mov.f32 %101, 0f00000000;\n"
        "mov.f32 %102, 0f00000000;\n"
        "mov.f32 %103, 0f00000000;\n"
        "mov.f32 %104, 0f00000000;\n"
        "mov.f32 %105, 0f00000000;\n"
        "mov.f32 %106, 0f00000000;\n"
        "mov.f32 %107, 0f00000000;\n"
        "mov.f32 %108, 0f00000000;\n"
        "mov.f32 %109, 0f00000000;\n"
        "mov.f32 %110, 0f00000000;\n"
        "mov.f32 %111, 0f00000000;\n"
        "mov.f32 %112, 0f00000000;\n"
        "mov.f32 %113, 0f00000000;\n"
        "mov.f32 %114, 0f00000000;\n"
        "mov.f32 %115, 0f00000000;\n"
        "mov.f32 %116, 0f00000000;\n"
        "mov.f32 %117, 0f00000000;\n"
        "mov.f32 %118, 0f00000000;\n"
        "mov.f32 %119, 0f00000000;\n"
        "mov.f32 %120, 0f00000000;\n"
        "mov.f32 %121, 0f00000000;\n"
        "mov.f32 %122, 0f00000000;\n"
        "mov.f32 %123, 0f00000000;\n"
        "mov.f32 %124, 0f00000000;\n"
        "mov.f32 %125, 0f00000000;\n"
        "mov.f32 %126, 0f00000000;\n"
        "mov.f32 %127, 0f00000000;\n"
        "mov.f32 %128, 0f00000000;\n"
        "mov.f32 %129, 0f00000000;\n"
        "mov.f32 %130, 0f00000000;\n"
        "mov.f32 %131, 0f00000000;\n"
        "mov.f32 %132, 0f00000000;\n"
        "mov.f32 %133, 0f00000000;\n"
        "mov.f32 %134, 0f00000000;\n"
        "mov.f32 %135, 0f00000000;\n"
        "mov.f32 %136, 0f00000000;\n"
        "mov.f32 %137, 0f00000000;\n"
        "mov.f32 %138, 0f00000000;\n"
        "mov.f32 %139, 0f00000000;\n"
        "mov.f32 %140, 0f00000000;\n"
        "mov.f32 %141, 0f00000000;\n"
        "mov.f32 %142, 0f00000000;\n"
        "mov.f32 %143, 0f00000000;\n"
        "mov.f32 %144, 0f00000000;\n"
        "mov.f32 %145, 0f00000000;\n"
        "mov.f32 %146, 0f00000000;\n"
        "mov.f32 %147, 0f00000000;\n"
        "mov.f32 %148, 0f00000000;\n"
        "mov.f32 %149, 0f00000000;\n"
        "mov.f32 %150, 0f00000000;\n"
        "mov.f32 %151, 0f00000000;\n"
        "setp.ne.u32 pf, 0, 0;\n"
        "add.u32 v0, %186, %191;\n"
        "shfl.sync.idx.b32 so, v0, 0, 31, 0xffffffff;\n"
        "mov.u32 npar, 0;\n"
        "shfl.sync.idx.b32 uz, %191, 7, 31, 0xffffffff;\n"
        "add.u32 bend, %187, " STR(NP * 16) ";\n"
        "add.u32 v0, %191, 8;\n"
        "shfl.sync.idx.b32 dh0, v0, 0, 31, 0xffffffff;\n"
        "shfl.sync.idx.b32 dh1, v0, 1, 31, 0xffffffff;\n"
        "shfl.sync.idx.b32 dh2, v0, 2, 31, 0xffffffff;\n"
        "shfl.sync.idx.b32 dh3, v0, 3, 31, 0xffffffff;\n"
        "add.u32 v0, %191, 0xc0000010;\n"
        "shfl.sync.idx.b32 dh4, v0, 4, 31, 0xffffffff;\n"
        "shfl.sync.idx.b32 dh5, v0, 5, 31, 0xffffffff;\n"
        "add.u32 v0, %191, %188;\n"
        "shfl.sync.idx.b32 eb0, v0, 0, 31, 0xffffffff;\n"
        "mov.u32 q, 0;\n"
        "mov.u32 pl, %190;\n"
        "shr.u32 nbar, so, 9;\n"
        "add.u32 nbar, nbar, %187;\n"
        "elect.sync _|plead, 0xffffffff;\n"
        "mov.b64 de0, {%188, dh4};\n"
        "mov.b64 de1, {eb0, dh5};\n"
        "mov.b32 hYa0, 0;\n"
        "mov.b32 hYa1, 0;\n"
        "mov.b32 hYa2, 0;\n"
        "mov.b32 hYa3, 0;\n"
        "mov.b32 hYa4, 0;\n"
        "mov.b32 hYa5, 0;\n"
        "mov.b32 hYa6, 0;\n"
        "mov.b32 hYa7, 0;\n"
        "mov.b32 hYb0, 0;\n"
        "mov.b32 hYb1, 0;\n"
        "mov.b32 hYb2, 0;\n"
        "mov.b32 hYb3, 0;\n"
        "mov.b32 hYb4, 0;\n"
        "mov.b32 hYb5, 0;\n"
        "mov.b32 hYb6, 0;\n"
        "mov.b32 hYb7, 0;\n"
        "mov.u32 ctm, 0x10001000;\n"
        "setp.lt.f16x2 t0|u0, ctm, cz;\n"
        "abs.f16x2 v3, ctm;\n"
        "setp.ge.f16x2 t1|u1, v3, ca;\n"
        "setp.geu.f16x2 t2|u2, v3, cb;\n"
        "ld.shared.v2.u32 {ctl, ctm}, [pl];\n"
        "add.u32 pl, pl, 8;\n"
        "add.u32 rbar, %187, " STR(DUMB) ";\n"
        "mov.b64 daX, {%189, dh0};\n"
        "mov.b64 dbX, {%189, dh1};\n"
        "mov.b64 daY, {%189, dh2};\n"
        "mov.b64 dbY, {%189, dh3};\n"
        "mov.u32 bar, nbar;\n"
        "mov.u32 par, npar;\n"
        "sub.u32 so, bar, %187;\n"
        "shl.b32 so, so, 9;\n"
        "add.u32 v0, %184, so;\n"
        "add.u32 v1, %185, so;\n"
        "add.u32 nbar, nbar, 16;\n"
        "setp.eq.u32 p, nbar, bend;\n"
        "selp.b32 nbar, %187, nbar, p;\n"
        "@p xor.b32 npar, npar, 1;\n"
        "SLOW:\n"
        "mov.u32 cnt, 0;\n"
        "W1:\n"
        "mbarrier.try_wait.parity.shared.b64 p, [bar], par;\n"
        "@p bra.uni RES;\n"
        "add.u32 cnt, cnt, 1;\n"
        "setp.lt.u32 p, cnt, 4000000;\n"
        "@p bra.uni W1;\n"
        "trap;\n"
        "CX:\n"
        "mbarrier.test_wait.parity.shared.b64 pok, [nbar], npar;\n"
        "and.b32 dl, q, 0x60;\n"
        "add.u32 dl, dl, %189;\n"
        "add.u32 v3, dl, 0;\n"
        "mov.b64 {v2, dh0}, daX;\n"
        "mov.b64 daX, {v3, dh0};\n"
        "add.u32 v3, dl, 257;\n"
        "mov.b64 {v2, dh1}, dbX;\n"
        "mov.b64 dbX, {v3, dh1};\n"
        "add.u32 v3, dl, 514;\n"
        "mov.b64 {v2, dh2}, daY;\n"
        "mov.b64 daY, {v3, dh2};\n"
        "add.u32 v3, dl, 771;\n"
        "mov.b64 {v2, dh3}, dbY;\n"
        "mov.b64 dbY, {v3, dh3};\n"
        "add.u32 q, q, 32;\n"
        "and.b32 qe, q, 0xe0;\n"
        "add.u32 v3, qe, %188;\n"
        "mov.b64 {v2, dh4}, de0;\n"
        "mov.b64 de0, {v3, dh4};\n"
        "mov.b64 {v2, dh5}, de1;\n"
        "mov.b64 de1, {v3, dh5};\n"
        "setp.lt.f16x2 t0|u0, ctl, cz;\n"
        "abs.f16x2 v3, ctl;\n"
        "setp.ge.f16x2 t1|u1, v3, ca;\n"
        "setp.geu.f16x2 t2|u2, v3, cb;\n"
        "wgmma.wait_group.sync.aligned 2;\n"
        "cvt.rn.bf16x2.f32 pX0, r1, r0;\n"
        "cvt.rn.bf16x2.f32 pX1, r3, r2;\n"
        "cvt.rn.bf16x2.f32 pX2, r9, r8;\n"
        "cvt.rn.bf16x2.f32 pX3, r11, r10;\n"
        "cvt.rn.bf16x2.f32 pY0, r5, r4;\n"
        "cvt.rn.bf16x2.f32 pY1, r7, r6;\n"
        "cvt.rn.bf16x2.f32 pY2, r13, r12;\n"
        "cvt.rn.bf16x2.f32 pY3, r15, r14;\n"
        "mov.b32 {sl, sh}, pX0;\n"
        "mov.b32 pp, {sl, sl};\n"
        "mul.rn.bf16x2 hXa0, hLa0, pp;\n"
        "mul.rn.bf16x2 hXa2, hLa2, pp;\n"
        "mov.b32 {sl, sh}, pX1;\n"
        "mov.b32 pp, {sl, sl};\n"
        "mul.rn.bf16x2 hXa1, hLa1, pp;\n"
        "mul.rn.bf16x2 hXa3, hLa3, pp;\n"
        "mov.b32 {sl, sh}, pX2;\n"
        "mov.b32 pp, {sl, sl};\n"
        "mul.rn.bf16x2 hXa4, hLa4, pp;\n"
        "mul.rn.bf16x2 hXa6, hLa6, pp;\n"
        "mov.b32 {sl, sh}, pX3;\n"
        "mov.b32 pp, {sl, sl};\n"
        "mul.rn.bf16x2 hXa5, hLa5, pp;\n"
        "mul.rn.bf16x2 hXa7, hLa7, pp;\n"
        "mov.b32 {sl, sh}, pX0;\n"
        "mov.b32 pp, {sh, sh};\n"
        "mul.rn.bf16x2 hXb0, hLb0, pp;\n"
        "mul.rn.bf16x2 hXb2, hLb2, pp;\n"
        "mov.b32 {sl, sh}, pX1;\n"
        "mov.b32 pp, {sh, sh};\n"
        "mul.rn.bf16x2 hXb1, hLb1, pp;\n"
        "mul.rn.bf16x2 hXb3, hLb3, pp;\n"
        "mov.b32 {sl, sh}, pX2;\n"
        "mov.b32 pp, {sh, sh};\n"
        "mul.rn.bf16x2 hXb4, hLb4, pp;\n"
        "mul.rn.bf16x2 hXb6, hLb6, pp;\n"
        "mov.b32 {sl, sh}, pX3;\n"
        "mov.b32 pp, {sh, sh};\n"
        "mul.rn.bf16x2 hXb5, hLb5, pp;\n"
        "mul.rn.bf16x2 hXb7, hLb7, pp;\n"
        "ldmatrix.sync.aligned.m8n8.x4.trans.shared.b16 {hLa0,hLa1,hLa2,hLa3}, [v0+4096];\n"
        "ldmatrix.sync.aligned.m8n8.x4.trans.shared.b16 {hLa4,hLa5,hLa6,hLa7}, [v1+4096];\n"
        "ldmatrix.sync.aligned.m8n8.x4.trans.shared.b16 {hLb0,hLb1,hLb2,hLb3}, [v0+6144];\n"
        "ldmatrix.sync.aligned.m8n8.x4.trans.shared.b16 {hLb4,hLb5,hLb6,hLb7}, [v1+6144];\n"
        "@t2 bra.uni T4X;\n"
        "@t1 bra.uni T2X;\n"
        "@t0 bra.uni L1X;\n"
        "L0X:\n"
        "wgmma.fence.sync.aligned;\n"
        "wgmma.mma_async.sync.aligned.m64n24k16.f32.bf16.bf16 {%0,%1,%2,%3,%4,%5,%6,%7,%8,%9,%10,%11}, {hXa0,hXa1,hXa2,hXa3}, daX, 1, 1, 1, 0;\n"
        "wgmma.mma_async.sync.aligned.m64n24k16.f32.bf16.bf16 {%76,%77,%78,%79,%80,%81,%82,%83,%84,%85,%86,%87}, {hXa4,hXa5,hXa6,hXa7}, daX, 1, 1, 1, 0;\n"
        "wgmma.commit_group.sync.aligned;\n"
        "@u2 bra.uni T4Xb;\n"
        "@u1 bra.uni T2Xb;\n"
        "@u0 bra.uni L1Xb;\n"
        "bra.uni L0Xb;\n"
        "L1X:\n"
        "wgmma.fence.sync.aligned;\n"
        "wgmma.mma_async.sync.aligned.m64n24k16.f32.bf16.bf16 {%12,%13,%14,%15,%16,%17,%18,%19,%20,%21,%22,%23}, {hXa0,hXa1,hXa2,hXa3}, daX, 1, 1, 1, 0;\n"
        "wgmma.mma_async.sync.aligned.m64n24k16.f32.bf16.bf16 {%88,%89,%90,%91,%92,%93,%94,%95,%96,%97,%98,%99}, {hXa4,hXa5,hXa6,hXa7}, daX, 1, 1, 1, 0;\n"
        "wgmma.commit_group.sync.aligned;\n"
        "@u2 bra.uni T4Xb;\n"
        "@u1 bra.uni T2Xb;\n"
        "@u0 bra.uni L1Xb;\n"
        "bra.uni L0Xb;\n"
        "T2X:\n"
        "@t0 bra.uni L3X;\n"
        "L2X:\n"
        "wgmma.fence.sync.aligned;\n"
        "wgmma.mma_async.sync.aligned.m64n24k16.f32.bf16.bf16 {%24,%25,%26,%27,%28,%29,%30,%31,%32,%33,%34,%35}, {hXa0,hXa1,hXa2,hXa3}, daX, 1, 1, 1, 0;\n"
        "wgmma.mma_async.sync.aligned.m64n24k16.f32.bf16.bf16 {%100,%101,%102,%103,%104,%105,%106,%107,%108,%109,%110,%111}, {hXa4,hXa5,hXa6,hXa7}, daX, 1, 1, 1, 0;\n"
        "wgmma.commit_group.sync.aligned;\n"
        "@u2 bra.uni T4Xb;\n"
        "@u1 bra.uni T2Xb;\n"
        "@u0 bra.uni L1Xb;\n"
        "bra.uni L0Xb;\n"
        "L3X:\n"
        "wgmma.fence.sync.aligned;\n"
        "wgmma.mma_async.sync.aligned.m64n24k16.f32.bf16.bf16 {%36,%37,%38,%39,%40,%41,%42,%43,%44,%45,%46,%47}, {hXa0,hXa1,hXa2,hXa3}, daX, 1, 1, 1, 0;\n"
        "wgmma.mma_async.sync.aligned.m64n24k16.f32.bf16.bf16 {%112,%113,%114,%115,%116,%117,%118,%119,%120,%121,%122,%123}, {hXa4,hXa5,hXa6,hXa7}, daX, 1, 1, 1, 0;\n"
        "wgmma.commit_group.sync.aligned;\n"
        "@u2 bra.uni T4Xb;\n"
        "@u1 bra.uni T2Xb;\n"
        "@u0 bra.uni L1Xb;\n"
        "bra.uni L0Xb;\n"
        "T4X:\n"
        "@!t1 bra.uni LEXIT;\n"
        "@t0 bra.uni L5X;\n"
        "L4X:\n"
        "wgmma.fence.sync.aligned;\n"
        "wgmma.mma_async.sync.aligned.m64n24k16.f32.bf16.bf16 {%48,%49,%50,%51,%52,%53,%54,%55,%56,%57,%58,%59}, {hXa0,hXa1,hXa2,hXa3}, daX, 1, 1, 1, 0;\n"
        "wgmma.mma_async.sync.aligned.m64n24k16.f32.bf16.bf16 {%124,%125,%126,%127,%128,%129,%130,%131,%132,%133,%134,%135}, {hXa4,hXa5,hXa6,hXa7}, daX, 1, 1, 1, 0;\n"
        "wgmma.commit_group.sync.aligned;\n"
        "@u2 bra.uni T4Xb;\n"
        "@u1 bra.uni T2Xb;\n"
        "@u0 bra.uni L1Xb;\n"
        "bra.uni L0Xb;\n"
        "L5X:\n"
        "wgmma.fence.sync.aligned;\n"
        "wgmma.mma_async.sync.aligned.m64n32k16.f32.bf16.bf16 {%60,%61,%62,%63,%64,%65,%66,%67,%68,%69,%70,%71,%72,%73,%74,%75}, {hXa0,hXa1,hXa2,hXa3}, daX, 1, 1, 1, 0;\n"
        "wgmma.mma_async.sync.aligned.m64n32k16.f32.bf16.bf16 {%136,%137,%138,%139,%140,%141,%142,%143,%144,%145,%146,%147,%148,%149,%150,%151}, {hXa4,hXa5,hXa6,hXa7}, daX, 1, 1, 1, 0;\n"
        "wgmma.commit_group.sync.aligned;\n"
        "@u2 bra.uni T4Xb;\n"
        "@u1 bra.uni T2Xb;\n"
        "@u0 bra.uni L1Xb;\n"
        "L0Xb:\n"
        "wgmma.fence.sync.aligned;\n"
        "wgmma.mma_async.sync.aligned.m64n24k16.f32.bf16.bf16 {%0,%1,%2,%3,%4,%5,%6,%7,%8,%9,%10,%11}, {hXb0,hXb1,hXb2,hXb3}, dbX, 1, 1, 1, 0;\n"
        "wgmma.mma_async.sync.aligned.m64n24k16.f32.bf16.bf16 {%76,%77,%78,%79,%80,%81,%82,%83,%84,%85,%86,%87}, {hXb4,hXb5,hXb6,hXb7}, dbX, 1, 1, 1, 0;\n"
        "wgmma.commit_group.sync.aligned;\n"
        "bra.uni CY;\n"
        "L1Xb:\n"
        "wgmma.fence.sync.aligned;\n"
        "wgmma.mma_async.sync.aligned.m64n24k16.f32.bf16.bf16 {%12,%13,%14,%15,%16,%17,%18,%19,%20,%21,%22,%23}, {hXb0,hXb1,hXb2,hXb3}, dbX, 1, 1, 1, 0;\n"
        "wgmma.mma_async.sync.aligned.m64n24k16.f32.bf16.bf16 {%88,%89,%90,%91,%92,%93,%94,%95,%96,%97,%98,%99}, {hXb4,hXb5,hXb6,hXb7}, dbX, 1, 1, 1, 0;\n"
        "wgmma.commit_group.sync.aligned;\n"
        "bra.uni CY;\n"
        "T2Xb:\n"
        "@u0 bra.uni L3Xb;\n"
        "L2Xb:\n"
        "wgmma.fence.sync.aligned;\n"
        "wgmma.mma_async.sync.aligned.m64n24k16.f32.bf16.bf16 {%24,%25,%26,%27,%28,%29,%30,%31,%32,%33,%34,%35}, {hXb0,hXb1,hXb2,hXb3}, dbX, 1, 1, 1, 0;\n"
        "wgmma.mma_async.sync.aligned.m64n24k16.f32.bf16.bf16 {%100,%101,%102,%103,%104,%105,%106,%107,%108,%109,%110,%111}, {hXb4,hXb5,hXb6,hXb7}, dbX, 1, 1, 1, 0;\n"
        "wgmma.commit_group.sync.aligned;\n"
        "bra.uni CY;\n"
        "L3Xb:\n"
        "wgmma.fence.sync.aligned;\n"
        "wgmma.mma_async.sync.aligned.m64n24k16.f32.bf16.bf16 {%36,%37,%38,%39,%40,%41,%42,%43,%44,%45,%46,%47}, {hXb0,hXb1,hXb2,hXb3}, dbX, 1, 1, 1, 0;\n"
        "wgmma.mma_async.sync.aligned.m64n24k16.f32.bf16.bf16 {%112,%113,%114,%115,%116,%117,%118,%119,%120,%121,%122,%123}, {hXb4,hXb5,hXb6,hXb7}, dbX, 1, 1, 1, 0;\n"
        "wgmma.commit_group.sync.aligned;\n"
        "bra.uni CY;\n"
        "T4Xb:\n"
        "@u0 bra.uni L5Xb;\n"
        "L4Xb:\n"
        "wgmma.fence.sync.aligned;\n"
        "wgmma.mma_async.sync.aligned.m64n24k16.f32.bf16.bf16 {%48,%49,%50,%51,%52,%53,%54,%55,%56,%57,%58,%59}, {hXb0,hXb1,hXb2,hXb3}, dbX, 1, 1, 1, 0;\n"
        "wgmma.mma_async.sync.aligned.m64n24k16.f32.bf16.bf16 {%124,%125,%126,%127,%128,%129,%130,%131,%132,%133,%134,%135}, {hXb4,hXb5,hXb6,hXb7}, dbX, 1, 1, 1, 0;\n"
        "wgmma.commit_group.sync.aligned;\n"
        "bra.uni CY;\n"
        "L5Xb:\n"
        "wgmma.fence.sync.aligned;\n"
        "wgmma.mma_async.sync.aligned.m64n32k16.f32.bf16.bf16 {%60,%61,%62,%63,%64,%65,%66,%67,%68,%69,%70,%71,%72,%73,%74,%75}, {hXb0,hXb1,hXb2,hXb3}, dbX, 1, 1, 1, 0;\n"
        "wgmma.mma_async.sync.aligned.m64n32k16.f32.bf16.bf16 {%136,%137,%138,%139,%140,%141,%142,%143,%144,%145,%146,%147,%148,%149,%150,%151}, {hXb4,hXb5,hXb6,hXb7}, dbX, 1, 1, 1, 0;\n"
        "wgmma.commit_group.sync.aligned;\n"
        "bra.uni CY;\n"
        "CY:\n"
        "mov.u32 rbar, bar;\n"
        "mov.u32 bar, nbar;\n"
        "mov.u32 par, npar;\n"
        "sub.u32 so, bar, %187;\n"
        "shl.b32 so, so, 9;\n"
        "add.u32 v0, %184, so;\n"
        "add.u32 v1, %185, so;\n"
        "add.u32 nbar, nbar, 16;\n"
        "setp.eq.u32 p, nbar, bend;\n"
        "selp.b32 nbar, %187, nbar, p;\n"
        "@p xor.b32 npar, npar, 1;\n"
        "wgmma.wait_group.sync.aligned 2;\n"
        "lop3.b32 v2, hLa3, hLa7, hLb3, 0x80;\n"
        "lop3.b32 v2, v2, hLb7, uz, 0x80;\n"
        "add.u32 v2, v2, rbar;\n"
        "@plead mbarrier.arrive.shared.b64 _, [v2+8];\n"
        "setp.lt.f16x2 t0|u0, ctm, cz;\n"
        "abs.f16x2 v3, ctm;\n"
        "setp.ge.f16x2 t1|u1, v3, ca;\n"
        "setp.geu.f16x2 t2|u2, v3, cb;\n"
        "ld.shared.v2.u32 {ctl, ctm}, [pl];\n"
        "add.u32 pl, pl, 8;\n"
        "mov.b32 {sl, sh}, pY0;\n"
        "mov.b32 pp, {sl, sl};\n"
        "mul.rn.bf16x2 hYa0, hLa0, pp;\n"
        "mul.rn.bf16x2 hYa2, hLa2, pp;\n"
        "mov.b32 {sl, sh}, pY1;\n"
        "mov.b32 pp, {sl, sl};\n"
        "mul.rn.bf16x2 hYa1, hLa1, pp;\n"
        "mul.rn.bf16x2 hYa3, hLa3, pp;\n"
        "mov.b32 {sl, sh}, pY2;\n"
        "mov.b32 pp, {sl, sl};\n"
        "mul.rn.bf16x2 hYa4, hLa4, pp;\n"
        "mul.rn.bf16x2 hYa6, hLa6, pp;\n"
        "mov.b32 {sl, sh}, pY3;\n"
        "mov.b32 pp, {sl, sl};\n"
        "mul.rn.bf16x2 hYa5, hLa5, pp;\n"
        "mul.rn.bf16x2 hYa7, hLa7, pp;\n"
        "mov.b32 {sl, sh}, pY0;\n"
        "mov.b32 pp, {sh, sh};\n"
        "mul.rn.bf16x2 hYb0, hLb0, pp;\n"
        "mul.rn.bf16x2 hYb2, hLb2, pp;\n"
        "mov.b32 {sl, sh}, pY1;\n"
        "mov.b32 pp, {sh, sh};\n"
        "mul.rn.bf16x2 hYb1, hLb1, pp;\n"
        "mul.rn.bf16x2 hYb3, hLb3, pp;\n"
        "mov.b32 {sl, sh}, pY2;\n"
        "mov.b32 pp, {sh, sh};\n"
        "mul.rn.bf16x2 hYb4, hLb4, pp;\n"
        "mul.rn.bf16x2 hYb6, hLb6, pp;\n"
        "mov.b32 {sl, sh}, pY3;\n"
        "mov.b32 pp, {sh, sh};\n"
        "mul.rn.bf16x2 hYb5, hLb5, pp;\n"
        "mul.rn.bf16x2 hYb7, hLb7, pp;\n"
        "@!pok bra.uni SLOW;\n"
        "RES:\n"
        "ldmatrix.sync.aligned.m8n8.x4.trans.shared.b16 {hLa0,hLa1,hLa2,hLa3}, [v0+0];\n"
        "ldmatrix.sync.aligned.m8n8.x4.trans.shared.b16 {hLa4,hLa5,hLa6,hLa7}, [v1+0];\n"
        "ldmatrix.sync.aligned.m8n8.x4.trans.shared.b16 {hLb0,hLb1,hLb2,hLb3}, [v0+2048];\n"
        "ldmatrix.sync.aligned.m8n8.x4.trans.shared.b16 {hLb4,hLb5,hLb6,hLb7}, [v1+2048];\n"
        "wgmma.wait_group.sync.aligned 0;\n"
        "@t2 bra.uni T4Y;\n"
        "@t1 bra.uni T2Y;\n"
        "@t0 bra.uni L1Y;\n"
        "L0Y:\n"
        "wgmma.fence.sync.aligned;\n"
        "wgmma.mma_async.sync.aligned.m64n16k16.f32.bf16.bf16 {r0,r1,r2,r3,r4,r5,r6,r7}, {wa0,wa1,wa2,wa3}, de0, pf, 1, 1, 0;\n"
        "wgmma.mma_async.sync.aligned.m64n16k16.f32.bf16.bf16 {r8,r9,r10,r11,r12,r13,r14,r15}, {wa4,wa5,wa6,wa7}, de1, pf, 1, 1, 0;\n"
        "wgmma.commit_group.sync.aligned;\n"
        "wgmma.mma_async.sync.aligned.m64n24k16.f32.bf16.bf16 {%0,%1,%2,%3,%4,%5,%6,%7,%8,%9,%10,%11}, {hYa0,hYa1,hYa2,hYa3}, daY, 1, 1, 1, 0;\n"
        "wgmma.mma_async.sync.aligned.m64n24k16.f32.bf16.bf16 {%76,%77,%78,%79,%80,%81,%82,%83,%84,%85,%86,%87}, {hYa4,hYa5,hYa6,hYa7}, daY, 1, 1, 1, 0;\n"
        "wgmma.commit_group.sync.aligned;\n"
        "@u2 bra.uni T4Yb;\n"
        "@u1 bra.uni T2Yb;\n"
        "@u0 bra.uni L1Yb;\n"
        "bra.uni L0Yb;\n"
        "L1Y:\n"
        "wgmma.fence.sync.aligned;\n"
        "wgmma.mma_async.sync.aligned.m64n16k16.f32.bf16.bf16 {r0,r1,r2,r3,r4,r5,r6,r7}, {wa0,wa1,wa2,wa3}, de0, pf, 1, 1, 0;\n"
        "wgmma.mma_async.sync.aligned.m64n16k16.f32.bf16.bf16 {r8,r9,r10,r11,r12,r13,r14,r15}, {wa4,wa5,wa6,wa7}, de1, pf, 1, 1, 0;\n"
        "wgmma.commit_group.sync.aligned;\n"
        "wgmma.mma_async.sync.aligned.m64n24k16.f32.bf16.bf16 {%12,%13,%14,%15,%16,%17,%18,%19,%20,%21,%22,%23}, {hYa0,hYa1,hYa2,hYa3}, daY, 1, 1, 1, 0;\n"
        "wgmma.mma_async.sync.aligned.m64n24k16.f32.bf16.bf16 {%88,%89,%90,%91,%92,%93,%94,%95,%96,%97,%98,%99}, {hYa4,hYa5,hYa6,hYa7}, daY, 1, 1, 1, 0;\n"
        "wgmma.commit_group.sync.aligned;\n"
        "@u2 bra.uni T4Yb;\n"
        "@u1 bra.uni T2Yb;\n"
        "@u0 bra.uni L1Yb;\n"
        "bra.uni L0Yb;\n"
        "T2Y:\n"
        "@t0 bra.uni L3Y;\n"
        "L2Y:\n"
        "wgmma.fence.sync.aligned;\n"
        "wgmma.mma_async.sync.aligned.m64n16k16.f32.bf16.bf16 {r0,r1,r2,r3,r4,r5,r6,r7}, {wa0,wa1,wa2,wa3}, de0, pf, 1, 1, 0;\n"
        "wgmma.mma_async.sync.aligned.m64n16k16.f32.bf16.bf16 {r8,r9,r10,r11,r12,r13,r14,r15}, {wa4,wa5,wa6,wa7}, de1, pf, 1, 1, 0;\n"
        "wgmma.commit_group.sync.aligned;\n"
        "wgmma.mma_async.sync.aligned.m64n24k16.f32.bf16.bf16 {%24,%25,%26,%27,%28,%29,%30,%31,%32,%33,%34,%35}, {hYa0,hYa1,hYa2,hYa3}, daY, 1, 1, 1, 0;\n"
        "wgmma.mma_async.sync.aligned.m64n24k16.f32.bf16.bf16 {%100,%101,%102,%103,%104,%105,%106,%107,%108,%109,%110,%111}, {hYa4,hYa5,hYa6,hYa7}, daY, 1, 1, 1, 0;\n"
        "wgmma.commit_group.sync.aligned;\n"
        "@u2 bra.uni T4Yb;\n"
        "@u1 bra.uni T2Yb;\n"
        "@u0 bra.uni L1Yb;\n"
        "bra.uni L0Yb;\n"
        "L3Y:\n"
        "wgmma.fence.sync.aligned;\n"
        "wgmma.mma_async.sync.aligned.m64n16k16.f32.bf16.bf16 {r0,r1,r2,r3,r4,r5,r6,r7}, {wa0,wa1,wa2,wa3}, de0, pf, 1, 1, 0;\n"
        "wgmma.mma_async.sync.aligned.m64n16k16.f32.bf16.bf16 {r8,r9,r10,r11,r12,r13,r14,r15}, {wa4,wa5,wa6,wa7}, de1, pf, 1, 1, 0;\n"
        "wgmma.commit_group.sync.aligned;\n"
        "wgmma.mma_async.sync.aligned.m64n24k16.f32.bf16.bf16 {%36,%37,%38,%39,%40,%41,%42,%43,%44,%45,%46,%47}, {hYa0,hYa1,hYa2,hYa3}, daY, 1, 1, 1, 0;\n"
        "wgmma.mma_async.sync.aligned.m64n24k16.f32.bf16.bf16 {%112,%113,%114,%115,%116,%117,%118,%119,%120,%121,%122,%123}, {hYa4,hYa5,hYa6,hYa7}, daY, 1, 1, 1, 0;\n"
        "wgmma.commit_group.sync.aligned;\n"
        "@u2 bra.uni T4Yb;\n"
        "@u1 bra.uni T2Yb;\n"
        "@u0 bra.uni L1Yb;\n"
        "bra.uni L0Yb;\n"
        "T4Y:\n"
        "@t0 bra.uni L5Y;\n"
        "L4Y:\n"
        "wgmma.fence.sync.aligned;\n"
        "wgmma.mma_async.sync.aligned.m64n16k16.f32.bf16.bf16 {r0,r1,r2,r3,r4,r5,r6,r7}, {wa0,wa1,wa2,wa3}, de0, pf, 1, 1, 0;\n"
        "wgmma.mma_async.sync.aligned.m64n16k16.f32.bf16.bf16 {r8,r9,r10,r11,r12,r13,r14,r15}, {wa4,wa5,wa6,wa7}, de1, pf, 1, 1, 0;\n"
        "wgmma.commit_group.sync.aligned;\n"
        "wgmma.mma_async.sync.aligned.m64n24k16.f32.bf16.bf16 {%48,%49,%50,%51,%52,%53,%54,%55,%56,%57,%58,%59}, {hYa0,hYa1,hYa2,hYa3}, daY, 1, 1, 1, 0;\n"
        "wgmma.mma_async.sync.aligned.m64n24k16.f32.bf16.bf16 {%124,%125,%126,%127,%128,%129,%130,%131,%132,%133,%134,%135}, {hYa4,hYa5,hYa6,hYa7}, daY, 1, 1, 1, 0;\n"
        "wgmma.commit_group.sync.aligned;\n"
        "@u2 bra.uni T4Yb;\n"
        "@u1 bra.uni T2Yb;\n"
        "@u0 bra.uni L1Yb;\n"
        "bra.uni L0Yb;\n"
        "L5Y:\n"
        "wgmma.fence.sync.aligned;\n"
        "wgmma.mma_async.sync.aligned.m64n16k16.f32.bf16.bf16 {r0,r1,r2,r3,r4,r5,r6,r7}, {wa0,wa1,wa2,wa3}, de0, pf, 1, 1, 0;\n"
        "wgmma.mma_async.sync.aligned.m64n16k16.f32.bf16.bf16 {r8,r9,r10,r11,r12,r13,r14,r15}, {wa4,wa5,wa6,wa7}, de1, pf, 1, 1, 0;\n"
        "wgmma.commit_group.sync.aligned;\n"
        "wgmma.mma_async.sync.aligned.m64n32k16.f32.bf16.bf16 {%60,%61,%62,%63,%64,%65,%66,%67,%68,%69,%70,%71,%72,%73,%74,%75}, {hYa0,hYa1,hYa2,hYa3}, daY, 1, 1, 1, 0;\n"
        "wgmma.mma_async.sync.aligned.m64n32k16.f32.bf16.bf16 {%136,%137,%138,%139,%140,%141,%142,%143,%144,%145,%146,%147,%148,%149,%150,%151}, {hYa4,hYa5,hYa6,hYa7}, daY, 1, 1, 1, 0;\n"
        "wgmma.commit_group.sync.aligned;\n"
        "@u2 bra.uni T4Yb;\n"
        "@u1 bra.uni T2Yb;\n"
        "@u0 bra.uni L1Yb;\n"
        "L0Yb:\n"
        "wgmma.fence.sync.aligned;\n"
        "wgmma.mma_async.sync.aligned.m64n24k16.f32.bf16.bf16 {%0,%1,%2,%3,%4,%5,%6,%7,%8,%9,%10,%11}, {hYb0,hYb1,hYb2,hYb3}, dbY, 1, 1, 1, 0;\n"
        "wgmma.mma_async.sync.aligned.m64n24k16.f32.bf16.bf16 {%76,%77,%78,%79,%80,%81,%82,%83,%84,%85,%86,%87}, {hYb4,hYb5,hYb6,hYb7}, dbY, 1, 1, 1, 0;\n"
        "wgmma.commit_group.sync.aligned;\n"
        "bra.uni CX;\n"
        "L1Yb:\n"
        "wgmma.fence.sync.aligned;\n"
        "wgmma.mma_async.sync.aligned.m64n24k16.f32.bf16.bf16 {%12,%13,%14,%15,%16,%17,%18,%19,%20,%21,%22,%23}, {hYb0,hYb1,hYb2,hYb3}, dbY, 1, 1, 1, 0;\n"
        "wgmma.mma_async.sync.aligned.m64n24k16.f32.bf16.bf16 {%88,%89,%90,%91,%92,%93,%94,%95,%96,%97,%98,%99}, {hYb4,hYb5,hYb6,hYb7}, dbY, 1, 1, 1, 0;\n"
        "wgmma.commit_group.sync.aligned;\n"
        "bra.uni CX;\n"
        "T2Yb:\n"
        "@u0 bra.uni L3Yb;\n"
        "L2Yb:\n"
        "wgmma.fence.sync.aligned;\n"
        "wgmma.mma_async.sync.aligned.m64n24k16.f32.bf16.bf16 {%24,%25,%26,%27,%28,%29,%30,%31,%32,%33,%34,%35}, {hYb0,hYb1,hYb2,hYb3}, dbY, 1, 1, 1, 0;\n"
        "wgmma.mma_async.sync.aligned.m64n24k16.f32.bf16.bf16 {%100,%101,%102,%103,%104,%105,%106,%107,%108,%109,%110,%111}, {hYb4,hYb5,hYb6,hYb7}, dbY, 1, 1, 1, 0;\n"
        "wgmma.commit_group.sync.aligned;\n"
        "bra.uni CX;\n"
        "L3Yb:\n"
        "wgmma.fence.sync.aligned;\n"
        "wgmma.mma_async.sync.aligned.m64n24k16.f32.bf16.bf16 {%36,%37,%38,%39,%40,%41,%42,%43,%44,%45,%46,%47}, {hYb0,hYb1,hYb2,hYb3}, dbY, 1, 1, 1, 0;\n"
        "wgmma.mma_async.sync.aligned.m64n24k16.f32.bf16.bf16 {%112,%113,%114,%115,%116,%117,%118,%119,%120,%121,%122,%123}, {hYb4,hYb5,hYb6,hYb7}, dbY, 1, 1, 1, 0;\n"
        "wgmma.commit_group.sync.aligned;\n"
        "bra.uni CX;\n"
        "T4Yb:\n"
        "@u0 bra.uni L5Yb;\n"
        "L4Yb:\n"
        "wgmma.fence.sync.aligned;\n"
        "wgmma.mma_async.sync.aligned.m64n24k16.f32.bf16.bf16 {%48,%49,%50,%51,%52,%53,%54,%55,%56,%57,%58,%59}, {hYb0,hYb1,hYb2,hYb3}, dbY, 1, 1, 1, 0;\n"
        "wgmma.mma_async.sync.aligned.m64n24k16.f32.bf16.bf16 {%124,%125,%126,%127,%128,%129,%130,%131,%132,%133,%134,%135}, {hYb4,hYb5,hYb6,hYb7}, dbY, 1, 1, 1, 0;\n"
        "wgmma.commit_group.sync.aligned;\n"
        "bra.uni CX;\n"
        "L5Yb:\n"
        "wgmma.fence.sync.aligned;\n"
        "wgmma.mma_async.sync.aligned.m64n32k16.f32.bf16.bf16 {%60,%61,%62,%63,%64,%65,%66,%67,%68,%69,%70,%71,%72,%73,%74,%75}, {hYb0,hYb1,hYb2,hYb3}, dbY, 1, 1, 1, 0;\n"
        "wgmma.mma_async.sync.aligned.m64n32k16.f32.bf16.bf16 {%136,%137,%138,%139,%140,%141,%142,%143,%144,%145,%146,%147,%148,%149,%150,%151}, {hYb4,hYb5,hYb6,hYb7}, dbY, 1, 1, 1, 0;\n"
        "wgmma.commit_group.sync.aligned;\n"
        "bra.uni CX;\n"
        "LEXIT:\n"
        "mov.u32 v2, %%tid.x;\n"
        "shr.u32 v3, v2, 4;\n"
        "and.b32 v0, v3, 1;\n"
        "mad.lo.u32 v0, v0, 1024, %200;\n"
        "and.b32 v1, v2, 7;\n"
        "mad.lo.u32 v0, v1, 128, v0;\n"
        "shr.u32 pp, v2, 3;\n"
        "lop3.b32 v3, v3, pp, 6, 0xe4;\n"
        "add.u32 pp, v2, 1;\n"
        "lop3.b32 pp, v3, pp, 7, 0x28;\n"
        "mad.lo.u32 v1, pp, 16, v0;\n"
        "lop3.b32 pp, v3, v2, 7, 0x28;\n"
        "mad.lo.u32 v0, pp, 16, v0;\n"
        "@pok bra.uni LW;\n"
        "mov.u32 cnt, 0;\n"
        "W2:\n"
        "mbarrier.try_wait.parity.shared.b64 p, [nbar], npar;\n"
        "@p bra.uni LW;\n"
        "add.u32 cnt, cnt, 1;\n"
        "setp.lt.u32 p, cnt, 4000000;\n"
        "@p bra.uni W2;\n"
        "trap;\n"
        "LW:\n"
        "ldmatrix.sync.aligned.m8n8.x4.trans.shared.b16 {hLa0,hLa1,hLa2,hLa3}, [v0+" STR((NP - 2) * 8192 + 0 * SM_ODD + 0) "];\n"
        "ldmatrix.sync.aligned.m8n8.x4.trans.shared.b16 {hLa4,hLa5,hLa6,hLa7}, [v0+" STR((NP - 2) * 8192 + 0 * SM_ODD + 2048) "];\n"
        "wgmma.wait_group.sync.aligned 0;\n"
        "ldmatrix.sync.aligned.m8n8.x4.trans.shared.b16 {hLb0,hLb1,hLb2,hLb3}, [v0+" STR((NP - 2) * 8192 + 0 * SM_ODD + 4096) "];\n"
        "ldmatrix.sync.aligned.m8n8.x4.trans.shared.b16 {hLb4,hLb5,hLb6,hLb7}, [v0+" STR((NP - 2) * 8192 + 0 * SM_ODD + 6144) "];\n"
        "ldmatrix.sync.aligned.m8n8.x4.trans.shared.b16 {hXa0,hXa1,hXa2,hXa3}, [v1+" STR((NP - 2) * 8192 + 1 * SM_ODD + 0) "];\n"
        "ldmatrix.sync.aligned.m8n8.x4.trans.shared.b16 {hXa4,hXa5,hXa6,hXa7}, [v1+" STR((NP - 2) * 8192 + 1 * SM_ODD + 2048) "];\n"
        "ldmatrix.sync.aligned.m8n8.x4.trans.shared.b16 {hXb0,hXb1,hXb2,hXb3}, [v1+" STR((NP - 2) * 8192 + 1 * SM_ODD + 4096) "];\n"
        "ldmatrix.sync.aligned.m8n8.x4.trans.shared.b16 {hXb4,hXb5,hXb6,hXb7}, [v1+" STR((NP - 2) * 8192 + 1 * SM_ODD + 6144) "];\n"
        "mov.b32 %152, hLa0;\n"
        "mov.b32 %153, hLa1;\n"
        "mov.b32 %154, hLa2;\n"
        "mov.b32 %155, hLa3;\n"
        "mov.b32 %156, hLa4;\n"
        "mov.b32 %157, hLa5;\n"
        "mov.b32 %158, hLa6;\n"
        "mov.b32 %159, hLa7;\n"
        "mov.b32 %160, hLb0;\n"
        "mov.b32 %161, hLb1;\n"
        "mov.b32 %162, hLb2;\n"
        "mov.b32 %163, hLb3;\n"
        "mov.b32 %164, hLb4;\n"
        "mov.b32 %165, hLb5;\n"
        "mov.b32 %166, hLb6;\n"
        "mov.b32 %167, hLb7;\n"
        "mov.b32 %168, hXa0;\n"
        "mov.b32 %169, hXa1;\n"
        "mov.b32 %170, hXa2;\n"
        "mov.b32 %171, hXa3;\n"
        "mov.b32 %172, hXa4;\n"
        "mov.b32 %173, hXa5;\n"
        "mov.b32 %174, hXa6;\n"
        "mov.b32 %175, hXa7;\n"
        "mov.b32 %176, hXb0;\n"
        "mov.b32 %177, hXb1;\n"
        "mov.b32 %178, hXb2;\n"
        "mov.b32 %179, hXb3;\n"
        "mov.b32 %180, hXb4;\n"
        "mov.b32 %181, hXb5;\n"
        "mov.b32 %182, hXb6;\n"
        "mov.b32 %183, hXb7;\n"
        "}\n"
        : "=f"(acc[0][0][0]), "=f"(acc[0][0][1]), "=f"(acc[0][0][2]), "=f"(acc[0][0][3]),
          "=f"(acc[0][1][0]), "=f"(acc[0][1][1]), "=f"(acc[0][1][2]), "=f"(acc[0][1][3]),
          "=f"(acc[0][2][0]), "=f"(acc[0][2][1]), "=f"(acc[0][2][2]), "=f"(acc[0][2][3]),
          "=f"(acc[0][3][0]), "=f"(acc[0][3][1]), "=f"(acc[0][3][2]), "=f"(acc[0][3][3]),
          "=f"(acc[0][4][0]), "=f"(acc[0][4][1]), "=f"(acc[0][4][2]), "=f"(acc[0][4][3]),
          "=f"(acc[0][5][0]), "=f"(acc[0][5][1]), "=f"(acc[0][5][2]), "=f"(acc[0][5][3]),
          "=f"(acc[0][6][0]), "=f"(acc[0][6][1]), "=f"(acc[0][6][2]), "=f"(acc[0][6][3]),
          "=f"(acc[0][7][0]), "=f"(acc[0][7][1]), "=f"(acc[0][7][2]), "=f"(acc[0][7][3]),
          "=f"(acc[0][8][0]), "=f"(acc[0][8][1]), "=f"(acc[0][8][2]), "=f"(acc[0][8][3]),
          "=f"(acc[0][9][0]), "=f"(acc[0][9][1]), "=f"(acc[0][9][2]), "=f"(acc[0][9][3]),
          "=f"(acc[0][10][0]), "=f"(acc[0][10][1]), "=f"(acc[0][10][2]), "=f"(acc[0][10][3]),
          "=f"(acc[0][11][0]), "=f"(acc[0][11][1]), "=f"(acc[0][11][2]), "=f"(acc[0][11][3]),
          "=f"(acc[0][12][0]), "=f"(acc[0][12][1]), "=f"(acc[0][12][2]), "=f"(acc[0][12][3]),
          "=f"(acc[0][13][0]), "=f"(acc[0][13][1]), "=f"(acc[0][13][2]), "=f"(acc[0][13][3]),
          "=f"(acc[0][14][0]), "=f"(acc[0][14][1]), "=f"(acc[0][14][2]), "=f"(acc[0][14][3]),
          "=f"(acc[0][15][0]), "=f"(acc[0][15][1]), "=f"(acc[0][15][2]), "=f"(acc[0][15][3]),
          "=f"(acc[0][16][0]), "=f"(acc[0][16][1]), "=f"(acc[0][16][2]), "=f"(acc[0][16][3]),
          "=f"(acc[0][17][0]), "=f"(acc[0][17][1]), "=f"(acc[0][17][2]), "=f"(acc[0][17][3]),
          "=f"(acc[0][18][0]), "=f"(acc[0][18][1]), "=f"(acc[0][18][2]), "=f"(acc[0][18][3]),
          "=f"(acc[1][0][0]), "=f"(acc[1][0][1]), "=f"(acc[1][0][2]), "=f"(acc[1][0][3]),
          "=f"(acc[1][1][0]), "=f"(acc[1][1][1]), "=f"(acc[1][1][2]), "=f"(acc[1][1][3]),
          "=f"(acc[1][2][0]), "=f"(acc[1][2][1]), "=f"(acc[1][2][2]), "=f"(acc[1][2][3]),
          "=f"(acc[1][3][0]), "=f"(acc[1][3][1]), "=f"(acc[1][3][2]), "=f"(acc[1][3][3]),
          "=f"(acc[1][4][0]), "=f"(acc[1][4][1]), "=f"(acc[1][4][2]), "=f"(acc[1][4][3]),
          "=f"(acc[1][5][0]), "=f"(acc[1][5][1]), "=f"(acc[1][5][2]), "=f"(acc[1][5][3]),
          "=f"(acc[1][6][0]), "=f"(acc[1][6][1]), "=f"(acc[1][6][2]), "=f"(acc[1][6][3]),
          "=f"(acc[1][7][0]), "=f"(acc[1][7][1]), "=f"(acc[1][7][2]), "=f"(acc[1][7][3]),
          "=f"(acc[1][8][0]), "=f"(acc[1][8][1]), "=f"(acc[1][8][2]), "=f"(acc[1][8][3]),
          "=f"(acc[1][9][0]), "=f"(acc[1][9][1]), "=f"(acc[1][9][2]), "=f"(acc[1][9][3]),
          "=f"(acc[1][10][0]), "=f"(acc[1][10][1]), "=f"(acc[1][10][2]), "=f"(acc[1][10][3]),
          "=f"(acc[1][11][0]), "=f"(acc[1][11][1]), "=f"(acc[1][11][2]), "=f"(acc[1][11][3]),
          "=f"(acc[1][12][0]), "=f"(acc[1][12][1]), "=f"(acc[1][12][2]), "=f"(acc[1][12][3]),
          "=f"(acc[1][13][0]), "=f"(acc[1][13][1]), "=f"(acc[1][13][2]), "=f"(acc[1][13][3]),
          "=f"(acc[1][14][0]), "=f"(acc[1][14][1]), "=f"(acc[1][14][2]), "=f"(acc[1][14][3]),
          "=f"(acc[1][15][0]), "=f"(acc[1][15][1]), "=f"(acc[1][15][2]), "=f"(acc[1][15][3]),
          "=f"(acc[1][16][0]), "=f"(acc[1][16][1]), "=f"(acc[1][16][2]), "=f"(acc[1][16][3]),
          "=f"(acc[1][17][0]), "=f"(acc[1][17][1]), "=f"(acc[1][17][2]), "=f"(acc[1][17][3]),
          "=f"(acc[1][18][0]), "=f"(acc[1][18][1]), "=f"(acc[1][18][2]), "=f"(acc[1][18][3]),
          "=r"(wo[0][0]), "=r"(wo[0][1]), "=r"(wo[0][2]), "=r"(wo[0][3]),
          "=r"(wo[1][0]), "=r"(wo[1][1]), "=r"(wo[1][2]), "=r"(wo[1][3]),
          "=r"(wo[2][0]), "=r"(wo[2][1]), "=r"(wo[2][2]), "=r"(wo[2][3]),
          "=r"(wo[3][0]), "=r"(wo[3][1]), "=r"(wo[3][2]), "=r"(wo[3][3]),
          "=r"(wo[4][0]), "=r"(wo[4][1]), "=r"(wo[4][2]), "=r"(wo[4][3]),
          "=r"(wo[5][0]), "=r"(wo[5][1]), "=r"(wo[5][2]), "=r"(wo[5][3]),
          "=r"(wo[6][0]), "=r"(wo[6][1]), "=r"(wo[6][2]), "=r"(wo[6][3]),
          "=r"(wo[7][0]), "=r"(wo[7][1]), "=r"(wo[7][2]), "=r"(wo[7][3])
        : "r"(xa0), "r"(xa1), "r"(so0), "r"(bar0), "r"(ea0), "r"(d0), "r"(pl0), "r"(lz), "r"(wa[0]), "r"(wa[1]), "r"(wa[2]),
          "r"(wa[3]), "r"(wa[4]), "r"(wa[5]), "r"(wa[6]), "r"(wa[7]), "r"(ring)
        : "memory");
}
#define CH0 4
#define CH1 7
#define CH2 8
#define CH3 10
#define CH4 9
__device__ __forceinline__ void wgmma_out(float (&o)[4][4], const uint32_t (&a)[4], uint64_t db, bool acc) {
    if (!acc)
        asm volatile(
            "wgmma.mma_async.sync.aligned.m64n32k16.f32.bf16.bf16 {%0,%1,%2,%3,%4,%5,%6,%7,%8,%9,%10,%11,%12,%13,%14,%15}, {%16,%17,%18,%19}, %20, 0, 1, 1, 1;"
            : "=f"(o[0][0]), "=f"(o[0][1]), "=f"(o[0][2]), "=f"(o[0][3]),
              "=f"(o[1][0]), "=f"(o[1][1]), "=f"(o[1][2]), "=f"(o[1][3]),
              "=f"(o[2][0]), "=f"(o[2][1]), "=f"(o[2][2]), "=f"(o[2][3]),
              "=f"(o[3][0]), "=f"(o[3][1]), "=f"(o[3][2]), "=f"(o[3][3])
            : "r"(a[0]), "r"(a[1]), "r"(a[2]), "r"(a[3]), "l"(db)
            : "memory");
    else
        asm volatile(
            "wgmma.mma_async.sync.aligned.m64n32k16.f32.bf16.bf16 {%0,%1,%2,%3,%4,%5,%6,%7,%8,%9,%10,%11,%12,%13,%14,%15}, {%16,%17,%18,%19}, %20, 1, 1, 1, 1;"
            : "+f"(o[0][0]), "+f"(o[0][1]), "+f"(o[0][2]), "+f"(o[0][3]),
              "+f"(o[1][0]), "+f"(o[1][1]), "+f"(o[1][2]), "+f"(o[1][3]),
              "+f"(o[2][0]), "+f"(o[2][1]), "+f"(o[2][2]), "+f"(o[2][3]),
              "+f"(o[3][0]), "+f"(o[3][1]), "+f"(o[3][2]), "+f"(o[3][3])
            : "r"(a[0]), "r"(a[1]), "r"(a[2]), "r"(a[3]), "l"(db)
            : "memory");
}
__device__ __forceinline__ void wgmma_out(float (&o)[7][4], const uint32_t (&a)[4], uint64_t db, bool acc) {
    if (!acc)
        asm volatile(
            "wgmma.mma_async.sync.aligned.m64n56k16.f32.bf16.bf16 {%0,%1,%2,%3,%4,%5,%6,%7,%8,%9,%10,%11,%12,%13,%14,%15,%16,%17,%18,%19,%20,%21,%22,%23,%24,%25,%26,%27}, {%28,%29,%30,%31}, %32, 0, 1, 1, 1;"
            : "=f"(o[0][0]), "=f"(o[0][1]), "=f"(o[0][2]), "=f"(o[0][3]),
              "=f"(o[1][0]), "=f"(o[1][1]), "=f"(o[1][2]), "=f"(o[1][3]),
              "=f"(o[2][0]), "=f"(o[2][1]), "=f"(o[2][2]), "=f"(o[2][3]),
              "=f"(o[3][0]), "=f"(o[3][1]), "=f"(o[3][2]), "=f"(o[3][3]),
              "=f"(o[4][0]), "=f"(o[4][1]), "=f"(o[4][2]), "=f"(o[4][3]),
              "=f"(o[5][0]), "=f"(o[5][1]), "=f"(o[5][2]), "=f"(o[5][3]),
              "=f"(o[6][0]), "=f"(o[6][1]), "=f"(o[6][2]), "=f"(o[6][3])
            : "r"(a[0]), "r"(a[1]), "r"(a[2]), "r"(a[3]), "l"(db)
            : "memory");
    else
        asm volatile(
            "wgmma.mma_async.sync.aligned.m64n56k16.f32.bf16.bf16 {%0,%1,%2,%3,%4,%5,%6,%7,%8,%9,%10,%11,%12,%13,%14,%15,%16,%17,%18,%19,%20,%21,%22,%23,%24,%25,%26,%27}, {%28,%29,%30,%31}, %32, 1, 1, 1, 1;"
            : "+f"(o[0][0]), "+f"(o[0][1]), "+f"(o[0][2]), "+f"(o[0][3]),
              "+f"(o[1][0]), "+f"(o[1][1]), "+f"(o[1][2]), "+f"(o[1][3]),
              "+f"(o[2][0]), "+f"(o[2][1]), "+f"(o[2][2]), "+f"(o[2][3]),
              "+f"(o[3][0]), "+f"(o[3][1]), "+f"(o[3][2]), "+f"(o[3][3]),
              "+f"(o[4][0]), "+f"(o[4][1]), "+f"(o[4][2]), "+f"(o[4][3]),
              "+f"(o[5][0]), "+f"(o[5][1]), "+f"(o[5][2]), "+f"(o[5][3]),
              "+f"(o[6][0]), "+f"(o[6][1]), "+f"(o[6][2]), "+f"(o[6][3])
            : "r"(a[0]), "r"(a[1]), "r"(a[2]), "r"(a[3]), "l"(db)
            : "memory");
}
__device__ __forceinline__ void wgmma_out(float (&o)[8][4], const uint32_t (&a)[4], uint64_t db, bool acc) {
    if (!acc)
        asm volatile(
            "wgmma.mma_async.sync.aligned.m64n64k16.f32.bf16.bf16 {%0,%1,%2,%3,%4,%5,%6,%7,%8,%9,%10,%11,%12,%13,%14,%15,%16,%17,%18,%19,%20,%21,%22,%23,%24,%25,%26,%27,%28,%29,%30,%31}, {%32,%33,%34,%35}, %36, 0, 1, 1, 1;"
            : "=f"(o[0][0]), "=f"(o[0][1]), "=f"(o[0][2]), "=f"(o[0][3]),
              "=f"(o[1][0]), "=f"(o[1][1]), "=f"(o[1][2]), "=f"(o[1][3]),
              "=f"(o[2][0]), "=f"(o[2][1]), "=f"(o[2][2]), "=f"(o[2][3]),
              "=f"(o[3][0]), "=f"(o[3][1]), "=f"(o[3][2]), "=f"(o[3][3]),
              "=f"(o[4][0]), "=f"(o[4][1]), "=f"(o[4][2]), "=f"(o[4][3]),
              "=f"(o[5][0]), "=f"(o[5][1]), "=f"(o[5][2]), "=f"(o[5][3]),
              "=f"(o[6][0]), "=f"(o[6][1]), "=f"(o[6][2]), "=f"(o[6][3]),
              "=f"(o[7][0]), "=f"(o[7][1]), "=f"(o[7][2]), "=f"(o[7][3])
            : "r"(a[0]), "r"(a[1]), "r"(a[2]), "r"(a[3]), "l"(db)
            : "memory");
    else
        asm volatile(
            "wgmma.mma_async.sync.aligned.m64n64k16.f32.bf16.bf16 {%0,%1,%2,%3,%4,%5,%6,%7,%8,%9,%10,%11,%12,%13,%14,%15,%16,%17,%18,%19,%20,%21,%22,%23,%24,%25,%26,%27,%28,%29,%30,%31}, {%32,%33,%34,%35}, %36, 1, 1, 1, 1;"
            : "+f"(o[0][0]), "+f"(o[0][1]), "+f"(o[0][2]), "+f"(o[0][3]),
              "+f"(o[1][0]), "+f"(o[1][1]), "+f"(o[1][2]), "+f"(o[1][3]),
              "+f"(o[2][0]), "+f"(o[2][1]), "+f"(o[2][2]), "+f"(o[2][3]),
              "+f"(o[3][0]), "+f"(o[3][1]), "+f"(o[3][2]), "+f"(o[3][3]),
              "+f"(o[4][0]), "+f"(o[4][1]), "+f"(o[4][2]), "+f"(o[4][3]),
              "+f"(o[5][0]), "+f"(o[5][1]), "+f"(o[5][2]), "+f"(o[5][3]),
              "+f"(o[6][0]), "+f"(o[6][1]), "+f"(o[6][2]), "+f"(o[6][3]),
              "+f"(o[7][0]), "+f"(o[7][1]), "+f"(o[7][2]), "+f"(o[7][3])
            : "r"(a[0]), "r"(a[1]), "r"(a[2]), "r"(a[3]), "l"(db)
            : "memory");
}
__device__ __forceinline__ void wgmma_out(float (&o)[9][4], const uint32_t (&a)[4], uint64_t db, bool acc) {
    if (!acc)
        asm volatile(
            "wgmma.mma_async.sync.aligned.m64n72k16.f32.bf16.bf16 {%0,%1,%2,%3,%4,%5,%6,%7,%8,%9,%10,%11,%12,%13,%14,%15,%16,%17,%18,%19,%20,%21,%22,%23,%24,%25,%26,%27,%28,%29,%30,%31,%32,%33,%34,%35}, {%36,%37,%38,%39}, %40, 0, 1, 1, 1;"
            : "=f"(o[0][0]), "=f"(o[0][1]), "=f"(o[0][2]), "=f"(o[0][3]),
              "=f"(o[1][0]), "=f"(o[1][1]), "=f"(o[1][2]), "=f"(o[1][3]),
              "=f"(o[2][0]), "=f"(o[2][1]), "=f"(o[2][2]), "=f"(o[2][3]),
              "=f"(o[3][0]), "=f"(o[3][1]), "=f"(o[3][2]), "=f"(o[3][3]),
              "=f"(o[4][0]), "=f"(o[4][1]), "=f"(o[4][2]), "=f"(o[4][3]),
              "=f"(o[5][0]), "=f"(o[5][1]), "=f"(o[5][2]), "=f"(o[5][3]),
              "=f"(o[6][0]), "=f"(o[6][1]), "=f"(o[6][2]), "=f"(o[6][3]),
              "=f"(o[7][0]), "=f"(o[7][1]), "=f"(o[7][2]), "=f"(o[7][3]),
              "=f"(o[8][0]), "=f"(o[8][1]), "=f"(o[8][2]), "=f"(o[8][3])
            : "r"(a[0]), "r"(a[1]), "r"(a[2]), "r"(a[3]), "l"(db)
            : "memory");
    else
        asm volatile(
            "wgmma.mma_async.sync.aligned.m64n72k16.f32.bf16.bf16 {%0,%1,%2,%3,%4,%5,%6,%7,%8,%9,%10,%11,%12,%13,%14,%15,%16,%17,%18,%19,%20,%21,%22,%23,%24,%25,%26,%27,%28,%29,%30,%31,%32,%33,%34,%35}, {%36,%37,%38,%39}, %40, 1, 1, 1, 1;"
            : "+f"(o[0][0]), "+f"(o[0][1]), "+f"(o[0][2]), "+f"(o[0][3]),
              "+f"(o[1][0]), "+f"(o[1][1]), "+f"(o[1][2]), "+f"(o[1][3]),
              "+f"(o[2][0]), "+f"(o[2][1]), "+f"(o[2][2]), "+f"(o[2][3]),
              "+f"(o[3][0]), "+f"(o[3][1]), "+f"(o[3][2]), "+f"(o[3][3]),
              "+f"(o[4][0]), "+f"(o[4][1]), "+f"(o[4][2]), "+f"(o[4][3]),
              "+f"(o[5][0]), "+f"(o[5][1]), "+f"(o[5][2]), "+f"(o[5][3]),
              "+f"(o[6][0]), "+f"(o[6][1]), "+f"(o[6][2]), "+f"(o[6][3]),
              "+f"(o[7][0]), "+f"(o[7][1]), "+f"(o[7][2]), "+f"(o[7][3]),
              "+f"(o[8][0]), "+f"(o[8][1]), "+f"(o[8][2]), "+f"(o[8][3])
            : "r"(a[0]), "r"(a[1]), "r"(a[2]), "r"(a[3]), "l"(db)
            : "memory");
}
__device__ __forceinline__ void wgmma_out(float (&o)[10][4], const uint32_t (&a)[4], uint64_t db, bool acc) {
    if (!acc)
        asm volatile(
            "wgmma.mma_async.sync.aligned.m64n80k16.f32.bf16.bf16 {%0,%1,%2,%3,%4,%5,%6,%7,%8,%9,%10,%11,%12,%13,%14,%15,%16,%17,%18,%19,%20,%21,%22,%23,%24,%25,%26,%27,%28,%29,%30,%31,%32,%33,%34,%35,%36,%37,%38,%39}, {%40,%41,%42,%43}, %44, 0, 1, 1, 1;"
            : "=f"(o[0][0]), "=f"(o[0][1]), "=f"(o[0][2]), "=f"(o[0][3]),
              "=f"(o[1][0]), "=f"(o[1][1]), "=f"(o[1][2]), "=f"(o[1][3]),
              "=f"(o[2][0]), "=f"(o[2][1]), "=f"(o[2][2]), "=f"(o[2][3]),
              "=f"(o[3][0]), "=f"(o[3][1]), "=f"(o[3][2]), "=f"(o[3][3]),
              "=f"(o[4][0]), "=f"(o[4][1]), "=f"(o[4][2]), "=f"(o[4][3]),
              "=f"(o[5][0]), "=f"(o[5][1]), "=f"(o[5][2]), "=f"(o[5][3]),
              "=f"(o[6][0]), "=f"(o[6][1]), "=f"(o[6][2]), "=f"(o[6][3]),
              "=f"(o[7][0]), "=f"(o[7][1]), "=f"(o[7][2]), "=f"(o[7][3]),
              "=f"(o[8][0]), "=f"(o[8][1]), "=f"(o[8][2]), "=f"(o[8][3]),
              "=f"(o[9][0]), "=f"(o[9][1]), "=f"(o[9][2]), "=f"(o[9][3])
            : "r"(a[0]), "r"(a[1]), "r"(a[2]), "r"(a[3]), "l"(db)
            : "memory");
    else
        asm volatile(
            "wgmma.mma_async.sync.aligned.m64n80k16.f32.bf16.bf16 {%0,%1,%2,%3,%4,%5,%6,%7,%8,%9,%10,%11,%12,%13,%14,%15,%16,%17,%18,%19,%20,%21,%22,%23,%24,%25,%26,%27,%28,%29,%30,%31,%32,%33,%34,%35,%36,%37,%38,%39}, {%40,%41,%42,%43}, %44, 1, 1, 1, 1;"
            : "+f"(o[0][0]), "+f"(o[0][1]), "+f"(o[0][2]), "+f"(o[0][3]),
              "+f"(o[1][0]), "+f"(o[1][1]), "+f"(o[1][2]), "+f"(o[1][3]),
              "+f"(o[2][0]), "+f"(o[2][1]), "+f"(o[2][2]), "+f"(o[2][3]),
              "+f"(o[3][0]), "+f"(o[3][1]), "+f"(o[3][2]), "+f"(o[3][3]),
              "+f"(o[4][0]), "+f"(o[4][1]), "+f"(o[4][2]), "+f"(o[4][3]),
              "+f"(o[5][0]), "+f"(o[5][1]), "+f"(o[5][2]), "+f"(o[5][3]),
              "+f"(o[6][0]), "+f"(o[6][1]), "+f"(o[6][2]), "+f"(o[6][3]),
              "+f"(o[7][0]), "+f"(o[7][1]), "+f"(o[7][2]), "+f"(o[7][3]),
              "+f"(o[8][0]), "+f"(o[8][1]), "+f"(o[8][2]), "+f"(o[8][3]),
              "+f"(o[9][0]), "+f"(o[9][1]), "+f"(o[9][2]), "+f"(o[9][3])
            : "r"(a[0]), "r"(a[1]), "r"(a[2]), "r"(a[3]), "l"(db)
            : "memory");
}

__device__ __forceinline__ void slow_edge(int ee, int s, float* accn, const __nv_bfloat16* __restrict__ x,
                                          const __nv_bfloat16* __restrict__ sh, const __nv_bfloat16* __restrict__ ea,
                                          const __nv_bfloat16* __restrict__ cg, const __nv_bfloat16* __restrict__ wr,
                                          int lane) {
    float rwv[4] = {0.f, 0.f, 0.f, 0.f};
#pragma unroll 4
    for (int d = 0; d < 16; d++) {
        const float a = __bfloat162float(ea[(size_t)ee * 16 + d]);
        const uint2 wv = *(const uint2*)(wr + d * 128 + lane * 4);
        rwv[0] += a * __uint_as_float(wv.x << 16);
        rwv[1] += a * __uint_as_float(wv.x & 0xffff0000u);
        rwv[2] += a * __uint_as_float(wv.y << 16);
        rwv[3] += a * __uint_as_float(wv.y & 0xffff0000u);
    }
    float A = 0.f;
#pragma unroll
    for (int v = 0; v < 4; v++)
        A += __bfloat162float(cg[((lane >> 2) & 3) * 16 + v * 4 + (lane & 3)]) * __bfloat162float(sh[(size_t)ee * 4 + v]);
    float m[4][4];
#pragma unroll
    for (int w = 0; w < 4; w++)
#pragma unroll
        for (int j = 0; j < 4; j++) m[w][j] = 0.f;
#pragma unroll
    for (int u = 0; u < 4; u++) {
        const uint2 xv = *(const uint2*)(x + (size_t)s * 512 + u * 128 + lane * 4);
        const float x0 = __uint_as_float(xv.x << 16), x1 = __uint_as_float(xv.x & 0xffff0000u);
        const float x2 = __uint_as_float(xv.y << 16), x3 = __uint_as_float(xv.y & 0xffff0000u);
#pragma unroll
        for (int w = 0; w < 4; w++) {
            const float a = __shfl_sync(0xffffffffu, A, u * 4 + w);
            m[w][0] += a * x0;
            m[w][1] += a * x1;
            m[w][2] += a * x2;
            m[w][3] += a * x3;
        }
    }
#pragma unroll
    for (int w = 0; w < 4; w++)
#pragma unroll
        for (int j = 0; j < 4; j++) atomicAdd(accn + w * 128 + lane * 4 + j, m[w][j] * rwv[j]);
}

__device__ __forceinline__ void slow_out(const float* accn, const __nv_bfloat16* __restrict__ wout,
                                         __nv_bfloat16* __restrict__ outn, int lane) {
    float o[4][4];
#pragma unroll
    for (int w = 0; w < 4; w++)
#pragma unroll
        for (int j = 0; j < 4; j++) o[w][j] = 0.f;
#pragma unroll 2
    for (int c = 0; c < 128; c++) {
        const uint2 wv = *(const uint2*)(wout + c * 128 + lane * 4);
        const float w0 = __uint_as_float(wv.x << 16), w1 = __uint_as_float(wv.x & 0xffff0000u);
        const float w2 = __uint_as_float(wv.y << 16), w3 = __uint_as_float(wv.y & 0xffff0000u);
#pragma unroll
        for (int w = 0; w < 4; w++) {
            const float a = __bfloat162float(__float2bfloat16(accn[w * 128 + c]));
            o[w][0] += a * w0;
            o[w][1] += a * w1;
            o[w][2] += a * w2;
            o[w][3] += a * w3;
        }
    }
#pragma unroll
    for (int w = 0; w < 4; w++)
        *(uint2*)(outn + w * 128 + lane * 4) = make_uint2(pack_bf16(o[w][0], o[w][1]), pack_bf16(o[w][2], o[w][3]));
}

static_assert(NW > 2 * NP, "barriers");
#define PLC 0
#define PFT 45
#define PFC 1
#define PFS 1
#define BULK 0
#define PFX 200
#define PB 0
#define FPOS 1
#define PW 0
#define TWAIT mbar_lean_u
#define PWAIT mbar_lean
#define TMA_ROW(k) "@pl cp.async.bulk.tensor.2d.shared::cluster.global.mbarrier::complete_tx::bytes [d" #k "], [tm, {r" #k ", %2" #k "}], [b" #k "];\n"
#define TMA_PREP(k) "mad.lo.u32 d" #k ", dd, 512, %3" #k ";\nadd.u32 b" #k ", dd, %2" #k ";\n"
#define RDCLK(c) "mov.u64 ck, %%clock64;\ncvt.u32.u64 " c ", ck;\n"
#define BCAST(d, k) "selp.b32 " d ", a" #k ", 0, me;\nredux.sync.or.b32 " d ", " d ", 0xffffffff;\n"
#define PTIME(t, x, y, z) "shr.u32 " t ", " x ", 16;\nand.b32 c, " y ", 0xffff;\nadd.u32 " t ", " t ", c;\nmad.lo.u32 c, " t ", %13, %14;\nmul.lo.u32 " t ", " t ", %9;\nmin.u32 " t ", " t ", c;\nshr.u32 " t ", " t ", 5;\nadd.u32 " t ", " t ", %6;\nmin.u32 " t ", " t ", lim;\nlop3.b32 " t ", " t ", " z ", 7, 0xd8;\n"
#define PROWS(s, x, y) "and.b32 t0, " s ", 0xffc;\nsetp.gt.u32 p, t0, " STR(LNUL / 2) ";\nmad.lo.u32 t0, t0, 2, %5;\nld.shared.v2.u32 {" x ", " y "}, [t0];\nshr.u32 t0, " s ", 11;\nand.b32 t0, t0, 6;\nshr.u32 " s ", " s ", 15;\nadd.u32 t0, t0, " s ";\nselp.s32 " s ", " STR(NGR - 2) ", -2, p;\nadd.u32 t0, t0, " s ";\nmul.lo.s32 t0, t0, " STR(-KEYW) ";\nprmt.b32 t0, t0, 0, 0x1010;\nadd.u16x2 " x ", " x ", t0;\nadd.u16x2 " y ", " y ", t0;\n"
__device__ __forceinline__ void produce(const uint32_t (&pt)[2], const uint32_t (&pz)[8], const uint32_t (&pm)[8], uint32_t bar, uint32_t ps,
                                        int nit, uint32_t psrc, uint32_t tbase, uint32_t lim, uint32_t taug64, uint32_t taus, uint32_t n,
                                        int pr0, uint32_t tau2, uint32_t brk
) {
    asm volatile(
        "{\n.reg .pred p, pl, ok, me;\n.reg .b32 a<6>, u<4>, r<8>, d<8>, b<8>, ps, lim, n, it, pr, pe, tgt, tgu, c, dd, dn, par, t0, t1;\n"
        ".reg .b64 st, tm, ck;\n"
        "elect.sync _|pl, 0xffffffff;\n"
        "mov.b64 tm, {%0, %2};\n"
        "mov.u32 ps, %3;\n"
        "mov.u32 it, %4;\n"
        "mov.u32 lim, %7;\n"
        "mov.u32 n, %10;\n"
        "mov.u32 pr, %12;\n"
        "setp.le.s32 p, it, 0;\n"
        "bar.sync 4, " STR(NT) ";\n"
        "@p bra.uni PEND;\n"
        "PBAT:\n"
        "ld.shared.u16 c, [ps];\n"
        "ld.shared.u16 t1, [ps+4];\n"
        "add.u32 ps, ps, 256;\n"
        "mul.lo.u32 par, n, " STR(65536 / NP + 1) ";\n"
        "shr.u32 par, par, 16;\n"
        "mad.lo.s32 dn, par, " STR(-NP) ", n;\n"
        "add.u32 n, n, 32;\n"
        "not.b32 par, par;\n"
        PROWS("c", "a0", "a1") PROWS("t1", "a2", "a3")
        "min.s32 pe, it, 32;\n"
        "sub.s32 it, it, 32;\n"
        "add.u32 pe, pe, pr;\n"
        PTIME("a4", "a0", "a1", "dn") PTIME("a5", "a2", "a3", "par")
        "add.u32 lim, lim, %8;\n"
        "PLOOP:\n"
        "setp.eq.u32 me, n, pr;\n"
        "add.u32 pr, pr, 1;\n"
        BCAST("tgt", 4) BCAST("tgu", 5) BCAST("u0", 0) BCAST("u1", 1) BCAST("u2", 2) BCAST("u3", 3)
        "and.b32 dd, tgt, 7;\n"
        "mad.lo.u32 dd, dd, 16, %1;\n"
        "and.b32 par, tgu, 1;\n"
        "mbarrier.test_wait.parity.shared.b64 ok, [dd+8], par;\n"
        "prmt.b32 r0, u0, 0, 0x4104;\nprmt.b32 r1, u0, 0, 0x4324;\nprmt.b32 r2, u1, 0, 0x4104;\nprmt.b32 r3, u1, 0, 0x4324;\n"
        "prmt.b32 r4, u2, 0, 0x4104;\nprmt.b32 r5, u2, 0, 0x4324;\nprmt.b32 r6, u3, 0, 0x4104;\nprmt.b32 r7, u3, 0, 0x4324;\n"
        TMA_PREP(0) TMA_PREP(1) TMA_PREP(2) TMA_PREP(3) TMA_PREP(4) TMA_PREP(5) TMA_PREP(6) TMA_PREP(7)
        RDCLK("c")
        "sub.s32 c, c, tgt;\n"
        "setp.ge.and.s32 p, c, 0, ok;\n"
        "@!p bra.uni PSLP;\n"
        "PRES:\n"
        "@pl mbarrier.arrive.expect_tx.shared.b64 _, [b0], 8192;\n"
        TMA_ROW(0) TMA_ROW(1) TMA_ROW(2) TMA_ROW(3)
        RDCLK("c")
        "sub.s32 c, c, tgu;\n"
        "setp.lt.s32 p, c, 0;\n"
        "@p bra.uni PSL2;\n"
        "PRE2:\n"
        TMA_ROW(4) TMA_ROW(5) TMA_ROW(6) TMA_ROW(7)
        "setp.lt.u32 p, pr, pe;\n"
        "@p bra.uni PLOOP;\n"
        "setp.gt.s32 p, it, 0;\n"
        "@p bra.uni PBAT;\n"
        "bra.uni PEND;\n"
        "PSL2:\n"
        "nanosleep.u32 " STR(PSLEEP) ";\n"
        RDCLK("c")
        "sub.s32 c, c, tgu;\n"
        "setp.lt.s32 p, c, 0;\n"
        "@p bra.uni PSL2;\n"
        "bra.uni PRE2;\n"
        "PSL1:\n"
        "nanosleep.u32 " STR(PSLEEP) ";\n"
        RDCLK("c")
        "sub.s32 c, c, tgt;\n"
        "PSLP:\n"
        "setp.lt.s32 p, c, 0;\n"
        "@p bra.uni PSL1;\n"
        "@ok bra.uni PRES;\n"
        "mov.u32 c, 0;\n"
        "PW:\n"
        "mbarrier.try_wait.parity.shared.b64 p, [b0+8], par;\n"
        "@p bra.uni PRES;\n"
        "add.u32 c, c, 1;\n"
        "setp.lt.u32 p, c, 4000000;\n"
        "@p bra.uni PW;\n"
        "trap;\n"
        "PEND:\n}"
        :
        : "r"(pt[0]), "r"(bar), "r"(pt[1]), "r"(ps), "r"(nit), "r"(psrc), "r"(tbase), "r"(lim), "r"(taug64), "r"(taus), "r"(n), "n"(0),
          "r"(pr0), "r"(tau2), "r"(brk), "n"(0), "n"(0), "n"(0), "n"(0), "n"(0), "r"(pz[0]), "r"(pz[1]), "r"(pz[2]), "r"(pz[3]), "r"(pz[4]),
          "r"(pz[5]), "r"(pz[6]), "r"(pz[7]), "n"(0), "n"(0), "r"(pm[0]), "r"(pm[1]), "r"(pm[2]), "r"(pm[3]), "r"(pm[4]), "r"(pm[5]),
          "r"(pm[6]), "r"(pm[7])
        : "memory");
}
template <int J0, int JN>
__device__ __forceinline__ void put_agg(const float (&acc)[2][NJ][4], uint32_t tb, int u) {
    const int h = u & 1, j = u & ~1;
    const float(*a)[4] = acc[h] + J0 + (j < JN ? j : 0);
    if (j + 1 < JN)
        stsm4(tb + h * SM_ODD + (J0 + j) * 256, pack_bf16(a[0][0], a[0][1]), pack_bf16(a[0][2], a[0][3]), pack_bf16(a[1][0], a[1][1]),
              pack_bf16(a[1][2], a[1][3]));
    else if (j < JN)
        stsm2(tb + h * SM_ODD + (J0 + j) * 256, pack_bf16(a[0][0], a[0][1]), pack_bf16(a[0][2], a[0][3]));
}
template <int JN>
__device__ __forceinline__ void pin(float (&o)[JN][4]) {
#pragma unroll
    for (int j = 0; j < JN; j++)
#pragma unroll
        for (int k = 0; k < 4; k++) asm volatile("" : "+f"(o[j][k])::"memory");
}
#define WG_WAIT(n) asm volatile("wgmma.wait_group.sync.aligned %0;" ::"n"(n) : "memory")
#define WG_COMMIT() asm volatile("wgmma.commit_group.sync.aligned;" ::: "memory")
#define KA 2
template <int K0, int JN, class F>
__device__ __forceinline__ void mul_out(float (&o)[JN][4], const uint32_t (&a)[8][4], uint32_t db, F f) {
    asm volatile("wgmma.fence.sync.aligned;" ::: "memory");
#pragma unroll
    for (int ks = 0; ks < 8; ks++) {
        wgmma_out(o, a[ks], (uint64_t)(db + (((ks >> 2) * SM_ODD + (ks & 3) * (NJ * 256)) >> 4)) | (16ull << 32), ks);
        if (ks == K0 - 1 || ks == 7) WG_COMMIT();
        if (ks == K0 - 1) WG_WAIT(1);
        if (ks >= K0 - 1) f(K0 ? ks - K0 + 1 : ks);
    }
}
static_assert(CH1 <= 8 && CH2 <= 8 && CH3 <= 10 && CH4 <= 10 && KA <= 3 && NJ == 19 && NP == 5 && SM_EVEN == 0 && SM_ODD % 1024 == 128 && CH0 + CH2 <= 13 && CH1 <= 13 && CH0 + CH2 + CH4 <= 21 && CH1 + CH3 <= 21, "epilogue");
__device__ constexpr int out_n(int st) { return st == 0 ? CH0 : st == 1 ? CH1 : st == 2 ? CH2 : st == 3 ? CH3 : CH4; }
__device__ constexpr int out_j(int st) { return st == 1 ? CH0 : st == 2 ? CH0 + CH1 : st == 4 ? CH3 : 0; }
__device__ constexpr int out_at(int st) { return (NJ + (st == 2 ? CH0 : st == 3 ? CH1 : st == 4 ? CH0 + CH2 : 0)) * 1024 + (st & 1) * SM_ODD; }
#define WG_SYNC(w) asm volatile("bar.sync %0, 128;" ::"r"((w) + 1) : "memory")
#define HAND(st, w) asm volatile("bar.arrive %0, 192;" ::"r"(6 + 2 * (st) + (w)) : "memory")
template <int ST, int JN>
__device__ __forceinline__ void put_out(float (&o)[JN][4], uint32_t c, int u, int w) {
    if (u == 0) pin(o);
    const int j = 2 * u < JN ? 2 * u : 0;
    if (2 * u + 1 < JN)
        stsm4t(c + out_at(ST) + j * 1024, pack_bf16(o[j][0], o[j][1]), pack_bf16(o[j][2], o[j][3]), pack_bf16(o[j + 1][0], o[j + 1][1]),
               pack_bf16(o[j + 1][2], o[j + 1][3]));
    else if (2 * u < JN)
        stsm2t(c + out_at(ST) + j * 1024, pack_bf16(o[j][0], o[j][1]), pack_bf16(o[j][2], o[j][3]));
    if (u == (JN - 1) / 2) HAND(ST, w);
}
__device__ __forceinline__ void get_w(uint32_t (&a)[8][4], uint32_t ce, uint32_t co, int ks) {
    if (ks >= 0 && ks < 8)
        asm volatile("ldmatrix.sync.aligned.m8n8.x4.trans.shared.b16 {%0,%1,%2,%3}, [%4];"
                     : "=r"(a[ks & 7][0]), "=r"(a[ks & 7][1]), "=r"(a[ks & 7][2]), "=r"(a[ks & 7][3])
                     : "r"((ks < 4 ? ce : co + SM_ODD) + (ks & 3) * 2048)
                     : "memory");
}
#define TB 8
#define DELAY 2500
#define NULW 0xf0000000
#define DREF 0
#define K0(npr) ((2 * NP - 2 - (npr) % NP) % NP)
#define GCODE(g) ((((g) >> 1) + 1) << 12 | ((g) & 1) << 15)
#define SYNC() asm volatile("bar.sync 0;" ::: "memory")
#define LISTS() asm volatile("bar.sync 4, %0;" ::"n"(NT) : "memory")
#define NB (2 * NGR * 32)
#define PREF(p, tot, k0, n)                                                                                       \
    {                                                                                                             \
        _Pragma("unroll") for (int k = (k0); k < (k0) + (n); k++) {                                                \
            const int l = (k * nbins + bin) * 128 + tid - NB;                                                     \
            if (l < (tot)) asm volatile("prefetch.global.L2 [%0];" ::"l"(p + (size_t)l * 64) : "memory");         \
        }                                                                                                         \
    }
#define WX 010
#define WS 0011
#define WE 000
#define PL 8
#define PLE 0
#define DG(v, i) ((v) >> (6 - 3 * (i)) & 7)
#define PREW(i)                                                                                \
    PREF(x, N * 8, (i > 0 ? DG(WX, 0) : 0) + (i > 1 ? DG(WX, 1) : 0), DG(WX, i))                \
    PREF(sh, E / 16, (i > 0 ? DG(WS, 0) : 0) + (i > 1 ? DG(WS, 1) : 0), DG(WS, i))              \
    PREF(ea, E / 4, (i > 0 ? DG(WE, 0) : 0) + (i > 1 ? DG(WE, 1) : 0), DG(WE, i))
#define PFN (DG(WX, 0) + DG(WX, 1) + DG(WX, 2))
#define PFE (DG(WE, 0) + DG(WE, 1) + DG(WE, 2))
__global__ void __launch_bounds__(NT, 1)
main_kernel(const int* __restrict__ dst, const int* __restrict__ src, uint4* __restrict__ gbin, int E, int nbins, int fast_ok,
            int npb, unsigned npb_magic, int N, const __grid_constant__ CUtensorMap tme,
            const __grid_constant__ CUtensorMap tmx, const __grid_constant__ CUtensorMap tmw,
            const __grid_constant__ CUtensorMap tmo, const __nv_bfloat16* __restrict__ x,
            const __nv_bfloat16* __restrict__ sh, const __nv_bfloat16* __restrict__ ea,
            const __nv_bfloat16* __restrict__ cg, const __nv_bfloat16* __restrict__ wr,
            const __nv_bfloat16* __restrict__ wout, __nv_bfloat16* __restrict__ out, int tau16, int toff, int delay,
            int tau2, int brk) {
    extern __shared__ __align__(1024) unsigned char smem[];
    const uint32_t sb = __shfl_sync(0xffffffffu, s2u(smem), 0);
    const int tid = threadIdx.x;
    const int warp = __shfl_sync(0xffffffffu, tid >> 5, 0), lane = tid & 31;
    const int g = lane >> 2, t = lane & 3;

    TLSTAMP(0);
    TLINIT();
    const int bin = blockIdx.x;
    const int node0 = bin * npb, hpb = npb >> 1;
    uint32_t wa[8];
    uint2 c0 = make_uint2(0, 0), c1 = c0;
    bool fast = fast_ok;
    if (fast_ok) {
        int pd[EPS], ps[EPS];
        const int e0 = (warp * nbins + bin) * 32 + lane;
#pragma unroll
        for (int k = 0; k < EPS; k++)
            asm volatile("ld.global.nc.u32 %0, [%1];" : "=r"(pd[k]) : "l"(dst + min(e0 + k * NT * nbins, E - 1)));
#pragma unroll
        for (int k = 0; k < EPS; k++)
            asm volatile("ld.global.nc.u32 %0, [%1];" : "=r"(ps[k]) : "l"(src + min(e0 + k * NT * nbins, E - 1)));
        const unsigned ck0 = clock();
        const uint32_t cnt0 = (sb + SC_CNT + 8191) & ~8191;
        {
            const uint32_t nul = NULW + ((bin & 3) * 8 + (tid & 7)) * (80 << 15);
#pragma unroll
            for (int k = 0; k < 4; k++) {
                const int i = tid + k * NT;
                if (i < SC_EXT / 16 ? (tid & 7) != 7 : i < SC_TAB / 16) sts_v4(sb + SC_ENT + i * 16, make_uint4(nul, nul, nul, nul));
            }
            if (warp == NW - 1) {
                uint32_t now;
                asm volatile("mov.u32 %0, %%globaltimer_lo;" : "=r"(now));
                now = __shfl_sync(0xffffffffu, (now & 0x7ffff) | nul, 7);
#pragma unroll
                for (int k = 0; k < MAXBINS / 32; k++) sts_v4(sb + SC_ENT + (k * 32 + lane) * 128 + 112, make_uint4(now, now, now, now));
                if (lane == 0) {
                    asm volatile("prefetch.tensormap [%0];" ::"l"(&tme) : "memory");
                    asm volatile("prefetch.tensormap [%0];" ::"l"(&tmx) : "memory");
                    asm volatile("prefetch.tensormap [%0];" ::"l"(&tmw) : "memory");
                    asm volatile("prefetch.tensormap [%0];" ::"l"(&tmo) : "memory");
                    sts_v2(sb + SM_MISC + MI_INT, 0, now);
                    sts_u32(sb + SM_MISC + MI_INT + 44, 0);
                    sts_u32(sb + SM_MISC + MI_INT + 24, 0);
                }
            }
            sts_v4(cnt0 + tid * 16, make_uint4(0, 0, 0, 0));
            if (tid < (SC_END - SC_HIST) / 16) {
                const uint32_t v = (tid >> 3) == MAXBINS / 32 ? 0x80000000u : 0;
                sts_v4(sb + SC_HIST + tid * 16, make_uint4(v, v, v, v));
            }
            if (tid < 2 * HPB) {
                const int w = tid >= hpb, loc = tid - (w ? hpb : 0), gr = min(loc * 43 >> 8, NGR - 1);
                sts_u32(sb + SC_TAB + tid * 4, ((w ? NGR : 0) + gr) * (KEYW << 15) + loc - gr * GSZ);
            }
        }
        TLS(1);
        __syncthreads();
        {
            const uint32_t z = lds_u32(sb + SM_MISC + MI_INT);
            int pb[EPS], pr[EPS];
            uint32_t v[EPS];
#pragma unroll
            for (int k = 0; k < EPS; k++) {
                pb[k] = (int)__umulhi((unsigned)pd[k], npb_magic + z);
                v[k] = lds_u32(sb + SC_TAB + (pd[k] - pb[k] * npb) * 4);
                pr[k] = atoms_add(sb + SC_HIST + (e0 + k * NT * nbins < E ? pb[k] : MAXBINS + lane) * 4, 4);
            }
            int mx = 0;
#pragma unroll
            for (int k = 0; k < EPS; k++) {
                v[k] += ps[k] * (32768 + z) + (k * NT + tid + 32) * 8;
                asm volatile("{\n.reg .pred p;\nsetp.lt.u32 p, %0, 128;\n@p st.shared.u32 [%1], %2;\n}" ::"r"(pr[k]),
                             "r"(sb + SC_ENT + pb[k] * 128 + pr[k]), "r"(v[k])
                             : "memory");
                mx = max(mx, pr[k]);
            }
            if (mx >= 128) {
#pragma unroll
                for (int k = 0; k < EPS; k++)
                    if (pr[k] >= 128 && pr[k] < 192) sts_u32(sb + SC_EXT - 128 + pb[k] * 64 + pr[k], v[k]);
            }
        }
        FENCE_ASYNC();
        TLS(6);
        __syncthreads();
        const unsigned c6 = DREF ? ck0 : clock();
        if (warp == NW - 1 && elect()) {
            tma_store(&tme, sb + SC_ENT, bin * 32, 0);
            asm volatile("cp.async.bulk.commit_group;" ::: "memory");
        }
        if (tid < nbins && lds_u32(sb + SC_HIST + tid * 4) >= 128) {
#pragma unroll 1
            for (int k = 0; k < 4; k++) __stcg(gbin + GEX + (tid * nbins + bin) * 4 + k, lds_v4(sb + SC_EXT + tid * 64 + k * 16));
        }
        if (elect()) {
#pragma unroll
            for (int k = 0; k < (NP > 5 ? 4 : 2); k++) mbar_init(sb + SM_BAR + (warp * (NP > 5 ? 4 : 2) + k) * 8, 3 + (k & 1));
        }
#pragma unroll
        for (int k = 0; k < TS / 2; k++) sts_v4(sb + SM_BT + (tid + k * NT) * 16, make_uint4(0, 0, 0, 0));
        if (tid < 8) sts_v4(sb + SM_BT + (tid + TS / 2 * NT) * 16, make_uint4(0, 0, 0, 0));
        if (tid < 4) {
            sts_u16(sb + SM_SRC + (LNUL + tid) * 2, N);
            sts_u32(sb + SM_EID + (LNUL + tid) * 4, 0x80000000u);
        }
        FENCE_ASYNC();
#pragma unroll
        for (int k = 0; k < EPS; k++) {
            if (ps[k] < (N * PFT >> 10)) {
                const uint32_t p = atoms_add(sb + SM_MISC + MI_INT + 24, 4);
                if (p < PFC * 512) sts_u32(sb + SM_EA + p, min(e0 + k * NT * nbins, E - 1));
            }
        }
        if (warp >= 2 * NGR) {
            uint2 wv[4];
#pragma unroll
            for (int k = 0; k < 4; k++)
                asm volatile("ld.global.nc.v2.u32 {%0,%1}, [%2];" : "=r"(wv[k].x), "=r"(wv[k].y) : "l"((const uint2*)wr + (tid - NB) + k * 128));
#pragma unroll
            for (int k = 0; k < 4; k++) sts_v2(sb + SC_WR + (lane >> 1) * 272 + (warp - 2 * NGR + k * 4) * 16 + (lane & 1) * 8, wv[k].x, wv[k].y);
            PREW(0);
            const int w = warp & 1, j = (warp >> 1) & 1;
            const uint32_t bar0 = sb + SM_BAR + w * NP * 16, ring = sb + w * RING_BYTES + j * 4096;
            uint32_t pz[8], pm[8], pt[2];
            const uint32_t lz = lane & (E >> 31);
            {
                const uint32_t d0 = ring - j * 2048 - bar0 * 512 + lz;
#pragma unroll
                for (int k = 0; k < 8; k++) {
                    pz[k] = __shfl_sync(0xffffffffu, lz, k);
                    pm[k] = __shfl_sync(0xffffffffu, d0 + (k & 1) * SM_ODD + (k >> 1 & 1) * 1024 + (k >> 2) * 4096, 0);
                }
                asm("mov.b64 {%0, %1}, %2;" : "=r"(pt[0]), "=r"(pt[1]) : "l"(&tmx));
                pt[0] = __shfl_sync(0xffffffffu, pt[0] + lz, 0);
                pt[1] = __shfl_sync(0xffffffffu, pt[1] + lz, 0);
            }
            uint32_t sg0 = 0x01010101 | ((lane & 1) << 8 | (lane & 2) << 15 | (lane & 4) << 22) * 0xfe;
            uint32_t sg2 = (0x0101 | ((lane >> 3 & 1) | (lane & 16) << 4) * 0xfe) * 0x10001 ^ 0xfefe0000;
            uint32_t cand = ((lane & 1) << 3 | (lane & 2) << 5 | (lane & 4) << 7 | (lane & 8) << 9) * 7 + (lane & 16) * (15 << 11);
            uint32_t sg1 = __shfl_sync(0xffffffffu, sg0 ^ 0xfefefefe, lane), gb = cnt0 + (warp & 2) * NBK + lane * 8;
            sg0 = __shfl_sync(0xffffffffu, sg0, lane), sg2 = __shfl_sync(0xffffffffu, sg2, lane);
            cand = __shfl_sync(0xffffffffu, cand, lane), gb = __shfl_sync(0xffffffffu, gb, lane);
            const uint32_t wm = __shfl_sync(0xffffffffu, lz - w, lane);
            FENCE_ASYNC();
            asm volatile("bar.sync 8, %0;" ::"n"(NT) : "memory");
            while ((int)(clock() - c6) < delay + PFX) {}
            {
                const uint32_t n = lds_u32(sb + SM_MISC + MI_INT + 24);
#pragma unroll
                for (int k = 0; k < PFC; k++) {
                    const uint32_t i = (tid - NB + k * 128) * 4, e = lds_u32(sb + SM_EA + i);
                    if (i < n) {
                        asm volatile("prefetch.global.L2 [%0];" ::"l"(ea + (size_t)e * 16) : "memory");
                        asm volatile("prefetch.global.L2 [%0];" ::"l"(sh + (size_t)e * 4) : "memory");
                    }
                }
            }
            SYNC();
            PREW(1);
            if (warp == NW - 1 && elect()) {
                asm volatile("cp.async.bulk.global.shared::cta.bulk_group [%0], [%1], %2;" ::"l"(gbin + bin * nbins * 8), "r"(sb + SM_BT),
                             "r"(nbins * 128)
                             : "memory");
                asm volatile("cp.async.bulk.commit_group;" ::: "memory");
                const uint32_t t0 = lds_u32(sb + SM_MISC + MI_INT + 4);
                uint32_t now, ck;
                asm volatile(
                    "{\n.reg .pred p;\n.reg .b32 a, n;\nmov.u32 a, %%globaltimer_lo;\nmov.u32 n, 0;\n"
                    "TK:\nmov.u32 %0, %%globaltimer_lo;\nmov.u32 %1, %%clock;\nadd.u32 n, n, 1;\n"
                    "setp.lt.u32 p, n, " STR(TB) ";\nsetp.eq.and.u32 p, %0, a, p;\n@p bra TK;\n}"
                    : "=r"(now), "=r"(ck));
                sts_u32(sb + SM_MISC + MI_INT + 4, ck - (min((now - t0) & 0x7ffff, 1u << 16) * 63 >> 5) + toff);
            }
            asm volatile("bar.sync 5, %0;" ::"n"(NT) : "memory");
            const uint4 nb = lds_v4(sb + SM_MISC + MI_INT + 32);
            const unsigned tbase = lds_u32(sb + SM_MISC + MI_INT + 4);
            fast = nb.w == 0;
            int df;
            asm("{\n.reg .s32 a;\ndp4a.u32.s32 a, %1, %4, 0;\ndp4a.u32.s32 a, %2, %5, a;\ndp4a.u32.s32 %0, %3, %6, a;\n}"
                : "=r"(df)
                : "r"(nb.x), "r"(nb.y), "r"(nb.z), "r"(sg0), "r"(sg1), "r"(sg2));
            const uint32_t best = __reduce_min_sync(0xffffffffu, abs(df) << (NJ + 1) | (df < 0) << NJ | cand);
            uint32_t swp = best ^ -w;
            uint32_t ga[NGR];
#pragma unroll
            for (int k = 0; k < NGR; k++) {
                const int sh = k < 4 ? 3 * k : 3 * k - 9;
                ga[k] = gb + (((k < 4 ? best : best >> 9) ^ wm) & 1 << sh) * (NGR * NBK * 4 >> sh);
            }
            asm volatile("bar.sync %0, %1;" ::"r"(6 + (ga[0] & ga[1] & ga[2] & ga[3] & ga[4] & ga[5] & lz)), "n"(NT) : "memory");
            TLA(1, 0);
            if (fast) {
                uint32_t v[NGR][2], mx = 0;
#pragma unroll
                for (int k = 0; k < NGR; k++) {
                    const uint2 u = lds_v2(ga[k] + k * (NBK * 4));
                    v[k][0] = u.x, v[k][1] = u.y;
                }
                const uint32_t sq = sb + SM_SEQ + w * SEQCAP * 2;
                const int all = __dp4a(nb.x, 0x01010101u, __dp4a(nb.y, 0x01010101u, __dp4a(nb.z, 0x01010101u, 0u))), d = best >> (NJ + 1);
                const int nst = (all + ((swp >> NJ) & 1 ? -d : d)) >> 1;
                const int npr = __shfl_sync(0xffffffffu, (nst + 3) >> 2, 0), k0 = K0(npr);
                const unsigned taug = __float2uint_rz(__fdividef((float)(N * tau16 >> 4), (float)max(npr, 1)));
                const uint32_t lim = tbase + (N * tau16 >> 8) + lane * taug;
                uint32_t a = -(__popc(swp & 0111111) * (NGR * GCAP + GEXT) + NGR * (NGR - 1) / 2 * GCAP + NGR * 4) + 2 * sq;
#pragma unroll
                for (int k = 0; k < NGR; k++) a += v[k][0] & 0xffc;
                a >>= 1;
                const uint32_t a0 = a;
#pragma unroll
                for (int c = 0; c < 2; c++)
#pragma unroll
                    for (int k = 0; k < NGR; k++) {
                        asm volatile(
                            "{\n.reg .pred p, q;\n.reg .b16 h;\n"
                            "setp.ge.u32 p, %1, 0x10000;\nsetp.ge.u32 q, %1, 0x40000;\n"
                            "cvt.u16.u32 h, %1;\n@p st.shared.u16 [%0], h;\n"
                            "add.u16 h, h, 4;\n@q st.shared.u16 [%0+2], h;\n}" ::"r"(a), "r"(v[k][c])
                            : "memory");
                        a += v[k][c] >> 16;
                        mx = max(mx, v[k][c]);
                    }
                if (mx >= 0x60000) {
                    a = a0;
#pragma unroll
                    for (int c = 0; c < 2; c++)
#pragma unroll
                        for (int k = 0; k < NGR; k++) {
#pragma unroll 1
                            for (uint32_t n = 4; n < v[k][c] >> 16; n += 2) sts_u16(a + n, v[k][c] + 2 * n);
                            a += v[k][c] >> 16;
                        }
                }
                if (!j) {
                    sts_u16(sq + (nst + lane) * 2, (LNUL + 4) | (lane < (-nst & 3) ? GCODE(0) : 0x7c01));
                    if (lane < k0) {
                        mbar_arrive_cnt(sb + SM_BAR + (w * NP + lane) * 16, 3);
                        mbar_arrive_cnt(sb + SM_BAR + (w * NP + lane) * 16 + 8, 4);
                    }
                    if (lane == 0) {
                        sts_v2(sb + SM_MISC + MI_INT + 8 + w * 8, npr, k0);
                        sts_u32(sb + SM_MISC + MI_INT + 48 + w * 4, swp);
                    }
                }
                TLA(10, 0);
                asm volatile("cp.async.bulk.wait_group.read 0;" ::: "memory");
                asm volatile("bar.arrive 3, %0;" ::"n"(NT) : "memory");
                PREW(2);
                TLS(5);
                asm volatile("setmaxnreg.dec.sync.aligned.u32 %0;" ::"n"(PREG));
                produce(pt, pz, pm, bar0, sq + j * 2 + lane * 8, npr, sb + SM_SRC - 8, tbase, lim, taug * 32, tau16, k0 + lane, k0 + 32, tau2, brk
                );
        if (elect()) {
            const uint32_t d = ring + (NP - 2) * 8192 + j * (SM_ODD - 4096);
            const uint32_t fb = bar0 + (NP - 2) * 16, par = ~((lds_u32(sb + SM_MISC + MI_INT + 8 + w * 8) + 1) / NP) & 1;
            mbar_wait(fb + 24, par);
            mbar_arrive_cnt(fb + j * 16, j ? 1 : 3);
            mbar_expect_tx(fb + 16, 8192);
            tma_2d(d, &tmw, fb + 16, 0, j * 64);
            if (j) mbar_arrive(bar0 + DUMB);
            mbar_expect_tx(bar0 + DUMB, 8192);
            tma_2d(d + 8192, &tmw, bar0 + DUMB, 64, j * 64);
        }
        TLMAX(12);
        swp = lds_u32(sb + SM_MISC + MI_INT + 48 + w * 4);
        const int row = 2 * lane < hpb ? (node0 + ((swp >> lane) & 1) * hpb) * 4 + lane * 8 : N * 4;
        const CUtensorMap* po = &tmo;
        asm volatile("" : "+l"(po));
#pragma unroll
        for (int st = 0; st < 5; st++) {
            int rw[5];
#pragma unroll
            for (int k = 0; k < 5; k++)
                if (2 * k < out_n(st)) rw[k] = __shfl_sync(0xffffffffu, row, out_j(st) + 2 * k + (2 * k + 1 < out_n(st) ? j : j * (31 - out_j(st) - 2 * k)));
            asm volatile("bar.sync %0, 192;" ::"r"(6 + 2 * st + w) : "memory");
            FENCE_ASYNC();
            if (elect()) {
#pragma unroll
                for (int k = 0; k < 5; k++)
                    if (2 * k < out_n(st)) tma_store(po, ring - j * 3072 + out_at(st) + k * 2048, st < 3 ? 0 : 64, rw[k]);
                asm volatile("cp.async.bulk.commit_group;" ::: "memory");
            }
        }
        asm volatile("cp.async.bulk.wait_group.read 0;" ::: "memory");
        TLMAX(4);
        TLEND();
        return;
            }
        } else {
        asm volatile("bar.arrive 8, %0;" ::"n"(NT) : "memory");
        uint32_t en[5][4], es[5][4], rank[5][4], ca[5][4];
        if (warp >= 8 && (g >> 2) == (t >> 1)) {
            const uint2* cp = (const uint2*)cg + (g & 3) * 4 + (t & 1) * 2;
            asm volatile("ld.global.nc.v2.u32 {%0,%1}, [%2];" : "=r"(c0.x), "=r"(c0.y) : "l"(cp));
            asm volatile("ld.global.nc.v2.u32 {%0,%1}, [%2];" : "=r"(c1.x), "=r"(c1.y) : "l"(cp + 1));
        }
        const int sg[5] = {tid >> 3, (tid >> 3) + NB / 8, (tid >> 3) + NB / 4, (tid >> 3) + (lane & 4) * (NB / 32), (tid >> 3) + NB / 4};
        const uint4* gp[5];
        gp[0] = gbin + bin * nbins * 8 + tid;
        gp[1] = gp[0] + NB;
        gp[2] = gp[0] + 2 * NB;
        gp[3] = gbin + GEX + (bin * nbins + sg[3]) * 4 + (lane & 3);
        gp[4] = gbin + GEX + (bin * nbins + sg[4]) * 4 + (lane & 3);
        unsigned pend = (sg[0] < nbins) | (sg[1] < nbins) << 1 | (sg[2] < nbins) << 2;
#pragma unroll
        for (int k = 0; k < 5; k++) en[k][0] = en[k][1] = en[k][2] = en[k][3] = NULW + lane * (80 << 15);
        auto fetch = [&](int k) {
            asm volatile("{\n.reg .pred p;\nsetp.ne.u32 p, %5, 0;\n@p ld.relaxed.gpu.global.v4.u32 {%0,%1,%2,%3}, [%4];\n}"
                         : "+r"(en[k][0]), "+r"(en[k][1]), "+r"(en[k][2]), "+r"(en[k][3])
                         : "l"(gp[k]), "r"(pend & (1u << k))
                         : "memory");
        };
        int spin = 0;
        auto poll = [&](int k0, int k1) {
            for (;;) {
#pragma unroll
                for (int k = k0; k < k1; k++)
                    if (min(min(en[k][0], en[k][1]), min(en[k][2], en[k][3]))) pend &= ~(1u << k);
                if (!__any_sync(0xffffffffu, pend)) break;
#pragma unroll
                for (int k = k0; k < k1; k++) fetch(k);
                if (++spin > 10000000) __trap();
            }
        };
        auto count = [&](int k) {
#pragma unroll
            for (int c = 0; c < 4; c++) {
                const uint32_t v = en[k][c];
                ca[k][c] = (__umulhi(v, 6554) & 0x1ffc) | cnt0;
                rank[k][c] = atoms_add(ca[k][c], 1);
                asm volatile("{\n.reg .b32 a, b;\nprmt.b32 a, %1, %2, 0x6540;\nand.b32 b, %1, 0x7f00;\nmad.lo.u32 %0, b, %3, a;\n}"
                             : "=r"(es[k][c])
                             : "r"(v), "r"(sg[k] - nbins), "r"(nbins));
            }
        };
        while ((int)(clock() - c6) < delay) {}
        TLS(7);
        fetch(0);
        fetch(1);
        fetch(2);
        poll(0, 3);
        TLS(2);
        const bool more = __any_sync(0xffffffffu, (lane & 7) == 7 && min(min(en[0][3], en[1][3]), en[2][3]) < NULW);
        const bool rest = NB / 4 + warp * 4 < nbins;
        if (more) {
            const uint32_t l0 = __shfl_sync(0xffffffffu, en[0][3], lane | 7), l1 = __shfl_sync(0xffffffffu, en[1][3], lane | 7);
            const uint32_t l2 = __shfl_sync(0xffffffffu, en[2][3], lane | 7);
            pend = ((lane & 4 ? l1 : l0) < NULW) << 3 | (!(lane & 4) && l2 < NULW) << 4;
            fetch(3);
            fetch(4);
        }
        if (tid == 7 && en[0][3] >= NULW) sts_u32(sb + SM_MISC + MI_INT + 4, en[0][3]);
        count(0);
        count(1);
        if (rest) count(2);
        if (more) {
            const unsigned ext = pend;
            poll(3, 5);
#pragma unroll
            for (int k = 3; k < 5; k++) {
                if ((ext >> k) & 1) {
                    __stcg((uint4*)gp[k], make_uint4(0, 0, 0, 0));
                    if ((lane & 3) == 3 && en[k][3] < NULW) sts_u32(sb + SM_MISC + MI_INT + 44, 1);
                }
            }
            count(3);
            count(4);
        }
        TLS(9);
        SYNC();
        {
            const int w0 = warp >= NGR, gr = warp - w0 * NGR;
            const uint32_t cp = cnt0 + (warp * NBK + lane * (NBK / 32)) * 4;
            uint32_t r[5];
            const uint4 cv = lds_v4(cp);
            r[0] = 0, r[1] = cv.x, r[2] = cv.x + cv.y, r[3] = r[2] + cv.z, r[4] = r[3] + cv.w;
            const uint32_t tot = __reduce_add_sync(0xffffffffu, r[NBK / 32]);
            const uint32_t base = warp * GCAP + w0 * GEXT;
            const bool full = tot > GCAP + (gr == NGR - 1 ? GEXT : 0);
            asm volatile("st.shared.u8 [%0], %1;" ::"r"(sb + SM_MISC + MI_INT + 32 + (full ? 12 : (gr < 4 ? w0 * 4 : 4 + w0 * 2) + gr)), "r"(full ? 1 : (tot + 3) >> 2) : "memory");
            asm volatile("bar.arrive 5, %0;" ::"n"(NT) : "memory");
            const uint32_t off = warp_incl_scan(r[NBK / 32], lane, lds_u32(sb + SM_MISC + MI_INT)) - r[NBK / 32] + base + 7 - CE + GCODE(gr);
            if (lane == 31) r[NBK / 32] += CE;
#pragma unroll
            for (int c = 0; c <= NBK / 32; c++) r[c] += off;
#pragma unroll
            for (int c = 0; c < NBK / 32; c++) r[c] += ((r[c + 1] & ~3) - (r[c] & ~3)) << 15;
            sts_v4(cp, make_uint4(r[0], r[1], r[2], r[3]));
            asm volatile("{\n.reg .pred p;\n.reg .b16 h;\nsetp.lt.u32 p, %0, %1;\ncvt.u16.u32 h, %3;\n@p st.shared.u16 [%2], h;\n@p st.shared.u32 [%4], 0x80000000;\n}" ::"r"(lane),
                         "r"(full ? 0 : -tot & 3), "r"(sb + SM_SRC + (base + tot + lane) * 2), "r"(N + warp * KEYW), "r"(sb + SM_EID + (base + tot + lane) * 4)
                         : "memory");
        }
        TLS(10);
        asm volatile("bar.arrive 6, %0;" ::"n"(NT) : "memory");
#pragma unroll
        for (int h = 0; h < 2; h++)
            asm volatile("ldmatrix.sync.aligned.m8n8.x4.trans.shared.b16 {%0,%1,%2,%3}, [%4];"
                         : "=r"(wa[h * 4]), "=r"(wa[h * 4 + 1]), "=r"(wa[h * 4 + 2]), "=r"(wa[h * 4 + 3])
                         : "r"(sb + SC_WR + (h * 8 + (warp & 3) * 2 + ((lane >> 3) & 1)) * 272 + (lane >> 4) * 128 + (lane & 7) * 16));
        asm volatile("bar.sync 7, %0;" ::"n"(NB) : "memory");
        auto place0 = [&](int k) {
#pragma unroll
            for (int c = 0; c < 4; c++)
                asm volatile("{\n.reg .pred p;\nsetp.lt.u32 p, %1, " STR(NULW) ";\n@p ld.shared.u16 %0, [%0];\n}" : "+r"(ca[k][c]) : "r"(en[k][c]));
#pragma unroll
            for (int c = 0; c < 4; c++) ca[k][c] = (ca[k][c] & 0xfff) + rank[k][c];
        };
        auto place1 = [&](int k) {
#pragma unroll
            for (int c = 0; c < 4; c++)
                asm volatile(
                    "{\n.reg .pred p;\n.reg .b32 t;\n.reg .b16 h;\n"
                    "setp.lt.u32 p, %0, " STR(NULW) ";\n"
                    "shr.u32 t, %0, 15;\ncvt.u16.u32 h, t;\n"
                    "@p st.shared.u16 [%1], h;\n}" ::"r"(en[k][c]),
                    "r"(sb + SM_SRC - (7 - CE) * 2 + ca[k][c] * 2)
                    : "memory");
        };
        auto place2 = [&](int k) {
#pragma unroll
            for (int c = 0; c < 4; c++)
                asm volatile("{\n.reg .pred p;\nsetp.lt.u32 p, %0, " STR(NULW) ";\n@p st.shared.u32 [%1], %2;\n}" ::"r"(en[k][c]),
                             "r"(sb + SM_EID - (7 - CE) * 4 + ca[k][c] * 4), "r"(es[k][c])
                             : "memory");
        };
        auto all = [&](auto f) {
            f(0);
            f(1);
            if (rest) f(2);
            if (more) f(3), f(4);
        };
        fast = lds_u32(sb + SM_MISC + MI_INT + 44) == 0;
        if (fast) {
            all([&](int k) { place0(k), place2(k), place1(k); });
            TLS(14);
            TLA(14, 0);
            if (warp < 8) asm volatile("bar.arrive 3, %0;" ::"n"(NT) : "memory");
            FENCE_ASYNC();
        }
        }
    }

    if (fast && (warp >> 2) == 2) {
        asm volatile("bar.arrive 4, %0;" ::"n"(NT) : "memory");
        asm volatile("setmaxnreg.dec.sync.aligned.u32 %0;" ::"n"(HREG));
        const int w = warp & 1, j = (warp >> 1) & 1;
        const uint32_t bar0 = sb + SM_BAR + w * NP * 16;
        const int blk = (lane >> 4) * 2 + (t >> 1);
        uint32_t fseq = sb + SM_SEQ + w * SEQCAP * 2 + j * 8 + blk * 2;
        const uint32_t feid = sb + SM_EID - 16 + (g & 3) * 4;
        uint32_t pea = sb + SM_EA + w * 4096 + j * 512 + (lane ^ ((lane >> 3) & 1)) * 16;
        const uint32_t psd = sb + SM_SIDE + (warp - 8) * 512 + (lane >> 1) * 16 + (lane & 1) * 4;
        const uint32_t pt = sb + SM_BT + w * (TS * 256) + j * 512 + blk * BT_B + ((lane ^ (lane >> 3)) & 1) * BT_K + (g & 3) * 4;
        const char* gea = (const char*)ea + (lane & 1) * 16;
        uint32_t es, va[2], ta[2], old[2] = {pt, pt}, dea = 2048;
        auto ids = [&]() {
            es = lds_u32(feid + (lds_u16(fseq) & 0xffc) * 4);
            fseq += 16;
        };
        uint32_t wf[4];
        wf[0] = __byte_perm(c0.x, c1.x, 0x5410), wf[1] = __byte_perm(c0.x, c1.x, 0x7632);
        wf[2] = __byte_perm(c0.y, c1.y, 0x5410), wf[3] = __byte_perm(c0.y, c1.y, 0x7632);
        int pfl = lane < PL ? PFN * nbins * 128 + (bin * 4 + warp - 8) * PL + lane - N * 8 : 0;
        int pfs = nbins * (4 * PL);
        const char* pfb = (const char*)(x + (size_t)N * 512);
        auto run = [&](auto odd) {
            auto fetch = [&](int i) {
                asm volatile(
                    "{\n.reg .pred p, q;\n.reg .b32 e;\n.reg .b64 a;\n"
                    "setp.lt.s32 p, %0, 0;\n"
                    "and.b32 e, %0, 0x7ffffff8;\n"
                    "mad.wide.u32 a, e, 4, %1;\n"
                    "cp.async.cg.shared.global [%2], [a], 16, p;\n"
                    "}" ::"r"(es), "l"(gea), "r"(pea + i * 1024) : "memory");
                va[i] = psd + (es & 8);
                ta[i] = pt + (es & 7) * 64;
                if (odd.value) {
                    cp_async4(va[i] + i * 256, (const char*)sh + (es & 0x7ffffff8) + (lane & 1) * 4, (int)es >= 0 ? 4 : 0);
                } else {
                    asm volatile(
                        "{\n.reg .pred p;\n.reg .b32 e;\n.reg .b64 a;\n"
                        "setp.lt.s32 p, %0, 0;\n"
                        "and.b32 e, %0, 0x7ffffff0;\n"
                        "mad.wide.u32 a, e, 1, %1;\n"
                        "cp.async.cg.shared.global [%2], [a], 16, p;\n"
                        "}" ::"r"(es), "l"(sh), "r"((psd & ~15) + i * 256) : "memory");
                }
                asm volatile("cp.async.commit_group;" ::: "memory");
                if (i) pea += dea, dea = -dea;
            };
            asm volatile("bar.sync 3, %0;" ::"n"(NT) : "memory");
            TLA(7, 0);
            const uint2 nk = lds_v2(sb + SM_MISC + MI_INT + 8 + w * 8);
            ids();
            fetch(0);
            ids();
            fetch(1);
            const int npr = __shfl_sync(0xffffffffu, nk.x, 0), kj = __shfl_sync(0xffffffffu, nk.y, 0) + j;
        uint32_t vf = bar0 + (kj < NP ? kj : 0) * 16;
        uint32_t pe = kj < NP;
#pragma unroll 1
            for (int m = (npr + 1 - j) >> 1; m > 0;) {
#pragma unroll
                for (int i = 0; i < 2; i++) {
                    asm volatile("cp.async.wait_group 1;" ::: "memory");
                    __syncwarp();
                    const uint32_t v = lds_u32(va[i] + i * 256);
                    ids();
                    float d0[4], d1[4];
                    mma_diag(d0, v, wf[0], wf[1]);
                    mma_diag(d1, v, wf[2], wf[3]);
                    uint32_t vn = vf + 32;
                    if (vn >= bar0 + NP * 16) vn -= NP * 16, pe ^= 1;
                    TWAIT(vn + 8, pe);
#pragma unroll
                    for (int k = 0; k < 4; k++) sts_u32(old[i] + i * 1024 + k * 16, 0);
                    old[i] = ta[i];
                    sts_u32(old[i] + i * 1024, pack_bf16(d0[0], d0[1]));
                    sts_u32(old[i] + i * 1024 + 16, pack_bf16(d0[2], d0[3]));
                    sts_u32(old[i] + i * 1024 + 32, pack_bf16(d1[0], d1[1]));
                    sts_u32(old[i] + i * 1024 + 48, pack_bf16(d1[2], d1[3]));
                    FENCE_ASYNC();
                    fetch(i);
                    __syncwarp();
                    if (lane == 0) mbar_arrive(vf);
                    asm volatile("{\n.reg .pred p;\n.reg .b64 a;\nsetp.lt.s32 p, %0, 0;\nmad.wide.s32 a, %0, 128, %1;\n@p prefetch.global.L2 [a];\n}" ::"r"(pfl),
                                 "l"(pfb));
                    pfl += pfs;
                    vf = vn;
                    if (--m <= 0) break;
                }
            }
        };
        if (E & 1) run(std::true_type()); else run(std::false_type());
        asm volatile("cp.async.wait_group 0;" ::: "memory");
        TLMAX(13);
    } else if (fast) {
        const int w = warp >> 2, wq = warp & 3;
        LISTS();
        asm volatile("setmaxnreg.inc.sync.aligned.u32 %0;" ::"n"(CREG));
        const int k0 = __shfl_sync(0xffffffffu, lds_u32(sb + SM_MISC + MI_INT + 12 + w * 8), 0);
        const uint32_t ring = sb + w * RING_BYTES, bar0 = sb + SM_BAR + w * NP * 16;
        float acc[2][NJ][4];
        uint32_t a0[8][4], a1[8][4];
        {
            const int e = (lane >> 1) & 3, m = lane >> 3;
            const int line = 2 * ((lane & 1) + 2 * ((m >> 1) ^ (e >> 1))), ch = 2 * wq + (m & 1);
            const uint32_t xb = ring + (e & 1 ? SM_ODD : SM_EVEN) + (e >> 1) * 1024 + line * 128;
            consume(acc, a0, ring, xb + ((ch ^ ((line + (e & 1)) & 7)) * 16), xb + 128 + ((ch ^ ((line + 1 + (e & 1)) & 7)) * 16),
                    k0 * 8192, bar0, (((sb + SM_EA + w * 4096) & 0x3ffff) >> 4) | (1 << 16),
                    (((sb + SM_BT + w * (TS * 256)) & 0x3ffff) >> 4) | (BT_K / 16 << 16), sb + SM_SEQ + w * SEQCAP * 2, lane & (E >> 31),
                    wa);
        }
        const uint32_t tb = ring + wq * (NJ * 256) + lane * 16, db = (ring >> 4) + (8 << 16);
        const uint32_t cr = ring + (lane & 7) * 128 + (lane >> 4) * 1024, cc = 2 * wq + ((lane >> 3) & 1);
        const uint32_t ce = cr + (cc ^ (lane & 7)) * 16, co = cr + (cc ^ ((lane + 1) & 7)) * 16;
        float o0[CH0][4], o1[CH1][4], o2[CH2][4], o3[CH3][4], o4[CH4][4];
        TLMAX(11);
#pragma unroll
        for (int u = 0; u <= CH0; u++) put_agg<0, CH0>(acc, tb, u);
        TLE(1);
        FENCE_ASYNC();
        WG_SYNC(w);
        TLE(6);
        mul_out<0>(o0, a0, db, [&](int u) { put_agg<CH0, CH1>(acc, tb, u); });
        const bool ok1 = mbar_test(bar0 + DUMB, 0);
        FENCE_ASYNC();
        WG_SYNC(w);
        TLE(7);
        mul_out<KA>(o1, a0, db + CH0 * 16, [&](int u) {
            if (u == 0) {
                TLE(2);
#pragma unroll
                for (int k = 0; 2 * k < CH0; k++) put_out<0>(o0, ce, k, w);
                TLMAX(3);
            } else {
                put_agg<CH0 + CH1, CH2>(acc, tb, 2 * u - 2);
                put_agg<CH0 + CH1, CH2>(acc, tb, 2 * u - 1);
            }
        });
        FENCE_ASYNC();
        if (!ok1) mbar_wait(bar0 + DUMB, 0);
        WG_SYNC(w);
        TLE(9);
        mul_out<KA>(o2, a0, db + (CH0 + CH1) * 16, [&](int u) {
            put_out<1>(o1, co, 2 * u, w);
            put_out<1>(o1, co, 2 * u + 1, w);
            if (u == 1) TLE(5);
            get_w(a1, ce + (NP - 1) * 8192, co + (NP - 1) * 8192, 2 * u - 4);
            get_w(a1, ce + (NP - 1) * 8192, co + (NP - 1) * 8192, 2 * u - 3);
        });
        mul_out<KA>(o3, a1, db, [&](int u) {
            if (u == 0) TLE(10);
            put_out<2>(o2, ce, u, w);
            if (u == 8 - KA) WG_SYNC(w);
        });
        mul_out<KA>(o4, a1, db + CH3 * 16, [&](int u) { put_out<3>(o3, co, u, w); });
        TLE(14);
        WG_WAIT(0);
#pragma unroll
        for (int u = 0; 2 * u < CH4; u++) put_out<4>(o4, ce, u, w);
        TLMAX(15);
    } else {
        float* accs = (float*)smem;
        constexpr int NACC = SM_EID / 2048;
        const int nnodes = max(0, min(npb, N - node0));
#pragma unroll 1
        for (int nb = 0; nb < nnodes; nb += NACC) {
            __syncthreads();
            for (int i = tid; i < NACC * 512; i += NT) accs[i] = 0.f;
            __syncthreads();
#pragma unroll 1
            for (int base = warp * 32; base < E; base += NT) {
                const int e = base + lane;
                int dl = e < E ? dst[e] - node0 - nb : -1;
                if (dl + nb >= nnodes) dl = -1;
                unsigned mask = __ballot_sync(0xffffffffu, dl >= 0 && dl < NACC);
#pragma unroll 1
                while (mask) {
                    const int l = __ffs(mask) - 1;
                    mask &= mask - 1;
                    const int ee = __shfl_sync(0xffffffffu, e, l);
                    const int dd = __shfl_sync(0xffffffffu, dl, l);
                    slow_edge(ee, src[ee], accs + dd * 512, x, sh, ea, cg, wr, lane);
                }
            }
            __syncthreads();
#pragma unroll 1
            for (int nl = warp; nl < NACC && nb + nl < nnodes; nl += NW)
                slow_out(accs + nl * 512, wout, out + (size_t)(node0 + nb + nl) * 512, lane);
        }
        __syncthreads();
    }

    TLMAX(4);
    TLEND();
}

typedef CUresult (*EncodeTiledFn)(CUtensorMap*, CUtensorMapDataType, cuuint32_t, void*, const cuuint64_t*,
                                  const cuuint64_t*, const cuuint32_t*, const cuuint32_t*, CUtensorMapInterleave,
                                  CUtensorMapSwizzle, CUtensorMapL2promotion, CUtensorMapFloatOOBfill);

extern "C" void kernel_launch(void* const* d_in, const int* in_sizes, int n_in, void* d_out, int out_size) {
    const __nv_bfloat16* x = (const __nv_bfloat16*)d_in[0];
    const int* src = (const int*)d_in[1];
    const int* dst = (const int*)d_in[2];
    const __nv_bfloat16* sh = (const __nv_bfloat16*)d_in[3];
    const __nv_bfloat16* ea = (const __nv_bfloat16*)d_in[4];
    const __nv_bfloat16* cg = (const __nv_bfloat16*)d_in[5];
    const __nv_bfloat16* wr = (const __nv_bfloat16*)d_in[6];
    const __nv_bfloat16* wout = (const __nv_bfloat16*)d_in[7];
    __nv_bfloat16* out = (__nv_bfloat16*)d_out;
    const int N = in_sizes[0] / 512;
    const int E = in_sizes[1];

    static int num_sms = 0;
    static EncodeTiledFn encode = nullptr;
    static uint4* gbin = nullptr;
    if (num_sms == 0) {
        int dev = 0;
        cudaGetDevice(&dev);
        cudaDeviceGetAttribute(&num_sms, cudaDevAttrMultiProcessorCount, dev);
        cudaFuncSetAttribute(main_kernel, cudaFuncAttributeMaxDynamicSharedMemorySize, SM_TOTAL + TLX);
        cudaGetSymbolAddress((void**)&gbin, g_bin);
        void* fn = nullptr;
        cudaDriverEntryPointQueryResult qr;
        cudaGetDriverEntryPoint("cuTensorMapEncodeTiled", &fn, cudaEnableDefault, &qr);
        encode = (EncodeTiledFn)fn;
    }
    const int nbins = num_sms < NB * 3 / 8 ? num_sms : NB * 3 / 8;
    int npb = ((N + nbins - 1) / nbins + 3) & ~3;
    if (npb < 32) npb = 32;
    const int fast_ok = E > 0 && npb <= 2 * HPB && N <= (NBK - 1) * 80 - 8 && E <= EPS * NT * nbins;
    auto map2d = [&](CUtensorMap* tm, const void* p, int d0, int d1, int b1) {
        const cuuint64_t gd[2] = {(cuuint64_t)d0, (cuuint64_t)d1};
        const cuuint64_t gs[1] = {(cuuint64_t)d0 * 2};
        const cuuint32_t bx[2] = {64, (cuuint32_t)b1};
        const cuuint32_t es[2] = {1, 1};
        encode(tm, CU_TENSOR_MAP_DATA_TYPE_BFLOAT16, 2, (void*)p, gd, gs, bx, es, CU_TENSOR_MAP_INTERLEAVE_NONE,
               CU_TENSOR_MAP_SWIZZLE_128B, CU_TENSOR_MAP_L2_PROMOTION_NONE, CU_TENSOR_MAP_FLOAT_OOB_FILL_NONE);
    };
    CUtensorMap tme, tmx, tmw, tmo;
    {
        const cuuint64_t gd[2] = {(cuuint64_t)nbins * 32, (cuuint64_t)nbins};
        const cuuint64_t gs[1] = {(cuuint64_t)nbins * 128};
        const cuuint32_t bx[2] = {32, (cuuint32_t)nbins};
        const cuuint32_t es[2] = {1, 1};
        encode(&tme, CU_TENSOR_MAP_DATA_TYPE_UINT32, 2, (void*)gbin, gd, gs, bx, es, CU_TENSOR_MAP_INTERLEAVE_NONE,
               CU_TENSOR_MAP_SWIZZLE_NONE, CU_TENSOR_MAP_L2_PROMOTION_NONE, CU_TENSOR_MAP_FLOAT_OOB_FILL_NONE);
    }
    {
        const cuuint64_t gd[2] = {(cuuint64_t)N * 256 - 224, 8};
        const cuuint64_t gs[1] = {128};
        const cuuint32_t bx[2] = {32, 8};
        const cuuint32_t es[2] = {1, 1};
        encode(&tmx, CU_TENSOR_MAP_DATA_TYPE_UINT32, 2, (void*)x, gd, gs, bx, es, CU_TENSOR_MAP_INTERLEAVE_NONE,
               CU_TENSOR_MAP_SWIZZLE_128B, CU_TENSOR_MAP_L2_PROMOTION_NONE, CU_TENSOR_MAP_FLOAT_OOB_FILL_NONE);
    }
    map2d(&tmw, wout, 128, 128, 64);
    map2d(&tmo, out, 128, N * 4, 8);
    const unsigned npb_magic = (unsigned)((0x100000000ull + npb - 1) / npb);
    const int chunk = (E + nbins - 1) / nbins;
    int tau16 = (int)fmin((double)PACE * 16.0 * chunk / N, 100000.0), toff = TOFF, delay = DELAY;
    int tau2 = tau16 * PACE2 / 100, brk = BRK;
    brk = (tau16 - tau2) * (N * brk / 50);
    main_kernel<<<nbins, NT, SM_TOTAL + TLX, cudaStreamPerThread>>>(dst, src, gbin, E, nbins, fast_ok, npb, npb_magic, N, tme, tmx, tmw,
                                                              tmo, x, sh, ea, cg, wr, wout, out, tau16, toff, delay, tau2, brk);
}
```

```cpp
#include <cuda_runtime.h>
#include <cuda.h>
#include <cuda_bf16.h>
#include <stdint.h>
#include <stdlib.h>
#include <type_traits>

#define MAXBINS 160
#define NW 16
#define NT (NW * 32)
#define HPB 38
#define GCAP 280
#define GEXT 72
#define NGR 6
#define LNUL (2 * (NGR * GCAP + GEXT))
#define NBK 128
#define KEYW 10240
#define CE 2
#define GSZ 6
#define NS 10
#define RING_BYTES 40960
static_assert(RING_BYTES == NS * 4096, "ring");
#define NP (NS / 2)
#define CREG 224
#define PREG 24
#define HREG 40
#define TS 8
#define SM_EVEN 0
#define SM_MISC (2 * RING_BYTES)
#define SM_ODD (SM_MISC + 128)
#define SM_EA (SM_BT + TS * 4096 + 128)
#define SM_BT (SM_ODD + 2 * RING_BYTES)
#define BT_B (TS * 512 + 16)
#define BT_K (4 * BT_B)
#define SM_SIDE (SM_EA + 8192)
#define SM_EID (SM_SIDE + 2048)
#define SM_SRC (SM_EID + (LNUL + 4) * 4)
#define SEQCAP ((LNUL / 8 + 32 + 7) / 8 * 8)
#define SM_SEQ (SM_SRC + (LNUL + 8) * 2)
#define SM_BAR ((SM_SEQ + 2 * SEQCAP * 2 + 63) / 64 * 64)
#define SM_TOTAL (SM_BAR + NW * (NP > 5 ? 32 : 16))
#define DUMB (2 * NP * 16)
#define MI_INT 0
#define EPS 5
#define SC_ENT 0
#define SC_EXT (SC_ENT + MAXBINS * 128)
#define SC_TAB (SC_EXT + MAXBINS * 64)
#define SC_HIST (SC_TAB + 320)
#define SC_END (SC_HIST + MAXBINS * 4 + 128)
#define SC_WR SC_END
#define SC_CNT (SC_WR + 4352)
static_assert(SC_END % 16 == 0 && SC_HIST % 16 == 0 && SC_END - SC_HIST <= NT * 16 && SC_CNT + 16384 <= SM_MISC && SC_TAB <= 4 * NT * 16 && 2 * HPB <= 80 && MAXBINS >= 24 * NGR, "scratch");
static_assert(LNUL >= 3072 && LNUL + 8 <= 4096 && GCAP % 4 == 0 && GEXT % 4 == 0, "lists");
static_assert(SM_TOTAL <= 232448 && SM_BAR % 16 == 0 && SM_SEQ % 16 == 0 && SM_SRC % 16 == 0 && SM_EA % 256 == 0, "smem");
#define PACE 18.6
#define PACE2 96
#define BRK 85
#define TOFF 7900
#define PSLEEP 20

#define GEX (MAXBINS * MAXBINS * 8)
__device__ __align__(128) uint4 g_bin[GEX + GEX / 2];
#define STR2(x) #x
#define STR(x) STR2(x)
#define TLINIT()
#define TLEND()
#define TLX 0
#define TLSTAMP(i)
#define TLMAX(i)

#define TLA(i, d)
#define TLS(i) TLMAX(i)
#define TLE(i)
__device__ __forceinline__ uint32_t pack_bf16(float lo, float hi) {
    uint32_t r;
    asm("cvt.rn.bf16x2.f32 %0, %1, %2;" : "=r"(r) : "f"(hi), "f"(lo));
    return r;
}
__device__ __forceinline__ void mma1688_z(float (&d)[4], uint32_t a0, uint32_t a1, uint32_t b0) {
    asm("mma.sync.aligned.m16n8k8.row.col.f32.bf16.bf16.f32 {%0,%1,%2,%3}, {%4,%5}, {%6}, {%7,%7,%7,%7};"
        : "=f"(d[0]), "=f"(d[1]), "=f"(d[2]), "=f"(d[3])
        : "r"(a0), "r"(a1), "r"(b0), "f"(0.f));
}
__device__ __forceinline__ void mma_diag(float (&d)[4], uint32_t a, uint32_t b0, uint32_t b1) {
    asm("mma.sync.aligned.m16n8k16.row.col.f32.bf16.bf16.f32 {%0,%1,%2,%3}, {%4,%8,%8,%4}, {%5,%6}, {%7,%7,%7,%7};"
        : "=f"(d[0]), "=f"(d[1]), "=f"(d[2]), "=f"(d[3])
        : "r"(a), "r"(b0), "r"(b1), "f"(0.f), "r"(0));
}
__device__ __forceinline__ uint32_t s2u(const void* p) { return (uint32_t)__cvta_generic_to_shared(p); }
__device__ __forceinline__ void mbar_init(uint32_t a, int c) {
    asm volatile("mbarrier.init.shared.b64 [%0], %1;" ::"r"(a), "r"(c));
}
__device__ __forceinline__ void mbar_expect_tx(uint32_t a, int bytes) {
    asm volatile("mbarrier.arrive.expect_tx.shared.b64 _, [%0], %1;" ::"r"(a), "r"(bytes) : "memory");
}
__device__ __forceinline__ void mbar_arrive(uint32_t a) {
    asm volatile("mbarrier.arrive.shared.b64 _, [%0];" ::"r"(a) : "memory");
}
__device__ __forceinline__ void mbar_arrive_cnt(uint32_t a, int c) {
    asm volatile("mbarrier.arrive.shared.b64 _, [%0], %1;" ::"r"(a), "r"(c) : "memory");
}
__device__ __forceinline__ void mbar_wait(uint32_t a, int parity) {
    asm volatile(
        "{\n.reg .pred p;\n.reg .u32 c;\n"
        "mov.u32 c, 0;\n"
        "LAB_WAIT:\n"
        "mbarrier.try_wait.parity.shared.b64 p, [%0], %1, 2000;\n"
        "@p bra DONE;\n"
        "add.u32 c, c, 1;\n"
        "setp.lt.u32 p, c, 2000000;\n"
        "@p bra LAB_WAIT;\n"
        "trap;\n"
        "DONE:\n}" ::"r"(a),
        "r"(parity)
        : "memory");
}
__device__ __forceinline__ void mbar_wait_u(uint32_t a, int parity) {
    asm volatile(
        "{\n.reg .pred p;\n.reg .u32 c;\n"
        "mov.u32 c, 0;\n"
        "LAB_WAIT:\n"
        "mbarrier.try_wait.parity.shared.b64 p, [%0], %1, 2000;\n"
        "@p bra.uni DONE;\n"
        "add.u32 c, c, 1;\n"
        "setp.lt.u32 p, c, 2000000;\n"
        "@p bra.uni LAB_WAIT;\n"
        "trap;\n"
        "DONE:\n}" ::"r"(a),
        "r"(parity)
        : "memory");
}
__device__ __forceinline__ void mbar_spin_u(uint32_t a, int parity) {
    asm volatile(
        "{\n.reg .pred p;\n.reg .u32 c;\n"
        "mov.u32 c, 0;\n"
        "LAB_WAIT:\n"
        "mbarrier.test_wait.parity.shared.b64 p, [%0], %1;\n"
        "@p bra.uni DONE;\n"
        "add.u32 c, c, 1;\n"
        "setp.lt.u32 p, c, 20000000;\n"
        "@p bra.uni LAB_WAIT;\n"
        "trap;\n"
        "DONE:\n}" ::"r"(a),
        "r"(parity)
        : "memory");
}
__device__ __forceinline__ void mbar_lean(uint32_t a, int parity) {
    asm volatile(
        "{\n.reg .pred p;\n.reg .u32 c;\n"
        "mov.u32 c, 0;\n"
        "LAB_WAIT:\n"
        "mbarrier.try_wait.parity.shared.b64 p, [%0], %1;\n"
        "@p bra DONE;\n"
        "add.u32 c, c, 1;\n"
        "setp.lt.u32 p, c, 4000000;\n"
        "@p bra LAB_WAIT;\n"
        "trap;\n"
        "DONE:\n}" ::"r"(a),
        "r"(parity)
        : "memory");
}
__device__ __forceinline__ void mbar_lean_u(uint32_t a, int parity) {
    asm volatile(
        "{\n.reg .pred p;\n.reg .u32 c;\n"
        "mov.u32 c, 0;\n"
        "LAB_WAIT:\n"
        "mbarrier.try_wait.parity.shared.b64 p, [%0], %1;\n"
        "@p bra.uni DONE;\n"
        "add.u32 c, c, 1;\n"
        "setp.lt.u32 p, c, 4000000;\n"
        "@p bra.uni LAB_WAIT;\n"
        "trap;\n"
        "DONE:\n}" ::"r"(a),
        "r"(parity)
        : "memory");
}
__device__ __forceinline__ bool mbar_test(uint32_t a, int parity) {
    uint32_t p;
    asm volatile("{\n.reg .pred P;\nmbarrier.test_wait.parity.shared.b64 P, [%1], %2;\nselp.u32 %0, 1, 0, P;\n}"
                 : "=r"(p)
                 : "r"(a), "r"(parity)
                 : "memory");
    return p;
}
__device__ __forceinline__ bool elect() {
    uint32_t p;
    asm volatile("{\n.reg .pred P;\nelect.sync _|P, 0xffffffff;\nselp.u32 %0, 1, 0, P;\n}" : "=r"(p));
    return p;
}
__device__ __forceinline__ void tma_2d(uint32_t dst, const CUtensorMap* tm, uint32_t bar, int c0, int c1) {
    asm volatile(
        "cp.async.bulk.tensor.2d.shared::cluster.global.mbarrier::complete_tx::bytes [%0], [%1, {%3, %4}], [%2];" ::"r"(dst),
        "l"(tm), "r"(bar), "r"(c0), "r"(c1)
        : "memory");
}
__device__ __forceinline__ void tma_row(uint32_t dst, const CUtensorMap* tm, uint32_t bar, int row8) {
    tma_2d(dst, tm, bar, 0, row8);
}
__device__ __forceinline__ void tma_store(const CUtensorMap* tm, uint32_t src, int c0, int c1) {
    asm volatile("cp.async.bulk.tensor.2d.global.shared::cta.bulk_group [%0, {%2, %3}], [%1];" ::"l"(tm), "r"(src),
                 "r"(c0), "r"(c1)
                 : "memory");
}
__device__ __forceinline__ uint2 lds_v2(uint32_t a) {
    uint2 v;
    asm volatile("ld.shared.v2.u32 {%0,%1}, [%2];" : "=r"(v.x), "=r"(v.y) : "r"(a));
    return v;
}
__device__ __forceinline__ uint4 lds_v4(uint32_t a) {
    uint4 v;
    asm volatile("ld.shared.v4.u32 {%0,%1,%2,%3}, [%4];" : "=r"(v.x), "=r"(v.y), "=r"(v.z), "=r"(v.w) : "r"(a));
    return v;
}
__device__ __forceinline__ uint32_t lds_u32(uint32_t a) {
    uint32_t v;
    asm volatile("ld.shared.u32 %0, [%1];" : "=r"(v) : "r"(a));
    return v;
}
__device__ __forceinline__ uint32_t lds_u16(uint32_t a) {
    uint32_t v;
    asm volatile("ld.shared.u16 %0, [%1];" : "=r"(v) : "r"(a));
    return v;
}
__device__ __forceinline__ void sts_v2(uint32_t a, uint32_t x, uint32_t y) {
    asm volatile("st.shared.v2.u32 [%0], {%1,%2};" ::"r"(a), "r"(x), "r"(y) : "memory");
}
__device__ __forceinline__ void sts_v4(uint32_t a, uint4 v) {
    asm volatile("st.shared.v4.u32 [%0], {%1,%2,%3,%4};" ::"r"(a), "r"(v.x), "r"(v.y), "r"(v.z), "r"(v.w) : "memory");
}
__device__ __forceinline__ void stsm4(uint32_t a, uint32_t r0, uint32_t r1, uint32_t r2, uint32_t r3) {
    asm volatile("stmatrix.sync.aligned.m8n8.x4.shared.b16 [%0], {%1,%2,%3,%4};" ::"r"(a), "r"(r0), "r"(r1), "r"(r2), "r"(r3)
                 : "memory");
}
__device__ __forceinline__ void stsm2(uint32_t a, uint32_t r0, uint32_t r1) {
    asm volatile("stmatrix.sync.aligned.m8n8.x2.shared.b16 [%0], {%1,%2};" ::"r"(a), "r"(r0), "r"(r1) : "memory");
}
__device__ __forceinline__ void stsm4t(uint32_t a, uint32_t r0, uint32_t r1, uint32_t r2, uint32_t r3) {
    asm volatile("stmatrix.sync.aligned.m8n8.x4.trans.shared.b16 [%0], {%1,%2,%3,%4};" ::"r"(a), "r"(r0), "r"(r1), "r"(r2),
                 "r"(r3)
                 : "memory");
}
__device__ __forceinline__ void stsm2t(uint32_t a, uint32_t r0, uint32_t r1) {
    asm volatile("stmatrix.sync.aligned.m8n8.x2.trans.shared.b16 [%0], {%1,%2};" ::"r"(a), "r"(r0), "r"(r1) : "memory");
}
__device__ __forceinline__ void cp_async16(uint32_t d, const void* s, int n) {
    asm volatile("cp.async.cg.shared.global [%0], [%1], 16, %2;" ::"r"(d), "l"(s), "r"(n) : "memory");
}
__device__ __forceinline__ void cp_async4(uint32_t d, const void* s, int n) {
    asm volatile("cp.async.ca.shared.global [%0], [%1], 4, %2;" ::"r"(d), "l"(s), "r"(n) : "memory");
}
__device__ __forceinline__ void sts_u32(uint32_t a, uint32_t x) {
    asm volatile("st.shared.u32 [%0], %1;" ::"r"(a), "r"(x) : "memory");
}
#define FENCE_ASYNC() asm volatile("fence.proxy.async.shared::cta;" ::: "memory")
#define ZS 4
__device__ __forceinline__ int warp_incl_scan(int v, int lane, int z) {
#pragma unroll
    for (int o = 1; o < 32; o <<= 1) {
        const int y = __shfl_up_sync(0xffffffffu, v, o);
        if (lane >= o) v += y;
        if (o == ZS) v += z;
    }
    return v;
}

__device__ __forceinline__ uint32_t atoms_add(uint32_t a, uint32_t v) {
    uint32_t r;
    asm volatile("atom.shared.add.u32 %0, [%1], %2;" : "=r"(r) : "r"(a), "r"(v) : "memory");
    return r;
}
__device__ __forceinline__ void sts_u16(uint32_t a, uint32_t x) {
    asm volatile("{\n.reg .b16 h;\ncvt.u16.u32 h, %1;\nst.shared.u16 [%0], h;\n}" ::"r"(a), "r"(x) : "memory");
}
#define NJ 19
__device__ __forceinline__ void consume(float (&acc)[2][NJ][4], uint32_t (&wo)[8][4], uint32_t ring, uint32_t xa0, uint32_t xa1, uint32_t so0, uint32_t bar0,
                                        uint32_t ea0, uint32_t d0, uint32_t pl0, int lz, const uint32_t (&wa)[8]) {
    asm volatile(
        "{\n"
        ".reg .pred p, pf, plead, pok, t0, t1, t2, u0, u1, u2;\n"
        ".reg .b32 ca, cb, cz, rbar;\n"
        "mov.b32 cz, 0;\n"
        "mov.b32 ca, 0x20002000;\n"
        "mov.b32 cb, 0x30003000;\n"
        ".reg .b32 cnt, so, q, qe, bar, nbar, pl, ctl, ctm, ix, iy, dl, v0, v1, v2, v3, pp;\n"
        ".reg .b16 sl, sh;\n"
        ".reg .b32 hXa0, hXa1, hXa2, hXa3, hXa4, hXa5, hXa6, hXa7, hXb0, hXb1, hXb2, hXb3, hXb4, hXb5, hXb6, hXb7, hYa0, hYa1, hYa2, hYa3, hYa4, hYa5, hYa6, hYa7, hYb0, hYb1, hYb2, hYb3, hYb4, hYb5, hYb6, hYb7, hLa0, hLa1, hLa2, hLa3, hLa4, hLa5, hLa6, hLa7, hLb0, hLb1, hLb2, hLb3, hLb4, hLb5, hLb6, hLb7;\n"
        ".reg .b32 pX0, pX1, pX2, pX3, pY0, pY1, pY2, pY3;\n"
        ".reg .f32 r0, r1, r2, r3, r4, r5, r6, r7, r8, r9, r10, r11, r12, r13, r14, r15;\n"
        ".reg .b64 daX, dbX, daY, dbY, de0, de1;\n"
        ".reg .b32 dh<6>, eb0, par, npar, wa<8>, uz, bend;\n"
        "add.u32 wa0, %192, %191;\n"
        "add.u32 wa1, %193, %191;\n"
        "add.u32 wa2, %194, %191;\n"
        "add.u32 wa3, %195, %191;\n"
        "add.u32 wa4, %196, %191;\n"
        "add.u32 wa5, %197, %191;\n"
        "add.u32 wa6, %198, %191;\n"
        "add.u32 wa7, %199, %191;\n"
        "mov.f32 %0, 0f00000000;\n"
        "mov.f32 %1, 0f00000000;\n"
        "mov.f32 %2, 0f00000000;\n"
        "mov.f32 %3, 0f00000000;\n"
        "mov.f32 %4, 0f00000000;\n"
        "mov.f32 %5, 0f00000000;\n"
        "mov.f32 %6, 0f00000000;\n"
        "mov.f32 %7, 0f00000000;\n"
        "mov.f32 %8, 0f00000000;\n"
        "mov.f32 %9, 0f00000000;\n"
        "mov.f32 %10, 0f00000000;\n"
        "mov.f32 %11, 0f00000000;\n"
        "mov.f32 %12, 0f00000000;\n"
        "mov.f32 %13, 0f00000000;\n"
        "mov.f32 %14, 0f00000000;\n"
        "mov.f32 %15, 0f00000000;\n"
        "mov.f32 %16, 0f00000000;\n"
        "mov.f32 %17, 0f00000000;\n"
        "mov.f32 %18, 0f00000000;\n"
        "mov.f32 %19, 0f00000000;\n"
        "mov.f32 %20, 0f00000000;\n"
        "mov.f32 %21, 0f00000000;\n"
        "mov.f32 %22, 0f00000000;\n"
        "mov.f32 %23, 0f00000000;\n"
        "mov.f32 %24, 0f00000000;\n"
        "mov.f32 %25, 0f00000000;\n"
        "mov.f32 %26, 0f00000000;\n"
        "mov.f32 %27, 0f00000000;\n"
        "mov.f32 %28, 0f00000000;\n"
        "mov.f32 %29, 0f00000000;\n"
        "mov.f32 %30, 0f00000000;\n"
        "mov.f32 %31, 0f00000000;\n"
        "mov.f32 %32, 0f00000000;\n"
        "mov.f32 %33, 0f00000000;\n"
        "mov.f32 %34, 0f00000000;\n"
        "mov.f32 %35, 0f00000000;\n"
        "mov.f32 %36, 0f00000000;\n"
        "mov.f32 %37, 0f00000000;\n"
        "mov.f32 %38, 0f00000000;\n"
        "mov.f32 %39, 0f00000000;\n"
        "mov.f32 %40, 0f00000000;\n"
        "mov.f32 %41, 0f00000000;\n"
        "mov.f32 %42, 0f00000000;\n"
        "mov.f32 %43, 0f00000000;\n"
        "mov.f32 %44, 0f00000000;\n"
        "mov.f32 %45, 0f00000000;\n"
        "mov.f32 %46, 0f00000000;\n"
        "mov.f32 %47, 0f00000000;\n"
        "mov.f32 %48, 0f00000000;\n"
        "mov.f32 %49, 0f00000000;\n"
        "mov.f32 %50, 0f00000000;\n"
        "mov.f32 %51, 0f00000000;\n"
        "mov.f32 %52, 0f00000000;\n"
        "mov.f32 %53, 0f00000000;\n"
        "mov.f32 %54, 0f00000000;\n"
        "mov.f32 %55, 0f00000000;\n"
        "mov.f32 %56, 0f00000000;\n"
        "mov.f32 %57, 0f00000000;\n"
        "mov.f32 %58, 0f00000000;\n"
        "mov.f32 %59, 0f00000000;\n"
        "mov.f32 %60, 0f00000000;\n"
        "mov.f32 %61, 0f00000000;\n"
        "mov.f32 %62, 0f00000000;\n"
        "mov.f32 %63, 0f00000000;\n"
        "mov.f32 %64, 0f00000000;\n"
        "mov.f32 %65, 0f00000000;\n"
        "mov.f32 %66, 0f00000000;\n"
        "mov.f32 %67, 0f00000000;\n"
        "mov.f32 %68, 0f00000000;\n"
        "mov.f32 %69, 0f00000000;\n"
        "mov.f32 %70, 0f00000000;\n"
        "mov.f32 %71, 0f00000000;\n"
        "mov.f32 %72, 0f00000000;\n"
        "mov.f32 %73, 0f00000000;\n"
        "mov.f32 %74, 0f00000000;\n"
        "mov.f32 %75, 0f00000000;\n"
        "mov.f32 %76, 0f00000000;\n"
        "mov.f32 %77, 0f00000000;\n"
        "mov.f32 %78, 0f00000000;\n"
        "mov.f32 %79, 0f00000000;\n"
        "mov.f32 %80, 0f00000000;\n"
        "mov.f32 %81, 0f00000000;\n"
        "mov.f32 %82, 0f00000000;\n"
        "mov.f32 %83, 0f00000000;\n"
        "mov.f32 %84, 0f00000000;\n"
        "mov.f32 %85, 0f00000000;\n"
        "mov.f32 %86, 0f00000000;\n"
        "mov.f32 %87, 0f00000000;\n"
        "mov.f32 %88, 0f00000000;\n"
        "mov.f32 %89, 0f00000000;\n"
        "mov.f32 %90, 0f00000000;\n"
        "mov.f32 %91, 0f00000000;\n"
        "mov.f32 %92, 0f00000000;\n"
        "mov.f32 %93, 0f00000000;\n"
        "mov.f32 %94, 0f00000000;\n"
        "mov.f32 %95, 0f00000000;\n"
        "mov.f32 %96, 0f00000000;\n"
        "mov.f32 %97, 0f00000000;\n"
        "mov.f32 %98, 0f00000000;\n"
        "mov.f32 %99, 0f00000000;\n"
        "mov.f32 %100, 0f00000000;\n"
        "mov.f32 %101, 0f00000000;\n"
        "mov.f32 %102, 0f00000000;\n"
        "mov.f32 %103, 0f00000000;\n"
        "mov.f32 %104, 0f00000000;\n"
        "mov.f32 %105, 0f00000000;\n"
        "mov.f32 %106, 0f00000000;\n"
        "mov.f32 %107, 0f00000000;\n"
        "mov.f32 %108, 0f00000000;\n"
        "mov.f32 %109, 0f00000000;\n"
        "mov.f32 %110, 0f00000000;\n"
        "mov.f32 %111, 0f00000000;\n"
        "mov.f32 %112, 0f00000000;\n"
        "mov.f32 %113, 0f00000000;\n"
        "mov.f32 %114, 0f00000000;\n"
        "mov.f32 %115, 0f00000000;\n"
        "mov.f32 %116, 0f00000000;\n"
        "mov.f32 %117, 0f00000000;\n"
        "mov.f32 %118, 0f00000000;\n"
        "mov.f32 %119, 0f00000000;\n"
        "mov.f32 %120, 0f00000000;\n"
        "mov.f32 %121, 0f00000000;\n"
        "mov.f32 %122, 0f00000000;\n"
        "mov.f32 %123, 0f00000000;\n"
        "mov.f32 %124, 0f00000000;\n"
        "mov.f32 %125, 0f00000000;\n"
        "mov.f32 %126, 0f00000000;\n"
        "mov.f32 %127, 0f00000000;\n"
        "mov.f32 %128, 0f00000000;\n"
        "mov.f32 %129, 0f00000000;\n"
        "mov.f32 %130, 0f00000000;\n"
        "mov.f32 %131, 0f00000000;\n"
        "mov.f32 %132, 0f00000000;\n"
        "mov.f32 %133, 0f00000000;\n"
        "mov.f32 %134, 0f00000000;\n"
        "mov.f32 %135, 0f00000000;\n"
        "mov.f32 %136, 0f00000000;\n"
        "mov.f32 %137, 0f00000000;\n"
        "mov.f32 %138, 0f00000000;\n"
        "mov.f32 %139, 0f00000000;\n"
        "mov.f32 %140, 0f00000000;\n"
        "mov.f32 %141, 0f00000000;\n"
        "mov.f32 %142, 0f00000000;\n"
        "mov.f32 %143, 0f00000000;\n"
        "mov.f32 %144, 0f00000000;\n"
        "mov.f32 %145, 0f00000000;\n"
        "mov.f32 %146, 0f00000000;\n"
        "mov.f32 %147, 0f00000000;\n"
        "mov.f32 %148, 0f00000000;\n"
        "mov.f32 %149, 0f00000000;\n"
        "mov.f32 %150, 0f00000000;\n"
        "mov.f32 %151, 0f00000000;\n"
        "setp.ne.u32 pf, 0, 0;\n"
        "add.u32 v0, %186, %191;\n"
        "shfl.sync.idx.b32 so, v0, 0, 31, 0xffffffff;\n"
        "mov.u32 npar, 0;\n"
        "shfl.sync.idx.b32 uz, %191, 7, 31, 0xffffffff;\n"
        "add.u32 bend, %187, " STR(NP * 16) ";\n"
        "add.u32 v0, %191, 8;\n"
        "shfl.sync.idx.b32 dh0, v0, 0, 31, 0xffffffff;\n"
        "shfl.sync.idx.b32 dh1, v0, 1, 31, 0xffffffff;\n"
        "shfl.sync.idx.b32 dh2, v0, 2, 31, 0xffffffff;\n"
        "shfl.sync.idx.b32 dh3, v0, 3, 31, 0xffffffff;\n"
        "add.u32 v0, %191, 0xc0000010;\n"
        "shfl.sync.idx.b32 dh4, v0, 4, 31, 0xffffffff;\n"
        "shfl.sync.idx.b32 dh5, v0, 5, 31, 0xffffffff;\n"
        "add.u32 v0, %191, %188;\n"
        "shfl.sync.idx.b32 eb0, v0, 0, 31, 0xffffffff;\n"
        "mov.u32 q, 0;\n"
        "mov.u32 pl, %190;\n"
        "shr.u32 nbar, so, 9;\n"
        "add.u32 nbar, nbar, %187;\n"
        "elect.sync _|plead, 0xffffffff;\n"
        "mov.b64 de0, {%188, dh4};\n"
        "mov.b64 de1, {eb0, dh5};\n"
        "mov.b32 hYa0, 0;\n"
        "mov.b32 hYa1, 0;\n"
        "mov.b32 hYa2, 0;\n"
        "mov.b32 hYa3, 0;\n"
        "mov.b32 hYa4, 0;\n"
        "mov.b32 hYa5, 0;\n"
        "mov.b32 hYa6, 0;\n"
        "mov.b32 hYa7, 0;\n"
        "mov.b32 hYb0, 0;\n"
        "mov.b32 hYb1, 0;\n"
        "mov.b32 hYb2, 0;\n"
        "mov.b32 hYb3, 0;\n"
        "mov.b32 hYb4, 0;\n"
        "mov.b32 hYb5, 0;\n"
        "mov.b32 hYb6, 0;\n"
        "mov.b32 hYb7, 0;\n"
        "mov.u32 ctm, 0x10001000;\n"
        "setp.lt.f16x2 t0|u0, ctm, cz;\n"
        "abs.f16x2 v3, ctm;\n"
        "setp.ge.f16x2 t1|u1, v3, ca;\n"
        "setp.geu.f16x2 t2|u2, v3, cb;\n"
        "ld.shared.v2.u32 {ctl, ctm}, [pl];\n"
        "add.u32 pl, pl, 8;\n"
        "add.u32 rbar, %187, " STR(DUMB) ";\n"
        "mov.b64 daX, {%189, dh0};\n"
        "mov.b64 dbX, {%189, dh1};\n"
        "mov.b64 daY, {%189, dh2};\n"
        "mov.b64 dbY, {%189, dh3};\n"
        "mov.u32 bar, nbar;\n"
        "mov.u32 par, npar;\n"
        "sub.u32 so, bar, %187;\n"
        "shl.b32 so, so, 9;\n"
        "add.u32 v0, %184, so;\n"
        "add.u32 v1, %185, so;\n"
        "add.u32 nbar, nbar, 16;\n"
        "setp.eq.u32 p, nbar, bend;\n"
        "selp.b32 nbar, %187, nbar, p;\n"
        "@p xor.b32 npar, npar, 1;\n"
        "SLOW:\n"
        "mov.u32 cnt, 0;\n"
        "W1:\n"
        "mbarrier.try_wait.parity.shared.b64 p, [bar], par;\n"
        "@p bra.uni RES;\n"
        "add.u32 cnt, cnt, 1;\n"
        "setp.lt.u32 p, cnt, 4000000;\n"
        "@p bra.uni W1;\n"
        "trap;\n"
        "CX:\n"
        "mbarrier.test_wait.parity.shared.b64 pok, [nbar], npar;\n"
        "and.b32 dl, q, 0x60;\n"
        "add.u32 dl, dl, %189;\n"
        "add.u32 v3, dl, 0;\n"
        "mov.b64 {v2, dh0}, daX;\n"
        "mov.b64 daX, {v3, dh0};\n"
        "add.u32 v3, dl, 257;\n"
        "mov.b64 {v2, dh1}, dbX;\n"
        "mov.b64 dbX, {v3, dh1};\n"
        "add.u32 v3, dl, 514;\n"
        "mov.b64 {v2, dh2}, daY;\n"
        "mov.b64 daY, {v3, dh2};\n"
        "add.u32 v3, dl, 771;\n"
        "mov.b64 {v2, dh3}, dbY;\n"
        "mov.b64 dbY, {v3, dh3};\n"
        "add.u32 q, q, 32;\n"
        "and.b32 qe, q, 0xe0;\n"
        "add.u32 v3, qe, %188;\n"
        "mov.b64 {v2, dh4}, de0;\n"
        "mov.b64 de0, {v3, dh4};\n"
        "mov.b64 {v2, dh5}, de1;\n"
        "mov.b64 de1, {v3, dh5};\n"
        "setp.lt.f16x2 t0|u0, ctl, cz;\n"
        "abs.f16x2 v3, ctl;\n"
        "setp.ge.f16x2 t1|u1, v3, ca;\n"
        "setp.geu.f16x2 t2|u2, v3, cb;\n"
        "wgmma.wait_group.sync.aligned 2;\n"
        "cvt.rn.bf16x2.f32 pX0, r1, r0;\n"
        "cvt.rn.bf16x2.f32 pX1, r3, r2;\n"
        "cvt.rn.bf16x2.f32 pX2, r9, r8;\n"
        "cvt.rn.bf16x2.f32 pX3, r11, r10;\n"
        "cvt.rn.bf16x2.f32 pY0, r5, r4;\n"
        "cvt.rn.bf16x2.f32 pY1, r7, r6;\n"
        "cvt.rn.bf16x2.f32 pY2, r13, r12;\n"
        "cvt.rn.bf16x2.f32 pY3, r15, r14;\n"
        "mov.b32 {sl, sh}, pX0;\n"
        "mov.b32 pp, {sl, sl};\n"
        "mul.rn.bf16x2 hXa0, hLa0, pp;\n"
        "mul.rn.bf16x2 hXa2, hLa2, pp;\n"
        "mov.b32 {sl, sh}, pX1;\n"
        "mov.b32 pp, {sl, sl};\n"
        "mul.rn.bf16x2 hXa1, hLa1, pp;\n"
        "mul.rn.bf16x2 hXa3, hLa3, pp;\n"
        "mov.b32 {sl, sh}, pX2;\n"
        "mov.b32 pp, {sl, sl};\n"
        "mul.rn.bf16x2 hXa4, hLa4, pp;\n"
        "mul.rn.bf16x2 hXa6, hLa6, pp;\n"
        "mov.b32 {sl, sh}, pX3;\n"
        "mov.b32 pp, {sl, sl};\n"
        "mul.rn.bf16x2 hXa5, hLa5, pp;\n"
        "mul.rn.bf16x2 hXa7, hLa7, pp;\n"
        "mov.b32 {sl, sh}, pX0;\n"
        "mov.b32 pp, {sh, sh};\n"
        "mul.rn.bf16x2 hXb0, hLb0, pp;\n"
        "mul.rn.bf16x2 hXb2, hLb2, pp;\n"
        "mov.b32 {sl, sh}, pX1;\n"
        "mov.b32 pp, {sh, sh};\n"
        "mul.rn.bf16x2 hXb1, hLb1, pp;\n"
        "mul.rn.bf16x2 hXb3, hLb3, pp;\n"
        "mov.b32 {sl, sh}, pX2;\n"
        "mov.b32 pp, {sh, sh};\n"
        "mul.rn.bf16x2 hXb4, hLb4, pp;\n"
        "mul.rn.bf16x2 hXb6, hLb6, pp;\n"
        "mov.b32 {sl, sh}, pX3;\n"
        "mov.b32 pp, {sh, sh};\n"
        "mul.rn.bf16x2 hXb5, hLb5, pp;\n"
        "mul.rn.bf16x2 hXb7, hLb7, pp;\n"
        "ldmatrix.sync.aligned.m8n8.x4.trans.shared.b16 {hLa0,hLa1,hLa2,hLa3}, [v0+4096];\n"
        "ldmatrix.sync.aligned.m8n8.x4.trans.shared.b16 {hLa4,hLa5,hLa6,hLa7}, [v1+4096];\n"
        "ldmatrix.sync.aligned.m8n8.x4.trans.shared.b16 {hLb0,hLb1,hLb2,hLb3}, [v0+6144];\n"
        "ldmatrix.sync.aligned.m8n8.x4.trans.shared.b16 {hLb4,hLb5,hLb6,hLb7}, [v1+6144];\n"
        "@t2 bra.uni T4X;\n"
        "@t1 bra.uni T2X;\n"
        "@t0 bra.uni L1X;\n"
        "L0X:\n"
        "wgmma.fence.sync.aligned;\n"
        "wgmma.mma_async.sync.aligned.m64n24k16.f32.bf16.bf16 {%0,%1,%2,%3,%4,%5,%6,%7,%8,%9,%10,%11}, {hXa0,hXa1,hXa2,hXa3}, daX, 1, 1, 1, 0;\n"
        "wgmma.mma_async.sync.aligned.m64n24k16.f32.bf16.bf16 {%76,%77,%78,%79,%80,%81,%82,%83,%84,%85,%86,%87}, {hXa4,hXa5,hXa6,hXa7}, daX, 1, 1, 1, 0;\n"
        "wgmma.commit_group.sync.aligned;\n"
        "@u2 bra.uni T4Xb;\n"
        "@u1 bra.uni T2Xb;\n"
        "@u0 bra.uni L1Xb;\n"
        "bra.uni L0Xb;\n"
        "L1X:\n"
        "wgmma.fence.sync.aligned;\n"
        "wgmma.mma_async.sync.aligned.m64n24k16.f32.bf16.bf16 {%12,%13,%14,%15,%16,%17,%18,%19,%20,%21,%22,%23}, {hXa0,hXa1,hXa2,hXa3}, daX, 1, 1, 1, 0;\n"
        "wgmma.mma_async.sync.aligned.m64n24k16.f32.bf16.bf16 {%88,%89,%90,%91,%92,%93,%94,%95,%96,%97,%98,%99}, {hXa4,hXa5,hXa6,hXa7}, daX, 1, 1, 1, 0;\n"
        "wgmma.commit_group.sync.aligned;\n"
        "@u2 bra.uni T4Xb;\n"
        "@u1 bra.uni T2Xb;\n"
        "@u0 bra.uni L1Xb;\n"
        "bra.uni L0Xb;\n"
        "T2X:\n"
        "@t0 bra.uni L3X;\n"
        "L2X:\n"
        "wgmma.fence.sync.aligned;\n"
        "wgmma.mma_async.sync.aligned.m64n24k16.f32.bf16.bf16 {%24,%25,%26,%27,%28,%29,%30,%31,%32,%33,%34,%35}, {hXa0,hXa1,hXa2,hXa3}, daX, 1, 1, 1, 0;\n"
        "wgmma.mma_async.sync.aligned.m64n24k16.f32.bf16.bf16 {%100,%101,%102,%103,%104,%105,%106,%107,%108,%109,%110,%111}, {hXa4,hXa5,hXa6,hXa7}, daX, 1, 1, 1, 0;\n"
        "wgmma.commit_group.sync.aligned;\n"
        "@u2 bra.uni T4Xb;\n"
        "@u1 bra.uni T2Xb;\n"
        "@u0 bra.uni L1Xb;\n"
        "bra.uni L0Xb;\n"
        "L3X:\n"
        "wgmma.fence.sync.aligned;\n"
        "wgmma.mma_async.sync.aligned.m64n24k16.f32.bf16.bf16 {%36,%37,%38,%39,%40,%41,%42,%43,%44,%45,%46,%47}, {hXa0,hXa1,hXa2,hXa3}, daX, 1, 1, 1, 0;\n"
        "wgmma.mma_async.sync.aligned.m64n24k16.f32.bf16.bf16 {%112,%113,%114,%115,%116,%117,%118,%119,%120,%121,%122,%123}, {hXa4,hXa5,hXa6,hXa7}, daX, 1, 1, 1, 0;\n"
        "wgmma.commit_group.sync.aligned;\n"
        "@u2 bra.uni T4Xb;\n"
        "@u1 bra.uni T2Xb;\n"
        "@u0 bra.uni L1Xb;\n"
        "bra.uni L0Xb;\n"
        "T4X:\n"
        "@!t1 bra.uni LEXIT;\n"
        "@t0 bra.uni L5X;\n"
        "L4X:\n"
        "wgmma.fence.sync.aligned;\n"
        "wgmma.mma_async.sync.aligned.m64n24k16.f32.bf16.bf16 {%48,%49,%50,%51,%52,%53,%54,%55,%56,%57,%58,%59}, {hXa0,hXa1,hXa2,hXa3}, daX, 1, 1, 1, 0;\n"
        "wgmma.mma_async.sync.aligned.m64n24k16.f32.bf16.bf16 {%124,%125,%126,%127,%128,%129,%130,%131,%132,%133,%134,%135}, {hXa4,hXa5,hXa6,hXa7}, daX, 1, 1, 1, 0;\n"
        "wgmma.commit_group.sync.aligned;\n"
        "@u2 bra.uni T4Xb;\n"
        "@u1 bra.uni T2Xb;\n"
        "@u0 bra.uni L1Xb;\n"
        "bra.uni L0Xb;\n"
        "L5X:\n"
        "wgmma.fence.sync.aligned;\n"
        "wgmma.mma_async.sync.aligned.m64n32k16.f32.bf16.bf16 {%60,%61,%62,%63,%64,%65,%66,%67,%68,%69,%70,%71,%72,%73,%74,%75}, {hXa0,hXa1,hXa2,hXa3}, daX, 1, 1, 1, 0;\n"
        "wgmma.mma_async.sync.aligned.m64n32k16.f32.bf16.bf16 {%136,%137,%138,%139,%140,%141,%142,%143,%144,%145,%146,%147,%148,%149,%150,%151}, {hXa4,hXa5,hXa6,hXa7}, daX, 1, 1, 1, 0;\n"
        "wgmma.commit_group.sync.aligned;\n"
        "@u2 bra.uni T4Xb;\n"
        "@u1 bra.uni T2Xb;\n"
        "@u0 bra.uni L1Xb;\n"
        "L0Xb:\n"
        "wgmma.fence.sync.aligned;\n"
        "wgmma.mma_async.sync.aligned.m64n24k16.f32.bf16.bf16 {%0,%1,%2,%3,%4,%5,%6,%7,%8,%9,%10,%11}, {hXb0,hXb1,hXb2,hXb3}, dbX, 1, 1, 1, 0;\n"
        "wgmma.mma_async.sync.aligned.m64n24k16.f32.bf16.bf16 {%76,%77,%78,%79,%80,%81,%82,%83,%84,%85,%86,%87}, {hXb4,hXb5,hXb6,hXb7}, dbX, 1, 1, 1, 0;\n"
        "wgmma.commit_group.sync.aligned;\n"
        "bra.uni CY;\n"
        "L1Xb:\n"
        "wgmma.fence.sync.aligned;\n"
        "wgmma.mma_async.sync.aligned.m64n24k16.f32.bf16.bf16 {%12,%13,%14,%15,%16,%17,%18,%19,%20,%21,%22,%23}, {hXb0,hXb1,hXb2,hXb3}, dbX, 1, 1, 1, 0;\n"
        "wgmma.mma_async.sync.aligned.m64n24k16.f32.bf16.bf16 {%88,%89,%90,%91,%92,%93,%94,%95,%96,%97,%98,%99}, {hXb4,hXb5,hXb6,hXb7}, dbX, 1, 1, 1, 0;\n"
        "wgmma.commit_group.sync.aligned;\n"
        "bra.uni CY;\n"
        "T2Xb:\n"
        "@u0 bra.uni L3Xb;\n"
        "L2Xb:\n"
        "wgmma.fence.sync.aligned;\n"
        "wgmma.mma_async.sync.aligned.m64n24k16.f32.bf16.bf16 {%24,%25,%26,%27,%28,%29,%30,%31,%32,%33,%34,%35}, {hXb0,hXb1,hXb2,hXb3}, dbX, 1, 1, 1, 0;\n"
        "wgmma.mma_async.sync.aligned.m64n24k16.f32.bf16.bf16 {%100,%101,%102,%103,%104,%105,%106,%107,%108,%109,%110,%111}, {hXb4,hXb5,hXb6,hXb7}, dbX, 1, 1, 1, 0;\n"
        "wgmma.commit_group.sync.aligned;\n"
        "bra.uni CY;\n"
        "L3Xb:\n"
        "wgmma.fence.sync.aligned;\n"
        "wgmma.mma_async.sync.aligned.m64n24k16.f32.bf16.bf16 {%36,%37,%38,%39,%40,%41,%42,%43,%44,%45,%46,%47}, {hXb0,hXb1,hXb2,hXb3}, dbX, 1, 1, 1, 0;\n"
        "wgmma.mma_async.sync.aligned.m64n24k16.f32.bf16.bf16 {%112,%113,%114,%115,%116,%117,%118,%119,%120,%121,%122,%123}, {hXb4,hXb5,hXb6,hXb7}, dbX, 1, 1, 1, 0;\n"
        "wgmma.commit_group.sync.aligned;\n"
        "bra.uni CY;\n"
        "T4Xb:\n"
        "@u0 bra.uni L5Xb;\n"
        "L4Xb:\n"
        "wgmma.fence.sync.aligned;\n"
        "wgmma.mma_async.sync.aligned.m64n24k16.f32.bf16.bf16 {%48,%49,%50,%51,%52,%53,%54,%55,%56,%57,%58,%59}, {hXb0,hXb1,hXb2,hXb3}, dbX, 1, 1, 1, 0;\n"
        "wgmma.mma_async.sync.aligned.m64n24k16.f32.bf16.bf16 {%124,%125,%126,%127,%128,%129,%130,%131,%132,%133,%134,%135}, {hXb4,hXb5,hXb6,hXb7}, dbX, 1, 1, 1, 0;\n"
        "wgmma.commit_group.sync.aligned;\n"
        "bra.uni CY;\n"
        "L5Xb:\n"
        "wgmma.fence.sync.aligned;\n"
        "wgmma.mma_async.sync.aligned.m64n32k16.f32.bf16.bf16 {%60,%61,%62,%63,%64,%65,%66,%67,%68,%69,%70,%71,%72,%73,%74,%75}, {hXb0,hXb1,hXb2,hXb3}, dbX, 1, 1, 1, 0;\n"
        "wgmma.mma_async.sync.aligned.m64n32k16.f32.bf16.bf16 {%136,%137,%138,%139,%140,%141,%142,%143,%144,%145,%146,%147,%148,%149,%150,%151}, {hXb4,hXb5,hXb6,hXb7}, dbX, 1, 1, 1, 0;\n"
        "wgmma.commit_group.sync.aligned;\n"
        "bra.uni CY;\n"
        "CY:\n"
        "mov.u32 rbar, bar;\n"
        "mov.u32 bar, nbar;\n"
        "mov.u32 par, npar;\n"
        "sub.u32 so, bar, %187;\n"
        "shl.b32 so, so, 9;\n"
        "add.u32 v0, %184, so;\n"
        "add.u32 v1, %185, so;\n"
        "add.u32 nbar, nbar, 16;\n"
        "setp.eq.u32 p, nbar, bend;\n"
        "selp.b32 nbar, %187, nbar, p;\n"
        "@p xor.b32 npar, npar, 1;\n"
        "wgmma.wait_group.sync.aligned 2;\n"
        "lop3.b32 v2, hLa3, hLa7, hLb3, 0x80;\n"
        "lop3.b32 v2, v2, hLb7, uz, 0x80;\n"
        "add.u32 v2, v2, rbar;\n"
        "@plead mbarrier.arrive.shared.b64 _, [v2+8];\n"
        "setp.lt.f16x2 t0|u0, ctm, cz;\n"
        "abs.f16x2 v3, ctm;\n"
        "setp.ge.f16x2 t1|u1, v3, ca;\n"
        "setp.geu.f16x2 t2|u2, v3, cb;\n"
        "ld.shared.v2.u32 {ctl, ctm}, [pl];\n"
        "add.u32 pl, pl, 8;\n"
        "mov.b32 {sl, sh}, pY0;\n"
        "mov.b32 pp, {sl, sl};\n"
        "mul.rn.bf16x2 hYa0, hLa0, pp;\n"
        "mul.rn.bf16x2 hYa2, hLa2, pp;\n"
        "mov.b32 {sl, sh}, pY1;\n"
        "mov.b32 pp, {sl, sl};\n"
        "mul.rn.bf16x2 hYa1, hLa1, pp;\n"
        "mul.rn.bf16x2 hYa3, hLa3, pp;\n"
        "mov.b32 {sl, sh}, pY2;\n"
        "mov.b32 pp, {sl, sl};\n"
        "mul.rn.bf16x2 hYa4, hLa4, pp;\n"
        "mul.rn.bf16x2 hYa6, hLa6, pp;\n"
        "mov.b32 {sl, sh}, pY3;\n"
        "mov.b32 pp, {sl, sl};\n"
        "mul.rn.bf16x2 hYa5, hLa5, pp;\n"
        "mul.rn.bf16x2 hYa7, hLa7, pp;\n"
        "mov.b32 {sl, sh}, pY0;\n"
        "mov.b32 pp, {sh, sh};\n"
        "mul.rn.bf16x2 hYb0, hLb0, pp;\n"
        "mul.rn.bf16x2 hYb2, hLb2, pp;\n"
        "mov.b32 {sl, sh}, pY1;\n"
        "mov.b32 pp, {sh, sh};\n"
        "mul.rn.bf16x2 hYb1, hLb1, pp;\n"
        "mul.rn.bf16x2 hYb3, hLb3, pp;\n"
        "mov.b32 {sl, sh}, pY2;\n"
        "mov.b32 pp, {sh, sh};\n"
        "mul.rn.bf16x2 hYb4, hLb4, pp;\n"
        "mul.rn.bf16x2 hYb6, hLb6, pp;\n"
        "mov.b32 {sl, sh}, pY3;\n"
        "mov.b32 pp, {sh, sh};\n"
        "mul.rn.bf16x2 hYb5, hLb5, pp;\n"
        "mul.rn.bf16x2 hYb7, hLb7, pp;\n"
        "@!pok bra.uni SLOW;\n"
        "RES:\n"
        "ldmatrix.sync.aligned.m8n8.x4.trans.shared.b16 {hLa0,hLa1,hLa2,hLa3}, [v0+0];\n"
        "ldmatrix.sync.aligned.m8n8.x4.trans.shared.b16 {hLa4,hLa5,hLa6,hLa7}, [v1+0];\n"
        "ldmatrix.sync.aligned.m8n8.x4.trans.shared.b16 {hLb0,hLb1,hLb2,hLb3}, [v0+2048];\n"
        "ldmatrix.sync.aligned.m8n8.x4.trans.shared.b16 {hLb4,hLb5,hLb6,hLb7}, [v1+2048];\n"
        "wgmma.wait_group.sync.aligned 0;\n"
        "@t2 bra.uni T4Y;\n"
        "@t1 bra.uni T2Y;\n"
        "@t0 bra.uni L1Y;\n"
        "L0Y:\n"
        "wgmma.fence.sync.aligned;\n"
        "wgmma.mma_async.sync.aligned.m64n16k16.f32.bf16.bf16 {r0,r1,r2,r3,r4,r5,r6,r7}, {wa0,wa1,wa2,wa3}, de0, pf, 1, 1, 0;\n"
        "wgmma.mma_async.sync.aligned.m64n16k16.f32.bf16.bf16 {r8,r9,r10,r11,r12,r13,r14,r15}, {wa4,wa5,wa6,wa7}, de1, pf, 1, 1, 0;\n"
        "wgmma.commit_group.sync.aligned;\n"
        "wgmma.mma_async.sync.aligned.m64n24k16.f32.bf16.bf16 {%0,%1,%2,%3,%4,%5,%6,%7,%8,%9,%10,%11}, {hYa0,hYa1,hYa2,hYa3}, daY, 1, 1, 1, 0;\n"
        "wgmma.mma_async.sync.aligned.m64n24k16.f32.bf16.bf16 {%76,%77,%78,%79,%80,%81,%82,%83,%84,%85,%86,%87}, {hYa4,hYa5,hYa6,hYa7}, daY, 1, 1, 1, 0;\n"
        "wgmma.commit_group.sync.aligned;\n"
        "@u2 bra.uni T4Yb;\n"
        "@u1 bra.uni T2Yb;\n"
        "@u0 bra.uni L1Yb;\n"
        "bra.uni L0Yb;\n"
        "L1Y:\n"
        "wgmma.fence.sync.aligned;\n"
        "wgmma.mma_async.sync.aligned.m64n16k16.f32.bf16.bf16 {r0,r1,r2,r3,r4,r5,r6,r7}, {wa0,wa1,wa2,wa3}, de0, pf, 1, 1, 0;\n"
        "wgmma.mma_async.sync.aligned.m64n16k16.f32.bf16.bf16 {r8,r9,r10,r11,r12,r13,r14,r15}, {wa4,wa5,wa6,wa7}, de1, pf, 1, 1, 0;\n"
        "wgmma.commit_group.sync.aligned;\n"
        "wgmma.mma_async.sync.aligned.m64n24k16.f32.bf16.bf16 {%12,%13,%14,%15,%16,%17,%18,%19,%20,%21,%22,%23}, {hYa0,hYa1,hYa2,hYa3}, daY, 1, 1, 1, 0;\n"
        "wgmma.mma_async.sync.aligned.m64n24k16.f32.bf16.bf16 {%88,%89,%90,%91,%92,%93,%94,%95,%96,%97,%98,%99}, {hYa4,hYa5,hYa6,hYa7}, daY, 1, 1, 1, 0;\n"
        "wgmma.commit_group.sync.aligned;\n"
        "@u2 bra.uni T4Yb;\n"
        "@u1 bra.uni T2Yb;\n"
        "@u0 bra.uni L1Yb;\n"
        "bra.uni L0Yb;\n"
        "T2Y:\n"
        "@t0 bra.uni L3Y;\n"
        "L2Y:\n"
        "wgmma.fence.sync.aligned;\n"
        "wgmma.mma_async.sync.aligned.m64n16k16.f32.bf16.bf16 {r0,r1,r2,r3,r4,r5,r6,r7}, {wa0,wa1,wa2,wa3}, de0, pf, 1, 1, 0;\n"
        "wgmma.mma_async.sync.aligned.m64n16k16.f32.bf16.bf16 {r8,r9,r10,r11,r12,r13,r14,r15}, {wa4,wa5,wa6,wa7}, de1, pf, 1, 1, 0;\n"
        "wgmma.commit_group.sync.aligned;\n"
        "wgmma.mma_async.sync.aligned.m64n24k16.f32.bf16.bf16 {%24,%25,%26,%27,%28,%29,%30,%31,%32,%33,%34,%35}, {hYa0,hYa1,hYa2,hYa3}, daY, 1, 1, 1, 0;\n"
        "wgmma.mma_async.sync.aligned.m64n24k16.f32.bf16.bf16 {%100,%101,%102,%103,%104,%105,%106,%107,%108,%109,%110,%111}, {hYa4,hYa5,hYa6,hYa7}, daY, 1, 1, 1, 0;\n"
        "wgmma.commit_group.sync.aligned;\n"
        "@u2 bra.uni T4Yb;\n"
        "@u1 bra.uni T2Yb;\n"
        "@u0 bra.uni L1Yb;\n"
        "bra.uni L0Yb;\n"
        "L3Y:\n"
        "wgmma.fence.sync.aligned;\n"
        "wgmma.mma_async.sync.aligned.m64n16k16.f32.bf16.bf16 {r0,r1,r2,r3,r4,r5,r6,r7}, {wa0,wa1,wa2,wa3}, de0, pf, 1, 1, 0;\n"
        "wgmma.mma_async.sync.aligned.m64n16k16.f32.bf16.bf16 {r8,r9,r10,r11,r12,r13,r14,r15}, {wa4,wa5,wa6,wa7}, de1, pf, 1, 1, 0;\n"
        "wgmma.commit_group.sync.aligned;\n"
        "wgmma.mma_async.sync.aligned.m64n24k16.f32.bf16.bf16 {%36,%37,%38,%39,%40,%41,%42,%43,%44,%45,%46,%47}, {hYa0,hYa1,hYa2,hYa3}, daY, 1, 1, 1, 0;\n"
        "wgmma.mma_async.sync.aligned.m64n24k16.f32.bf16.bf16 {%112,%113,%114,%115,%116,%117,%118,%119,%120,%121,%122,%123}, {hYa4,hYa5,hYa6,hYa7}, daY, 1, 1, 1, 0;\n"
        "wgmma.commit_group.sync.aligned;\n"
        "@u2 bra.uni T4Yb;\n"
        "@u1 bra.uni T2Yb;\n"
        "@u0 bra.uni L1Yb;\n"
        "bra.uni L0Yb;\n"
        "T4Y:\n"
        "@t0 bra.uni L5Y;\n"
        "L4Y:\n"
        "wgmma.fence.sync.aligned;\n"
        "wgmma.mma_async.sync.aligned.m64n16k16.f32.bf16.bf16 {r0,r1,r2,r3,r4,r5,r6,r7}, {wa0,wa1,wa2,wa3}, de0, pf, 1, 1, 0;\n"
        "wgmma.mma_async.sync.aligned.m64n16k16.f32.bf16.bf16 {r8,r9,r10,r11,r12,r13,r14,r15}, {wa4,wa5,wa6,wa7}, de1, pf, 1, 1, 0;\n"
        "wgmma.commit_group.sync.aligned;\n"
        "wgmma.mma_async.sync.aligned.m64n24k16.f32.bf16.bf16 {%48,%49,%50,%51,%52,%53,%54,%55,%56,%57,%58,%59}, {hYa0,hYa1,hYa2,hYa3}, daY, 1, 1, 1, 0;\n"
        "wgmma.mma_async.sync.aligned.m64n24k16.f32.bf16.bf16 {%124,%125,%126,%127,%128,%129,%130,%131,%132,%133,%134,%135}, {hYa4,hYa5,hYa6,hYa7}, daY, 1, 1, 1, 0;\n"
        "wgmma.commit_group.sync.aligned;\n"
        "@u2 bra.uni T4Yb;\n"
        "@u1 bra.uni T2Yb;\n"
        "@u0 bra.uni L1Yb;\n"
        "bra.uni L0Yb;\n"
        "L5Y:\n"
        "wgmma.fence.sync.aligned;\n"
        "wgmma.mma_async.sync.aligned.m64n16k16.f32.bf16.bf16 {r0,r1,r2,r3,r4,r5,r6,r7}, {wa0,wa1,wa2,wa3}, de0, pf, 1, 1, 0;\n"
        "wgmma.mma_async.sync.aligned.m64n16k16.f32.bf16.bf16 {r8,r9,r10,r11,r12,r13,r14,r15}, {wa4,wa5,wa6,wa7}, de1, pf, 1, 1, 0;\n"
        "wgmma.commit_group.sync.aligned;\n"
        "wgmma.mma_async.sync.aligned.m64n32k16.f32.bf16.bf16 {%60,%61,%62,%63,%64,%65,%66,%67,%68,%69,%70,%71,%72,%73,%74,%75}, {hYa0,hYa1,hYa2,hYa3}, daY, 1, 1, 1, 0;\n"
        "wgmma.mma_async.sync.aligned.m64n32k16.f32.bf16.bf16 {%136,%137,%138,%139,%140,%141,%142,%143,%144,%145,%146,%147,%148,%149,%150,%151}, {hYa4,hYa5,hYa6,hYa7}, daY, 1, 1, 1, 0;\n"
        "wgmma.commit_group.sync.aligned;\n"
        "@u2 bra.uni T4Yb;\n"
        "@u1 bra.uni T2Yb;\n"
        "@u0 bra.uni L1Yb;\n"
        "L0Yb:\n"
        "wgmma.fence.sync.aligned;\n"
        "wgmma.mma_async.sync.aligned.m64n24k16.f32.bf16.bf16 {%0,%1,%2,%3,%4,%5,%6,%7,%8,%9,%10,%11}, {hYb0,hYb1,hYb2,hYb3}, dbY, 1, 1, 1, 0;\n"
        "wgmma.mma_async.sync.aligned.m64n24k16.f32.bf16.bf16 {%76,%77,%78,%79,%80,%81,%82,%83,%84,%85,%86,%87}, {hYb4,hYb5,hYb6,hYb7}, dbY, 1, 1, 1, 0;\n"
        "wgmma.commit_group.sync.aligned;\n"
        "bra.uni CX;\n"
        "L1Yb:\n"
        "wgmma.fence.sync.aligned;\n"
        "wgmma.mma_async.sync.aligned.m64n24k16.f32.bf16.bf16 {%12,%13,%14,%15,%16,%17,%18,%19,%20,%21,%22,%23}, {hYb0,hYb1,hYb2,hYb3}, dbY, 1, 1, 1, 0;\n"
        "wgmma.mma_async.sync.aligned.m64n24k16.f32.bf16.bf16 {%88,%89,%90,%91,%92,%93,%94,%95,%96,%97,%98,%99}, {hYb4,hYb5,hYb6,hYb7}, dbY, 1, 1, 1, 0;\n"
        "wgmma.commit_group.sync.aligned;\n"
        "bra.uni CX;\n"
        "T2Yb:\n"
        "@u0 bra.uni L3Yb;\n"
        "L2Yb:\n"
        "wgmma.fence.sync.aligned;\n"
        "wgmma.mma_async.sync.aligned.m64n24k16.f32.bf16.bf16 {%24,%25,%26,%27,%28,%29,%30,%31,%32,%33,%34,%35}, {hYb0,hYb1,hYb2,hYb3}, dbY, 1, 1, 1, 0;\n"
        "wgmma.mma_async.sync.aligned.m64n24k16.f32.bf16.bf16 {%100,%101,%102,%103,%104,%105,%106,%107,%108,%109,%110,%111}, {hYb4,hYb5,hYb6,hYb7}, dbY, 1, 1, 1, 0;\n"
        "wgmma.commit_group.sync.aligned;\n"
        "bra.uni CX;\n"
        "L3Yb:\n"
        "wgmma.fence.sync.aligned;\n"
        "wgmma.mma_async.sync.aligned.m64n24k16.f32.bf16.bf16 {%36,%37,%38,%39,%40,%41,%42,%43,%44,%45,%46,%47}, {hYb0,hYb1,hYb2,hYb3}, dbY, 1, 1, 1, 0;\n"
        "wgmma.mma_async.sync.aligned.m64n24k16.f32.bf16.bf16 {%112,%113,%114,%115,%116,%117,%118,%119,%120,%121,%122,%123}, {hYb4,hYb5,hYb6,hYb7}, dbY, 1, 1, 1, 0;\n"
        "wgmma.commit_group.sync.aligned;\n"
        "bra.uni CX;\n"
        "T4Yb:\n"
        "@u0 bra.uni L5Yb;\n"
        "L4Yb:\n"
        "wgmma.fence.sync.aligned;\n"
        "wgmma.mma_async.sync.aligned.m64n24k16.f32.bf16.bf16 {%48,%49,%50,%51,%52,%53,%54,%55,%56,%57,%58,%59}, {hYb0,hYb1,hYb2,hYb3}, dbY, 1, 1, 1, 0;\n"
        "wgmma.mma_async.sync.aligned.m64n24k16.f32.bf16.bf16 {%124,%125,%126,%127,%128,%129,%130,%131,%132,%133,%134,%135}, {hYb4,hYb5,hYb6,hYb7}, dbY, 1, 1, 1, 0;\n"
        "wgmma.commit_group.sync.aligned;\n"
        "bra.uni CX;\n"
        "L5Yb:\n"
        "wgmma.fence.sync.aligned;\n"
        "wgmma.mma_async.sync.aligned.m64n32k16.f32.bf16.bf16 {%60,%61,%62,%63,%64,%65,%66,%67,%68,%69,%70,%71,%72,%73,%74,%75}, {hYb0,hYb1,hYb2,hYb3}, dbY, 1, 1, 1, 0;\n"
        "wgmma.mma_async.sync.aligned.m64n32k16.f32.bf16.bf16 {%136,%137,%138,%139,%140,%141,%142,%143,%144,%145,%146,%147,%148,%149,%150,%151}, {hYb4,hYb5,hYb6,hYb7}, dbY, 1, 1, 1, 0;\n"
        "wgmma.commit_group.sync.aligned;\n"
        "bra.uni CX;\n"
        "LEXIT:\n"
        "mov.u32 v2, %%tid.x;\n"
        "shr.u32 v3, v2, 4;\n"
        "and.b32 v0, v3, 1;\n"
        "mad.lo.u32 v0, v0, 1024, %200;\n"
        "and.b32 v1, v2, 7;\n"
        "mad.lo.u32 v0, v1, 128, v0;\n"
        "shr.u32 pp, v2, 3;\n"
        "lop3.b32 v3, v3, pp, 6, 0xe4;\n"
        "add.u32 pp, v2, 1;\n"
        "lop3.b32 pp, v3, pp, 7, 0x28;\n"
        "mad.lo.u32 v1, pp, 16, v0;\n"
        "lop3.b32 pp, v3, v2, 7, 0x28;\n"
        "mad.lo.u32 v0, pp, 16, v0;\n"
        "@pok bra.uni LW;\n"
        "mov.u32 cnt, 0;\n"
        "W2:\n"
        "mbarrier.try_wait.parity.shared.b64 p, [nbar], npar;\n"
        "@p bra.uni LW;\n"
        "add.u32 cnt, cnt, 1;\n"
        "setp.lt.u32 p, cnt, 4000000;\n"
        "@p bra.uni W2;\n"
        "trap;\n"
        "LW:\n"
        "ldmatrix.sync.aligned.m8n8.x4.trans.shared.b16 {hLa0,hLa1,hLa2,hLa3}, [v0+" STR((NP - 2) * 8192 + 0 * SM_ODD + 0) "];\n"
        "ldmatrix.sync.aligned.m8n8.x4.trans.shared.b16 {hLa4,hLa5,hLa6,hLa7}, [v0+" STR((NP - 2) * 8192 + 0 * SM_ODD + 2048) "];\n"
        "wgmma.wait_group.sync.aligned 0;\n"
        "ldmatrix.sync.aligned.m8n8.x4.trans.shared.b16 {hLb0,hLb1,hLb2,hLb3}, [v0+" STR((NP - 2) * 8192 + 0 * SM_ODD + 4096) "];\n"
        "ldmatrix.sync.aligned.m8n8.x4.trans.shared.b16 {hLb4,hLb5,hLb6,hLb7}, [v0+" STR((NP - 2) * 8192 + 0 * SM_ODD + 6144) "];\n"
        "ldmatrix.sync.aligned.m8n8.x4.trans.shared.b16 {hXa0,hXa1,hXa2,hXa3}, [v1+" STR((NP - 2) * 8192 + 1 * SM_ODD + 0) "];\n"
        "ldmatrix.sync.aligned.m8n8.x4.trans.shared.b16 {hXa4,hXa5,hXa6,hXa7}, [v1+" STR((NP - 2) * 8192 + 1 * SM_ODD + 2048) "];\n"
        "ldmatrix.sync.aligned.m8n8.x4.trans.shared.b16 {hXb0,hXb1,hXb2,hXb3}, [v1+" STR((NP - 2) * 8192 + 1 * SM_ODD + 4096) "];\n"
        "ldmatrix.sync.aligned.m8n8.x4.trans.shared.b16 {hXb4,hXb5,hXb6,hXb7}, [v1+" STR((NP - 2) * 8192 + 1 * SM_ODD + 6144) "];\n"
        "mov.b32 %152, hLa0;\n"
        "mov.b32 %153, hLa1;\n"
        "mov.b32 %154, hLa2;\n"
        "mov.b32 %155, hLa3;\n"
        "mov.b32 %156, hLa4;\n"
        "mov.b32 %157, hLa5;\n"
        "mov.b32 %158, hLa6;\n"
        "mov.b32 %159, hLa7;\n"
        "mov.b32 %160, hLb0;\n"
        "mov.b32 %161, hLb1;\n"
        "mov.b32 %162, hLb2;\n"
        "mov.b32 %163, hLb3;\n"
        "mov.b32 %164, hLb4;\n"
        "mov.b32 %165, hLb5;\n"
        "mov.b32 %166, hLb6;\n"
        "mov.b32 %167, hLb7;\n"
        "mov.b32 %168, hXa0;\n"
        "mov.b32 %169, hXa1;\n"
        "mov.b32 %170, hXa2;\n"
        "mov.b32 %171, hXa3;\n"
        "mov.b32 %172, hXa4;\n"
        "mov.b32 %173, hXa5;\n"
        "mov.b32 %174, hXa6;\n"
        "mov.b32 %175, hXa7;\n"
        "mov.b32 %176, hXb0;\n"
        "mov.b32 %177, hXb1;\n"
        "mov.b32 %178, hXb2;\n"
        "mov.b32 %179, hXb3;\n"
        "mov.b32 %180, hXb4;\n"
        "mov.b32 %181, hXb5;\n"
        "mov.b32 %182, hXb6;\n"
        "mov.b32 %183, hXb7;\n"
        "}\n"
        : "=f"(acc[0][0][0]), "=f"(acc[0][0][1]), "=f"(acc[0][0][2]), "=f"(acc[0][0][3]),
          "=f"(acc[0][1][0]), "=f"(acc[0][1][1]), "=f"(acc[0][1][2]), "=f"(acc[0][1][3]),
          "=f"(acc[0][2][0]), "=f"(acc[0][2][1]), "=f"(acc[0][2][2]), "=f"(acc[0][2][3]),
          "=f"(acc[0][3][0]), "=f"(acc[0][3][1]), "=f"(acc[0][3][2]), "=f"(acc[0][3][3]),
          "=f"(acc[0][4][0]), "=f"(acc[0][4][1]), "=f"(acc[0][4][2]), "=f"(acc[0][4][3]),
          "=f"(acc[0][5][0]), "=f"(acc[0][5][1]), "=f"(acc[0][5][2]), "=f"(acc[0][5][3]),
          "=f"(acc[0][6][0]), "=f"(acc[0][6][1]), "=f"(acc[0][6][2]), "=f"(acc[0][6][3]),
          "=f"(acc[0][7][0]), "=f"(acc[0][7][1]), "=f"(acc[0][7][2]), "=f"(acc[0][7][3]),
          "=f"(acc[0][8][0]), "=f"(acc[0][8][1]), "=f"(acc[0][8][2]), "=f"(acc[0][8][3]),
          "=f"(acc[0][9][0]), "=f"(acc[0][9][1]), "=f"(acc[0][9][2]), "=f"(acc[0][9][3]),
          "=f"(acc[0][10][0]), "=f"(acc[0][10][1]), "=f"(acc[0][10][2]), "=f"(acc[0][10][3]),
          "=f"(acc[0][11][0]), "=f"(acc[0][11][1]), "=f"(acc[0][11][2]), "=f"(acc[0][11][3]),
          "=f"(acc[0][12][0]), "=f"(acc[0][12][1]), "=f"(acc[0][12][2]), "=f"(acc[0][12][3]),
          "=f"(acc[0][13][0]), "=f"(acc[0][13][1]), "=f"(acc[0][13][2]), "=f"(acc[0][13][3]),
          "=f"(acc[0][14][0]), "=f"(acc[0][14][1]), "=f"(acc[0][14][2]), "=f"(acc[0][14][3]),
          "=f"(acc[0][15][0]), "=f"(acc[0][15][1]), "=f"(acc[0][15][2]), "=f"(acc[0][15][3]),
          "=f"(acc[0][16][0]), "=f"(acc[0][16][1]), "=f"(acc[0][16][2]), "=f"(acc[0][16][3]),
          "=f"(acc[0][17][0]), "=f"(acc[0][17][1]), "=f"(acc[0][17][2]), "=f"(acc[0][17][3]),
          "=f"(acc[0][18][0]), "=f"(acc[0][18][1]), "=f"(acc[0][18][2]), "=f"(acc[0][18][3]),
          "=f"(acc[1][0][0]), "=f"(acc[1][0][1]), "=f"(acc[1][0][2]), "=f"(acc[1][0][3]),
          "=f"(acc[1][1][0]), "=f"(acc[1][1][1]), "=f"(acc[1][1][2]), "=f"(acc[1][1][3]),
          "=f"(acc[1][2][0]), "=f"(acc[1][2][1]), "=f"(acc[1][2][2]), "=f"(acc[1][2][3]),
          "=f"(acc[1][3][0]), "=f"(acc[1][3][1]), "=f"(acc[1][3][2]), "=f"(acc[1][3][3]),
          "=f"(acc[1][4][0]), "=f"(acc[1][4][1]), "=f"(acc[1][4][2]), "=f"(acc[1][4][3]),
          "=f"(acc[1][5][0]), "=f"(acc[1][5][1]), "=f"(acc[1][5][2]), "=f"(acc[1][5][3]),
          "=f"(acc[1][6][0]), "=f"(acc[1][6][1]), "=f"(acc[1][6][2]), "=f"(acc[1][6][3]),
          "=f"(acc[1][7][0]), "=f"(acc[1][7][1]), "=f"(acc[1][7][2]), "=f"(acc[1][7][3]),
          "=f"(acc[1][8][0]), "=f"(acc[1][8][1]), "=f"(acc[1][8][2]), "=f"(acc[1][8][3]),
          "=f"(acc[1][9][0]), "=f"(acc[1][9][1]), "=f"(acc[1][9][2]), "=f"(acc[1][9][3]),
          "=f"(acc[1][10][0]), "=f"(acc[1][10][1]), "=f"(acc[1][10][2]), "=f"(acc[1][10][3]),
          "=f"(acc[1][11][0]), "=f"(acc[1][11][1]), "=f"(acc[1][11][2]), "=f"(acc[1][11][3]),
          "=f"(acc[1][12][0]), "=f"(acc[1][12][1]), "=f"(acc[1][12][2]), "=f"(acc[1][12][3]),
          "=f"(acc[1][13][0]), "=f"(acc[1][13][1]), "=f"(acc[1][13][2]), "=f"(acc[1][13][3]),
          "=f"(acc[1][14][0]), "=f"(acc[1][14][1]), "=f"(acc[1][14][2]), "=f"(acc[1][14][3]),
          "=f"(acc[1][15][0]), "=f"(acc[1][15][1]), "=f"(acc[1][15][2]), "=f"(acc[1][15][3]),
          "=f"(acc[1][16][0]), "=f"(acc[1][16][1]), "=f"(acc[1][16][2]), "=f"(acc[1][16][3]),
          "=f"(acc[1][17][0]), "=f"(acc[1][17][1]), "=f"(acc[1][17][2]), "=f"(acc[1][17][3]),
          "=f"(acc[1][18][0]), "=f"(acc[1][18][1]), "=f"(acc[1][18][2]), "=f"(acc[1][18][3]),
          "=r"(wo[0][0]), "=r"(wo[0][1]), "=r"(wo[0][2]), "=r"(wo[0][3]),
          "=r"(wo[1][0]), "=r"(wo[1][1]), "=r"(wo[1][2]), "=r"(wo[1][3]),
          "=r"(wo[2][0]), "=r"(wo[2][1]), "=r"(wo[2][2]), "=r"(wo[2][3]),
          "=r"(wo[3][0]), "=r"(wo[3][1]), "=r"(wo[3][2]), "=r"(wo[3][3]),
          "=r"(wo[4][0]), "=r"(wo[4][1]), "=r"(wo[4][2]), "=r"(wo[4][3]),
          "=r"(wo[5][0]), "=r"(wo[5][1]), "=r"(wo[5][2]), "=r"(wo[5][3]),
          "=r"(wo[6][0]), "=r"(wo[6][1]), "=r"(wo[6][2]), "=r"(wo[6][3]),
          "=r"(wo[7][0]), "=r"(wo[7][1]), "=r"(wo[7][2]), "=r"(wo[7][3])
        : "r"(xa0), "r"(xa1), "r"(so0), "r"(bar0), "r"(ea0), "r"(d0), "r"(pl0), "r"(lz), "r"(wa[0]), "r"(wa[1]), "r"(wa[2]),
          "r"(wa[3]), "r"(wa[4]), "r"(wa[5]), "r"(wa[6]), "r"(wa[7]), "r"(ring)
        : "memory");
}
#define CH0 4
#define CH1 7
#define CH2 8
#define CH3 10
#define CH4 9
__device__ __forceinline__ void wgmma_out(float (&o)[4][4], const uint32_t (&a)[4], uint64_t db, bool acc) {
    if (!acc)
        asm volatile(
            "wgmma.mma_async.sync.aligned.m64n32k16.f32.bf16.bf16 {%0,%1,%2,%3,%4,%5,%6,%7,%8,%9,%10,%11,%12,%13,%14,%15}, {%16,%17,%18,%19}, %20, 0, 1, 1, 1;"
            : "=f"(o[0][0]), "=f"(o[0][1]), "=f"(o[0][2]), "=f"(o[0][3]),
              "=f"(o[1][0]), "=f"(o[1][1]), "=f"(o[1][2]), "=f"(o[1][3]),
              "=f"(o[2][0]), "=f"(o[2][1]), "=f"(o[2][2]), "=f"(o[2][3]),
              "=f"(o[3][0]), "=f"(o[3][1]), "=f"(o[3][2]), "=f"(o[3][3])
            : "r"(a[0]), "r"(a[1]), "r"(a[2]), "r"(a[3]), "l"(db)
            : "memory");
    else
        asm volatile(
            "wgmma.mma_async.sync.aligned.m64n32k16.f32.bf16.bf16 {%0,%1,%2,%3,%4,%5,%6,%7,%8,%9,%10,%11,%12,%13,%14,%15}, {%16,%17,%18,%19}, %20, 1, 1, 1, 1;"
            : "+f"(o[0][0]), "+f"(o[0][1]), "+f"(o[0][2]), "+f"(o[0][3]),
              "+f"(o[1][0]), "+f"(o[1][1]), "+f"(o[1][2]), "+f"(o[1][3]),
              "+f"(o[2][0]), "+f"(o[2][1]), "+f"(o[2][2]), "+f"(o[2][3]),
              "+f"(o[3][0]), "+f"(o[3][1]), "+f"(o[3][2]), "+f"(o[3][3])
            : "r"(a[0]), "r"(a[1]), "r"(a[2]), "r"(a[3]), "l"(db)
            : "memory");
}
__device__ __forceinline__ void wgmma_out(float (&o)[7][4], const uint32_t (&a)[4], uint64_t db, bool acc) {
    if (!acc)
        asm volatile(
            "wgmma.mma_async.sync.aligned.m64n56k16.f32.bf16.bf16 {%0,%1,%2,%3,%4,%5,%6,%7,%8,%9,%10,%11,%12,%13,%14,%15,%16,%17,%18,%19,%20,%21,%22,%23,%24,%25,%26,%27}, {%28,%29,%30,%31}, %32, 0, 1, 1, 1;"
            : "=f"(o[0][0]), "=f"(o[0][1]), "=f"(o[0][2]), "=f"(o[0][3]),
              "=f"(o[1][0]), "=f"(o[1][1]), "=f"(o[1][2]), "=f"(o[1][3]),
              "=f"(o[2][0]), "=f"(o[2][1]), "=f"(o[2][2]), "=f"(o[2][3]),
              "=f"(o[3][0]), "=f"(o[3][1]), "=f"(o[3][2]), "=f"(o[3][3]),
              "=f"(o[4][0]), "=f"(o[4][1]), "=f"(o[4][2]), "=f"(o[4][3]),
              "=f"(o[5][0]), "=f"(o[5][1]), "=f"(o[5][2]), "=f"(o[5][3]),
              "=f"(o[6][0]), "=f"(o[6][1]), "=f"(o[6][2]), "=f"(o[6][3])
            : "r"(a[0]), "r"(a[1]), "r"(a[2]), "r"(a[3]), "l"(db)
            : "memory");
    else
        asm volatile(
            "wgmma.mma_async.sync.aligned.m64n56k16.f32.bf16.bf16 {%0,%1,%2,%3,%4,%5,%6,%7,%8,%9,%10,%11,%12,%13,%14,%15,%16,%17,%18,%19,%20,%21,%22,%23,%24,%25,%26,%27}, {%28,%29,%30,%31}, %32, 1, 1, 1, 1;"
            : "+f"(o[0][0]), "+f"(o[0][1]), "+f"(o[0][2]), "+f"(o[0][3]),
              "+f"(o[1][0]), "+f"(o[1][1]), "+f"(o[1][2]), "+f"(o[1][3]),
              "+f"(o[2][0]), "+f"(o[2][1]), "+f"(o[2][2]), "+f"(o[2][3]),
              "+f"(o[3][0]), "+f"(o[3][1]), "+f"(o[3][2]), "+f"(o[3][3]),
              "+f"(o[4][0]), "+f"(o[4][1]), "+f"(o[4][2]), "+f"(o[4][3]),
              "+f"(o[5][0]), "+f"(o[5][1]), "+f"(o[5][2]), "+f"(o[5][3]),
              "+f"(o[6][0]), "+f"(o[6][1]), "+f"(o[6][2]), "+f"(o[6][3])
            : "r"(a[0]), "r"(a[1]), "r"(a[2]), "r"(a[3]), "l"(db)
            : "memory");
}
__device__ __forceinline__ void wgmma_out(float (&o)[8][4], const uint32_t (&a)[4], uint64_t db, bool acc) {
    if (!acc)
        asm volatile(
            "wgmma.mma_async.sync.aligned.m64n64k16.f32.bf16.bf16 {%0,%1,%2,%3,%4,%5,%6,%7,%8,%9,%10,%11,%12,%13,%14,%15,%16,%17,%18,%19,%20,%21,%22,%23,%24,%25,%26,%27,%28,%29,%30,%31}, {%32,%33,%34,%35}, %36, 0, 1, 1, 1;"
            : "=f"(o[0][0]), "=f"(o[0][1]), "=f"(o[0][2]), "=f"(o[0][3]),
              "=f"(o[1][0]), "=f"(o[1][1]), "=f"(o[1][2]), "=f"(o[1][3]),
              "=f"(o[2][0]), "=f"(o[2][1]), "=f"(o[2][2]), "=f"(o[2][3]),
              "=f"(o[3][0]), "=f"(o[3][1]), "=f"(o[3][2]), "=f"(o[3][3]),
              "=f"(o[4][0]), "=f"(o[4][1]), "=f"(o[4][2]), "=f"(o[4][3]),
              "=f"(o[5][0]), "=f"(o[5][1]), "=f"(o[5][2]), "=f"(o[5][3]),
              "=f"(o[6][0]), "=f"(o[6][1]), "=f"(o[6][2]), "=f"(o[6][3]),
              "=f"(o[7][0]), "=f"(o[7][1]), "=f"(o[7][2]), "=f"(o[7][3])
            : "r"(a[0]), "r"(a[1]), "r"(a[2]), "r"(a[3]), "l"(db)
            : "memory");
    else
        asm volatile(
            "wgmma.mma_async.sync.aligned.m64n64k16.f32.bf16.bf16 {%0,%1,%2,%3,%4,%5,%6,%7,%8,%9,%10,%11,%12,%13,%14,%15,%16,%17,%18,%19,%20,%21,%22,%23,%24,%25,%26,%27,%28,%29,%30,%31}, {%32,%33,%34,%35}, %36, 1, 1, 1, 1;"
            : "+f"(o[0][0]), "+f"(o[0][1]), "+f"(o[0][2]), "+f"(o[0][3]),
              "+f"(o[1][0]), "+f"(o[1][1]), "+f"(o[1][2]), "+f"(o[1][3]),
              "+f"(o[2][0]), "+f"(o[2][1]), "+f"(o[2][2]), "+f"(o[2][3]),
              "+f"(o[3][0]), "+f"(o[3][1]), "+f"(o[3][2]), "+f"(o[3][3]),
              "+f"(o[4][0]), "+f"(o[4][1]), "+f"(o[4][2]), "+f"(o[4][3]),
              "+f"(o[5][0]), "+f"(o[5][1]), "+f"(o[5][2]), "+f"(o[5][3]),
              "+f"(o[6][0]), "+f"(o[6][1]), "+f"(o[6][2]), "+f"(o[6][3]),
              "+f"(o[7][0]), "+f"(o[7][1]), "+f"(o[7][2]), "+f"(o[7][3])
            : "r"(a[0]), "r"(a[1]), "r"(a[2]), "r"(a[3]), "l"(db)
            : "memory");
}
__device__ __forceinline__ void wgmma_out(float (&o)[9][4], const uint32_t (&a)[4], uint64_t db, bool acc) {
    if (!acc)
        asm volatile(
            "wgmma.mma_async.sync.aligned.m64n72k16.f32.bf16.bf16 {%0,%1,%2,%3,%4,%5,%6,%7,%8,%9,%10,%11,%12,%13,%14,%15,%16,%17,%18,%19,%20,%21,%22,%23,%24,%25,%26,%27,%28,%29,%30,%31,%32,%33,%34,%35}, {%36,%37,%38,%39}, %40, 0, 1, 1, 1;"
            : "=f"(o[0][0]), "=f"(o[0][1]), "=f"(o[0][2]), "=f"(o[0][3]),
              "=f"(o[1][0]), "=f"(o[1][1]), "=f"(o[1][2]), "=f"(o[1][3]),
              "=f"(o[2][0]), "=f"(o[2][1]), "=f"(o[2][2]), "=f"(o[2][3]),
              "=f"(o[3][0]), "=f"(o[3][1]), "=f"(o[3][2]), "=f"(o[3][3]),
              "=f"(o[4][0]), "=f"(o[4][1]), "=f"(o[4][2]), "=f"(o[4][3]),
              "=f"(o[5][0]), "=f"(o[5][1]), "=f"(o[5][2]), "=f"(o[5][3]),
              "=f"(o[6][0]), "=f"(o[6][1]), "=f"(o[6][2]), "=f"(o[6][3]),
              "=f"(o[7][0]), "=f"(o[7][1]), "=f"(o[7][2]), "=f"(o[7][3]),
              "=f"(o[8][0]), "=f"(o[8][1]), "=f"(o[8][2]), "=f"(o[8][3])
            : "r"(a[0]), "r"(a[1]), "r"(a[2]), "r"(a[3]), "l"(db)
            : "memory");
    else
        asm volatile(
            "wgmma.mma_async.sync.aligned.m64n72k16.f32.bf16.bf16 {%0,%1,%2,%3,%4,%5,%6,%7,%8,%9,%10,%11,%12,%13,%14,%15,%16,%17,%18,%19,%20,%21,%22,%23,%24,%25,%26,%27,%28,%29,%30,%31,%32,%33,%34,%35}, {%36,%37,%38,%39}, %40, 1, 1, 1, 1;"
            : "+f"(o[0][0]), "+f"(o[0][1]), "+f"(o[0][2]), "+f"(o[0][3]),
              "+f"(o[1][0]), "+f"(o[1][1]), "+f"(o[1][2]), "+f"(o[1][3]),
              "+f"(o[2][0]), "+f"(o[2][1]), "+f"(o[2][2]), "+f"(o[2][3]),
              "+f"(o[3][0]), "+f"(o[3][1]), "+f"(o[3][2]), "+f"(o[3][3]),
              "+f"(o[4][0]), "+f"(o[4][1]), "+f"(o[4][2]), "+f"(o[4][3]),
              "+f"(o[5][0]), "+f"(o[5][1]), "+f"(o[5][2]), "+f"(o[5][3]),
              "+f"(o[6][0]), "+f"(o[6][1]), "+f"(o[6][2]), "+f"(o[6][3]),
              "+f"(o[7][0]), "+f"(o[7][1]), "+f"(o[7][2]), "+f"(o[7][3]),
              "+f"(o[8][0]), "+f"(o[8][1]), "+f"(o[8][2]), "+f"(o[8][3])
            : "r"(a[0]), "r"(a[1]), "r"(a[2]), "r"(a[3]), "l"(db)
            : "memory");
}
__device__ __forceinline__ void wgmma_out(float (&o)[10][4], const uint32_t (&a)[4], uint64_t db, bool acc) {
    if (!acc)
        asm volatile(
            "wgmma.mma_async.sync.aligned.m64n80k16.f32.bf16.bf16 {%0,%1,%2,%3,%4,%5,%6,%7,%8,%9,%10,%11,%12,%13,%14,%15,%16,%17,%18,%19,%20,%21,%22,%23,%24,%25,%26,%27,%28,%29,%30,%31,%32,%33,%34,%35,%36,%37,%38,%39}, {%40,%41,%42,%43}, %44, 0, 1, 1, 1;"
            : "=f"(o[0][0]), "=f"(o[0][1]), "=f"(o[0][2]), "=f"(o[0][3]),
              "=f"(o[1][0]), "=f"(o[1][1]), "=f"(o[1][2]), "=f"(o[1][3]),
              "=f"(o[2][0]), "=f"(o[2][1]), "=f"(o[2][2]), "=f"(o[2][3]),
              "=f"(o[3][0]), "=f"(o[3][1]), "=f"(o[3][2]), "=f"(o[3][3]),
              "=f"(o[4][0]), "=f"(o[4][1]), "=f"(o[4][2]), "=f"(o[4][3]),
              "=f"(o[5][0]), "=f"(o[5][1]), "=f"(o[5][2]), "=f"(o[5][3]),
              "=f"(o[6][0]), "=f"(o[6][1]), "=f"(o[6][2]), "=f"(o[6][3]),
              "=f"(o[7][0]), "=f"(o[7][1]), "=f"(o[7][2]), "=f"(o[7][3]),
              "=f"(o[8][0]), "=f"(o[8][1]), "=f"(o[8][2]), "=f"(o[8][3]),
              "=f"(o[9][0]), "=f"(o[9][1]), "=f"(o[9][2]), "=f"(o[9][3])
            : "r"(a[0]), "r"(a[1]), "r"(a[2]), "r"(a[3]), "l"(db)
            : "memory");
    else
        asm volatile(
            "wgmma.mma_async.sync.aligned.m64n80k16.f32.bf16.bf16 {%0,%1,%2,%3,%4,%5,%6,%7,%8,%9,%10,%11,%12,%13,%14,%15,%16,%17,%18,%19,%20,%21,%22,%23,%24,%25,%26,%27,%28,%29,%30,%31,%32,%33,%34,%35,%36,%37,%38,%39}, {%40,%41,%42,%43}, %44, 1, 1, 1, 1;"
            : "+f"(o[0][0]), "+f"(o[0][1]), "+f"(o[0][2]), "+f"(o[0][3]),
              "+f"(o[1][0]), "+f"(o[1][1]), "+f"(o[1][2]), "+f"(o[1][3]),
              "+f"(o[2][0]), "+f"(o[2][1]), "+f"(o[2][2]), "+f"(o[2][3]),
              "+f"(o[3][0]), "+f"(o[3][1]), "+f"(o[3][2]), "+f"(o[3][3]),
              "+f"(o[4][0]), "+f"(o[4][1]), "+f"(o[4][2]), "+f"(o[4][3]),
              "+f"(o[5][0]), "+f"(o[5][1]), "+f"(o[5][2]), "+f"(o[5][3]),
              "+f"(o[6][0]), "+f"(o[6][1]), "+f"(o[6][2]), "+f"(o[6][3]),
              "+f"(o[7][0]), "+f"(o[7][1]), "+f"(o[7][2]), "+f"(o[7][3]),
              "+f"(o[8][0]), "+f"(o[8][1]), "+f"(o[8][2]), "+f"(o[8][3]),
              "+f"(o[9][0]), "+f"(o[9][1]), "+f"(o[9][2]), "+f"(o[9][3])
            : "r"(a[0]), "r"(a[1]), "r"(a[2]), "r"(a[3]), "l"(db)
            : "memory");
}

__device__ __forceinline__ void slow_edge(int ee, int s, float* accn, const __nv_bfloat16* __restrict__ x,
                                          const __nv_bfloat16* __restrict__ sh, const __nv_bfloat16* __restrict__ ea,
                                          const __nv_bfloat16* __restrict__ cg, const __nv_bfloat16* __restrict__ wr,
                                          int lane) {
    float rwv[4] = {0.f, 0.f, 0.f, 0.f};
#pragma unroll 4
    for (int d = 0; d < 16; d++) {
        const float a = __bfloat162float(ea[(size_t)ee * 16 + d]);
        const uint2 wv = *(const uint2*)(wr + d * 128 + lane * 4);
        rwv[0] += a * __uint_as_float(wv.x << 16);
        rwv[1] += a * __uint_as_float(wv.x & 0xffff0000u);
        rwv[2] += a * __uint_as_float(wv.y << 16);
        rwv[3] += a * __uint_as_float(wv.y & 0xffff0000u);
    }
    float A = 0.f;
#pragma unroll
    for (int v = 0; v < 4; v++)
        A += __bfloat162float(cg[((lane >> 2) & 3) * 16 + v * 4 + (lane & 3)]) * __bfloat162float(sh[(size_t)ee * 4 + v]);
    float m[4][4];
#pragma unroll
    for (int w = 0; w < 4; w++)
#pragma unroll
        for (int j = 0; j < 4; j++) m[w][j] = 0.f;
#pragma unroll
    for (int u = 0; u < 4; u++) {
        const uint2 xv = *(const uint2*)(x + (size_t)s * 512 + u * 128 + lane * 4);
        const float x0 = __uint_as_float(xv.x << 16), x1 = __uint_as_float(xv.x & 0xffff0000u);
        const float x2 = __uint_as_float(xv.y << 16), x3 = __uint_as_float(xv.y & 0xffff0000u);
#pragma unroll
        for (int w = 0; w < 4; w++) {
            const float a = __shfl_sync(0xffffffffu, A, u * 4 + w);
            m[w][0] += a * x0;
            m[w][1] += a * x1;
            m[w][2] += a * x2;
            m[w][3] += a * x3;
        }
    }
#pragma unroll
    for (int w = 0; w < 4; w++)
#pragma unroll
        for (int j = 0; j < 4; j++) atomicAdd(accn + w * 128 + lane * 4 + j, m[w][j] * rwv[j]);
}

__device__ __forceinline__ void slow_out(const float* accn, const __nv_bfloat16* __restrict__ wout,
                                         __nv_bfloat16* __restrict__ outn, int lane) {
    float o[4][4];
#pragma unroll
    for (int w = 0; w < 4; w++)
#pragma unroll
        for (int j = 0; j < 4; j++) o[w][j] = 0.f;
#pragma unroll 2
    for (int c = 0; c < 128; c++) {
        const uint2 wv = *(const uint2*)(wout + c * 128 + lane * 4);
        const float w0 = __uint_as_float(wv.x << 16), w1 = __uint_as_float(wv.x & 0xffff0000u);
        const float w2 = __uint_as_float(wv.y << 16), w3 = __uint_as_float(wv.y & 0xffff0000u);
#pragma unroll
        for (int w = 0; w < 4; w++) {
            const float a = __bfloat162float(__float2bfloat16(accn[w * 128 + c]));
            o[w][0] += a * w0;
            o[w][1] += a * w1;
            o[w][2] += a * w2;
            o[w][3] += a * w3;
        }
    }
#pragma unroll
    for (int w = 0; w < 4; w++)
        *(uint2*)(outn + w * 128 + lane * 4) = make_uint2(pack_bf16(o[w][0], o[w][1]), pack_bf16(o[w][2], o[w][3]));
}

static_assert(NW > 2 * NP, "barriers");
#define PLC 1
#define PFT 45
#define PFC 1
#define PFS 1
#define BULK 0
#define PFX 300
#define PX0 0
#define EZ 1
#define PFA 0
#define SPEC 0
#define SH 0
#define FE 2
#define PO 0
#define CL 0
#define HH 0
#define E0 1
#define SW 1
#define TA 0
#define FA 1
#define NA 0
#define PV 0
#define PB 0
#define FPOS 1
#define PW 0
#define TWAIT mbar_lean_u
#define PWAIT mbar_lean
#define TMA_ROW(k) "@pl cp.async.bulk.tensor.2d.shared::cluster.global.mbarrier::complete_tx::bytes [d" #k "], [tm, {r" #k ", %2" #k "}], [b" #k "];\n"
#define TMA_PREP(k) "mad.lo.u32 d" #k ", dd, 512, %3" #k ";\nadd.u32 b" #k ", dd, %2" #k ";\n"
#define RDCLK(c) "mov.u64 ck, %%clock64;\ncvt.u32.u64 " c ", ck;\n"
#define BCAST(d, k) "selp.b32 " d ", a" #k ", 0, me;\nredux.sync.or.b32 " d ", " d ", 0xffffffff;\n"
#define PTIME(t, x, y, z) "shr.u32 " t ", " x ", 16;\nand.b32 c, " y ", 0xffff;\nadd.u32 " t ", " t ", c;\nmad.lo.u32 c, " t ", %13, %14;\nmul.lo.u32 " t ", " t ", %9;\nmin.u32 " t ", " t ", c;\nshr.u32 " t ", " t ", 5;\nadd.u32 " t ", " t ", %6;\nmin.u32 " t ", " t ", lim;\nlop3.b32 " t ", " t ", " z ", 7, 0xd8;\n"
#define PROWA(s, t) "and.b32 " t ", " s ", 0xffc;\nsetp.gt.u32 p, " t ", " STR(LNUL / 2) ";\nmad.lo.u32 " t ", " t ", 2, %5;\nshr.u32 t0, " s ", 11;\nand.b32 t0, t0, 6;\nshr.u32 " s ", " s ", 15;\nadd.u32 t0, t0, " s ";\nselp.s32 " s ", " STR(NGR - 2) ", -2, p;\nadd.u32 t0, t0, " s ";\nmul.lo.s32 t0, t0, " STR(-KEYW) ";\nprmt.b32 " s ", t0, 0, 0x1010;\n"
#define PROWB(s, t, x, y) "ld.shared.v2.u32 {" x ", " y "}, [" t "];\nadd.u16x2 " x ", " x ", " s ";\nadd.u16x2 " y ", " y ", " s ";\n"
#define PROWS(s, x, y) "and.b32 t0, " s ", 0xffc;\nsetp.gt.u32 p, t0, " STR(LNUL / 2) ";\nmad.lo.u32 t0, t0, 2, %5;\nld.shared.v2.u32 {" x ", " y "}, [t0];\nshr.u32 t0, " s ", 11;\nand.b32 t0, t0, 6;\nshr.u32 " s ", " s ", 15;\nadd.u32 t0, t0, " s ";\nselp.s32 " s ", " STR(NGR - 2) ", -2, p;\nadd.u32 t0, t0, " s ";\nmul.lo.s32 t0, t0, " STR(-KEYW) ";\nprmt.b32 t0, t0, 0, 0x1010;\nadd.u16x2 " x ", " x ", t0;\nadd.u16x2 " y ", " y ", t0;\n"
__device__ __forceinline__ void produce(const uint32_t (&pt)[2], const uint32_t (&pz)[8], const uint32_t (&pm)[8], uint32_t bar, uint32_t ps,
                                        int nit, uint32_t psrc, uint32_t tbase, uint32_t lim, uint32_t taug64, uint32_t taus, uint32_t n,
                                        int pr0, uint32_t tau2, uint32_t brk
) {
    asm volatile(
        "{\n.reg .pred p, pl, ok, me;\n.reg .b32 a<6>, u<4>, r<8>, d<8>, b<8>, ps, lim, n, it, pr, pe, tgt, tgu, c, dd, dn, par, t0, t1;\n"
        ".reg .b64 st, tm, ck;\n"
        "elect.sync _|pl, 0xffffffff;\n"
        "mov.b64 tm, {%0, %2};\n"
        "mov.u32 ps, %3;\n"
        "mov.u32 it, %4;\n"
        "mov.u32 lim, %7;\n"
        "mov.u32 n, %10;\n"
        "mov.u32 pr, %12;\n"
        "setp.le.s32 p, it, 0;\n"
        "bar.sync 4, " STR(NT) ";\n"
        "@p bra.uni PEND;\n"
        "PBAT:\n"
        "ld.shared.u16 c, [ps];\n"
        "ld.shared.u16 t1, [ps+4];\n"
        "add.u32 ps, ps, 256;\n"
        "mul.lo.u32 par, n, " STR(65536 / NP + 1) ";\n"
        "shr.u32 par, par, 16;\n"
        "mad.lo.s32 dn, par, " STR(-NP) ", n;\n"
        "add.u32 n, n, 32;\n"
        "not.b32 par, par;\n"
        PROWS("c", "a0", "a1") PROWS("t1", "a2", "a3")
        "min.s32 pe, it, 32;\n"
        "sub.s32 it, it, 32;\n"
        "add.u32 pe, pe, pr;\n"
        PTIME("a4", "a0", "a1", "dn") PTIME("a5", "a2", "a3", "par")
        "add.u32 lim, lim, %8;\n"
        "PLOOP:\n"
        "setp.eq.u32 me, n, pr;\n"
        "add.u32 pr, pr, 1;\n"
        BCAST("tgt", 4) BCAST("tgu", 5) BCAST("u0", 0) BCAST("u1", 1) BCAST("u2", 2) BCAST("u3", 3)
        "and.b32 dd, tgt, 7;\n"
        "mad.lo.u32 dd, dd, 16, %1;\n"
        "and.b32 par, tgu, 1;\n"
        "mbarrier.test_wait.parity.shared.b64 ok, [dd+8], par;\n"
        "prmt.b32 r0, u0, 0, 0x4104;\nprmt.b32 r1, u0, 0, 0x4324;\nprmt.b32 r2, u1, 0, 0x4104;\nprmt.b32 r3, u1, 0, 0x4324;\n"
        "prmt.b32 r4, u2, 0, 0x4104;\nprmt.b32 r5, u2, 0, 0x4324;\nprmt.b32 r6, u3, 0, 0x4104;\nprmt.b32 r7, u3, 0, 0x4324;\n"
        TMA_PREP(0) TMA_PREP(1) TMA_PREP(2) TMA_PREP(3) TMA_PREP(4) TMA_PREP(5) TMA_PREP(6) TMA_PREP(7)
        RDCLK("c")
        "sub.s32 c, c, tgt;\n"
        "setp.ge.and.s32 p, c, 0, ok;\n"
        "@!p bra.uni PSLP;\n"
        "PRES:\n"
        "@pl mbarrier.arrive.expect_tx.shared.b64 _, [b0], 8192;\n"
        TMA_ROW(0) TMA_ROW(1) TMA_ROW(2) TMA_ROW(3)
        RDCLK("c")
        "sub.s32 c, c, tgu;\n"
        "setp.lt.s32 p, c, 0;\n"
        "@p bra.uni PSL2;\n"
        "PRE2:\n"
        TMA_ROW(4) TMA_ROW(5) TMA_ROW(6) TMA_ROW(7)
        "setp.lt.u32 p, pr, pe;\n"
        "@p bra.uni PLOOP;\n"
        "setp.gt.s32 p, it, 0;\n"
        "@p bra.uni PBAT;\n"
        "bra.uni PEND;\n"
        "PSL2:\n"
        "nanosleep.u32 " STR(PSLEEP) ";\n"
        RDCLK("c")
        "sub.s32 c, c, tgu;\n"
        "setp.lt.s32 p, c, 0;\n"
        "@p bra.uni PSL2;\n"
        "bra.uni PRE2;\n"
        "PSL1:\n"
        "nanosleep.u32 " STR(PSLEEP) ";\n"
        RDCLK("c")
        "sub.s32 c, c, tgt;\n"
        "PSLP:\n"
        "setp.lt.s32 p, c, 0;\n"
        "@p bra.uni PSL1;\n"
        "@ok bra.uni PRES;\n"
        "mov.u32 c, 0;\n"
        "PW:\n"
        "mbarrier.try_wait.parity.shared.b64 p, [b0+8], par;\n"
        "@p bra.uni PRES;\n"
        "add.u32 c, c, 1;\n"
        "setp.lt.u32 p, c, 4000000;\n"
        "@p bra.uni PW;\n"
        "trap;\n"
        "PEND:\n}"
        :
        : "r"(pt[0]), "r"(bar), "r"(pt[1]), "r"(ps), "r"(nit), "r"(psrc), "r"(tbase), "r"(lim), "r"(taug64), "r"(taus), "r"(n), "n"(0),
          "r"(pr0), "r"(tau2), "r"(brk), "n"(0), "n"(0), "n"(0), "n"(0), "n"(0), "r"(pz[0]), "r"(pz[1]), "r"(pz[2]), "r"(pz[3]), "r"(pz[4]),
          "r"(pz[5]), "r"(pz[6]), "r"(pz[7]), "n"(0), "n"(0), "r"(pm[0]), "r"(pm[1]), "r"(pm[2]), "r"(pm[3]), "r"(pm[4]), "r"(pm[5]),
          "r"(pm[6]), "r"(pm[7])
        : "memory");
}
template <int J0, int JN>
__device__ __forceinline__ void put_agg(const float (&acc)[2][NJ][4], uint32_t tb, int u) {
    const int h = u & 1, j = u & ~1;
    const float(*a)[4] = acc[h] + J0 + (j < JN ? j : 0);
    if (j + 1 < JN)
        stsm4(tb + h * SM_ODD + (J0 + j) * 256, pack_bf16(a[0][0], a[0][1]), pack_bf16(a[0][2], a[0][3]), pack_bf16(a[1][0], a[1][1]),
              pack_bf16(a[1][2], a[1][3]));
    else if (j < JN)
        stsm2(tb + h * SM_ODD + (J0 + j) * 256, pack_bf16(a[0][0], a[0][1]), pack_bf16(a[0][2], a[0][3]));
}
template <int JN>
__device__ __forceinline__ void pin(float (&o)[JN][4]) {
#pragma unroll
    for (int j = 0; j < JN; j++)
#pragma unroll
        for (int k = 0; k < 4; k++) asm volatile("" : "+f"(o[j][k])::"memory");
}
#define WG_WAIT(n) asm volatile("wgmma.wait_group.sync.aligned %0;" ::"n"(n) : "memory")
#define WG_COMMIT() asm volatile("wgmma.commit_group.sync.aligned;" ::: "memory")
#define KA 2
template <int K0, int JN, class F>
__device__ __forceinline__ void mul_out(float (&o)[JN][4], const uint32_t (&a)[8][4], uint32_t db, F f) {
    asm volatile("wgmma.fence.sync.aligned;" ::: "memory");
#pragma unroll
    for (int ks = 0; ks < 8; ks++) {
        wgmma_out(o, a[ks], (uint64_t)(db + (((ks >> 2) * SM_ODD + (ks & 3) * (NJ * 256)) >> 4)) | (16ull << 32), ks);
        if (ks == K0 - 1 || ks == 7) WG_COMMIT();
        if (ks == K0 - 1) WG_WAIT(1);
        if (ks >= K0 - 1) f(K0 ? ks - K0 + 1 : ks);
    }
}
static_assert(CH1 <= 8 && CH2 <= 8 && CH3 <= 10 && CH4 <= 10 && KA <= 3 && NJ == 19 && NP == 5 && SM_EVEN == 0 && SM_ODD % 1024 == 128 && CH0 + CH2 <= 13 && CH1 <= 13 && CH0 + CH2 + CH4 <= 21 && CH1 + CH3 <= 21, "epilogue");
__device__ constexpr int out_n(int st) { return st == 0 ? CH0 : st == 1 ? CH1 : st == 2 ? CH2 : st == 3 ? CH3 : CH4; }
__device__ constexpr int out_j(int st) { return st == 1 ? CH0 : st == 2 ? CH0 + CH1 : st == 4 ? CH3 : 0; }
__device__ constexpr int out_at(int st) { return (NJ + (st == 2 ? CH0 : st == 3 ? CH1 : st == 4 ? CH0 + CH2 : 0)) * 1024 + (st & 1) * SM_ODD; }
#define WG_SYNC(w) asm volatile("bar.sync %0, 128;" ::"r"((w) + 1) : "memory")
#define HAND(st, w) asm volatile("bar.arrive %0, 192;" ::"r"(6 + 2 * (st) + (w)) : "memory")
template <int ST, int JN>
__device__ __forceinline__ void put_out(float (&o)[JN][4], uint32_t c, int u, int w) {
    if (u == 0) pin(o);
    const int j = 2 * u < JN ? 2 * u : 0;
    if (2 * u + 1 < JN)
        stsm4t(c + out_at(ST) + j * 1024, pack_bf16(o[j][0], o[j][1]), pack_bf16(o[j][2], o[j][3]), pack_bf16(o[j + 1][0], o[j + 1][1]),
               pack_bf16(o[j + 1][2], o[j + 1][3]));
    else if (2 * u < JN)
        stsm2t(c + out_at(ST) + j * 1024, pack_bf16(o[j][0], o[j][1]), pack_bf16(o[j][2], o[j][3]));
    if (u == (JN - 1) / 2) HAND(ST, w);
}
__device__ __forceinline__ void get_w(uint32_t (&a)[8][4], uint32_t ce, uint32_t co, int ks) {
    if (ks >= 0 && ks < 8)
        asm volatile("ldmatrix.sync.aligned.m8n8.x4.trans.shared.b16 {%0,%1,%2,%3}, [%4];"
                     : "=r"(a[ks & 7][0]), "=r"(a[ks & 7][1]), "=r"(a[ks & 7][2]), "=r"(a[ks & 7][3])
                     : "r"((ks < 4 ? ce : co + SM_ODD) + (ks & 3) * 2048)
                     : "memory");
}
#define TB 8
#define DELAY 4100
#define NULW 0xf0000000
#define DREF 1
#define K0(npr) ((2 * NP - 2 - (npr) % NP) % NP)
#define GCODE(g) ((((g) >> 1) + 1) << 12 | ((g) & 1) << 15)
#define SYNC() asm volatile("bar.sync 0;" ::: "memory")
#define LISTS() asm volatile("bar.sync 4, %0;" ::"n"(NT) : "memory")
#define NB (2 * NGR * 32)
#define PREF(p, tot, k0, n)                                                                                       \
    {                                                                                                             \
        _Pragma("unroll") for (int k = (k0); k < (k0) + (n); k++) {                                                \
            const int l = (k * nbins + bin) * 128 + tid - NB;                                                     \
            if (l < (tot)) asm volatile("prefetch.global.L2 [%0];" ::"l"(p + (size_t)l * 64) : "memory");         \
        }                                                                                                         \
    }
#define WX 010
#define WS 0011
#define WE 000
#define PL 8
#define PLE 0
#define DG(v, i) ((v) >> (6 - 3 * (i)) & 7)
#define PREW(i)                                                                                \
    PREF(x, N * 8, (i > 0 ? DG(WX, 0) : 0) + (i > 1 ? DG(WX, 1) : 0), DG(WX, i))                \
    PREF(sh, E / 16, (i > 0 ? DG(WS, 0) : 0) + (i > 1 ? DG(WS, 1) : 0), DG(WS, i))              \
    PREF(ea, E / 4, (i > 0 ? DG(WE, 0) : 0) + (i > 1 ? DG(WE, 1) : 0), DG(WE, i))
#define PFN (DG(WX, 0) + DG(WX, 1) + DG(WX, 2))
#define PFE (DG(WE, 0) + DG(WE, 1) + DG(WE, 2))
__global__ void __launch_bounds__(NT, 1)
main_kernel(const int* __restrict__ dst, const int* __restrict__ src, uint4* __restrict__ gbin, int E, int nbins, int fast_ok,
            int npb, unsigned npb_magic, int N, const __grid_constant__ CUtensorMap tme,
            const __grid_constant__ CUtensorMap tmx, const __grid_constant__ CUtensorMap tmw,
            const __grid_constant__ CUtensorMap tmo, const __nv_bfloat16* __restrict__ x,
            const __nv_bfloat16* __restrict__ sh, const __nv_bfloat16* __restrict__ ea,
            const __nv_bfloat16* __restrict__ cg, const __nv_bfloat16* __restrict__ wr,
            const __nv_bfloat16* __restrict__ wout, __nv_bfloat16* __restrict__ out, int tau16, int toff, int delay,
            int tau2, int brk) {
    extern __shared__ __align__(1024) unsigned char smem[];
    const uint32_t sb = __shfl_sync(0xffffffffu, s2u(smem), 0);
    const int tid = threadIdx.x;
    const int warp = __shfl_sync(0xffffffffu, tid >> 5, 0), lane = tid & 31;
    const int g = lane >> 2, t = lane & 3;

    TLSTAMP(0);
    TLINIT();
    const int bin = blockIdx.x;
    const int node0 = bin * npb, hpb = npb >> 1;
    uint32_t wa[8];
    uint2 c0 = make_uint2(0, 0), c1 = c0;
    bool fast = fast_ok;
    if (fast_ok) {
        int pd[EPS], ps[EPS];
        const int e0 = ((tid >> 5) * nbins + bin) * 32 + lane;
#pragma unroll
        for (int k = 0; k < EPS; k++)
            asm volatile("ld.global.nc.u32 %0, [%1];" : "=r"(pd[k]) : "l"(dst + min(e0 + k * NT * nbins, E - 1)));
#pragma unroll
        for (int k = 0; k < EPS; k++)
            asm volatile("ld.global.nc.u32 %0, [%1];" : "=r"(ps[k]) : "l"(src + min(e0 + k * NT * nbins, E - 1)));
        const unsigned ck0 = clock();
        const uint32_t cnt0 = (sb + SC_CNT + 8191) & ~8191;
        {
            const int ch = (SW ? tid ^ tid >> 3 : tid) & 7;
            const uint32_t nul = NULW + ((bin & 3) * 8 + ch) * (80 << 15);
#pragma unroll
            for (int k = 0; k < 4; k++) {
                const int i = tid + k * NT;
                if (i < SC_EXT / 16 ? ch != 7 : i < SC_TAB / 16) sts_v4(sb + SC_ENT + i * 16, make_uint4(nul, nul, nul, nul));
            }
            if (warp == NW - 1) {
                uint32_t now;
                asm volatile("mov.u32 %0, %%globaltimer_lo;" : "=r"(now));
                now = __shfl_sync(0xffffffffu, (now & 0x7ffff) | nul, SW ? 7 ^ (NW - 1) * 4 % 8 : 7);
#pragma unroll
                for (int k = 0; k < MAXBINS / 32; k++) sts_v4(sb + SC_ENT + (k * 32 + lane) * 128 + (SW ? (~lane & 7) * 16 : 112), make_uint4(now, now, now, now));
                if (lane == 0) {
                    asm volatile("prefetch.tensormap [%0];" ::"l"(&tme) : "memory");
                    asm volatile("prefetch.tensormap [%0];" ::"l"(&tmx) : "memory");
                    asm volatile("prefetch.tensormap [%0];" ::"l"(&tmw) : "memory");
                    asm volatile("prefetch.tensormap [%0];" ::"l"(&tmo) : "memory");
                    sts_v2(sb + SM_MISC + MI_INT, 0, now);
                    sts_u32(sb + SM_MISC + MI_INT + 44, 0);
                    sts_u32(sb + SM_MISC + MI_INT + 24, 0);
                }
            }
            sts_v4(cnt0 + tid * 16, make_uint4(0, 0, 0, 0));
            if (tid < (SC_END - SC_HIST) / 16) {
                const uint32_t v = (tid >> 3) == MAXBINS / 32 ? 0x80000000u : 0;
                sts_v4(sb + SC_HIST + tid * 16, make_uint4(v, v, v, v));
            }
            if (tid < 2 * HPB) {
                const int w = tid >= hpb, loc = tid - (w ? hpb : 0), gr = min(loc * 43 >> 8, NGR - 1);
                sts_u32(sb + SC_TAB + tid * 4, ((w ? NGR : 0) + gr) * (KEYW << 15) + loc - gr * GSZ);
            }
        }
        if (elect()) {
#pragma unroll
            for (int k = 0; k < (NP > 5 ? 4 : 2); k++) mbar_init(sb + SM_BAR + (warp * (NP > 5 ? 4 : 2) + k) * 8, 3 + (k & 1));
        }
#pragma unroll
        for (int k = 0; k < TS / 2; k++) sts_v4(sb + SM_BT + (tid + k * NT) * 16, make_uint4(0, 0, 0, 0));
        if (tid < 8) sts_v4(sb + SM_BT + (tid + TS / 2 * NT) * 16, make_uint4(0, 0, 0, 0));
        if (tid < 4) {
            sts_u16(sb + SM_SRC + (LNUL + tid) * 2, N);
            sts_u32(sb + SM_EID + (LNUL + tid) * 4, 0x80000000u);
        }
        TLS(1);
        __syncthreads();
        {
            const uint32_t z = lds_u32(sb + SM_MISC + MI_INT);
            int pb[EPS], pr[EPS];
            uint32_t v[EPS];
#pragma unroll
            for (int k = 0; k < EPS; k++) {
                pb[k] = (int)__umulhi((unsigned)pd[k], npb_magic + z);
                v[k] = lds_u32(sb + SC_TAB + (pd[k] - pb[k] * npb) * 4);
                pr[k] = atoms_add(sb + SC_HIST + (e0 + k * NT * nbins < E ? pb[k] : MAXBINS + lane) * 4, 4);
            }
            int mx = 0;
#pragma unroll
            for (int k = 0; k < EPS; k++) {
                v[k] += ps[k] * (32768 + z) + (k * NT + tid + 32) * 8;
                asm volatile("{\n.reg .pred p;\nsetp.lt.u32 p, %0, 128;\n@p st.shared.u32 [%1], %2;\n}" ::"r"(pr[k]),
                             "r"(SW ? (sb + SC_ENT + pb[k] * 128 + (pb[k] & 7) * 16) ^ pr[k] : sb + SC_ENT + pb[k] * 128 + pr[k]), "r"(v[k])
                             : "memory");
                mx = max(mx, pr[k]);
            }
            if (mx >= 128) {
#pragma unroll
                for (int k = 0; k < EPS; k++)
                    if (pr[k] >= 128 && pr[k] < 192) sts_u32(sb + SC_EXT - 128 + pb[k] * 64 + pr[k], v[k]);
            }
        }
        TLS(6);
        __syncthreads();
        const unsigned c6 = DREF ? ck0 : clock();
        if (warp == NW - 1 && elect()) {
            FENCE_ASYNC();
            tma_store(&tme, sb + SC_ENT, bin * 32, 0);
            asm volatile("cp.async.bulk.commit_group;" ::: "memory");
        }
        if (tid < nbins && lds_u32(sb + SC_HIST + tid * 4) >= 128) {
#pragma unroll 1
            for (int k = 0; k < 4; k++) __stcg(gbin + GEX + (tid * nbins + bin) * 4 + k, lds_v4(sb + SC_EXT + tid * 64 + k * 16));
        }
#pragma unroll
        for (int k = 0; k < EPS; k++) {
            if (ps[k] < (N * PFT >> 10)) {
                const uint32_t p = atoms_add(sb + SM_MISC + MI_INT + 24, 4);
                if (p < PFC * 512) sts_u32(sb + SM_EA + p, min(e0 + k * NT * nbins, E - 1));
            }
        }
        if (warp >= 2 * NGR) {
            uint2 wv[4];
#pragma unroll
            for (int k = 0; k < 4; k++)
                asm volatile("ld.global.nc.v2.u32 {%0,%1}, [%2];" : "=r"(wv[k].x), "=r"(wv[k].y) : "l"((const uint2*)wr + (tid - NB) + k * 128));
#pragma unroll
            for (int k = 0; k < 4; k++) sts_v2(sb + SC_WR + (lane >> 1) * 272 + (warp - 2 * NGR + k * 4) * 16 + (lane & 1) * 8, wv[k].x, wv[k].y);
            PREW(0);
            const int w = warp & 1, j = (warp >> 1) & 1;
            const uint32_t bar0 = sb + SM_BAR + w * NP * 16, ring = sb + w * RING_BYTES + j * 4096;
            uint32_t pz[8], pm[8], pt[2];
            const uint32_t lz = lane & (E >> 31);
            {
                const uint32_t d0 = ring - j * 2048 - bar0 * 512 + lz;
#pragma unroll
                for (int k = 0; k < 8; k++) {
                    pz[k] = __shfl_sync(0xffffffffu, lz, k);
                    pm[k] = __shfl_sync(0xffffffffu, d0 + (k & 1) * SM_ODD + (k >> 1 & 1) * 1024 + (k >> 2) * 4096, 0);
                }
                asm("mov.b64 {%0, %1}, %2;" : "=r"(pt[0]), "=r"(pt[1]) : "l"(&tmx));
                pt[0] = __shfl_sync(0xffffffffu, pt[0] + lz, 0);
                pt[1] = __shfl_sync(0xffffffffu, pt[1] + lz, 0);
            }
            uint32_t sg0 = 0x01010101 | ((lane & 1) << 8 | (lane & 2) << 15 | (lane & 4) << 22) * 0xfe;
            uint32_t sg2 = (0x0101 | ((lane >> 3 & 1) | (lane & 16) << 4) * 0xfe) * 0x10001 ^ 0xfefe0000;
            uint32_t cand = ((lane & 1) << 3 | (lane & 2) << 5 | (lane & 4) << 7 | (lane & 8) << 9) * 7 + (lane & 16) * (15 << 11);
            uint32_t sg1 = __shfl_sync(0xffffffffu, sg0 ^ 0xfefefefe, lane), gb = cnt0 + (warp & 2) * NBK + lane * 8;
            sg0 = __shfl_sync(0xffffffffu, sg0, lane), sg2 = __shfl_sync(0xffffffffu, sg2, lane);
            cand = __shfl_sync(0xffffffffu, cand, lane), gb = __shfl_sync(0xffffffffu, gb, lane);
            const uint32_t wm = __shfl_sync(0xffffffffu, lz - w, lane);
            FENCE_ASYNC();
            asm volatile("bar.sync 8, %0;" ::"n"(NT) : "memory");
            while ((int)(clock() - c6) < (PFA ? PFA : delay + PFX)) {}
            {
                const uint32_t n = lds_u32(sb + SM_MISC + MI_INT + 24);
#pragma unroll
                for (int k = 0; k < PFC; k++) {
                    const uint32_t i = (tid - NB + k * 128) * 4, e = lds_u32(sb + SM_EA + i);
                    if (i < n) {
                        asm volatile("prefetch.global.L2 [%0];" ::"l"(ea + (size_t)e * 16) : "memory");
                        asm volatile("prefetch.global.L2 [%0];" ::"l"(sh + (size_t)e * 4) : "memory");
                    }
                }
            }
            SYNC();
            PREW(1);
            if (warp == NW - 1 && elect()) {
                asm volatile("cp.async.bulk.global.shared::cta.bulk_group [%0], [%1], %2;" ::"l"(gbin + bin * nbins * 8), "r"(sb + SM_BT),
                             "r"(nbins * 128)
                             : "memory");
                asm volatile("cp.async.bulk.commit_group;" ::: "memory");
                const uint32_t t0 = lds_u32(sb + SM_MISC + MI_INT + 4);
                uint32_t now, ck;
                asm volatile(
                    "{\n.reg .pred p;\n.reg .b32 a, n;\nmov.u32 a, %%globaltimer_lo;\nmov.u32 n, 0;\n"
                    "TK:\nmov.u32 %0, %%globaltimer_lo;\nmov.u32 %1, %%clock;\nadd.u32 n, n, 1;\n"
                    "setp.lt.u32 p, n, " STR(TB) ";\nsetp.eq.and.u32 p, %0, a, p;\n@p bra TK;\n}"
                    : "=r"(now), "=r"(ck));
                sts_u32(sb + SM_MISC + MI_INT + 4, ck - (min((now - t0) & 0x7ffff, 1u << 16) * 63 >> 5) + toff);
            }
            asm volatile("bar.sync 5, %0;" ::"n"(NT) : "memory");
            const uint4 nb = lds_v4(sb + SM_MISC + MI_INT + 32);
            const unsigned tbase = lds_u32(sb + SM_MISC + MI_INT + 4);
            fast = nb.w == 0;
            int df;
            asm("{\n.reg .s32 a;\ndp4a.u32.s32 a, %1, %4, 0;\ndp4a.u32.s32 a, %2, %5, a;\ndp4a.u32.s32 %0, %3, %6, a;\n}"
                : "=r"(df)
                : "r"(nb.x), "r"(nb.y), "r"(nb.z), "r"(sg0), "r"(sg1), "r"(sg2));
            const uint32_t best = __reduce_min_sync(0xffffffffu, abs(df) << (NJ + 1) | (df < 0) << NJ | cand);
            uint32_t swp = best ^ -w;
            uint32_t ga[NGR];
#pragma unroll
            for (int k = 0; k < NGR; k++) {
                const int sh = k < 4 ? 3 * k : 3 * k - 9;
                ga[k] = gb + (((k < 4 ? best : best >> 9) ^ wm) & 1 << sh) * (NGR * NBK * 4 >> sh);
            }
            asm volatile("bar.sync %0, %1;" ::"r"(6 + (ga[0] & ga[1] & ga[2] & ga[3] & ga[4] & ga[5] & lz)), "n"(NT) : "memory");
            TLA(1, 0);
            if (fast) {
                uint32_t v[NGR][2], mx = 0;
#pragma unroll
                for (int k = 0; k < NGR; k++) {
                    const uint2 u = lds_v2(ga[k] + k * (NBK * 4));
                    v[k][0] = u.x, v[k][1] = u.y;
                }
                const uint32_t sq = sb + SM_SEQ + w * SEQCAP * 2;
                const int all = __dp4a(nb.x, 0x01010101u, __dp4a(nb.y, 0x01010101u, __dp4a(nb.z, 0x01010101u, 0u))), d = best >> (NJ + 1);
                const int nst = (all + ((swp >> NJ) & 1 ? -d : d)) >> 1;
                const int npr = __shfl_sync(0xffffffffu, (nst + 3) >> 2, 0), k0 = K0(npr);
                const unsigned taug = __float2uint_rz(__fdividef((float)(N * tau16 >> 4), (float)max(npr, 1)));
                const uint32_t lim = tbase + (N * tau16 >> 8) + lane * taug;
                uint32_t a = -(__popc(swp & 0111111) * (NGR * GCAP + GEXT) + NGR * (NGR - 1) / 2 * GCAP + NGR * 4) + 2 * sq;
#pragma unroll
                for (int k = 0; k < NGR; k++) a += v[k][0] & 0xffc;
                a >>= 1;
                const uint32_t a0 = a;
#pragma unroll
                for (int c = 0; c < 2; c++)
#pragma unroll
                    for (int k = 0; k < NGR; k++) {
                        asm volatile(
                            "{\n.reg .pred p, q;\n.reg .b16 h;\n"
                            "setp.ge.u32 p, %1, 0x10000;\nsetp.ge.u32 q, %1, 0x40000;\n"
                            "cvt.u16.u32 h, %1;\n@p st.shared.u16 [%0], h;\n"
                            "add.u16 h, h, 4;\n@q st.shared.u16 [%0+2], h;\n}" ::"r"(a), "r"(v[k][c])
                            : "memory");
                        a += v[k][c] >> 16;
                        mx = max(mx, v[k][c]);
                    }
                if (mx >= 0x60000) {
                    a = a0;
#pragma unroll
                    for (int c = 0; c < 2; c++)
#pragma unroll
                        for (int k = 0; k < NGR; k++) {
#pragma unroll 1
                            for (uint32_t n = 4; n < v[k][c] >> 16; n += 2) sts_u16(a + n, v[k][c] + 2 * n);
                            a += v[k][c] >> 16;
                        }
                }
                if (!j) {
                    sts_u16(sq + (nst + lane) * 2, (LNUL + 4) | (lane < (-nst & 3) ? GCODE(0) : 0x7c01));
                    if (lane < k0) {
                        mbar_arrive_cnt(sb + SM_BAR + (w * NP + lane) * 16, 3);
                        mbar_arrive_cnt(sb + SM_BAR + (w * NP + lane) * 16 + 8, 4);
                    }
                    if (lane == 0) {
                        sts_v2(sb + SM_MISC + MI_INT + 8 + w * 8, npr, k0);
                        sts_u32(sb + SM_MISC + MI_INT + 48 + w * 4, swp);
                    }
                }
                TLA(10, 0);
                asm volatile("cp.async.bulk.wait_group.read 0;" ::: "memory");
                asm volatile("bar.arrive 3, %0;" ::"n"(NT) : "memory");
                PREW(2);
                TLS(5);
                FENCE_ASYNC();
                asm volatile("setmaxnreg.dec.sync.aligned.u32 %0;" ::"n"(PREG));
                produce(pt, pz, pm, bar0, sq + j * 2 + lane * 8, npr, sb + SM_SRC - 8, tbase, lim, taug * 32, tau16, k0 + lane, k0 + 32, tau2, brk
                );
        if (elect()) {
            const uint32_t d = ring + (NP - 2) * 8192 + j * (SM_ODD - 4096);
            const uint32_t fb = bar0 + (NP - 2) * 16, par = ~((lds_u32(sb + SM_MISC + MI_INT + 8 + w * 8) + 1) / NP) & 1;
            mbar_wait(fb + 24, par);
            mbar_arrive_cnt(fb + j * 16, j ? 1 : 3);
            mbar_expect_tx(fb + 16, 8192);
            tma_2d(d, &tmw, fb + 16, 0, j * 64);
            if (j) mbar_arrive(bar0 + DUMB);
            mbar_expect_tx(bar0 + DUMB, 8192);
            tma_2d(d + 8192, &tmw, bar0 + DUMB, 64, j * 64);
        }
        TLMAX(12);
        swp = lds_u32(sb + SM_MISC + MI_INT + 48 + w * 4);
        const int row = 2 * lane < hpb ? (node0 + ((swp >> lane) & 1) * hpb) * 4 + lane * 8 : N * 4;
        const CUtensorMap* po = &tmo;
        asm volatile("" : "+l"(po));
#pragma unroll
        for (int st = 0; st < 5; st++) {
            int rw[5];
#pragma unroll
            for (int k = 0; k < 5; k++)
                if (2 * k < out_n(st)) rw[k] = __shfl_sync(0xffffffffu, row, out_j(st) + 2 * k + (2 * k + 1 < out_n(st) ? j : j * (31 - out_j(st) - 2 * k)));
            asm volatile("bar.sync %0, 192;" ::"r"(6 + 2 * st + w) : "memory");
            FENCE_ASYNC();
            if (elect()) {
#pragma unroll
                for (int k = 0; k < 5; k++)
                    if (2 * k < out_n(st)) tma_store(po, ring - j * 3072 + out_at(st) + k * 2048, st < 3 ? 0 : 64, rw[k]);
                asm volatile("cp.async.bulk.commit_group;" ::: "memory");
            }
        }
        asm volatile("cp.async.bulk.wait_group.read 0;" ::: "memory");
        TLMAX(4);
        TLEND();
        return;
            }
        } else {
        asm volatile("bar.arrive 8, %0;" ::"n"(NT) : "memory");
        uint32_t en[5][4], es[5][4], rank[5][4], ca[5][4];
        if (warp >= 8 && (g >> 2) == (t >> 1)) {
            const uint2* cp = (const uint2*)cg + (g & 3) * 4 + (t & 1) * 2;
            asm volatile("ld.global.nc.v2.u32 {%0,%1}, [%2];" : "=r"(c0.x), "=r"(c0.y) : "l"(cp));
            asm volatile("ld.global.nc.v2.u32 {%0,%1}, [%2];" : "=r"(c1.x), "=r"(c1.y) : "l"(cp + 1));
        }
        const int sg[5] = {tid >> 3, (tid >> 3) + NB / 8, (tid >> 3) + NB / 4, (tid >> 3) + (lane & 4) * (NB / 32), (tid >> 3) + NB / 4};
        const uint4* gp[5];
        gp[0] = gbin + bin * nbins * 8 + tid;
        gp[1] = gp[0] + NB;
        gp[2] = gp[0] + 2 * NB;
        gp[3] = gbin + GEX + (bin * nbins + sg[3]) * 4 + (lane & 3);
        gp[4] = gbin + GEX + (bin * nbins + sg[4]) * 4 + (lane & 3);
        unsigned pend = (sg[0] < nbins) | (sg[1] < nbins) << 1 | (sg[2] < nbins) << 2;
#pragma unroll
        for (int k = 0; k < 5; k++) en[k][0] = en[k][1] = en[k][2] = en[k][3] = NULW + lane * (80 << 15);
        auto fetch = [&](int k) {
            asm volatile("{\n.reg .pred p;\nsetp.ne.u32 p, %5, 0;\n@p ld.relaxed.gpu.global.v4.u32 {%0,%1,%2,%3}, [%4];\n}"
                         : "+r"(en[k][0]), "+r"(en[k][1]), "+r"(en[k][2]), "+r"(en[k][3])
                         : "l"(gp[k]), "r"(pend & (1u << k))
                         : "memory");
        };
        int spin = 0;
        auto poll = [&](int k0, int k1) {
            for (;;) {
#pragma unroll
                for (int k = k0; k < k1; k++)
                    if (min(min(en[k][0], en[k][1]), min(en[k][2], en[k][3]))) pend &= ~(1u << k);
                if (!__any_sync(0xffffffffu, PV ? pend & ((1u << k1) - 1) : pend)) break;
#pragma unroll
                for (int k = k0; k < k1; k++) fetch(k);
                if (++spin > 10000000) __trap();
            }
        };
        auto count = [&](int k) {
#pragma unroll
            for (int c = 0; c < 4; c++) {
                const uint32_t v = en[k][c];
                ca[k][c] = (__umulhi(v, 6554) & 0x1ffc) | cnt0;
                rank[k][c] = atoms_add(ca[k][c], 1);
                asm volatile("{\n.reg .b32 a, b;\nprmt.b32 a, %1, %2, 0x6540;\nand.b32 b, %1, 0x7f00;\nmad.lo.u32 %0, b, %3, a;\n}"
                             : "=r"(es[k][c])
                             : "r"(v), "r"(sg[k] - nbins), "r"(nbins));
            }
        };
        while ((int)(clock() - c6) < delay) {}
        TLS(7);
        fetch(0);
        fetch(1);
        fetch(2);
        poll(0, 3);
        TLS(2);
        const bool more = __any_sync(0xffffffffu, (lane & 7) == 7 && min(min(en[0][3], en[1][3]), en[2][3]) < NULW);
        const bool rest = NB / 4 + warp * 4 < nbins;
        if (more) {
            const uint32_t l0 = __shfl_sync(0xffffffffu, en[0][3], lane | 7), l1 = __shfl_sync(0xffffffffu, en[1][3], lane | 7);
            const uint32_t l2 = __shfl_sync(0xffffffffu, en[2][3], lane | 7);
            pend = ((lane & 4 ? l1 : l0) < NULW) << 3 | (!(lane & 4) && l2 < NULW) << 4;
            fetch(3);
            fetch(4);
        }
        if (tid == 7 && en[0][3] >= NULW) sts_u32(sb + SM_MISC + MI_INT + 4, en[0][3]);
        count(0);
        count(1);
        if (rest) count(2);
        if (more) {
            const unsigned ext = pend;
            poll(3, 5);
#pragma unroll
            for (int k = 3; k < 5; k++) {
                if ((ext >> k) & 1) {
                    __stcg((uint4*)gp[k], make_uint4(0, 0, 0, 0));
                    if ((lane & 3) == 3 && en[k][3] < NULW) sts_u32(sb + SM_MISC + MI_INT + 44, 1);
                }
            }
            count(3);
            count(4);
        }
        TLS(9);
        SYNC();
        {
            const int w0 = warp >= NGR, gr = warp - w0 * NGR;
            const uint32_t cp = cnt0 + (warp * NBK + lane * (NBK / 32)) * 4;
            uint32_t r[5];
            const uint4 cv = lds_v4(cp);
            r[0] = 0, r[1] = cv.x, r[2] = cv.x + cv.y, r[3] = r[2] + cv.z, r[4] = r[3] + cv.w;
            const uint32_t tot = __reduce_add_sync(0xffffffffu, r[NBK / 32]);
            const uint32_t base = warp * GCAP + w0 * GEXT;
            const bool full = tot > GCAP + (gr == NGR - 1 ? GEXT : 0);
            asm volatile("st.shared.u8 [%0], %1;" ::"r"(sb + SM_MISC + MI_INT + 32 + (full ? 12 : (gr < 4 ? w0 * 4 : 4 + w0 * 2) + gr)), "r"(full ? 1 : (tot + 3) >> 2) : "memory");
            asm volatile("bar.arrive 5, %0;" ::"n"(NT) : "memory");
            const uint32_t off = warp_incl_scan(r[NBK / 32], lane, lds_u32(sb + SM_MISC + MI_INT)) - r[NBK / 32] + base + 7 - CE + GCODE(gr);
            if (lane == 31) r[NBK / 32] += CE;
#pragma unroll
            for (int c = 0; c <= NBK / 32; c++) r[c] += off;
#pragma unroll
            for (int c = 0; c < NBK / 32; c++) r[c] += ((r[c + 1] & ~3) - (r[c] & ~3)) << 15;
            sts_v4(cp, make_uint4(r[0], r[1], r[2], r[3]));
            asm volatile("{\n.reg .pred p;\n.reg .b16 h;\nsetp.lt.u32 p, %0, %1;\ncvt.u16.u32 h, %3;\n@p st.shared.u16 [%2], h;\n@p st.shared.u32 [%4], 0x80000000;\n}" ::"r"(lane),
                         "r"(full ? 0 : -tot & 3), "r"(sb + SM_SRC + (base + tot + lane) * 2), "r"(N + warp * KEYW), "r"(sb + SM_EID + (base + tot + lane) * 4)
                         : "memory");
        }
        TLS(10);
        asm volatile("bar.arrive 6, %0;" ::"n"(NT) : "memory");
#pragma unroll
        for (int h = 0; h < 2; h++)
            asm volatile("ldmatrix.sync.aligned.m8n8.x4.trans.shared.b16 {%0,%1,%2,%3}, [%4];"
                         : "=r"(wa[h * 4]), "=r"(wa[h * 4 + 1]), "=r"(wa[h * 4 + 2]), "=r"(wa[h * 4 + 3])
                         : "r"(sb + SC_WR + (h * 8 + (warp & 3) * 2 + ((lane >> 3) & 1)) * 272 + (lane >> 4) * 128 + (lane & 7) * 16));
        asm volatile("bar.sync 7, %0;" ::"n"(NB) : "memory");
        auto place0 = [&](int k) {
#pragma unroll
            for (int c = 0; c < 4; c++)
                asm volatile("{\n.reg .pred p;\nsetp.lt.u32 p, %1, " STR(NULW) ";\n@p ld.shared.u16 %0, [%0];\n}" : "+r"(ca[k][c]) : "r"(en[k][c]));
#pragma unroll
            for (int c = 0; c < 4; c++) ca[k][c] = (ca[k][c] & 0xfff) + rank[k][c];
        };
        auto place1 = [&](int k) {
#pragma unroll
            for (int c = 0; c < 4; c++)
                asm volatile(
                    "{\n.reg .pred p;\n.reg .b32 t;\n.reg .b16 h;\n"
                    "setp.lt.u32 p, %0, " STR(NULW) ";\n"
                    "shr.u32 t, %0, 15;\ncvt.u16.u32 h, t;\n"
                    "@p st.shared.u16 [%1], h;\n}" ::"r"(en[k][c]),
                    "r"(sb + SM_SRC - (7 - CE) * 2 + ca[k][c] * 2)
                    : "memory");
        };
        auto place2 = [&](int k) {
#pragma unroll
            for (int c = 0; c < 4; c++)
                asm volatile("{\n.reg .pred p;\nsetp.lt.u32 p, %0, " STR(NULW) ";\n@p st.shared.u32 [%1], %2;\n}" ::"r"(en[k][c]),
                             "r"(sb + SM_EID - (7 - CE) * 4 + ca[k][c] * 4), "r"(es[k][c])
                             : "memory");
        };
        auto all = [&](auto f) {
            f(0);
            f(1);
            if (rest) f(2);
            if (more) f(3), f(4);
        };
        fast = lds_u32(sb + SM_MISC + MI_INT + 44) == 0;
        if (fast) {
            all([&](int k) { place0(k), place1(k); });
            TLS(14);
            TLA(14, 0);
            LISTS();
            all(place2);
            if (warp < 8) asm volatile("bar.arrive 3, %0;" ::"n"(NT) : "memory");
        }
        }
    }

    if (fast && (warp >> 2) == 2) {
        asm volatile("setmaxnreg.dec.sync.aligned.u32 %0;" ::"n"(HREG));
        const int w = warp & 1, j = (warp >> 1) & 1;
        const uint32_t bar0 = sb + SM_BAR + w * NP * 16;
        const int blk = (lane >> 4) * 2 + (t >> 1);
        uint32_t fseq = sb + SM_SEQ + w * SEQCAP * 2 + j * 8 + blk * 2;
        const uint32_t feid = sb + SM_EID - 16 + (g & 3) * 4;
        uint32_t pea = sb + SM_EA + w * 4096 + j * 512 + (lane ^ ((lane >> 3) & 1)) * 16;
        const uint32_t psd = sb + SM_SIDE + (warp - 8) * 512 + (lane >> 1) * 16 + (lane & 1) * 4;
        const uint32_t pt = sb + SM_BT + w * (TS * 256) + j * 512 + blk * BT_B + ((lane ^ (lane >> 3)) & 1) * BT_K + (g & 3) * 4;
        const char* gea = (const char*)ea + (lane & 1) * 16;
        uint32_t es, va[2], ta[2], old[2] = {pt, pt}, dea = 2048;
        auto ids = [&]() {
            es = lds_u32(feid + (lds_u16(fseq) & 0xffc) * 4);
            fseq += 16;
        };
        uint32_t wf[4];
        wf[0] = __byte_perm(c0.x, c1.x, 0x5410), wf[1] = __byte_perm(c0.x, c1.x, 0x7632);
        wf[2] = __byte_perm(c0.y, c1.y, 0x5410), wf[3] = __byte_perm(c0.y, c1.y, 0x7632);
        int pfl = lane < PL ? PFN * nbins * 128 + (bin * 4 + warp - 8) * PL + lane - N * 8 : 0;
        int pfs = nbins * (4 * PL);
        const char* pfb = (const char*)(x + (size_t)N * 512);
        auto run = [&](auto odd) {
            auto fetch = [&](int i) {
                asm volatile(
                    "{\n.reg .pred p, q;\n.reg .b32 e;\n.reg .b64 a;\n"
                    "setp.lt.s32 p, %0, 0;\n"
                    "and.b32 e, %0, 0x7ffffff8;\n"
                    "mad.wide.u32 a, e, 4, %1;\n"
                    "cp.async.cg.shared.global [%2], [a], 16, p;\n"
                    "}" ::"r"(es), "l"(gea), "r"(pea + i * 1024) : "memory");
                va[i] = psd + (es & 8);
                ta[i] = pt + (es & 7) * 64;
                if (odd.value) {
                    cp_async4(va[i] + i * 256, (const char*)sh + (es & 0x7ffffff8) + (lane & 1) * 4, (int)es >= 0 ? 4 : 0);
                } else {
                    asm volatile(
                        "{\n.reg .pred p;\n.reg .b32 e;\n.reg .b64 a;\n"
                        "setp.lt.s32 p, %0, 0;\n"
                        "and.b32 e, %0, 0x7ffffff0;\n"
                        "mad.wide.u32 a, e, 1, %1;\n"
                        "cp.async.cg.shared.global [%2], [a], 16, p;\n"
                        "}" ::"r"(es), "l"(sh), "r"((psd & ~15) + i * 256) : "memory");
                }
                asm volatile("cp.async.commit_group;" ::: "memory");
                if (i) pea += dea, dea = -dea;
            };
            asm volatile("bar.sync 3, %0;" ::"n"(NT) : "memory");
            TLA(7, 0);
            const uint2 nk = lds_v2(sb + SM_MISC + MI_INT + 8 + w * 8);
            ids();
            fetch(0);
            ids();
            fetch(1);
            const int npr = __shfl_sync(0xffffffffu, nk.x, 0), kj = __shfl_sync(0xffffffffu, nk.y, 0) + j;
        uint32_t vf = bar0 + (kj < NP ? kj : 0) * 16;
        uint32_t pe = kj < NP;
#pragma unroll 1
            for (int m = (npr + 1 - j) >> 1; m > 0;) {
#pragma unroll
                for (int i = 0; i < 2; i++) {
                    asm volatile("cp.async.wait_group 1;" ::: "memory");
                    __syncwarp();
                    const uint32_t v = lds_u32(va[i] + i * 256);
                    ids();
                    float d0[4], d1[4];
                    mma_diag(d0, v, wf[0], wf[1]);
                    mma_diag(d1, v, wf[2], wf[3]);
                    uint32_t vn = vf + 32;
                    if (vn >= bar0 + NP * 16) vn -= NP * 16, pe ^= 1;
                    TWAIT(vn + 8, pe);
#pragma unroll
                    for (int k = 0; k < 4; k++) sts_u32(old[i] + i * 1024 + k * 16, 0);
                    old[i] = ta[i];
                    sts_u32(old[i] + i * 1024, pack_bf16(d0[0], d0[1]));
                    sts_u32(old[i] + i * 1024 + 16, pack_bf16(d0[2], d0[3]));
                    sts_u32(old[i] + i * 1024 + 32, pack_bf16(d1[0], d1[1]));
                    sts_u32(old[i] + i * 1024 + 48, pack_bf16(d1[2], d1[3]));
                    FENCE_ASYNC();
                    fetch(i);
                    __syncwarp();
                    if (lane == 0) mbar_arrive(vf);
                    asm volatile("{\n.reg .pred p;\n.reg .b64 a;\nsetp.lt.s32 p, %0, 0;\nmad.wide.s32 a, %0, 128, %1;\n@p prefetch.global.L2 [a];\n}" ::"r"(pfl),
                                 "l"(pfb));
                    pfl += pfs;
                    vf = vn;
                    if (--m <= 0) break;
                }
            }
        };
        if (E & 1) run(std::true_type()); else run(std::false_type());
        asm volatile("cp.async.wait_group 0;" ::: "memory");
        TLMAX(13);
    } else if (fast) {
        const int w = warp >> 2, wq = warp & 3;
        asm volatile("setmaxnreg.inc.sync.aligned.u32 %0;" ::"n"(CREG));
        const int k0 = __shfl_sync(0xffffffffu, lds_u32(sb + SM_MISC + MI_INT + 12 + w * 8), 0);
        const uint32_t ring = sb + w * RING_BYTES, bar0 = sb + SM_BAR + w * NP * 16;
        float acc[2][NJ][4];
        uint32_t a0[8][4], a1[8][4];
        {
            const int e = (lane >> 1) & 3, m = lane >> 3;
            const int line = 2 * ((lane & 1) + 2 * ((m >> 1) ^ (e >> 1))), ch = 2 * wq + (m & 1);
            const uint32_t xb = ring + (e & 1 ? SM_ODD : SM_EVEN) + (e >> 1) * 1024 + line * 128;
            consume(acc, a0, ring, xb + ((ch ^ ((line + (e & 1)) & 7)) * 16), xb + 128 + ((ch ^ ((line + 1 + (e & 1)) & 7)) * 16),
                    k0 * 8192, bar0, (((sb + SM_EA + w * 4096) & 0x3ffff) >> 4) | (1 << 16),
                    (((sb + SM_BT + w * (TS * 256)) & 0x3ffff) >> 4) | (BT_K / 16 << 16), sb + SM_SEQ + w * SEQCAP * 2, lane & (E >> 31),
                    wa);
        }
        const uint32_t tb = ring + wq * (NJ * 256) + lane * 16, db = (ring >> 4) + (8 << 16);
        const uint32_t cr = ring + (lane & 7) * 128 + (lane >> 4) * 1024, cc = 2 * wq + ((lane >> 3) & 1);
        const uint32_t ce = cr + (cc ^ (lane & 7)) * 16, co = cr + (cc ^ ((lane + 1) & 7)) * 16;
        float o0[CH0][4], o1[CH1][4], o2[CH2][4], o3[CH3][4], o4[CH4][4];
        TLMAX(11);
#pragma unroll
        for (int u = 0; u <= CH0; u++) put_agg<0, CH0>(acc, tb, u);
        TLE(1);
        FENCE_ASYNC();
        WG_SYNC(w);
        TLE(6);
        mul_out<0>(o0, a0, db, [&](int u) { put_agg<CH0, CH1>(acc, tb, u); });
        const bool ok1 = mbar_test(bar0 + DUMB, 0);
        FENCE_ASYNC();
        WG_SYNC(w);
        TLE(7);
        mul_out<KA>(o1, a0, db + CH0 * 16, [&](int u) {
            if (u == 0) {
                TLE(2);
#pragma unroll
                for (int k = 0; 2 * k < CH0; k++) put_out<0>(o0, ce, k, w);
                TLMAX(3);
            } else {
                put_agg<CH0 + CH1, CH2>(acc, tb, 2 * u - 2);
                put_agg<CH0 + CH1, CH2>(acc, tb, 2 * u - 1);
            }
        });
        FENCE_ASYNC();
        if (!ok1) mbar_wait(bar0 + DUMB, 0);
        WG_SYNC(w);
        TLE(9);
        mul_out<KA>(o2, a0, db + (CH0 + CH1) * 16, [&](int u) {
            put_out<1>(o1, co, 2 * u, w);
            put_out<1>(o1, co, 2 * u + 1, w);
            if (u == 1) TLE(5);
            get_w(a1, ce + (NP - 1) * 8192, co + (NP - 1) * 8192, 2 * u - 4);
            get_w(a1, ce + (NP - 1) * 8192, co + (NP - 1) * 8192, 2 * u - 3);
        });
        mul_out<KA>(o3, a1, db, [&](int u) {
            if (u == 0) TLE(10);
            put_out<2>(o2, ce, u, w);
            if (u == 8 - KA) WG_SYNC(w);
        });
        mul_out<KA>(o4, a1, db + CH3 * 16, [&](int u) { put_out<3>(o3, co, u, w); });
        TLE(14);
        WG_WAIT(0);
#pragma unroll
        for (int u = 0; 2 * u < CH4; u++) put_out<4>(o4, ce, u, w);
        TLMAX(15);
    } else {
        float* accs = (float*)smem;
        constexpr int NACC = SM_EID / 2048;
        const int nnodes = max(0, min(npb, N - node0));
#pragma unroll 1
        for (int nb = 0; nb < nnodes; nb += NACC) {
            __syncthreads();
            for (int i = tid; i < NACC * 512; i += NT) accs[i] = 0.f;
            __syncthreads();
#pragma unroll 1
            for (int base = warp * 32; base < E; base += NT) {
                const int e = base + lane;
                int dl = e < E ? dst[e] - node0 - nb : -1;
                if (dl + nb >= nnodes) dl = -1;
                unsigned mask = __ballot_sync(0xffffffffu, dl >= 0 && dl < NACC);
#pragma unroll 1
                while (mask) {
                    const int l = __ffs(mask) - 1;
                    mask &= mask - 1;
                    const int ee = __shfl_sync(0xffffffffu, e, l);
                    const int dd = __shfl_sync(0xffffffffu, dl, l);
                    slow_edge(ee, src[ee], accs + dd * 512, x, sh, ea, cg, wr, lane);
                }
            }
            __syncthreads();
#pragma unroll 1
            for (int nl = warp; nl < NACC && nb + nl < nnodes; nl += NW)
                slow_out(accs + nl * 512, wout, out + (size_t)(node0 + nb + nl) * 512, lane);
        }
        __syncthreads();
    }

    TLMAX(4);
    TLEND();
}

typedef CUresult (*EncodeTiledFn)(CUtensorMap*, CUtensorMapDataType, cuuint32_t, void*, const cuuint64_t*,
                                  const cuuint64_t*, const cuuint32_t*, const cuuint32_t*, CUtensorMapInterleave,
                                  CUtensorMapSwizzle, CUtensorMapL2promotion, CUtensorMapFloatOOBfill);

extern "C" void kernel_launch(void* const* d_in, const int* in_sizes, int n_in, void* d_out, int out_size) {
    const __nv_bfloat16* x = (const __nv_bfloat16*)d_in[0];
    const int* src = (const int*)d_in[1];
    const int* dst = (const int*)d_in[2];
    const __nv_bfloat16* sh = (const __nv_bfloat16*)d_in[3];
    const __nv_bfloat16* ea = (const __nv_bfloat16*)d_in[4];
    const __nv_bfloat16* cg = (const __nv_bfloat16*)d_in[5];
    const __nv_bfloat16* wr = (const __nv_bfloat16*)d_in[6];
    const __nv_bfloat16* wout = (const __nv_bfloat16*)d_in[7];
    __nv_bfloat16* out = (__nv_bfloat16*)d_out;
    const int N = in_sizes[0] / 512;
    const int E = in_sizes[1];

    static int num_sms = 0;
    static EncodeTiledFn encode = nullptr;
    static uint4* gbin = nullptr;
    if (num_sms == 0) {
        int dev = 0;
        cudaGetDevice(&dev);
        cudaDeviceGetAttribute(&num_sms, cudaDevAttrMultiProcessorCount, dev);
        cudaFuncSetAttribute(main_kernel, cudaFuncAttributeMaxDynamicSharedMemorySize, SM_TOTAL + TLX);
        cudaGetSymbolAddress((void**)&gbin, g_bin);
        void* fn = nullptr;
        cudaDriverEntryPointQueryResult qr;
        cudaGetDriverEntryPoint("cuTensorMapEncodeTiled", &fn, cudaEnableDefault, &qr);
        encode = (EncodeTiledFn)fn;
    }
    const int nbins = num_sms < NB * 3 / 8 ? num_sms : NB * 3 / 8;
    int npb = ((N + nbins - 1) / nbins + 3) & ~3;
    if (npb < 32) npb = 32;
    const int fast_ok = E > 0 && npb <= 2 * HPB && N <= (NBK - 1) * 80 - 8 && E <= EPS * NT * nbins;
    auto map2d = [&](CUtensorMap* tm, const void* p, int d0, int d1, int b1) {
        const cuuint64_t gd[2] = {(cuuint64_t)d0, (cuuint64_t)d1};
        const cuuint64_t gs[1] = {(cuuint64_t)d0 * 2};
        const cuuint32_t bx[2] = {64, (cuuint32_t)b1};
        const cuuint32_t es[2] = {1, 1};
        encode(tm, CU_TENSOR_MAP_DATA_TYPE_BFLOAT16, 2, (void*)p, gd, gs, bx, es, CU_TENSOR_MAP_INTERLEAVE_NONE,
               CU_TENSOR_MAP_SWIZZLE_128B, CU_TENSOR_MAP_L2_PROMOTION_NONE, CU_TENSOR_MAP_FLOAT_OOB_FILL_NONE);
    };
    CUtensorMap tme, tmx, tmw, tmo;
    {
        const cuuint64_t gd[2] = {(cuuint64_t)nbins * 32, (cuuint64_t)nbins};
        const cuuint64_t gs[1] = {(cuuint64_t)nbins * 128};
        const cuuint32_t bx[2] = {32, (cuuint32_t)nbins};
        const cuuint32_t es[2] = {1, 1};
        encode(&tme, CU_TENSOR_MAP_DATA_TYPE_UINT32, 2, (void*)gbin, gd, gs, bx, es, CU_TENSOR_MAP_INTERLEAVE_NONE,
               SW ? CU_TENSOR_MAP_SWIZZLE_128B : CU_TENSOR_MAP_SWIZZLE_NONE, CU_TENSOR_MAP_L2_PROMOTION_NONE, CU_TENSOR_MAP_FLOAT_OOB_FILL_NONE);
    }
    {
        const cuuint64_t gd[2] = {(cuuint64_t)N * 256 - 224, 8};
        const cuuint64_t gs[1] = {128};
        const cuuint32_t bx[2] = {32, 8};
        const cuuint32_t es[2] = {1, 1};
        encode(&tmx, CU_TENSOR_MAP_DATA_TYPE_UINT32, 2, (void*)x, gd, gs, bx, es, CU_TENSOR_MAP_INTERLEAVE_NONE,
               CU_TENSOR_MAP_SWIZZLE_128B, CU_TENSOR_MAP_L2_PROMOTION_NONE, CU_TENSOR_MAP_FLOAT_OOB_FILL_NONE);
    }
    map2d(&tmw, wout, 128, 128, 64);
    map2d(&tmo, out, 128, N * 4, 8);
    const unsigned npb_magic = (unsigned)((0x100000000ull + npb - 1) / npb);
    const int chunk = (E + nbins - 1) / nbins;
    int tau16 = (int)fmin((double)PACE * 16.0 * chunk / N, 100000.0), toff = TOFF, delay = DELAY;
    int tau2 = tau16 * PACE2 / 100, brk = BRK;
    brk = (tau16 - tau2) * (N * brk / 50);
    main_kernel<<<nbins, NT, SM_TOTAL + TLX, cudaStreamPerThread>>>(dst, src, gbin, E, nbins, fast_ok, npb, npb_magic, N, tme, tmx, tmw,
                                                              tmo, x, sh, ea, cg, wr, wout, out, tau16, toff, delay, tau2, brk);
}
```

```cpp
#include <cuda_runtime.h>
#include <cuda.h>
#include <cuda_bf16.h>
#include <stdint.h>
#include <stdlib.h>
#include <type_traits>

#define MAXBINS 160
#define NW 16
#define NT (NW * 32)
#define HPB 38
#define GCAP 280
#define GEXT 72
#define NGR 6
#define LNUL (2 * (NGR * GCAP + GEXT))
#define NBK 128
#define KEYW 10240
#define CE 2
#define GSZ 6
#define NS 10
#define RING_BYTES 40960
static_assert(RING_BYTES == NS * 4096, "ring");
#define NP (NS / 2)
#define CREG 224
#define PREG 24
#define HREG 40
#define TS 8
#define SM_EVEN 0
#define SM_MISC (2 * RING_BYTES)
#define SM_ODD (SM_MISC + 128)
#define SM_EA (SM_BT + TS * 4096 + 128)
#define SM_BT (SM_ODD + 2 * RING_BYTES)
#define BT_B (TS * 512 + 16)
#define BT_K (4 * BT_B)
#define SM_SIDE (SM_EA + 8192)
#define SM_EID (SM_SIDE + 2048)
#define SM_SRC (SM_EID + (LNUL + 4) * 4)
#define SEQCAP ((LNUL / 8 + 32 + 7) / 8 * 8)
#define SM_SEQ (SM_SRC + (LNUL + 8) * 2)
#define SM_BAR ((SM_SEQ + 2 * SEQCAP * 2 + 63) / 64 * 64)
#define XR 0
#define SM_TOTAL (SM_BAR + NW * 16)
#define DUMB (2 * NP * 16)
#define MI_INT 0
#define EPS 5
#define SC_ENT 0
#define SC_EXT (SC_ENT + MAXBINS * 128)
#define SC_TAB (SC_EXT + MAXBINS * 64)
#define SC_HIST (SC_TAB + 320)
#define SC_END (SC_HIST + MAXBINS * 4 + 128)
#define SC_WR SC_END
#define SC_CNT (SC_WR + 4352)
static_assert(SC_END % 16 == 0 && SC_HIST % 16 == 0 && SC_END - SC_HIST <= NT * 16 && SC_CNT + 16384 <= SM_MISC && SC_TAB <= 4 * NT * 16 && 2 * HPB <= 80 && MAXBINS >= 24 * NGR, "scratch");
static_assert(LNUL >= 3072 && LNUL + 8 <= 4096 && GCAP % 4 == 0 && GEXT % 4 == 0, "lists");
static_assert(SM_TOTAL <= 232448 && SM_BAR % 16 == 0 && SM_SEQ % 16 == 0 && SM_SRC % 16 == 0 && SM_EA % 256 == 0, "smem");
#define PACE 18.35
#define PACE2 96
#define BRK 85
#define TOFF 7900
#define PSLEEP 20

#define GEX (MAXBINS * MAXBINS * 8)
__device__ __align__(128) uint4 g_bin[GEX + GEX / 2];
#define STR2(x) #x
#define STR(x) STR2(x)
#define TLINIT()
#define TLEND()
#define TLX 0
#define TLSTAMP(i)
#define TLMAX(i)

#define TLA(i, d)
#define TLS(i) TLMAX(i)
#define TLE(i)
__device__ __forceinline__ uint32_t pack_bf16(float lo, float hi) {
    uint32_t r;
    asm("cvt.rn.bf16x2.f32 %0, %1, %2;" : "=r"(r) : "f"(hi), "f"(lo));
    return r;
}
__device__ __forceinline__ void mma1688_z(float (&d)[4], uint32_t a0, uint32_t a1, uint32_t b0) {
    asm("mma.sync.aligned.m16n8k8.row.col.f32.bf16.bf16.f32 {%0,%1,%2,%3}, {%4,%5}, {%6}, {%7,%7,%7,%7};"
        : "=f"(d[0]), "=f"(d[1]), "=f"(d[2]), "=f"(d[3])
        : "r"(a0), "r"(a1), "r"(b0), "f"(0.f));
}
__device__ __forceinline__ void mma_diag(float (&d)[4], uint32_t a, uint32_t b0, uint32_t b1) {
    asm("mma.sync.aligned.m16n8k16.row.col.f32.bf16.bf16.f32 {%0,%1,%2,%3}, {%4,%8,%8,%4}, {%5,%6}, {%7,%7,%7,%7};"
        : "=f"(d[0]), "=f"(d[1]), "=f"(d[2]), "=f"(d[3])
        : "r"(a), "r"(b0), "r"(b1), "f"(0.f), "r"(0));
}
__device__ __forceinline__ uint32_t s2u(const void* p) { return (uint32_t)__cvta_generic_to_shared(p); }
__device__ __forceinline__ void mbar_init(uint32_t a, int c) {
    asm volatile("mbarrier.init.shared.b64 [%0], %1;" ::"r"(a), "r"(c));
}
__device__ __forceinline__ void mbar_expect_tx(uint32_t a, int bytes) {
    asm volatile("mbarrier.arrive.expect_tx.shared.b64 _, [%0], %1;" ::"r"(a), "r"(bytes) : "memory");
}
__device__ __forceinline__ void mbar_arrive(uint32_t a) {
    asm volatile("mbarrier.arrive.shared.b64 _, [%0];" ::"r"(a) : "memory");
}
__device__ __forceinline__ void mbar_arrive_cnt(uint32_t a, int c) {
    asm volatile("mbarrier.arrive.shared.b64 _, [%0], %1;" ::"r"(a), "r"(c) : "memory");
}
__device__ __forceinline__ void mbar_wait(uint32_t a, int parity) {
    asm volatile(
        "{\n.reg .pred p;\n.reg .u32 c;\n"
        "mov.u32 c, 0;\n"
        "LAB_WAIT:\n"
        "mbarrier.try_wait.parity.shared.b64 p, [%0], %1, 2000;\n"
        "@p bra DONE;\n"
        "add.u32 c, c, 1;\n"
        "setp.lt.u32 p, c, 2000000;\n"
        "@p bra LAB_WAIT;\n"
        "trap;\n"
        "DONE:\n}" ::"r"(a),
        "r"(parity)
        : "memory");
}
__device__ __forceinline__ void mbar_wait_u(uint32_t a, int parity) {
    asm volatile(
        "{\n.reg .pred p;\n.reg .u32 c;\n"
        "mov.u32 c, 0;\n"
        "LAB_WAIT:\n"
        "mbarrier.try_wait.parity.shared.b64 p, [%0], %1, 2000;\n"
        "@p bra.uni DONE;\n"
        "add.u32 c, c, 1;\n"
        "setp.lt.u32 p, c, 2000000;\n"
        "@p bra.uni LAB_WAIT;\n"
        "trap;\n"
        "DONE:\n}" ::"r"(a),
        "r"(parity)
        : "memory");
}
__device__ __forceinline__ void mbar_spin_u(uint32_t a, int parity) {
    asm volatile(
        "{\n.reg .pred p;\n.reg .u32 c;\n"
        "mov.u32 c, 0;\n"
        "LAB_WAIT:\n"
        "mbarrier.test_wait.parity.shared.b64 p, [%0], %1;\n"
        "@p bra.uni DONE;\n"
        "add.u32 c, c, 1;\n"
        "setp.lt.u32 p, c, 20000000;\n"
        "@p bra.uni LAB_WAIT;\n"
        "trap;\n"
        "DONE:\n}" ::"r"(a),
        "r"(parity)
        : "memory");
}
__device__ __forceinline__ void mbar_lean(uint32_t a, int parity) {
    asm volatile(
        "{\n.reg .pred p;\n.reg .u32 c;\n"
        "mov.u32 c, 0;\n"
        "LAB_WAIT:\n"
        "mbarrier.try_wait.parity.shared.b64 p, [%0], %1;\n"
        "@p bra DONE;\n"
        "add.u32 c, c, 1;\n"
        "setp.lt.u32 p, c, 4000000;\n"
        "@p bra LAB_WAIT;\n"
        "trap;\n"
        "DONE:\n}" ::"r"(a),
        "r"(parity)
        : "memory");
}
__device__ __forceinline__ void mbar_lean_u(uint32_t a, int parity) {
    asm volatile(
        "{\n.reg .pred p;\n.reg .u32 c;\n"
        "mov.u32 c, 0;\n"
        "LAB_WAIT:\n"
        "mbarrier.try_wait.parity.shared.b64 p, [%0], %1;\n"
        "@p bra.uni DONE;\n"
        "add.u32 c, c, 1;\n"
        "setp.lt.u32 p, c, 4000000;\n"
        "@p bra.uni LAB_WAIT;\n"
        "trap;\n"
        "DONE:\n}" ::"r"(a),
        "r"(parity)
        : "memory");
}
__device__ __forceinline__ bool mbar_test(uint32_t a, int parity) {
    uint32_t p;
    asm volatile("{\n.reg .pred P;\nmbarrier.test_wait.parity.shared.b64 P, [%1], %2;\nselp.u32 %0, 1, 0, P;\n}"
                 : "=r"(p)
                 : "r"(a), "r"(parity)
                 : "memory");
    return p;
}
__device__ __forceinline__ bool elect() {
    uint32_t p;
    asm volatile("{\n.reg .pred P;\nelect.sync _|P, 0xffffffff;\nselp.u32 %0, 1, 0, P;\n}" : "=r"(p));
    return p;
}
__device__ __forceinline__ void tma_2d(uint32_t dst, const CUtensorMap* tm, uint32_t bar, int c0, int c1) {
    asm volatile(
        "cp.async.bulk.tensor.2d.shared::cluster.global.mbarrier::complete_tx::bytes [%0], [%1, {%3, %4}], [%2];" ::"r"(dst),
        "l"(tm), "r"(bar), "r"(c0), "r"(c1)
        : "memory");
}
__device__ __forceinline__ void tma_row(uint32_t dst, const CUtensorMap* tm, uint32_t bar, int row8) {
    tma_2d(dst, tm, bar, 0, row8);
}
__device__ __forceinline__ void tma_store(const CUtensorMap* tm, uint32_t src, int c0, int c1) {
    asm volatile("cp.async.bulk.tensor.2d.global.shared::cta.bulk_group [%0, {%2, %3}], [%1];" ::"l"(tm), "r"(src),
                 "r"(c0), "r"(c1)
                 : "memory");
}
__device__ __forceinline__ uint2 lds_v2(uint32_t a) {
    uint2 v;
    asm volatile("ld.shared.v2.u32 {%0,%1}, [%2];" : "=r"(v.x), "=r"(v.y) : "r"(a));
    return v;
}
__device__ __forceinline__ uint4 lds_v4(uint32_t a) {
    uint4 v;
    asm volatile("ld.shared.v4.u32 {%0,%1,%2,%3}, [%4];" : "=r"(v.x), "=r"(v.y), "=r"(v.z), "=r"(v.w) : "r"(a));
    return v;
}
__device__ __forceinline__ uint32_t lds_u32(uint32_t a) {
    uint32_t v;
    asm volatile("ld.shared.u32 %0, [%1];" : "=r"(v) : "r"(a));
    return v;
}
__device__ __forceinline__ uint32_t lds_u16(uint32_t a) {
    uint32_t v;
    asm volatile("ld.shared.u16 %0, [%1];" : "=r"(v) : "r"(a));
    return v;
}
__device__ __forceinline__ void sts_v2(uint32_t a, uint32_t x, uint32_t y) {
    asm volatile("st.shared.v2.u32 [%0], {%1,%2};" ::"r"(a), "r"(x), "r"(y) : "memory");
}
__device__ __forceinline__ void sts_v4(uint32_t a, uint4 v) {
    asm volatile("st.shared.v4.u32 [%0], {%1,%2,%3,%4};" ::"r"(a), "r"(v.x), "r"(v.y), "r"(v.z), "r"(v.w) : "memory");
}
__device__ __forceinline__ void stsm4(uint32_t a, uint32_t r0, uint32_t r1, uint32_t r2, uint32_t r3) {
    asm volatile("stmatrix.sync.aligned.m8n8.x4.shared.b16 [%0], {%1,%2,%3,%4};" ::"r"(a), "r"(r0), "r"(r1), "r"(r2), "r"(r3)
                 : "memory");
}
__device__ __forceinline__ void stsm2(uint32_t a, uint32_t r0, uint32_t r1) {
    asm volatile("stmatrix.sync.aligned.m8n8.x2.shared.b16 [%0], {%1,%2};" ::"r"(a), "r"(r0), "r"(r1) : "memory");
}
__device__ __forceinline__ void stsm4t(uint32_t a, uint32_t r0, uint32_t r1, uint32_t r2, uint32_t r3) {
    asm volatile("stmatrix.sync.aligned.m8n8.x4.trans.shared.b16 [%0], {%1,%2,%3,%4};" ::"r"(a), "r"(r0), "r"(r1), "r"(r2),
                 "r"(r3)
                 : "memory");
}
__device__ __forceinline__ void stsm2t(uint32_t a, uint32_t r0, uint32_t r1) {
    asm volatile("stmatrix.sync.aligned.m8n8.x2.trans.shared.b16 [%0], {%1,%2};" ::"r"(a), "r"(r0), "r"(r1) : "memory");
}
__device__ __forceinline__ void cp_async16(uint32_t d, const void* s, int n) {
    asm volatile("cp.async.cg.shared.global [%0], [%1], 16, %2;" ::"r"(d), "l"(s), "r"(n) : "memory");
}
__device__ __forceinline__ void cp_async4(uint32_t d, const void* s, int n) {
    asm volatile("cp.async.ca.shared.global [%0], [%1], 4, %2;" ::"r"(d), "l"(s), "r"(n) : "memory");
}
__device__ __forceinline__ void sts_u32(uint32_t a, uint32_t x) {
    asm volatile("st.shared.u32 [%0], %1;" ::"r"(a), "r"(x) : "memory");
}
#define FENCE_ASYNC() asm volatile("fence.proxy.async.shared::cta;" ::: "memory")
#define ZS 4
__device__ __forceinline__ int warp_incl_scan(int v, int lane, int z) {
#pragma unroll
    for (int o = 1; o < 32; o <<= 1) {
        const int y = __shfl_up_sync(0xffffffffu, v, o);
        if (lane >= o) v += y;
        if (o == ZS) v += z;
    }
    return v;
}

__device__ __forceinline__ uint32_t atoms_add(uint32_t a, uint32_t v) {
    uint32_t r;
    asm volatile("atom.shared.add.u32 %0, [%1], %2;" : "=r"(r) : "r"(a), "r"(v) : "memory");
    return r;
}
__device__ __forceinline__ void sts_u16(uint32_t a, uint32_t x) {
    asm volatile("{\n.reg .b16 h;\ncvt.u16.u32 h, %1;\nst.shared.u16 [%0], h;\n}" ::"r"(a), "r"(x) : "memory");
}
#define NJ 19
__device__ __forceinline__ void consume(float (&acc)[2][NJ][4], uint32_t (&wo)[8][4], uint32_t ring, uint32_t xa0, uint32_t xa1, uint32_t so0, uint32_t bar0,
                                        uint32_t ea0, uint32_t d0, uint32_t pl0, int lz, const uint32_t (&wa)[8]) {
    asm volatile(
        "{\n"
        ".reg .pred p, pf, plead, pok, t0, t1, t2, u0, u1, u2;\n"
        ".reg .b32 ca, cb, cz, rbar;\n"
        "mov.b32 cz, 0;\n"
        "mov.b32 ca, 0x20002000;\n"
        "mov.b32 cb, 0x30003000;\n"
        ".reg .b32 cnt, so, q, qe, bar, nbar, pl, ctl, ctm, ix, iy, dl, v0, v1, v2, v3, pp;\n"
        ".reg .b16 sl, sh;\n"
        ".reg .b32 hXa0, hXa1, hXa2, hXa3, hXa4, hXa5, hXa6, hXa7, hXb0, hXb1, hXb2, hXb3, hXb4, hXb5, hXb6, hXb7, hYa0, hYa1, hYa2, hYa3, hYa4, hYa5, hYa6, hYa7, hYb0, hYb1, hYb2, hYb3, hYb4, hYb5, hYb6, hYb7, hLa0, hLa1, hLa2, hLa3, hLa4, hLa5, hLa6, hLa7, hLb0, hLb1, hLb2, hLb3, hLb4, hLb5, hLb6, hLb7;\n"
        ".reg .b32 pX0, pX1, pX2, pX3, pY0, pY1, pY2, pY3;\n"
        ".reg .f32 r0, r1, r2, r3, r4, r5, r6, r7, r8, r9, r10, r11, r12, r13, r14, r15;\n"
        ".reg .b64 daX, dbX, daY, dbY, de0, de1;\n"
        ".reg .b32 dh<6>, eb0, par, npar, wa<8>, uz, bend;\n"
        "add.u32 wa0, %192, %191;\n"
        "add.u32 wa1, %193, %191;\n"
        "add.u32 wa2, %194, %191;\n"
        "add.u32 wa3, %195, %191;\n"
        "add.u32 wa4, %196, %191;\n"
        "add.u32 wa5, %197, %191;\n"
        "add.u32 wa6, %198, %191;\n"
        "add.u32 wa7, %199, %191;\n"
        "mov.f32 %0, 0f00000000;\n"
        "mov.f32 %1, 0f00000000;\n"
        "mov.f32 %2, 0f00000000;\n"
        "mov.f32 %3, 0f00000000;\n"
        "mov.f32 %4, 0f00000000;\n"
        "mov.f32 %5, 0f00000000;\n"
        "mov.f32 %6, 0f00000000;\n"
        "mov.f32 %7, 0f00000000;\n"
        "mov.f32 %8, 0f00000000;\n"
        "mov.f32 %9, 0f00000000;\n"
        "mov.f32 %10, 0f00000000;\n"
        "mov.f32 %11, 0f00000000;\n"
        "mov.f32 %12, 0f00000000;\n"
        "mov.f32 %13, 0f00000000;\n"
        "mov.f32 %14, 0f00000000;\n"
        "mov.f32 %15, 0f00000000;\n"
        "mov.f32 %16, 0f00000000;\n"
        "mov.f32 %17, 0f00000000;\n"
        "mov.f32 %18, 0f00000000;\n"
        "mov.f32 %19, 0f00000000;\n"
        "mov.f32 %20, 0f00000000;\n"
        "mov.f32 %21, 0f00000000;\n"
        "mov.f32 %22, 0f00000000;\n"
        "mov.f32 %23, 0f00000000;\n"
        "mov.f32 %24, 0f00000000;\n"
        "mov.f32 %25, 0f00000000;\n"
        "mov.f32 %26, 0f00000000;\n"
        "mov.f32 %27, 0f00000000;\n"
        "mov.f32 %28, 0f00000000;\n"
        "mov.f32 %29, 0f00000000;\n"
        "mov.f32 %30, 0f00000000;\n"
        "mov.f32 %31, 0f00000000;\n"
        "mov.f32 %32, 0f00000000;\n"
        "mov.f32 %33, 0f00000000;\n"
        "mov.f32 %34, 0f00000000;\n"
        "mov.f32 %35, 0f00000000;\n"
        "mov.f32 %36, 0f00000000;\n"
        "mov.f32 %37, 0f00000000;\n"
        "mov.f32 %38, 0f00000000;\n"
        "mov.f32 %39, 0f00000000;\n"
        "mov.f32 %40, 0f00000000;\n"
        "mov.f32 %41, 0f00000000;\n"
        "mov.f32 %42, 0f00000000;\n"
        "mov.f32 %43, 0f00000000;\n"
        "mov.f32 %44, 0f00000000;\n"
        "mov.f32 %45, 0f00000000;\n"
        "mov.f32 %46, 0f00000000;\n"
        "mov.f32 %47, 0f00000000;\n"
        "mov.f32 %48, 0f00000000;\n"
        "mov.f32 %49, 0f00000000;\n"
        "mov.f32 %50, 0f00000000;\n"
        "mov.f32 %51, 0f00000000;\n"
        "mov.f32 %52, 0f00000000;\n"
        "mov.f32 %53, 0f00000000;\n"
        "mov.f32 %54, 0f00000000;\n"
        "mov.f32 %55, 0f00000000;\n"
        "mov.f32 %56, 0f00000000;\n"
        "mov.f32 %57, 0f00000000;\n"
        "mov.f32 %58, 0f00000000;\n"
        "mov.f32 %59, 0f00000000;\n"
        "mov.f32 %60, 0f00000000;\n"
        "mov.f32 %61, 0f00000000;\n"
        "mov.f32 %62, 0f00000000;\n"
        "mov.f32 %63, 0f00000000;\n"
        "mov.f32 %64, 0f00000000;\n"
        "mov.f32 %65, 0f00000000;\n"
        "mov.f32 %66, 0f00000000;\n"
        "mov.f32 %67, 0f00000000;\n"
        "mov.f32 %68, 0f00000000;\n"
        "mov.f32 %69, 0f00000000;\n"
        "mov.f32 %70, 0f00000000;\n"
        "mov.f32 %71, 0f00000000;\n"
        "mov.f32 %72, 0f00000000;\n"
        "mov.f32 %73, 0f00000000;\n"
        "mov.f32 %74, 0f00000000;\n"
        "mov.f32 %75, 0f00000000;\n"
        "mov.f32 %76, 0f00000000;\n"
        "mov.f32 %77, 0f00000000;\n"
        "mov.f32 %78, 0f00000000;\n"
        "mov.f32 %79, 0f00000000;\n"
        "mov.f32 %80, 0f00000000;\n"
        "mov.f32 %81, 0f00000000;\n"
        "mov.f32 %82, 0f00000000;\n"
        "mov.f32 %83, 0f00000000;\n"
        "mov.f32 %84, 0f00000000;\n"
        "mov.f32 %85, 0f00000000;\n"
        "mov.f32 %86, 0f00000000;\n"
        "mov.f32 %87, 0f00000000;\n"
        "mov.f32 %88, 0f00000000;\n"
        "mov.f32 %89, 0f00000000;\n"
        "mov.f32 %90, 0f00000000;\n"
        "mov.f32 %91, 0f00000000;\n"
        "mov.f32 %92, 0f00000000;\n"
        "mov.f32 %93, 0f00000000;\n"
        "mov.f32 %94, 0f00000000;\n"
        "mov.f32 %95, 0f00000000;\n"
        "mov.f32 %96, 0f00000000;\n"
        "mov.f32 %97, 0f00000000;\n"
        "mov.f32 %98, 0f00000000;\n"
        "mov.f32 %99, 0f00000000;\n"
        "mov.f32 %100, 0f00000000;\n"
        "mov.f32 %101, 0f00000000;\n"
        "mov.f32 %102, 0f00000000;\n"
        "mov.f32 %103, 0f00000000;\n"
        "mov.f32 %104, 0f00000000;\n"
        "mov.f32 %105, 0f00000000;\n"
        "mov.f32 %106, 0f00000000;\n"
        "mov.f32 %107, 0f00000000;\n"
        "mov.f32 %108, 0f00000000;\n"
        "mov.f32 %109, 0f00000000;\n"
        "mov.f32 %110, 0f00000000;\n"
        "mov.f32 %111, 0f00000000;\n"
        "mov.f32 %112, 0f00000000;\n"
        "mov.f32 %113, 0f00000000;\n"
        "mov.f32 %114, 0f00000000;\n"
        "mov.f32 %115, 0f00000000;\n"
        "mov.f32 %116, 0f00000000;\n"
        "mov.f32 %117, 0f00000000;\n"
        "mov.f32 %118, 0f00000000;\n"
        "mov.f32 %119, 0f00000000;\n"
        "mov.f32 %120, 0f00000000;\n"
        "mov.f32 %121, 0f00000000;\n"
        "mov.f32 %122, 0f00000000;\n"
        "mov.f32 %123, 0f00000000;\n"
        "mov.f32 %124, 0f00000000;\n"
        "mov.f32 %125, 0f00000000;\n"
        "mov.f32 %126, 0f00000000;\n"
        "mov.f32 %127, 0f00000000;\n"
        "mov.f32 %128, 0f00000000;\n"
        "mov.f32 %129, 0f00000000;\n"
        "mov.f32 %130, 0f00000000;\n"
        "mov.f32 %131, 0f00000000;\n"
        "mov.f32 %132, 0f00000000;\n"
        "mov.f32 %133, 0f00000000;\n"
        "mov.f32 %134, 0f00000000;\n"
        "mov.f32 %135, 0f00000000;\n"
        "mov.f32 %136, 0f00000000;\n"
        "mov.f32 %137, 0f00000000;\n"
        "mov.f32 %138, 0f00000000;\n"
        "mov.f32 %139, 0f00000000;\n"
        "mov.f32 %140, 0f00000000;\n"
        "mov.f32 %141, 0f00000000;\n"
        "mov.f32 %142, 0f00000000;\n"
        "mov.f32 %143, 0f00000000;\n"
        "mov.f32 %144, 0f00000000;\n"
        "mov.f32 %145, 0f00000000;\n"
        "mov.f32 %146, 0f00000000;\n"
        "mov.f32 %147, 0f00000000;\n"
        "mov.f32 %148, 0f00000000;\n"
        "mov.f32 %149, 0f00000000;\n"
        "mov.f32 %150, 0f00000000;\n"
        "mov.f32 %151, 0f00000000;\n"
        "setp.ne.u32 pf, 0, 0;\n"
        "add.u32 v0, %186, %191;\n"
        "shfl.sync.idx.b32 so, v0, 0, 31, 0xffffffff;\n"
        "mov.u32 npar, 0;\n"
        "shfl.sync.idx.b32 uz, %191, 7, 31, 0xffffffff;\n"
        "add.u32 bend, %187, " STR(NP * 16) ";\n"
        "add.u32 v0, %191, 8;\n"
        "shfl.sync.idx.b32 dh0, v0, 0, 31, 0xffffffff;\n"
        "shfl.sync.idx.b32 dh1, v0, 1, 31, 0xffffffff;\n"
        "shfl.sync.idx.b32 dh2, v0, 2, 31, 0xffffffff;\n"
        "shfl.sync.idx.b32 dh3, v0, 3, 31, 0xffffffff;\n"
        "add.u32 v0, %191, 0xc0000010;\n"
        "shfl.sync.idx.b32 dh4, v0, 4, 31, 0xffffffff;\n"
        "shfl.sync.idx.b32 dh5, v0, 5, 31, 0xffffffff;\n"
        "add.u32 v0, %191, %188;\n"
        "shfl.sync.idx.b32 eb0, v0, 0, 31, 0xffffffff;\n"
        "mov.u32 q, 0;\n"
        "mov.u32 pl, %190;\n"
        "shr.u32 nbar, so, 9;\n"
        "add.u32 nbar, nbar, %187;\n"
        "elect.sync _|plead, 0xffffffff;\n"
        "mov.b64 de0, {%188, dh4};\n"
        "mov.b64 de1, {eb0, dh5};\n"
        "mov.b32 hYa0, 0;\n"
        "mov.b32 hYa1, 0;\n"
        "mov.b32 hYa2, 0;\n"
        "mov.b32 hYa3, 0;\n"
        "mov.b32 hYa4, 0;\n"
        "mov.b32 hYa5, 0;\n"
        "mov.b32 hYa6, 0;\n"
        "mov.b32 hYa7, 0;\n"
        "mov.b32 hYb0, 0;\n"
        "mov.b32 hYb1, 0;\n"
        "mov.b32 hYb2, 0;\n"
        "mov.b32 hYb3, 0;\n"
        "mov.b32 hYb4, 0;\n"
        "mov.b32 hYb5, 0;\n"
        "mov.b32 hYb6, 0;\n"
        "mov.b32 hYb7, 0;\n"
        "mov.u32 ctm, 0x10001000;\n"
        "setp.lt.f16x2 t0|u0, ctm, cz;\n"
        "abs.f16x2 v3, ctm;\n"
        "setp.ge.f16x2 t1|u1, v3, ca;\n"
        "setp.geu.f16x2 t2|u2, v3, cb;\n"
        "ld.shared.v2.u32 {ctl, ctm}, [pl];\n"
        "add.u32 pl, pl, 8;\n"
        "add.u32 rbar, %187, " STR(DUMB) ";\n"
        "mov.b64 daX, {%189, dh0};\n"
        "mov.b64 dbX, {%189, dh1};\n"
        "mov.b64 daY, {%189, dh2};\n"
        "mov.b64 dbY, {%189, dh3};\n"
        "mov.u32 bar, nbar;\n"
        "mov.u32 par, npar;\n"
        "sub.u32 so, bar, %187;\n"
        "shl.b32 so, so, 9;\n"
        "add.u32 v0, %184, so;\n"
        "add.u32 v1, %185, so;\n"
        "add.u32 nbar, nbar, 16;\n"
        "setp.eq.u32 p, nbar, bend;\n"
        "selp.b32 nbar, %187, nbar, p;\n"
        "@p xor.b32 npar, npar, 1;\n"
        "SLOW:\n"
        "mov.u32 cnt, 0;\n"
        "W1:\n"
        "mbarrier.try_wait.parity.shared.b64 p, [bar], par;\n"
        "@p bra.uni RES;\n"
        "add.u32 cnt, cnt, 1;\n"
        "setp.lt.u32 p, cnt, 4000000;\n"
        "@p bra.uni W1;\n"
        "trap;\n"
        "CX:\n"
        "mbarrier.test_wait.parity.shared.b64 pok, [nbar], npar;\n"
        "and.b32 dl, q, 0x60;\n"
        "add.u32 dl, dl, %189;\n"
        "add.u32 v3, dl, 0;\n"
        "mov.b64 {v2, dh0}, daX;\n"
        "mov.b64 daX, {v3, dh0};\n"
        "add.u32 v3, dl, 257;\n"
        "mov.b64 {v2, dh1}, dbX;\n"
        "mov.b64 dbX, {v3, dh1};\n"
        "add.u32 v3, dl, 514;\n"
        "mov.b64 {v2, dh2}, daY;\n"
        "mov.b64 daY, {v3, dh2};\n"
        "add.u32 v3, dl, 771;\n"
        "mov.b64 {v2, dh3}, dbY;\n"
        "mov.b64 dbY, {v3, dh3};\n"
        "add.u32 q, q, 32;\n"
        "and.b32 qe, q, 0xe0;\n"
        "add.u32 v3, qe, %188;\n"
        "mov.b64 {v2, dh4}, de0;\n"
        "mov.b64 de0, {v3, dh4};\n"
        "mov.b64 {v2, dh5}, de1;\n"
        "mov.b64 de1, {v3, dh5};\n"
        "setp.lt.f16x2 t0|u0, ctl, cz;\n"
        "abs.f16x2 v3, ctl;\n"
        "setp.ge.f16x2 t1|u1, v3, ca;\n"
        "setp.geu.f16x2 t2|u2, v3, cb;\n"
        "wgmma.wait_group.sync.aligned 2;\n"
        "cvt.rn.bf16x2.f32 pX0, r1, r0;\n"
        "cvt.rn.bf16x2.f32 pX1, r3, r2;\n"
        "cvt.rn.bf16x2.f32 pX2, r9, r8;\n"
        "cvt.rn.bf16x2.f32 pX3, r11, r10;\n"
        "cvt.rn.bf16x2.f32 pY0, r5, r4;\n"
        "cvt.rn.bf16x2.f32 pY1, r7, r6;\n"
        "cvt.rn.bf16x2.f32 pY2, r13, r12;\n"
        "cvt.rn.bf16x2.f32 pY3, r15, r14;\n"
        "mov.b32 {sl, sh}, pX0;\n"
        "mov.b32 pp, {sl, sl};\n"
        "mul.rn.bf16x2 hXa0, hLa0, pp;\n"
        "mul.rn.bf16x2 hXa2, hLa2, pp;\n"
        "mov.b32 {sl, sh}, pX1;\n"
        "mov.b32 pp, {sl, sl};\n"
        "mul.rn.bf16x2 hXa1, hLa1, pp;\n"
        "mul.rn.bf16x2 hXa3, hLa3, pp;\n"
        "mov.b32 {sl, sh}, pX2;\n"
        "mov.b32 pp, {sl, sl};\n"
        "mul.rn.bf16x2 hXa4, hLa4, pp;\n"
        "mul.rn.bf16x2 hXa6, hLa6, pp;\n"
        "mov.b32 {sl, sh}, pX3;\n"
        "mov.b32 pp, {sl, sl};\n"
        "mul.rn.bf16x2 hXa5, hLa5, pp;\n"
        "mul.rn.bf16x2 hXa7, hLa7, pp;\n"
        "mov.b32 {sl, sh}, pX0;\n"
        "mov.b32 pp, {sh, sh};\n"
        "mul.rn.bf16x2 hXb0, hLb0, pp;\n"
        "mul.rn.bf16x2 hXb2, hLb2, pp;\n"
        "mov.b32 {sl, sh}, pX1;\n"
        "mov.b32 pp, {sh, sh};\n"
        "mul.rn.bf16x2 hXb1, hLb1, pp;\n"
        "mul.rn.bf16x2 hXb3, hLb3, pp;\n"
        "mov.b32 {sl, sh}, pX2;\n"
        "mov.b32 pp, {sh, sh};\n"
        "mul.rn.bf16x2 hXb4, hLb4, pp;\n"
        "mul.rn.bf16x2 hXb6, hLb6, pp;\n"
        "mov.b32 {sl, sh}, pX3;\n"
        "mov.b32 pp, {sh, sh};\n"
        "mul.rn.bf16x2 hXb5, hLb5, pp;\n"
        "mul.rn.bf16x2 hXb7, hLb7, pp;\n"
        "ldmatrix.sync.aligned.m8n8.x4.trans.shared.b16 {hLa0,hLa1,hLa2,hLa3}, [v0+4096];\n"
        "ldmatrix.sync.aligned.m8n8.x4.trans.shared.b16 {hLa4,hLa5,hLa6,hLa7}, [v1+4096];\n"
        "ldmatrix.sync.aligned.m8n8.x4.trans.shared.b16 {hLb0,hLb1,hLb2,hLb3}, [v0+6144];\n"
        "ldmatrix.sync.aligned.m8n8.x4.trans.shared.b16 {hLb4,hLb5,hLb6,hLb7}, [v1+6144];\n"
        "@t2 bra.uni T4X;\n"
        "@t1 bra.uni T2X;\n"
        "@t0 bra.uni L1X;\n"
        "L0X:\n"
        "wgmma.fence.sync.aligned;\n"
        "wgmma.mma_async.sync.aligned.m64n24k16.f32.bf16.bf16 {%0,%1,%2,%3,%4,%5,%6,%7,%8,%9,%10,%11}, {hXa0,hXa1,hXa2,hXa3}, daX, 1, 1, 1, 0;\n"
        "wgmma.mma_async.sync.aligned.m64n24k16.f32.bf16.bf16 {%76,%77,%78,%79,%80,%81,%82,%83,%84,%85,%86,%87}, {hXa4,hXa5,hXa6,hXa7}, daX, 1, 1, 1, 0;\n"
        "wgmma.commit_group.sync.aligned;\n"
        "@u2 bra.uni T4Xb;\n"
        "@u1 bra.uni T2Xb;\n"
        "@u0 bra.uni L1Xb;\n"
        "bra.uni L0Xb;\n"
        "L1X:\n"
        "wgmma.fence.sync.aligned;\n"
        "wgmma.mma_async.sync.aligned.m64n24k16.f32.bf16.bf16 {%12,%13,%14,%15,%16,%17,%18,%19,%20,%21,%22,%23}, {hXa0,hXa1,hXa2,hXa3}, daX, 1, 1, 1, 0;\n"
        "wgmma.mma_async.sync.aligned.m64n24k16.f32.bf16.bf16 {%88,%89,%90,%91,%92,%93,%94,%95,%96,%97,%98,%99}, {hXa4,hXa5,hXa6,hXa7}, daX, 1, 1, 1, 0;\n"
        "wgmma.commit_group.sync.aligned;\n"
        "@u2 bra.uni T4Xb;\n"
        "@u1 bra.uni T2Xb;\n"
        "@u0 bra.uni L1Xb;\n"
        "bra.uni L0Xb;\n"
        "T2X:\n"
        "@t0 bra.uni L3X;\n"
        "L2X:\n"
        "wgmma.fence.sync.aligned;\n"
        "wgmma.mma_async.sync.aligned.m64n24k16.f32.bf16.bf16 {%24,%25,%26,%27,%28,%29,%30,%31,%32,%33,%34,%35}, {hXa0,hXa1,hXa2,hXa3}, daX, 1, 1, 1, 0;\n"
        "wgmma.mma_async.sync.aligned.m64n24k16.f32.bf16.bf16 {%100,%101,%102,%103,%104,%105,%106,%107,%108,%109,%110,%111}, {hXa4,hXa5,hXa6,hXa7}, daX, 1, 1, 1, 0;\n"
        "wgmma.commit_group.sync.aligned;\n"
        "@u2 bra.uni T4Xb;\n"
        "@u1 bra.uni T2Xb;\n"
        "@u0 bra.uni L1Xb;\n"
        "bra.uni L0Xb;\n"
        "L3X:\n"
        "wgmma.fence.sync.aligned;\n"
        "wgmma.mma_async.sync.aligned.m64n24k16.f32.bf16.bf16 {%36,%37,%38,%39,%40,%41,%42,%43,%44,%45,%46,%47}, {hXa0,hXa1,hXa2,hXa3}, daX, 1, 1, 1, 0;\n"
        "wgmma.mma_async.sync.aligned.m64n24k16.f32.bf16.bf16 {%112,%113,%114,%115,%116,%117,%118,%119,%120,%121,%122,%123}, {hXa4,hXa5,hXa6,hXa7}, daX, 1, 1, 1, 0;\n"
        "wgmma.commit_group.sync.aligned;\n"
        "@u2 bra.uni T4Xb;\n"
        "@u1 bra.uni T2Xb;\n"
        "@u0 bra.uni L1Xb;\n"
        "bra.uni L0Xb;\n"
        "T4X:\n"
        "@!t1 bra.uni LEXIT;\n"
        "@t0 bra.uni L5X;\n"
        "L4X:\n"
        "wgmma.fence.sync.aligned;\n"
        "wgmma.mma_async.sync.aligned.m64n24k16.f32.bf16.bf16 {%48,%49,%50,%51,%52,%53,%54,%55,%56,%57,%58,%59}, {hXa0,hXa1,hXa2,hXa3}, daX, 1, 1, 1, 0;\n"
        "wgmma.mma_async.sync.aligned.m64n24k16.f32.bf16.bf16 {%124,%125,%126,%127,%128,%129,%130,%131,%132,%133,%134,%135}, {hXa4,hXa5,hXa6,hXa7}, daX, 1, 1, 1, 0;\n"
        "wgmma.commit_group.sync.aligned;\n"
        "@u2 bra.uni T4Xb;\n"
        "@u1 bra.uni T2Xb;\n"
        "@u0 bra.uni L1Xb;\n"
        "bra.uni L0Xb;\n"
        "L5X:\n"
        "wgmma.fence.sync.aligned;\n"
        "wgmma.mma_async.sync.aligned.m64n32k16.f32.bf16.bf16 {%60,%61,%62,%63,%64,%65,%66,%67,%68,%69,%70,%71,%72,%73,%74,%75}, {hXa0,hXa1,hXa2,hXa3}, daX, 1, 1, 1, 0;\n"
        "wgmma.mma_async.sync.aligned.m64n32k16.f32.bf16.bf16 {%136,%137,%138,%139,%140,%141,%142,%143,%144,%145,%146,%147,%148,%149,%150,%151}, {hXa4,hXa5,hXa6,hXa7}, daX, 1, 1, 1, 0;\n"
        "wgmma.commit_group.sync.aligned;\n"
        "@u2 bra.uni T4Xb;\n"
        "@u1 bra.uni T2Xb;\n"
        "@u0 bra.uni L1Xb;\n"
        "L0Xb:\n"
        "wgmma.fence.sync.aligned;\n"
        "wgmma.mma_async.sync.aligned.m64n24k16.f32.bf16.bf16 {%0,%1,%2,%3,%4,%5,%6,%7,%8,%9,%10,%11}, {hXb0,hXb1,hXb2,hXb3}, dbX, 1, 1, 1, 0;\n"
        "wgmma.mma_async.sync.aligned.m64n24k16.f32.bf16.bf16 {%76,%77,%78,%79,%80,%81,%82,%83,%84,%85,%86,%87}, {hXb4,hXb5,hXb6,hXb7}, dbX, 1, 1, 1, 0;\n"
        "wgmma.commit_group.sync.aligned;\n"
        "bra.uni CY;\n"
        "L1Xb:\n"
        "wgmma.fence.sync.aligned;\n"
        "wgmma.mma_async.sync.aligned.m64n24k16.f32.bf16.bf16 {%12,%13,%14,%15,%16,%17,%18,%19,%20,%21,%22,%23}, {hXb0,hXb1,hXb2,hXb3}, dbX, 1, 1, 1, 0;\n"
        "wgmma.mma_async.sync.aligned.m64n24k16.f32.bf16.bf16 {%88,%89,%90,%91,%92,%93,%94,%95,%96,%97,%98,%99}, {hXb4,hXb5,hXb6,hXb7}, dbX, 1, 1, 1, 0;\n"
        "wgmma.commit_group.sync.aligned;\n"
        "bra.uni CY;\n"
        "T2Xb:\n"
        "@u0 bra.uni L3Xb;\n"
        "L2Xb:\n"
        "wgmma.fence.sync.aligned;\n"
        "wgmma.mma_async.sync.aligned.m64n24k16.f32.bf16.bf16 {%24,%25,%26,%27,%28,%29,%30,%31,%32,%33,%34,%35}, {hXb0,hXb1,hXb2,hXb3}, dbX, 1, 1, 1, 0;\n"
        "wgmma.mma_async.sync.aligned.m64n24k16.f32.bf16.bf16 {%100,%101,%102,%103,%104,%105,%106,%107,%108,%109,%110,%111}, {hXb4,hXb5,hXb6,hXb7}, dbX, 1, 1, 1, 0;\n"
        "wgmma.commit_group.sync.aligned;\n"
        "bra.uni CY;\n"
        "L3Xb:\n"
        "wgmma.fence.sync.aligned;\n"
        "wgmma.mma_async.sync.aligned.m64n24k16.f32.bf16.bf16 {%36,%37,%38,%39,%40,%41,%42,%43,%44,%45,%46,%47}, {hXb0,hXb1,hXb2,hXb3}, dbX, 1, 1, 1, 0;\n"
        "wgmma.mma_async.sync.aligned.m64n24k16.f32.bf16.bf16 {%112,%113,%114,%115,%116,%117,%118,%119,%120,%121,%122,%123}, {hXb4,hXb5,hXb6,hXb7}, dbX, 1, 1, 1, 0;\n"
        "wgmma.commit_group.sync.aligned;\n"
        "bra.uni CY;\n"
        "T4Xb:\n"
        "@u0 bra.uni L5Xb;\n"
        "L4Xb:\n"
        "wgmma.fence.sync.aligned;\n"
        "wgmma.mma_async.sync.aligned.m64n24k16.f32.bf16.bf16 {%48,%49,%50,%51,%52,%53,%54,%55,%56,%57,%58,%59}, {hXb0,hXb1,hXb2,hXb3}, dbX, 1, 1, 1, 0;\n"
        "wgmma.mma_async.sync.aligned.m64n24k16.f32.bf16.bf16 {%124,%125,%126,%127,%128,%129,%130,%131,%132,%133,%134,%135}, {hXb4,hXb5,hXb6,hXb7}, dbX, 1, 1, 1, 0;\n"
        "wgmma.commit_group.sync.aligned;\n"
        "bra.uni CY;\n"
        "L5Xb:\n"
        "wgmma.fence.sync.aligned;\n"
        "wgmma.mma_async.sync.aligned.m64n32k16.f32.bf16.bf16 {%60,%61,%62,%63,%64,%65,%66,%67,%68,%69,%70,%71,%72,%73,%74,%75}, {hXb0,hXb1,hXb2,hXb3}, dbX, 1, 1, 1, 0;\n"
        "wgmma.mma_async.sync.aligned.m64n32k16.f32.bf16.bf16 {%136,%137,%138,%139,%140,%141,%142,%143,%144,%145,%146,%147,%148,%149,%150,%151}, {hXb4,hXb5,hXb6,hXb7}, dbX, 1, 1, 1, 0;\n"
        "wgmma.commit_group.sync.aligned;\n"
        "bra.uni CY;\n"
        "CY:\n"
        "mov.u32 rbar, bar;\n"
        "mov.u32 bar, nbar;\n"
        "mov.u32 par, npar;\n"
        "sub.u32 so, bar, %187;\n"
        "shl.b32 so, so, 9;\n"
        "add.u32 v0, %184, so;\n"
        "add.u32 v1, %185, so;\n"
        "add.u32 nbar, nbar, 16;\n"
        "setp.eq.u32 p, nbar, bend;\n"
        "selp.b32 nbar, %187, nbar, p;\n"
        "@p xor.b32 npar, npar, 1;\n"
        "wgmma.wait_group.sync.aligned 2;\n"
        "lop3.b32 v2, hLa3, hLa7, hLb3, 0x80;\n"
        "lop3.b32 v2, v2, hLb7, uz, 0x80;\n"
        "add.u32 v2, v2, rbar;\n"
        "@plead mbarrier.arrive.shared.b64 _, [v2+8];\n"
        "setp.lt.f16x2 t0|u0, ctm, cz;\n"
        "abs.f16x2 v3, ctm;\n"
        "setp.ge.f16x2 t1|u1, v3, ca;\n"
        "setp.geu.f16x2 t2|u2, v3, cb;\n"
        "ld.shared.v2.u32 {ctl, ctm}, [pl];\n"
        "add.u32 pl, pl, 8;\n"
        "mov.b32 {sl, sh}, pY0;\n"
        "mov.b32 pp, {sl, sl};\n"
        "mul.rn.bf16x2 hYa0, hLa0, pp;\n"
        "mul.rn.bf16x2 hYa2, hLa2, pp;\n"
        "mov.b32 {sl, sh}, pY1;\n"
        "mov.b32 pp, {sl, sl};\n"
        "mul.rn.bf16x2 hYa1, hLa1, pp;\n"
        "mul.rn.bf16x2 hYa3, hLa3, pp;\n"
        "mov.b32 {sl, sh}, pY2;\n"
        "mov.b32 pp, {sl, sl};\n"
        "mul.rn.bf16x2 hYa4, hLa4, pp;\n"
        "mul.rn.bf16x2 hYa6, hLa6, pp;\n"
        "mov.b32 {sl, sh}, pY3;\n"
        "mov.b32 pp, {sl, sl};\n"
        "mul.rn.bf16x2 hYa5, hLa5, pp;\n"
        "mul.rn.bf16x2 hYa7, hLa7, pp;\n"
        "mov.b32 {sl, sh}, pY0;\n"
        "mov.b32 pp, {sh, sh};\n"
        "mul.rn.bf16x2 hYb0, hLb0, pp;\n"
        "mul.rn.bf16x2 hYb2, hLb2, pp;\n"
        "mov.b32 {sl, sh}, pY1;\n"
        "mov.b32 pp, {sh, sh};\n"
        "mul.rn.bf16x2 hYb1, hLb1, pp;\n"
        "mul.rn.bf16x2 hYb3, hLb3, pp;\n"
        "mov.b32 {sl, sh}, pY2;\n"
        "mov.b32 pp, {sh, sh};\n"
        "mul.rn.bf16x2 hYb4, hLb4, pp;\n"
        "mul.rn.bf16x2 hYb6, hLb6, pp;\n"
        "mov.b32 {sl, sh}, pY3;\n"
        "mov.b32 pp, {sh, sh};\n"
        "mul.rn.bf16x2 hYb5, hLb5, pp;\n"
        "mul.rn.bf16x2 hYb7, hLb7, pp;\n"
        "@!pok bra.uni SLOW;\n"
        "RES:\n"
        "ldmatrix.sync.aligned.m8n8.x4.trans.shared.b16 {hLa0,hLa1,hLa2,hLa3}, [v0+0];\n"
        "ldmatrix.sync.aligned.m8n8.x4.trans.shared.b16 {hLa4,hLa5,hLa6,hLa7}, [v1+0];\n"
        "ldmatrix.sync.aligned.m8n8.x4.trans.shared.b16 {hLb0,hLb1,hLb2,hLb3}, [v0+2048];\n"
        "ldmatrix.sync.aligned.m8n8.x4.trans.shared.b16 {hLb4,hLb5,hLb6,hLb7}, [v1+2048];\n"
        "wgmma.wait_group.sync.aligned 0;\n"
        "@t2 bra.uni T4Y;\n"
        "@t1 bra.uni T2Y;\n"
        "@t0 bra.uni L1Y;\n"
        "L0Y:\n"
        "wgmma.fence.sync.aligned;\n"
        "wgmma.mma_async.sync.aligned.m64n16k16.f32.bf16.bf16 {r0,r1,r2,r3,r4,r5,r6,r7}, {wa0,wa1,wa2,wa3}, de0, pf, 1, 1, 0;\n"
        "wgmma.mma_async.sync.aligned.m64n16k16.f32.bf16.bf16 {r8,r9,r10,r11,r12,r13,r14,r15}, {wa4,wa5,wa6,wa7}, de1, pf, 1, 1, 0;\n"
        "wgmma.commit_group.sync.aligned;\n"
        "wgmma.mma_async.sync.aligned.m64n24k16.f32.bf16.bf16 {%0,%1,%2,%3,%4,%5,%6,%7,%8,%9,%10,%11}, {hYa0,hYa1,hYa2,hYa3}, daY, 1, 1, 1, 0;\n"
        "wgmma.mma_async.sync.aligned.m64n24k16.f32.bf16.bf16 {%76,%77,%78,%79,%80,%81,%82,%83,%84,%85,%86,%87}, {hYa4,hYa5,hYa6,hYa7}, daY, 1, 1, 1, 0;\n"
        "wgmma.commit_group.sync.aligned;\n"
        "@u2 bra.uni T4Yb;\n"
        "@u1 bra.uni T2Yb;\n"
        "@u0 bra.uni L1Yb;\n"
        "bra.uni L0Yb;\n"
        "L1Y:\n"
        "wgmma.fence.sync.aligned;\n"
        "wgmma.mma_async.sync.aligned.m64n16k16.f32.bf16.bf16 {r0,r1,r2,r3,r4,r5,r6,r7}, {wa0,wa1,wa2,wa3}, de0, pf, 1, 1, 0;\n"
        "wgmma.mma_async.sync.aligned.m64n16k16.f32.bf16.bf16 {r8,r9,r10,r11,r12,r13,r14,r15}, {wa4,wa5,wa6,wa7}, de1, pf, 1, 1, 0;\n"
        "wgmma.commit_group.sync.aligned;\n"
        "wgmma.mma_async.sync.aligned.m64n24k16.f32.bf16.bf16 {%12,%13,%14,%15,%16,%17,%18,%19,%20,%21,%22,%23}, {hYa0,hYa1,hYa2,hYa3}, daY, 1, 1, 1, 0;\n"
        "wgmma.mma_async.sync.aligned.m64n24k16.f32.bf16.bf16 {%88,%89,%90,%91,%92,%93,%94,%95,%96,%97,%98,%99}, {hYa4,hYa5,hYa6,hYa7}, daY, 1, 1, 1, 0;\n"
        "wgmma.commit_group.sync.aligned;\n"
        "@u2 bra.uni T4Yb;\n"
        "@u1 bra.uni T2Yb;\n"
        "@u0 bra.uni L1Yb;\n"
        "bra.uni L0Yb;\n"
        "T2Y:\n"
        "@t0 bra.uni L3Y;\n"
        "L2Y:\n"
        "wgmma.fence.sync.aligned;\n"
        "wgmma.mma_async.sync.aligned.m64n16k16.f32.bf16.bf16 {r0,r1,r2,r3,r4,r5,r6,r7}, {wa0,wa1,wa2,wa3}, de0, pf, 1, 1, 0;\n"
        "wgmma.mma_async.sync.aligned.m64n16k16.f32.bf16.bf16 {r8,r9,r10,r11,r12,r13,r14,r15}, {wa4,wa5,wa6,wa7}, de1, pf, 1, 1, 0;\n"
        "wgmma.commit_group.sync.aligned;\n"
        "wgmma.mma_async.sync.aligned.m64n24k16.f32.bf16.bf16 {%24,%25,%26,%27,%28,%29,%30,%31,%32,%33,%34,%35}, {hYa0,hYa1,hYa2,hYa3}, daY, 1, 1, 1, 0;\n"
        "wgmma.mma_async.sync.aligned.m64n24k16.f32.bf16.bf16 {%100,%101,%102,%103,%104,%105,%106,%107,%108,%109,%110,%111}, {hYa4,hYa5,hYa6,hYa7}, daY, 1, 1, 1, 0;\n"
        "wgmma.commit_group.sync.aligned;\n"
        "@u2 bra.uni T4Yb;\n"
        "@u1 bra.uni T2Yb;\n"
        "@u0 bra.uni L1Yb;\n"
        "bra.uni L0Yb;\n"
        "L3Y:\n"
        "wgmma.fence.sync.aligned;\n"
        "wgmma.mma_async.sync.aligned.m64n16k16.f32.bf16.bf16 {r0,r1,r2,r3,r4,r5,r6,r7}, {wa0,wa1,wa2,wa3}, de0, pf, 1, 1, 0;\n"
        "wgmma.mma_async.sync.aligned.m64n16k16.f32.bf16.bf16 {r8,r9,r10,r11,r12,r13,r14,r15}, {wa4,wa5,wa6,wa7}, de1, pf, 1, 1, 0;\n"
        "wgmma.commit_group.sync.aligned;\n"
        "wgmma.mma_async.sync.aligned.m64n24k16.f32.bf16.bf16 {%36,%37,%38,%39,%40,%41,%42,%43,%44,%45,%46,%47}, {hYa0,hYa1,hYa2,hYa3}, daY, 1, 1, 1, 0;\n"
        "wgmma.mma_async.sync.aligned.m64n24k16.f32.bf16.bf16 {%112,%113,%114,%115,%116,%117,%118,%119,%120,%121,%122,%123}, {hYa4,hYa5,hYa6,hYa7}, daY, 1, 1, 1, 0;\n"
        "wgmma.commit_group.sync.aligned;\n"
        "@u2 bra.uni T4Yb;\n"
        "@u1 bra.uni T2Yb;\n"
        "@u0 bra.uni L1Yb;\n"
        "bra.uni L0Yb;\n"
        "T4Y:\n"
        "@t0 bra.uni L5Y;\n"
        "L4Y:\n"
        "wgmma.fence.sync.aligned;\n"
        "wgmma.mma_async.sync.aligned.m64n16k16.f32.bf16.bf16 {r0,r1,r2,r3,r4,r5,r6,r7}, {wa0,wa1,wa2,wa3}, de0, pf, 1, 1, 0;\n"
        "wgmma.mma_async.sync.aligned.m64n16k16.f32.bf16.bf16 {r8,r9,r10,r11,r12,r13,r14,r15}, {wa4,wa5,wa6,wa7}, de1, pf, 1, 1, 0;\n"
        "wgmma.commit_group.sync.aligned;\n"
        "wgmma.mma_async.sync.aligned.m64n24k16.f32.bf16.bf16 {%48,%49,%50,%51,%52,%53,%54,%55,%56,%57,%58,%59}, {hYa0,hYa1,hYa2,hYa3}, daY, 1, 1, 1, 0;\n"
        "wgmma.mma_async.sync.aligned.m64n24k16.f32.bf16.bf16 {%124,%125,%126,%127,%128,%129,%130,%131,%132,%133,%134,%135}, {hYa4,hYa5,hYa6,hYa7}, daY, 1, 1, 1, 0;\n"
        "wgmma.commit_group.sync.aligned;\n"
        "@u2 bra.uni T4Yb;\n"
        "@u1 bra.uni T2Yb;\n"
        "@u0 bra.uni L1Yb;\n"
        "bra.uni L0Yb;\n"
        "L5Y:\n"
        "wgmma.fence.sync.aligned;\n"
        "wgmma.mma_async.sync.aligned.m64n16k16.f32.bf16.bf16 {r0,r1,r2,r3,r4,r5,r6,r7}, {wa0,wa1,wa2,wa3}, de0, pf, 1, 1, 0;\n"
        "wgmma.mma_async.sync.aligned.m64n16k16.f32.bf16.bf16 {r8,r9,r10,r11,r12,r13,r14,r15}, {wa4,wa5,wa6,wa7}, de1, pf, 1, 1, 0;\n"
        "wgmma.commit_group.sync.aligned;\n"
        "wgmma.mma_async.sync.aligned.m64n32k16.f32.bf16.bf16 {%60,%61,%62,%63,%64,%65,%66,%67,%68,%69,%70,%71,%72,%73,%74,%75}, {hYa0,hYa1,hYa2,hYa3}, daY, 1, 1, 1, 0;\n"
        "wgmma.mma_async.sync.aligned.m64n32k16.f32.bf16.bf16 {%136,%137,%138,%139,%140,%141,%142,%143,%144,%145,%146,%147,%148,%149,%150,%151}, {hYa4,hYa5,hYa6,hYa7}, daY, 1, 1, 1, 0;\n"
        "wgmma.commit_group.sync.aligned;\n"
        "@u2 bra.uni T4Yb;\n"
        "@u1 bra.uni T2Yb;\n"
        "@u0 bra.uni L1Yb;\n"
        "L0Yb:\n"
        "wgmma.fence.sync.aligned;\n"
        "wgmma.mma_async.sync.aligned.m64n24k16.f32.bf16.bf16 {%0,%1,%2,%3,%4,%5,%6,%7,%8,%9,%10,%11}, {hYb0,hYb1,hYb2,hYb3}, dbY, 1, 1, 1, 0;\n"
        "wgmma.mma_async.sync.aligned.m64n24k16.f32.bf16.bf16 {%76,%77,%78,%79,%80,%81,%82,%83,%84,%85,%86,%87}, {hYb4,hYb5,hYb6,hYb7}, dbY, 1, 1, 1, 0;\n"
        "wgmma.commit_group.sync.aligned;\n"
        "bra.uni CX;\n"
        "L1Yb:\n"
        "wgmma.fence.sync.aligned;\n"
        "wgmma.mma_async.sync.aligned.m64n24k16.f32.bf16.bf16 {%12,%13,%14,%15,%16,%17,%18,%19,%20,%21,%22,%23}, {hYb0,hYb1,hYb2,hYb3}, dbY, 1, 1, 1, 0;\n"
        "wgmma.mma_async.sync.aligned.m64n24k16.f32.bf16.bf16 {%88,%89,%90,%91,%92,%93,%94,%95,%96,%97,%98,%99}, {hYb4,hYb5,hYb6,hYb7}, dbY, 1, 1, 1, 0;\n"
        "wgmma.commit_group.sync.aligned;\n"
        "bra.uni CX;\n"
        "T2Yb:\n"
        "@u0 bra.uni L3Yb;\n"
        "L2Yb:\n"
        "wgmma.fence.sync.aligned;\n"
        "wgmma.mma_async.sync.aligned.m64n24k16.f32.bf16.bf16 {%24,%25,%26,%27,%28,%29,%30,%31,%32,%33,%34,%35}, {hYb0,hYb1,hYb2,hYb3}, dbY, 1, 1, 1, 0;\n"
        "wgmma.mma_async.sync.aligned.m64n24k16.f32.bf16.bf16 {%100,%101,%102,%103,%104,%105,%106,%107,%108,%109,%110,%111}, {hYb4,hYb5,hYb6,hYb7}, dbY, 1, 1, 1, 0;\n"
        "wgmma.commit_group.sync.aligned;\n"
        "bra.uni CX;\n"
        "L3Yb:\n"
        "wgmma.fence.sync.aligned;\n"
        "wgmma.mma_async.sync.aligned.m64n24k16.f32.bf16.bf16 {%36,%37,%38,%39,%40,%41,%42,%43,%44,%45,%46,%47}, {hYb0,hYb1,hYb2,hYb3}, dbY, 1, 1, 1, 0;\n"
        "wgmma.mma_async.sync.aligned.m64n24k16.f32.bf16.bf16 {%112,%113,%114,%115,%116,%117,%118,%119,%120,%121,%122,%123}, {hYb4,hYb5,hYb6,hYb7}, dbY, 1, 1, 1, 0;\n"
        "wgmma.commit_group.sync.aligned;\n"
        "bra.uni CX;\n"
        "T4Yb:\n"
        "@u0 bra.uni L5Yb;\n"
        "L4Yb:\n"
        "wgmma.fence.sync.aligned;\n"
        "wgmma.mma_async.sync.aligned.m64n24k16.f32.bf16.bf16 {%48,%49,%50,%51,%52,%53,%54,%55,%56,%57,%58,%59}, {hYb0,hYb1,hYb2,hYb3}, dbY, 1, 1, 1, 0;\n"
        "wgmma.mma_async.sync.aligned.m64n24k16.f32.bf16.bf16 {%124,%125,%126,%127,%128,%129,%130,%131,%132,%133,%134,%135}, {hYb4,hYb5,hYb6,hYb7}, dbY, 1, 1, 1, 0;\n"
        "wgmma.commit_group.sync.aligned;\n"
        "bra.uni CX;\n"
        "L5Yb:\n"
        "wgmma.fence.sync.aligned;\n"
        "wgmma.mma_async.sync.aligned.m64n32k16.f32.bf16.bf16 {%60,%61,%62,%63,%64,%65,%66,%67,%68,%69,%70,%71,%72,%73,%74,%75}, {hYb0,hYb1,hYb2,hYb3}, dbY, 1, 1, 1, 0;\n"
        "wgmma.mma_async.sync.aligned.m64n32k16.f32.bf16.bf16 {%136,%137,%138,%139,%140,%141,%142,%143,%144,%145,%146,%147,%148,%149,%150,%151}, {hYb4,hYb5,hYb6,hYb7}, dbY, 1, 1, 1, 0;\n"
        "wgmma.commit_group.sync.aligned;\n"
        "bra.uni CX;\n"
        "LEXIT:\n"
        "mov.u32 v2, %%tid.x;\n"
        "shr.u32 v3, v2, 4;\n"
        "and.b32 v0, v3, 1;\n"
        "mad.lo.u32 v0, v0, 1024, %200;\n"
        "and.b32 v1, v2, 7;\n"
        "mad.lo.u32 v0, v1, 128, v0;\n"
        "shr.u32 pp, v2, 3;\n"
        "lop3.b32 v3, v3, pp, 6, 0xe4;\n"
        "add.u32 pp, v2, 1;\n"
        "lop3.b32 pp, v3, pp, 7, 0x28;\n"
        "mad.lo.u32 v1, pp, 16, v0;\n"
        "lop3.b32 pp, v3, v2, 7, 0x28;\n"
        "mad.lo.u32 v0, pp, 16, v0;\n"
        "@pok bra.uni LW;\n"
        "mov.u32 cnt, 0;\n"
        "W2:\n"
        "mbarrier.try_wait.parity.shared.b64 p, [nbar], npar;\n"
        "@p bra.uni LW;\n"
        "add.u32 cnt, cnt, 1;\n"
        "setp.lt.u32 p, cnt, 4000000;\n"
        "@p bra.uni W2;\n"
        "trap;\n"
        "LW:\n"
        "ldmatrix.sync.aligned.m8n8.x4.trans.shared.b16 {hLa0,hLa1,hLa2,hLa3}, [v0+" STR((NP - 2) * 8192 + 0 * SM_ODD + 0) "];\n"
        "ldmatrix.sync.aligned.m8n8.x4.trans.shared.b16 {hLa4,hLa5,hLa6,hLa7}, [v0+" STR((NP - 2) * 8192 + 0 * SM_ODD + 2048) "];\n"
        "wgmma.wait_group.sync.aligned 0;\n"
        "ldmatrix.sync.aligned.m8n8.x4.trans.shared.b16 {hLb0,hLb1,hLb2,hLb3}, [v0+" STR((NP - 2) * 8192 + 0 * SM_ODD + 4096) "];\n"
        "ldmatrix.sync.aligned.m8n8.x4.trans.shared.b16 {hLb4,hLb5,hLb6,hLb7}, [v0+" STR((NP - 2) * 8192 + 0 * SM_ODD + 6144) "];\n"
        "ldmatrix.sync.aligned.m8n8.x4.trans.shared.b16 {hXa0,hXa1,hXa2,hXa3}, [v1+" STR((NP - 2) * 8192 + 1 * SM_ODD + 0) "];\n"
        "ldmatrix.sync.aligned.m8n8.x4.trans.shared.b16 {hXa4,hXa5,hXa6,hXa7}, [v1+" STR((NP - 2) * 8192 + 1 * SM_ODD + 2048) "];\n"
        "ldmatrix.sync.aligned.m8n8.x4.trans.shared.b16 {hXb0,hXb1,hXb2,hXb3}, [v1+" STR((NP - 2) * 8192 + 1 * SM_ODD + 4096) "];\n"
        "ldmatrix.sync.aligned.m8n8.x4.trans.shared.b16 {hXb4,hXb5,hXb6,hXb7}, [v1+" STR((NP - 2) * 8192 + 1 * SM_ODD + 6144) "];\n"
        "mov.b32 %152, hLa0;\n"
        "mov.b32 %153, hLa1;\n"
        "mov.b32 %154, hLa2;\n"
        "mov.b32 %155, hLa3;\n"
        "mov.b32 %156, hLa4;\n"
        "mov.b32 %157, hLa5;\n"
        "mov.b32 %158, hLa6;\n"
        "mov.b32 %159, hLa7;\n"
        "mov.b32 %160, hLb0;\n"
        "mov.b32 %161, hLb1;\n"
        "mov.b32 %162, hLb2;\n"
        "mov.b32 %163, hLb3;\n"
        "mov.b32 %164, hLb4;\n"
        "mov.b32 %165, hLb5;\n"
        "mov.b32 %166, hLb6;\n"
        "mov.b32 %167, hLb7;\n"
        "mov.b32 %168, hXa0;\n"
        "mov.b32 %169, hXa1;\n"
        "mov.b32 %170, hXa2;\n"
        "mov.b32 %171, hXa3;\n"
        "mov.b32 %172, hXa4;\n"
        "mov.b32 %173, hXa5;\n"
        "mov.b32 %174, hXa6;\n"
        "mov.b32 %175, hXa7;\n"
        "mov.b32 %176, hXb0;\n"
        "mov.b32 %177, hXb1;\n"
        "mov.b32 %178, hXb2;\n"
        "mov.b32 %179, hXb3;\n"
        "mov.b32 %180, hXb4;\n"
        "mov.b32 %181, hXb5;\n"
        "mov.b32 %182, hXb6;\n"
        "mov.b32 %183, hXb7;\n"
        "}\n"
        : "=f"(acc[0][0][0]), "=f"(acc[0][0][1]), "=f"(acc[0][0][2]), "=f"(acc[0][0][3]),
          "=f"(acc[0][1][0]), "=f"(acc[0][1][1]), "=f"(acc[0][1][2]), "=f"(acc[0][1][3]),
          "=f"(acc[0][2][0]), "=f"(acc[0][2][1]), "=f"(acc[0][2][2]), "=f"(acc[0][2][3]),
          "=f"(acc[0][3][0]), "=f"(acc[0][3][1]), "=f"(acc[0][3][2]), "=f"(acc[0][3][3]),
          "=f"(acc[0][4][0]), "=f"(acc[0][4][1]), "=f"(acc[0][4][2]), "=f"(acc[0][4][3]),
          "=f"(acc[0][5][0]), "=f"(acc[0][5][1]), "=f"(acc[0][5][2]), "=f"(acc[0][5][3]),
          "=f"(acc[0][6][0]), "=f"(acc[0][6][1]), "=f"(acc[0][6][2]), "=f"(acc[0][6][3]),
          "=f"(acc[0][7][0]), "=f"(acc[0][7][1]), "=f"(acc[0][7][2]), "=f"(acc[0][7][3]),
          "=f"(acc[0][8][0]), "=f"(acc[0][8][1]), "=f"(acc[0][8][2]), "=f"(acc[0][8][3]),
          "=f"(acc[0][9][0]), "=f"(acc[0][9][1]), "=f"(acc[0][9][2]), "=f"(acc[0][9][3]),
          "=f"(acc[0][10][0]), "=f"(acc[0][10][1]), "=f"(acc[0][10][2]), "=f"(acc[0][10][3]),
          "=f"(acc[0][11][0]), "=f"(acc[0][11][1]), "=f"(acc[0][11][2]), "=f"(acc[0][11][3]),
          "=f"(acc[0][12][0]), "=f"(acc[0][12][1]), "=f"(acc[0][12][2]), "=f"(acc[0][12][3]),
          "=f"(acc[0][13][0]), "=f"(acc[0][13][1]), "=f"(acc[0][13][2]), "=f"(acc[0][13][3]),
          "=f"(acc[0][14][0]), "=f"(acc[0][14][1]), "=f"(acc[0][14][2]), "=f"(acc[0][14][3]),
          "=f"(acc[0][15][0]), "=f"(acc[0][15][1]), "=f"(acc[0][15][2]), "=f"(acc[0][15][3]),
          "=f"(acc[0][16][0]), "=f"(acc[0][16][1]), "=f"(acc[0][16][2]), "=f"(acc[0][16][3]),
          "=f"(acc[0][17][0]), "=f"(acc[0][17][1]), "=f"(acc[0][17][2]), "=f"(acc[0][17][3]),
          "=f"(acc[0][18][0]), "=f"(acc[0][18][1]), "=f"(acc[0][18][2]), "=f"(acc[0][18][3]),
          "=f"(acc[1][0][0]), "=f"(acc[1][0][1]), "=f"(acc[1][0][2]), "=f"(acc[1][0][3]),
          "=f"(acc[1][1][0]), "=f"(acc[1][1][1]), "=f"(acc[1][1][2]), "=f"(acc[1][1][3]),
          "=f"(acc[1][2][0]), "=f"(acc[1][2][1]), "=f"(acc[1][2][2]), "=f"(acc[1][2][3]),
          "=f"(acc[1][3][0]), "=f"(acc[1][3][1]), "=f"(acc[1][3][2]), "=f"(acc[1][3][3]),
          "=f"(acc[1][4][0]), "=f"(acc[1][4][1]), "=f"(acc[1][4][2]), "=f"(acc[1][4][3]),
          "=f"(acc[1][5][0]), "=f"(acc[1][5][1]), "=f"(acc[1][5][2]), "=f"(acc[1][5][3]),
          "=f"(acc[1][6][0]), "=f"(acc[1][6][1]), "=f"(acc[1][6][2]), "=f"(acc[1][6][3]),
          "=f"(acc[1][7][0]), "=f"(acc[1][7][1]), "=f"(acc[1][7][2]), "=f"(acc[1][7][3]),
          "=f"(acc[1][8][0]), "=f"(acc[1][8][1]), "=f"(acc[1][8][2]), "=f"(acc[1][8][3]),
          "=f"(acc[1][9][0]), "=f"(acc[1][9][1]), "=f"(acc[1][9][2]), "=f"(acc[1][9][3]),
          "=f"(acc[1][10][0]), "=f"(acc[1][10][1]), "=f"(acc[1][10][2]), "=f"(acc[1][10][3]),
          "=f"(acc[1][11][0]), "=f"(acc[1][11][1]), "=f"(acc[1][11][2]), "=f"(acc[1][11][3]),
          "=f"(acc[1][12][0]), "=f"(acc[1][12][1]), "=f"(acc[1][12][2]), "=f"(acc[1][12][3]),
          "=f"(acc[1][13][0]), "=f"(acc[1][13][1]), "=f"(acc[1][13][2]), "=f"(acc[1][13][3]),
          "=f"(acc[1][14][0]), "=f"(acc[1][14][1]), "=f"(acc[1][14][2]), "=f"(acc[1][14][3]),
          "=f"(acc[1][15][0]), "=f"(acc[1][15][1]), "=f"(acc[1][15][2]), "=f"(acc[1][15][3]),
          "=f"(acc[1][16][0]), "=f"(acc[1][16][1]), "=f"(acc[1][16][2]), "=f"(acc[1][16][3]),
          "=f"(acc[1][17][0]), "=f"(acc[1][17][1]), "=f"(acc[1][17][2]), "=f"(acc[1][17][3]),
          "=f"(acc[1][18][0]), "=f"(acc[1][18][1]), "=f"(acc[1][18][2]), "=f"(acc[1][18][3]),
          "=r"(wo[0][0]), "=r"(wo[0][1]), "=r"(wo[0][2]), "=r"(wo[0][3]),
          "=r"(wo[1][0]), "=r"(wo[1][1]), "=r"(wo[1][2]), "=r"(wo[1][3]),
          "=r"(wo[2][0]), "=r"(wo[2][1]), "=r"(wo[2][2]), "=r"(wo[2][3]),
          "=r"(wo[3][0]), "=r"(wo[3][1]), "=r"(wo[3][2]), "=r"(wo[3][3]),
          "=r"(wo[4][0]), "=r"(wo[4][1]), "=r"(wo[4][2]), "=r"(wo[4][3]),
          "=r"(wo[5][0]), "=r"(wo[5][1]), "=r"(wo[5][2]), "=r"(wo[5][3]),
          "=r"(wo[6][0]), "=r"(wo[6][1]), "=r"(wo[6][2]), "=r"(wo[6][3]),
          "=r"(wo[7][0]), "=r"(wo[7][1]), "=r"(wo[7][2]), "=r"(wo[7][3])
        : "r"(xa0), "r"(xa1), "r"(so0), "r"(bar0), "r"(ea0), "r"(d0), "r"(pl0), "r"(lz), "r"(wa[0]), "r"(wa[1]), "r"(wa[2]),
          "r"(wa[3]), "r"(wa[4]), "r"(wa[5]), "r"(wa[6]), "r"(wa[7]), "r"(ring)
        : "memory");
}
#define CH0 4
#define CH1 7
#define CH2 8
#define CH3 10
#define CH4 9
__device__ __forceinline__ void wgmma_out(float (&o)[4][4], const uint32_t (&a)[4], uint64_t db, bool acc) {
    if (!acc)
        asm volatile(
            "wgmma.mma_async.sync.aligned.m64n32k16.f32.bf16.bf16 {%0,%1,%2,%3,%4,%5,%6,%7,%8,%9,%10,%11,%12,%13,%14,%15}, {%16,%17,%18,%19}, %20, 0, 1, 1, 1;"
            : "=f"(o[0][0]), "=f"(o[0][1]), "=f"(o[0][2]), "=f"(o[0][3]),
              "=f"(o[1][0]), "=f"(o[1][1]), "=f"(o[1][2]), "=f"(o[1][3]),
              "=f"(o[2][0]), "=f"(o[2][1]), "=f"(o[2][2]), "=f"(o[2][3]),
              "=f"(o[3][0]), "=f"(o[3][1]), "=f"(o[3][2]), "=f"(o[3][3])
            : "r"(a[0]), "r"(a[1]), "r"(a[2]), "r"(a[3]), "l"(db)
            : "memory");
    else
        asm volatile(
            "wgmma.mma_async.sync.aligned.m64n32k16.f32.bf16.bf16 {%0,%1,%2,%3,%4,%5,%6,%7,%8,%9,%10,%11,%12,%13,%14,%15}, {%16,%17,%18,%19}, %20, 1, 1, 1, 1;"
            : "+f"(o[0][0]), "+f"(o[0][1]), "+f"(o[0][2]), "+f"(o[0][3]),
              "+f"(o[1][0]), "+f"(o[1][1]), "+f"(o[1][2]), "+f"(o[1][3]),
              "+f"(o[2][0]), "+f"(o[2][1]), "+f"(o[2][2]), "+f"(o[2][3]),
              "+f"(o[3][0]), "+f"(o[3][1]), "+f"(o[3][2]), "+f"(o[3][3])
            : "r"(a[0]), "r"(a[1]), "r"(a[2]), "r"(a[3]), "l"(db)
            : "memory");
}
__device__ __forceinline__ void wgmma_out(float (&o)[7][4], const uint32_t (&a)[4], uint64_t db, bool acc) {
    if (!acc)
        asm volatile(
            "wgmma.mma_async.sync.aligned.m64n56k16.f32.bf16.bf16 {%0,%1,%2,%3,%4,%5,%6,%7,%8,%9,%10,%11,%12,%13,%14,%15,%16,%17,%18,%19,%20,%21,%22,%23,%24,%25,%26,%27}, {%28,%29,%30,%31}, %32, 0, 1, 1, 1;"
            : "=f"(o[0][0]), "=f"(o[0][1]), "=f"(o[0][2]), "=f"(o[0][3]),
              "=f"(o[1][0]), "=f"(o[1][1]), "=f"(o[1][2]), "=f"(o[1][3]),
              "=f"(o[2][0]), "=f"(o[2][1]), "=f"(o[2][2]), "=f"(o[2][3]),
              "=f"(o[3][0]), "=f"(o[3][1]), "=f"(o[3][2]), "=f"(o[3][3]),
              "=f"(o[4][0]), "=f"(o[4][1]), "=f"(o[4][2]), "=f"(o[4][3]),
              "=f"(o[5][0]), "=f"(o[5][1]), "=f"(o[5][2]), "=f"(o[5][3]),
              "=f"(o[6][0]), "=f"(o[6][1]), "=f"(o[6][2]), "=f"(o[6][3])
            : "r"(a[0]), "r"(a[1]), "r"(a[2]), "r"(a[3]), "l"(db)
            : "memory");
    else
        asm volatile(
            "wgmma.mma_async.sync.aligned.m64n56k16.f32.bf16.bf16 {%0,%1,%2,%3,%4,%5,%6,%7,%8,%9,%10,%11,%12,%13,%14,%15,%16,%17,%18,%19,%20,%21,%22,%23,%24,%25,%26,%27}, {%28,%29,%30,%31}, %32, 1, 1, 1, 1;"
            : "+f"(o[0][0]), "+f"(o[0][1]), "+f"(o[0][2]), "+f"(o[0][3]),
              "+f"(o[1][0]), "+f"(o[1][1]), "+f"(o[1][2]), "+f"(o[1][3]),
              "+f"(o[2][0]), "+f"(o[2][1]), "+f"(o[2][2]), "+f"(o[2][3]),
              "+f"(o[3][0]), "+f"(o[3][1]), "+f"(o[3][2]), "+f"(o[3][3]),
              "+f"(o[4][0]), "+f"(o[4][1]), "+f"(o[4][2]), "+f"(o[4][3]),
              "+f"(o[5][0]), "+f"(o[5][1]), "+f"(o[5][2]), "+f"(o[5][3]),
              "+f"(o[6][0]), "+f"(o[6][1]), "+f"(o[6][2]), "+f"(o[6][3])
            : "r"(a[0]), "r"(a[1]), "r"(a[2]), "r"(a[3]), "l"(db)
            : "memory");
}
__device__ __forceinline__ void wgmma_out(float (&o)[8][4], const uint32_t (&a)[4], uint64_t db, bool acc) {
    if (!acc)
        asm volatile(
            "wgmma.mma_async.sync.aligned.m64n64k16.f32.bf16.bf16 {%0,%1,%2,%3,%4,%5,%6,%7,%8,%9,%10,%11,%12,%13,%14,%15,%16,%17,%18,%19,%20,%21,%22,%23,%24,%25,%26,%27,%28,%29,%30,%31}, {%32,%33,%34,%35}, %36, 0, 1, 1, 1;"
            : "=f"(o[0][0]), "=f"(o[0][1]), "=f"(o[0][2]), "=f"(o[0][3]),
              "=f"(o[1][0]), "=f"(o[1][1]), "=f"(o[1][2]), "=f"(o[1][3]),
              "=f"(o[2][0]), "=f"(o[2][1]), "=f"(o[2][2]), "=f"(o[2][3]),
              "=f"(o[3][0]), "=f"(o[3][1]), "=f"(o[3][2]), "=f"(o[3][3]),
              "=f"(o[4][0]), "=f"(o[4][1]), "=f"(o[4][2]), "=f"(o[4][3]),
              "=f"(o[5][0]), "=f"(o[5][1]), "=f"(o[5][2]), "=f"(o[5][3]),
              "=f"(o[6][0]), "=f"(o[6][1]), "=f"(o[6][2]), "=f"(o[6][3]),
              "=f"(o[7][0]), "=f"(o[7][1]), "=f"(o[7][2]), "=f"(o[7][3])
            : "r"(a[0]), "r"(a[1]), "r"(a[2]), "r"(a[3]), "l"(db)
            : "memory");
    else
        asm volatile(
            "wgmma.mma_async.sync.aligned.m64n64k16.f32.bf16.bf16 {%0,%1,%2,%3,%4,%5,%6,%7,%8,%9,%10,%11,%12,%13,%14,%15,%16,%17,%18,%19,%20,%21,%22,%23,%24,%25,%26,%27,%28,%29,%30,%31}, {%32,%33,%34,%35}, %36, 1, 1, 1, 1;"
            : "+f"(o[0][0]), "+f"(o[0][1]), "+f"(o[0][2]), "+f"(o[0][3]),
              "+f"(o[1][0]), "+f"(o[1][1]), "+f"(o[1][2]), "+f"(o[1][3]),
              "+f"(o[2][0]), "+f"(o[2][1]), "+f"(o[2][2]), "+f"(o[2][3]),
              "+f"(o[3][0]), "+f"(o[3][1]), "+f"(o[3][2]), "+f"(o[3][3]),
              "+f"(o[4][0]), "+f"(o[4][1]), "+f"(o[4][2]), "+f"(o[4][3]),
              "+f"(o[5][0]), "+f"(o[5][1]), "+f"(o[5][2]), "+f"(o[5][3]),
              "+f"(o[6][0]), "+f"(o[6][1]), "+f"(o[6][2]), "+f"(o[6][3]),
              "+f"(o[7][0]), "+f"(o[7][1]), "+f"(o[7][2]), "+f"(o[7][3])
            : "r"(a[0]), "r"(a[1]), "r"(a[2]), "r"(a[3]), "l"(db)
            : "memory");
}
__device__ __forceinline__ void wgmma_out(float (&o)[9][4], const uint32_t (&a)[4], uint64_t db, bool acc) {
    if (!acc)
        asm volatile(
            "wgmma.mma_async.sync.aligned.m64n72k16.f32.bf16.bf16 {%0,%1,%2,%3,%4,%5,%6,%7,%8,%9,%10,%11,%12,%13,%14,%15,%16,%17,%18,%19,%20,%21,%22,%23,%24,%25,%26,%27,%28,%29,%30,%31,%32,%33,%34,%35}, {%36,%37,%38,%39}, %40, 0, 1, 1, 1;"
            : "=f"(o[0][0]), "=f"(o[0][1]), "=f"(o[0][2]), "=f"(o[0][3]),
              "=f"(o[1][0]), "=f"(o[1][1]), "=f"(o[1][2]), "=f"(o[1][3]),
              "=f"(o[2][0]), "=f"(o[2][1]), "=f"(o[2][2]), "=f"(o[2][3]),
              "=f"(o[3][0]), "=f"(o[3][1]), "=f"(o[3][2]), "=f"(o[3][3]),
              "=f"(o[4][0]), "=f"(o[4][1]), "=f"(o[4][2]), "=f"(o[4][3]),
              "=f"(o[5][0]), "=f"(o[5][1]), "=f"(o[5][2]), "=f"(o[5][3]),
              "=f"(o[6][0]), "=f"(o[6][1]), "=f"(o[6][2]), "=f"(o[6][3]),
              "=f"(o[7][0]), "=f"(o[7][1]), "=f"(o[7][2]), "=f"(o[7][3]),
              "=f"(o[8][0]), "=f"(o[8][1]), "=f"(o[8][2]), "=f"(o[8][3])
            : "r"(a[0]), "r"(a[1]), "r"(a[2]), "r"(a[3]), "l"(db)
            : "memory");
    else
        asm volatile(
            "wgmma.mma_async.sync.aligned.m64n72k16.f32.bf16.bf16 {%0,%1,%2,%3,%4,%5,%6,%7,%8,%9,%10,%11,%12,%13,%14,%15,%16,%17,%18,%19,%20,%21,%22,%23,%24,%25,%26,%27,%28,%29,%30,%31,%32,%33,%34,%35}, {%36,%37,%38,%39}, %40, 1, 1, 1, 1;"
            : "+f"(o[0][0]), "+f"(o[0][1]), "+f"(o[0][2]), "+f"(o[0][3]),
              "+f"(o[1][0]), "+f"(o[1][1]), "+f"(o[1][2]), "+f"(o[1][3]),
              "+f"(o[2][0]), "+f"(o[2][1]), "+f"(o[2][2]), "+f"(o[2][3]),
              "+f"(o[3][0]), "+f"(o[3][1]), "+f"(o[3][2]), "+f"(o[3][3]),
              "+f"(o[4][0]), "+f"(o[4][1]), "+f"(o[4][2]), "+f"(o[4][3]),
              "+f"(o[5][0]), "+f"(o[5][1]), "+f"(o[5][2]), "+f"(o[5][3]),
              "+f"(o[6][0]), "+f"(o[6][1]), "+f"(o[6][2]), "+f"(o[6][3]),
              "+f"(o[7][0]), "+f"(o[7][1]), "+f"(o[7][2]), "+f"(o[7][3]),
              "+f"(o[8][0]), "+f"(o[8][1]), "+f"(o[8][2]), "+f"(o[8][3])
            : "r"(a[0]), "r"(a[1]), "r"(a[2]), "r"(a[3]), "l"(db)
            : "memory");
}
__device__ __forceinline__ void wgmma_out(float (&o)[10][4], const uint32_t (&a)[4], uint64_t db, bool acc) {
    if (!acc)
        asm volatile(
            "wgmma.mma_async.sync.aligned.m64n80k16.f32.bf16.bf16 {%0,%1,%2,%3,%4,%5,%6,%7,%8,%9,%10,%11,%12,%13,%14,%15,%16,%17,%18,%19,%20,%21,%22,%23,%24,%25,%26,%27,%28,%29,%30,%31,%32,%33,%34,%35,%36,%37,%38,%39}, {%40,%41,%42,%43}, %44, 0, 1, 1, 1;"
            : "=f"(o[0][0]), "=f"(o[0][1]), "=f"(o[0][2]), "=f"(o[0][3]),
              "=f"(o[1][0]), "=f"(o[1][1]), "=f"(o[1][2]), "=f"(o[1][3]),
              "=f"(o[2][0]), "=f"(o[2][1]), "=f"(o[2][2]), "=f"(o[2][3]),
              "=f"(o[3][0]), "=f"(o[3][1]), "=f"(o[3][2]), "=f"(o[3][3]),
              "=f"(o[4][0]), "=f"(o[4][1]), "=f"(o[4][2]), "=f"(o[4][3]),
              "=f"(o[5][0]), "=f"(o[5][1]), "=f"(o[5][2]), "=f"(o[5][3]),
              "=f"(o[6][0]), "=f"(o[6][1]), "=f"(o[6][2]), "=f"(o[6][3]),
              "=f"(o[7][0]), "=f"(o[7][1]), "=f"(o[7][2]), "=f"(o[7][3]),
              "=f"(o[8][0]), "=f"(o[8][1]), "=f"(o[8][2]), "=f"(o[8][3]),
              "=f"(o[9][0]), "=f"(o[9][1]), "=f"(o[9][2]), "=f"(o[9][3])
            : "r"(a[0]), "r"(a[1]), "r"(a[2]), "r"(a[3]), "l"(db)
            : "memory");
    else
        asm volatile(
            "wgmma.mma_async.sync.aligned.m64n80k16.f32.bf16.bf16 {%0,%1,%2,%3,%4,%5,%6,%7,%8,%9,%10,%11,%12,%13,%14,%15,%16,%17,%18,%19,%20,%21,%22,%23,%24,%25,%26,%27,%28,%29,%30,%31,%32,%33,%34,%35,%36,%37,%38,%39}, {%40,%41,%42,%43}, %44, 1, 1, 1, 1;"
            : "+f"(o[0][0]), "+f"(o[0][1]), "+f"(o[0][2]), "+f"(o[0][3]),
              "+f"(o[1][0]), "+f"(o[1][1]), "+f"(o[1][2]), "+f"(o[1][3]),
              "+f"(o[2][0]), "+f"(o[2][1]), "+f"(o[2][2]), "+f"(o[2][3]),
              "+f"(o[3][0]), "+f"(o[3][1]), "+f"(o[3][2]), "+f"(o[3][3]),
              "+f"(o[4][0]), "+f"(o[4][1]), "+f"(o[4][2]), "+f"(o[4][3]),
              "+f"(o[5][0]), "+f"(o[5][1]), "+f"(o[5][2]), "+f"(o[5][3]),
              "+f"(o[6][0]), "+f"(o[6][1]), "+f"(o[6][2]), "+f"(o[6][3]),
              "+f"(o[7][0]), "+f"(o[7][1]), "+f"(o[7][2]), "+f"(o[7][3]),
              "+f"(o[8][0]), "+f"(o[8][1]), "+f"(o[8][2]), "+f"(o[8][3]),
              "+f"(o[9][0]), "+f"(o[9][1]), "+f"(o[9][2]), "+f"(o[9][3])
            : "r"(a[0]), "r"(a[1]), "r"(a[2]), "r"(a[3]), "l"(db)
            : "memory");
}

__device__ __forceinline__ void slow_edge(int ee, int s, float* accn, const __nv_bfloat16* __restrict__ x,
                                          const __nv_bfloat16* __restrict__ sh, const __nv_bfloat16* __restrict__ ea,
                                          const __nv_bfloat16* __restrict__ cg, const __nv_bfloat16* __restrict__ wr,
                                          int lane) {
    float rwv[4] = {0.f, 0.f, 0.f, 0.f};
#pragma unroll 4
    for (int d = 0; d < 16; d++) {
        const float a = __bfloat162float(ea[(size_t)ee * 16 + d]);
        const uint2 wv = *(const uint2*)(wr + d * 128 + lane * 4);
        rwv[0] += a * __uint_as_float(wv.x << 16);
        rwv[1] += a * __uint_as_float(wv.x & 0xffff0000u);
        rwv[2] += a * __uint_as_float(wv.y << 16);
        rwv[3] += a * __uint_as_float(wv.y & 0xffff0000u);
    }
    float A = 0.f;
#pragma unroll
    for (int v = 0; v < 4; v++)
        A += __bfloat162float(cg[((lane >> 2) & 3) * 16 + v * 4 + (lane & 3)]) * __bfloat162float(sh[(size_t)ee * 4 + v]);
    float m[4][4];
#pragma unroll
    for (int w = 0; w < 4; w++)
#pragma unroll
        for (int j = 0; j < 4; j++) m[w][j] = 0.f;
#pragma unroll
    for (int u = 0; u < 4; u++) {
        const uint2 xv = *(const uint2*)(x + (size_t)s * 512 + u * 128 + lane * 4);
        const float x0 = __uint_as_float(xv.x << 16), x1 = __uint_as_float(xv.x & 0xffff0000u);
        const float x2 = __uint_as_float(xv.y << 16), x3 = __uint_as_float(xv.y & 0xffff0000u);
#pragma unroll
        for (int w = 0; w < 4; w++) {
            const float a = __shfl_sync(0xffffffffu, A, u * 4 + w);
            m[w][0] += a * x0;
            m[w][1] += a * x1;
            m[w][2] += a * x2;
            m[w][3] += a * x3;
        }
    }
#pragma unroll
    for (int w = 0; w < 4; w++)
#pragma unroll
        for (int j = 0; j < 4; j++) atomicAdd(accn + w * 128 + lane * 4 + j, m[w][j] * rwv[j]);
}

__device__ __forceinline__ void slow_out(const float* accn, const __nv_bfloat16* __restrict__ wout,
                                         __nv_bfloat16* __restrict__ outn, int lane) {
    float o[4][4];
#pragma unroll
    for (int w = 0; w < 4; w++)
#pragma unroll
        for (int j = 0; j < 4; j++) o[w][j] = 0.f;
#pragma unroll 2
    for (int c = 0; c < 128; c++) {
        const uint2 wv = *(const uint2*)(wout + c * 128 + lane * 4);
        const float w0 = __uint_as_float(wv.x << 16), w1 = __uint_as_float(wv.x & 0xffff0000u);
        const float w2 = __uint_as_float(wv.y << 16), w3 = __uint_as_float(wv.y & 0xffff0000u);
#pragma unroll
        for (int w = 0; w < 4; w++) {
            const float a = __bfloat162float(__float2bfloat16(accn[w * 128 + c]));
            o[w][0] += a * w0;
            o[w][1] += a * w1;
            o[w][2] += a * w2;
            o[w][3] += a * w3;
        }
    }
#pragma unroll
    for (int w = 0; w < 4; w++)
        *(uint2*)(outn + w * 128 + lane * 4) = make_uint2(pack_bf16(o[w][0], o[w][1]), pack_bf16(o[w][2], o[w][3]));
}

static_assert(NW > 2 * NP, "barriers");
#define MS 0
#define EO -1
#define EF 22
#define OWN 0
#define PLC 1
#define PFT 45
#define PFC 1
#define PFS 1
#define BULK 0
#define PFX 300
#define PX0 0
#define EZ 1
#define PFA 0
#define SPEC 0
#define SH 0
#define FE 2
#define PO 0
#define CL 0
#define HH 0
#define E0 1
#define SW 1
#define TA 0
#define FA 1
#define NA 0
#define PV 0
#define PB 0
#define FPOS 1
#define PW 0
#define TWAIT mbar_lean_u
#define PWAIT mbar_lean
#define TMA_ROW(k) "@pl cp.async.bulk.tensor.2d.shared::cluster.global.mbarrier::complete_tx::bytes [d" #k "], [tm, {r" #k ", %2" #k "}], [b" #k "];\n"
#define TMA_PREP(k) "mad.lo.u32 d" #k ", dd, 512, %3" #k ";\nadd.u32 b" #k ", dd, %2" #k ";\n"
#define RDCLK(c) "mov.u64 ck, %%clock64;\ncvt.u32.u64 " c ", ck;\n"
#define BCAST(d, k) "selp.b32 " d ", a" #k ", 0, me;\nredux.sync.or.b32 " d ", " d ", 0xffffffff;\n"
#define PTIME(t, x, y, z) "shr.u32 " t ", " x ", 16;\nand.b32 c, " y ", 0xffff;\nadd.u32 " t ", " t ", c;\nmad.lo.u32 c, " t ", %13, %14;\nmul.lo.u32 " t ", " t ", %9;\nmin.u32 " t ", " t ", c;\nshr.u32 " t ", " t ", 5;\nadd.u32 " t ", " t ", %6;\nmin.u32 " t ", " t ", lim;\nlop3.b32 " t ", " t ", " z ", 7, 0xd8;\n"
#define PROWA(s, t) "and.b32 " t ", " s ", 0xffc;\nsetp.gt.u32 p, " t ", " STR(LNUL / 2) ";\nmad.lo.u32 " t ", " t ", 2, %5;\nshr.u32 t0, " s ", 11;\nand.b32 t0, t0, 6;\nshr.u32 " s ", " s ", 15;\nadd.u32 t0, t0, " s ";\nselp.s32 " s ", " STR(NGR - 2) ", -2, p;\nadd.u32 t0, t0, " s ";\nmul.lo.s32 t0, t0, " STR(-KEYW) ";\nprmt.b32 " s ", t0, 0, 0x1010;\n"
#define PROWB(s, t, x, y) "ld.shared.v2.u32 {" x ", " y "}, [" t "];\nadd.u16x2 " x ", " x ", " s ";\nadd.u16x2 " y ", " y ", " s ";\n"
#define PROWS(s, x, y) "and.b32 t0, " s ", 0xffc;\nsetp.gt.u32 p, t0, " STR(LNUL / 2) ";\nmad.lo.u32 t0, t0, 2, %5;\nld.shared.v2.u32 {" x ", " y "}, [t0];\nshr.u32 t0, " s ", 11;\nand.b32 t0, t0, 6;\nshr.u32 " s ", " s ", 15;\nadd.u32 t0, t0, " s ";\nselp.s32 " s ", " STR(NGR - 2) ", -2, p;\nadd.u32 t0, t0, " s ";\nmul.lo.s32 t0, t0, " STR(-KEYW) ";\nprmt.b32 t0, t0, 0, 0x1010;\nadd.u16x2 " x ", " x ", t0;\nadd.u16x2 " y ", " y ", t0;\n"
__device__ __forceinline__ void produce(const uint32_t (&pt)[2], const uint32_t (&pz)[8], const uint32_t (&pm)[8], uint32_t bar, uint32_t ps,
                                        int nit, uint32_t psrc, uint32_t tbase, uint32_t lim, uint32_t taug64, uint32_t taus, uint32_t n,
                                        int pr0, uint32_t tau2, uint32_t brk
) {
    asm volatile(
        "{\n.reg .pred p, pl, ok, me;\n.reg .b32 a<6>, u<4>, r<8>, d<8>, b<8>, ps, lim, n, it, pr, pe, tgt, tgu, c, dd, dn, par, t0, t1;\n"
        ".reg .b64 st, tm, ck;\n"
        "elect.sync _|pl, 0xffffffff;\n"
        "mov.b64 tm, {%0, %2};\n"
        "mov.u32 ps, %3;\n"
        "mov.u32 it, %4;\n"
        "mov.u32 lim, %7;\n"
        "mov.u32 n, %10;\n"
        "mov.u32 pr, %12;\n"
        "setp.le.s32 p, it, 0;\n"
        "bar.sync 4, " STR(NT) ";\n"
        "@p bra.uni PEND;\n"
        "PBAT:\n"
        "ld.shared.u16 c, [ps];\n"
        "ld.shared.u16 t1, [ps+4];\n"
        "add.u32 ps, ps, 256;\n"
        "mul.lo.u32 par, n, " STR(65536 / NP + 1) ";\n"
        "shr.u32 par, par, 16;\n"
        "mad.lo.s32 dn, par, " STR(-NP) ", n;\n"
        "add.u32 n, n, 32;\n"
        "not.b32 par, par;\n"
        PROWS("c", "a0", "a1") PROWS("t1", "a2", "a3")
        "min.s32 pe, it, 32;\n"
        "sub.s32 it, it, 32;\n"
        "add.u32 pe, pe, pr;\n"
        PTIME("a4", "a0", "a1", "dn") PTIME("a5", "a2", "a3", "par")
        "add.u32 lim, lim, %8;\n"
        "PLOOP:\n"
        "setp.eq.u32 me, n, pr;\n"
        "add.u32 pr, pr, 1;\n"
        BCAST("tgt", 4) BCAST("tgu", 5) BCAST("u0", 0) BCAST("u1", 1) BCAST("u2", 2) BCAST("u3", 3)
        "and.b32 dd, tgt, 7;\n"
        "mad.lo.u32 dd, dd, 16, %1;\n"
        "and.b32 par, tgu, 1;\n"
        "mbarrier.test_wait.parity.shared.b64 ok, [dd+8], par;\n"
        "prmt.b32 r0, u0, 0, 0x4104;\nprmt.b32 r1, u0, 0, 0x4324;\nprmt.b32 r2, u1, 0, 0x4104;\nprmt.b32 r3, u1, 0, 0x4324;\n"
        "prmt.b32 r4, u2, 0, 0x4104;\nprmt.b32 r5, u2, 0, 0x4324;\nprmt.b32 r6, u3, 0, 0x4104;\nprmt.b32 r7, u3, 0, 0x4324;\n"
        TMA_PREP(0) TMA_PREP(1) TMA_PREP(2) TMA_PREP(3) TMA_PREP(4) TMA_PREP(5) TMA_PREP(6) TMA_PREP(7)
        RDCLK("c")
        "sub.s32 c, c, tgt;\n"
        "setp.ge.and.s32 p, c, 0, ok;\n"
        "@!p bra.uni PSLP;\n"
        "PRES:\n"
        "@pl mbarrier.arrive.expect_tx.shared.b64 _, [b0], 8192;\n"
        TMA_ROW(0) TMA_ROW(1) TMA_ROW(2) TMA_ROW(3)
        RDCLK("c")
        "sub.s32 c, c, tgu;\n"
        "setp.lt.s32 p, c, 0;\n"
        "@p bra.uni PSL2;\n"
        "PRE2:\n"
        TMA_ROW(4) TMA_ROW(5) TMA_ROW(6) TMA_ROW(7)
        "setp.lt.u32 p, pr, pe;\n"
        "@p bra.uni PLOOP;\n"
        "setp.gt.s32 p, it, 0;\n"
        "@p bra.uni PBAT;\n"
        "bra.uni PEND;\n"
        "PSL2:\n"
        "nanosleep.u32 " STR(PSLEEP) ";\n"
        RDCLK("c")
        "sub.s32 c, c, tgu;\n"
        "setp.lt.s32 p, c, 0;\n"
        "@p bra.uni PSL2;\n"
        "bra.uni PRE2;\n"
        "PSL1:\n"
        "nanosleep.u32 " STR(PSLEEP) ";\n"
        RDCLK("c")
        "sub.s32 c, c, tgt;\n"
        "PSLP:\n"
        "setp.lt.s32 p, c, 0;\n"
        "@p bra.uni PSL1;\n"
        "@ok bra.uni PRES;\n"
        "mov.u32 c, 0;\n"
        "PW:\n"
        "mbarrier.try_wait.parity.shared.b64 p, [b0+8], par;\n"
        "@p bra.uni PRES;\n"
        "add.u32 c, c, 1;\n"
        "setp.lt.u32 p, c, 4000000;\n"
        "@p bra.uni PW;\n"
        "trap;\n"
        "PEND:\n}"
        :
        : "r"(pt[0]), "r"(bar), "r"(pt[1]), "r"(ps), "r"(nit), "r"(psrc), "r"(tbase), "r"(lim), "r"(taug64), "r"(taus), "r"(n), "n"(0),
          "r"(pr0), "r"(tau2), "r"(brk), "n"(0), "n"(0), "n"(0), "n"(0), "n"(0), "r"(pz[0]), "r"(pz[1]), "r"(pz[2]), "r"(pz[3]), "r"(pz[4]),
          "r"(pz[5]), "r"(pz[6]), "r"(pz[7]), "n"(0), "n"(0), "r"(pm[0]), "r"(pm[1]), "r"(pm[2]), "r"(pm[3]), "r"(pm[4]), "r"(pm[5]),
          "r"(pm[6]), "r"(pm[7])
        : "memory");
}
template <int J0, int JN>
__device__ __forceinline__ void put_agg(const float (&acc)[2][NJ][4], uint32_t tb, int u) {
    const int h = u & 1, j = u & ~1;
    const float(*a)[4] = acc[h] + J0 + (j < JN ? j : 0);
    if (j + 1 < JN)
        stsm4(tb + h * SM_ODD + (J0 + j) * 256, pack_bf16(a[0][0], a[0][1]), pack_bf16(a[0][2], a[0][3]), pack_bf16(a[1][0], a[1][1]),
              pack_bf16(a[1][2], a[1][3]));
    else if (j < JN)
        stsm2(tb + h * SM_ODD + (J0 + j) * 256, pack_bf16(a[0][0], a[0][1]), pack_bf16(a[0][2], a[0][3]));
}
template <int JN>
__device__ __forceinline__ void pin(float (&o)[JN][4]) {
#pragma unroll
    for (int j = 0; j < JN; j++)
#pragma unroll
        for (int k = 0; k < 4; k++) asm volatile("" : "+f"(o[j][k])::"memory");
}
#define WG_WAIT(n) asm volatile("wgmma.wait_group.sync.aligned %0;" ::"n"(n) : "memory")
#define WG_COMMIT() asm volatile("wgmma.commit_group.sync.aligned;" ::: "memory")
#define KA 2
template <int K0, int JN, class F>
__device__ __forceinline__ void mul_out(float (&o)[JN][4], const uint32_t (&a)[8][4], uint32_t db, F f) {
    asm volatile("wgmma.fence.sync.aligned;" ::: "memory");
#pragma unroll
    for (int ks = 0; ks < 8; ks++) {
        wgmma_out(o, a[ks], (uint64_t)(db + (((ks >> 2) * SM_ODD + (ks & 3) * (NJ * 256)) >> 4)) | (16ull << 32), ks);
        if (ks == K0 - 1 || ks == 7) WG_COMMIT();
        if (ks == K0 - 1) WG_WAIT(1);
        if (ks >= K0 - 1) f(K0 ? ks - K0 + 1 : ks);
    }
}
static_assert(CH1 <= 8 && CH2 <= 8 && CH3 <= 10 && CH4 <= 10 && KA <= 3 && NJ == 19 && NP == 5 && SM_EVEN == 0 && SM_ODD % 1024 == 128 && CH0 + CH2 <= 13 && CH1 <= 13 && CH0 + CH2 + CH4 <= 21 && CH1 + CH3 <= 21, "epilogue");
__device__ constexpr int out_n(int st) { return st == 0 ? CH0 : st == 1 ? CH1 : st == 2 ? CH2 : st == 3 ? CH3 : CH4; }
__device__ constexpr int out_j(int st) { return st == 1 ? CH0 : st == 2 ? CH0 + CH1 : st == 4 ? CH3 : 0; }
__device__ constexpr int out_at(int st) { return (NJ + (st == 2 ? CH0 : st == 3 ? CH1 : st == 4 ? CH0 + CH2 : 0)) * 1024 + (st & 1) * SM_ODD; }
#define WG_SYNC(w) asm volatile("bar.sync %0, 128;" ::"r"((w) + 1) : "memory")
#define HAND(st, w) asm volatile("bar.arrive %0, %1;" ::"r"(6 + 2 * (st) + (w)), "n"(OWN ? 160 : 192) : "memory")
template <int R>
__device__ __forceinline__ void store_out(const CUtensorMap* po, uint32_t sb, int w, int j, int node0, int hpb, int lane) {
    const uint32_t swp = lds_u32(sb + SM_MISC + MI_INT + 48 + w * 4), ring = sb + w * RING_BYTES;
    const int row = 2 * lane < hpb ? (node0 + ((swp >> lane) & 1) * hpb) * 4 + lane * 8 : 1 << 30;
    asm volatile("" : "+l"(po));
#pragma unroll
    for (int st = 0; st < 5; st++) {
        if ((OWN >> (3 * st + 1) & 1) == R && (OWN >> 3 * st & 1) == j) {
            int rw[10];
#pragma unroll
            for (int k = 0; k < 10; k++)
                if (k < out_n(st)) rw[k] = __shfl_sync(0xffffffffu, row, out_j(st) + k);
            asm volatile("bar.sync %0, 160;" ::"r"(6 + 2 * st + w) : "memory");
            FENCE_ASYNC();
            if (elect()) {
#pragma unroll
                for (int k = 0; k < 10; k++)
                    if (k < out_n(st)) tma_store(po, ring + out_at(st) + k * 1024, st < 3 ? 0 : 64, rw[k]);
                asm volatile("cp.async.bulk.commit_group;" ::: "memory");
            }
        }
    }
    asm volatile("cp.async.bulk.wait_group.read 0;" ::: "memory");
}
template <int ST, int JN>
__device__ __forceinline__ void put_out(float (&o)[JN][4], uint32_t c, int u, int w) {
    if (u == 0) pin(o);
    const int j = 2 * u < JN ? 2 * u : 0;
    if (2 * u + 1 < JN)
        stsm4t(c + out_at(ST) + j * 1024, pack_bf16(o[j][0], o[j][1]), pack_bf16(o[j][2], o[j][3]), pack_bf16(o[j + 1][0], o[j + 1][1]),
               pack_bf16(o[j + 1][2], o[j + 1][3]));
    else if (2 * u < JN)
        stsm2t(c + out_at(ST) + j * 1024, pack_bf16(o[j][0], o[j][1]), pack_bf16(o[j][2], o[j][3]));
    if (u == (JN - 1) / 2) {
        if (EF >> ST & 1) FENCE_ASYNC();
        HAND(ST, w);
    }
}
__device__ __forceinline__ void get_w(uint32_t (&a)[8][4], uint32_t ce, uint32_t co, int ks) {
    if (ks >= 0 && ks < 8)
        asm volatile("ldmatrix.sync.aligned.m8n8.x4.trans.shared.b16 {%0,%1,%2,%3}, [%4];"
                     : "=r"(a[ks & 7][0]), "=r"(a[ks & 7][1]), "=r"(a[ks & 7][2]), "=r"(a[ks & 7][3])
                     : "r"((ks < 4 ? ce : co + SM_ODD) + (ks & 3) * 2048)
                     : "memory");
}
#define TB 8
#define DELAY 4100
#define NULW 0xf0000000
#define LW 128
#define DREF 1
#define K0(npr) ((2 * NP - 2 - (npr) % NP) % NP)
#define GCODE(g) ((((g) >> 1) + 1) << 12 | ((g) & 1) << 15)
#define SYNC() asm volatile("bar.sync 0;" ::: "memory")
#define LISTS() asm volatile("bar.sync 4, %0;" ::"n"(NT) : "memory")
#define NB (2 * NGR * 32)
#define PREF(p, tot, k0, n)                                                                                       \
    {                                                                                                             \
        _Pragma("unroll") for (int k = (k0); k < (k0) + (n); k++) {                                                \
            const int l = (k * nbins + bin) * 128 + tid - NB;                                                     \
            if (l < (tot)) asm volatile("prefetch.global.L2 [%0];" ::"l"(p + (size_t)l * 64) : "memory");         \
        }                                                                                                         \
    }
#define WX 010
#define WS 0011
#define WE 000
#define PL 8
#define PLE 0
#define DG(v, i) ((v) >> (6 - 3 * (i)) & 7)
#define PREW(i)                                                                                \
    PREF(x, N * 8, (i > 0 ? DG(WX, 0) : 0) + (i > 1 ? DG(WX, 1) : 0), DG(WX, i))                \
    PREF(sh, E / 16, (i > 0 ? DG(WS, 0) : 0) + (i > 1 ? DG(WS, 1) : 0), DG(WS, i))              \
    PREF(ea, E / 4, (i > 0 ? DG(WE, 0) : 0) + (i > 1 ? DG(WE, 1) : 0), DG(WE, i))
#define PFN (DG(WX, 0) + DG(WX, 1) + DG(WX, 2))
#define PFE (DG(WE, 0) + DG(WE, 1) + DG(WE, 2))
__global__ void __launch_bounds__(NT, 1)
main_kernel(const int* __restrict__ dst, const int* __restrict__ src, uint4* __restrict__ gbin, int E, int nbins, int fast_ok,
            int npb, unsigned npb_magic, int N, const __grid_constant__ CUtensorMap tme,
            const __grid_constant__ CUtensorMap tmx, const __grid_constant__ CUtensorMap tmw,
            const __grid_constant__ CUtensorMap tmo, const __nv_bfloat16* __restrict__ x,
            const __nv_bfloat16* __restrict__ sh, const __nv_bfloat16* __restrict__ ea,
            const __nv_bfloat16* __restrict__ cg, const __nv_bfloat16* __restrict__ wr,
            const __nv_bfloat16* __restrict__ wout, __nv_bfloat16* __restrict__ out, int tau16, int toff, int delay,
            int tau2, int brk) {
    extern __shared__ __align__(1024) unsigned char smem[];
    const uint32_t sb = __shfl_sync(0xffffffffu, s2u(smem), 0);
    const int tid = threadIdx.x;
    const int warp = __shfl_sync(0xffffffffu, tid >> 5, 0), lane = tid & 31;
    const int g = lane >> 2, t = lane & 3;

    TLSTAMP(0);
    TLINIT();
    const int bin = blockIdx.x;
    const int node0 = bin * npb, hpb = npb >> 1;
    uint32_t wa[8];
    uint2 c0 = make_uint2(0, 0), c1 = c0;
    bool fast = fast_ok;
    if (fast_ok) {
        int pd[EPS], ps[EPS];
        const int e0 = ((tid >> 5) * nbins + bin) * 32 + lane;
#pragma unroll
        for (int k = 0; k < EPS; k++)
            asm volatile("ld.global.nc.u32 %0, [%1];" : "=r"(pd[k]) : "l"(dst + min(e0 + k * NT * nbins, E - 1)));
#pragma unroll
        for (int k = 0; k < EPS; k++)
            asm volatile("ld.global.nc.u32 %0, [%1];" : "=r"(ps[k]) : "l"(src + min(e0 + k * NT * nbins, E - 1)));
        const unsigned ck0 = clock();
        const uint32_t cnt0 = (sb + SC_CNT + 8191) & ~8191;
        {
            const int ch = (SW ? tid ^ tid >> 3 : tid) & 7;
            const uint32_t nul = NULW + ((bin & 3) * 8 + ch) * (80 << 15);
#pragma unroll
            for (int k = 0; k < 4; k++) {
                const int i = tid + k * NT;
                if (i < SC_EXT / 16 ? ch != 7 : i < SC_TAB / 16) sts_v4(sb + SC_ENT + i * 16, make_uint4(nul, nul, nul, nul));
            }
            if (warp == NW - 1) {
                uint32_t now;
                asm volatile("mov.u32 %0, %%globaltimer_lo;" : "=r"(now));
                now = __shfl_sync(0xffffffffu, (now & 0x7ffff) | nul, SW ? 7 ^ (NW - 1) * 4 % 8 : 7);
#pragma unroll
                for (int k = 0; k < MAXBINS / 32; k++) sts_v4(sb + SC_ENT + (k * 32 + lane) * 128 + (SW ? (~lane & 7) * 16 : 112), make_uint4(now, now, now, MS ? ~0u : now));
                if (lane == 0) {
                    asm volatile("prefetch.tensormap [%0];" ::"l"(&tme) : "memory");
                    asm volatile("prefetch.tensormap [%0];" ::"l"(&tmx) : "memory");
                    asm volatile("prefetch.tensormap [%0];" ::"l"(&tmw) : "memory");
                    asm volatile("prefetch.tensormap [%0];" ::"l"(&tmo) : "memory");
                    sts_v2(sb + SM_MISC + MI_INT, 0, now);
                    sts_u32(sb + SM_MISC + MI_INT + 44, 0);
                    sts_u32(sb + SM_MISC + MI_INT + 24, 0);
                }
            }
            sts_v4(cnt0 + tid * 16, make_uint4(0, 0, 0, 0));
            if (tid < (SC_END - SC_HIST) / 16) {
                const uint32_t v = (tid >> 3) == MAXBINS / 32 ? 0x80000000u : 0;
                sts_v4(sb + SC_HIST + tid * 16, make_uint4(v, v, v, v));
            }
            if (tid < 2 * HPB) {
                const int w = tid >= hpb, loc = tid - (w ? hpb : 0), gr = min(loc * 43 >> 8, NGR - 1);
                sts_u32(sb + SC_TAB + tid * 4, ((w ? NGR : 0) + gr) * (KEYW << 15) + loc - gr * GSZ);
            }
        }
        if (elect()) {
#pragma unroll
            for (int k = 0; k < (NP > 5 || XR ? 4 : 2); k++) mbar_init(sb + SM_BAR + (warp * (NP > 5 || XR ? 4 : 2) + k) * 8, 3 + (k & 1));
        }
#pragma unroll
        for (int k = 0; k < TS / 2; k++) sts_v4(sb + SM_BT + (tid + k * NT) * 16, make_uint4(0, 0, 0, 0));
        if (tid < 8) sts_v4(sb + SM_BT + (tid + TS / 2 * NT) * 16, make_uint4(0, 0, 0, 0));
        if (tid < 4) {
            sts_u16(sb + SM_SRC + (LNUL + tid) * 2, N);
            sts_u32(sb + SM_EID + (LNUL + tid) * 4, 0x80000000u);
        }
        TLS(1);
        __syncthreads();
        {
            const uint32_t z = lds_u32(sb + SM_MISC + MI_INT);
            int pb[EPS], pr[EPS];
            uint32_t v[EPS];
#pragma unroll
            for (int k = 0; k < EPS; k++) {
                pb[k] = (int)__umulhi((unsigned)pd[k], npb_magic + z);
                v[k] = lds_u32(sb + SC_TAB + (pd[k] - pb[k] * npb) * 4);
                pr[k] = atoms_add(sb + SC_HIST + (e0 + k * NT * nbins < E ? pb[k] : MAXBINS + lane) * 4, 4);
            }
            int mx = 0;
#pragma unroll
            for (int k = 0; k < EPS; k++) {
                v[k] += ps[k] * (32768 + z) + (k * NT + tid + 32) * 8;
                asm volatile("{\n.reg .pred p;\nsetp.lt.u32 p, %0, " STR(LW) ";\n@p st.shared.u32 [%1], %2;\n}" ::"r"(pr[k]),
                             "r"(SW ? (sb + SC_ENT + pb[k] * 128 + (pb[k] & 7) * 16) ^ pr[k] : sb + SC_ENT + pb[k] * 128 + pr[k]), "r"(v[k])
                             : "memory");
                mx = max(mx, pr[k]);
            }
            if (mx >= LW) {
#pragma unroll
                for (int k = 0; k < EPS; k++)
                    if (pr[k] >= LW && pr[k] < LW + 64) {
                        sts_u32(sb + SC_EXT + pb[k] * 64 + (MS ? (pr[k] - LW & 28) * 2 + (pr[k] - LW >> 5) * 4 : pr[k] - LW), v[k]);
                    }
            }
        }
        TLS(6);
        __syncthreads();
        const unsigned c6 = DREF ? ck0 : clock();
        if (warp == NW - 1 && elect()) {
            FENCE_ASYNC();
            tma_store(&tme, sb + SC_ENT, bin * 32, 0);
            asm volatile("cp.async.bulk.commit_group;" ::: "memory");
        }
        if (tid < nbins && lds_u32(sb + SC_HIST + tid * 4) >= 128) {
#pragma unroll 1
            for (int k = 0; k < 4; k++) __stcg(gbin + GEX + (tid * nbins + bin) * 4 + k, lds_v4(sb + SC_EXT + tid * 64 + k * 16));
        }
#pragma unroll
        for (int k = 0; k < EPS; k++) {
            if (ps[k] < (N * PFT >> 10)) {
                const uint32_t p = atoms_add(sb + SM_MISC + MI_INT + 24, 4);
                if (p < PFC * 512) sts_u32(sb + SM_EA + p, min(e0 + k * NT * nbins, E - 1));
            }
        }
        if (warp >= 2 * NGR) {
            uint2 wv[4];
#pragma unroll
            for (int k = 0; k < 4; k++)
                asm volatile("ld.global.nc.v2.u32 {%0,%1}, [%2];" : "=r"(wv[k].x), "=r"(wv[k].y) : "l"((const uint2*)wr + (tid - NB) + k * 128));
#pragma unroll
            for (int k = 0; k < 4; k++) sts_v2(sb + SC_WR + (lane >> 1) * 272 + (warp - 2 * NGR + k * 4) * 16 + (lane & 1) * 8, wv[k].x, wv[k].y);
            PREW(0);
            const int w = warp & 1, j = (warp >> 1) & 1;
            const uint32_t bar0 = sb + SM_BAR + w * NP * 16, ring = sb + w * RING_BYTES + j * 4096;
            uint32_t pz[8], pm[8], pt[2];
            const uint32_t lz = lane & (E >> 31);
            {
                const uint32_t d0 = ring - j * 2048 - bar0 * 512 + lz;
#pragma unroll
                for (int k = 0; k < 8; k++) {
                    pz[k] = __shfl_sync(0xffffffffu, lz, k);
                    pm[k] = __shfl_sync(0xffffffffu, d0 + (k & 1) * SM_ODD + (k >> 1 & 1) * 1024 + (k >> 2) * 4096, 0);
                }
                asm("mov.b64 {%0, %1}, %2;" : "=r"(pt[0]), "=r"(pt[1]) : "l"(&tmx));
                pt[0] = __shfl_sync(0xffffffffu, pt[0] + lz, 0);
                pt[1] = __shfl_sync(0xffffffffu, pt[1] + lz, 0);
            }
            uint32_t sg0 = 0x01010101 | ((lane & 1) << 8 | (lane & 2) << 15 | (lane & 4) << 22) * 0xfe;
            uint32_t sg2 = (0x0101 | ((lane >> 3 & 1) | (lane & 16) << 4) * 0xfe) * 0x10001 ^ 0xfefe0000;
            uint32_t cand = ((lane & 1) << 3 | (lane & 2) << 5 | (lane & 4) << 7 | (lane & 8) << 9) * 7 + (lane & 16) * (15 << 11);
            uint32_t sg1 = __shfl_sync(0xffffffffu, sg0 ^ 0xfefefefe, lane), gb = cnt0 + (warp & 2) * NBK + lane * 8;
            sg0 = __shfl_sync(0xffffffffu, sg0, lane), sg2 = __shfl_sync(0xffffffffu, sg2, lane);
            cand = __shfl_sync(0xffffffffu, cand, lane), gb = __shfl_sync(0xffffffffu, gb, lane);
            const uint32_t wm = __shfl_sync(0xffffffffu, lz - w, lane);
            FENCE_ASYNC();
            asm volatile("bar.sync 8, %0;" ::"n"(NT) : "memory");
            while ((int)(clock() - c6) < (PFA ? PFA : delay + PFX)) {}
            {
                const uint32_t n = lds_u32(sb + SM_MISC + MI_INT + 24);
#pragma unroll
                for (int k = 0; k < PFC; k++) {
                    const uint32_t i = (tid - NB + k * 128) * 4, e = lds_u32(sb + SM_EA + i);
                    if (i < n) {
                        asm volatile("prefetch.global.L2 [%0];" ::"l"(ea + (size_t)e * 16) : "memory");
                        asm volatile("prefetch.global.L2 [%0];" ::"l"(sh + (size_t)e * 4) : "memory");
                    }
                }
            }
            SYNC();
            PREW(1);
            if (warp == NW - 1 && elect()) {
                asm volatile("cp.async.bulk.global.shared::cta.bulk_group [%0], [%1], %2;" ::"l"(gbin + bin * nbins * 8), "r"(sb + SM_BT),
                             "r"(nbins * 128)
                             : "memory");
                asm volatile("cp.async.bulk.commit_group;" ::: "memory");
                const uint32_t t0 = lds_u32(sb + SM_MISC + MI_INT + 4);
                uint32_t now, ck;
                asm volatile(
                    "{\n.reg .pred p;\n.reg .b32 a, n;\nmov.u32 a, %%globaltimer_lo;\nmov.u32 n, 0;\n"
                    "TK:\nmov.u32 %0, %%globaltimer_lo;\nmov.u32 %1, %%clock;\nadd.u32 n, n, 1;\n"
                    "setp.lt.u32 p, n, " STR(TB) ";\nsetp.eq.and.u32 p, %0, a, p;\n@p bra TK;\n}"
                    : "=r"(now), "=r"(ck));
                sts_u32(sb + SM_MISC + MI_INT + 4, ck - (min((now - t0) & 0x7ffff, 1u << 16) * 63 >> 5) + toff);
            }
            asm volatile("bar.sync 5, %0;" ::"n"(NT) : "memory");
            const uint4 nb = lds_v4(sb + SM_MISC + MI_INT + 32);
            const unsigned tbase = lds_u32(sb + SM_MISC + MI_INT + 4);
            fast = nb.w == 0;
            int df;
            asm("{\n.reg .s32 a;\ndp4a.u32.s32 a, %1, %4, 0;\ndp4a.u32.s32 a, %2, %5, a;\ndp4a.u32.s32 %0, %3, %6, a;\n}"
                : "=r"(df)
                : "r"(nb.x), "r"(nb.y), "r"(nb.z), "r"(sg0), "r"(sg1), "r"(sg2));
            const uint32_t best = __reduce_min_sync(0xffffffffu, abs(df) << (NJ + 1) | (df < 0) << NJ | cand);
            uint32_t swp = best ^ -w;
            uint32_t ga[NGR];
#pragma unroll
            for (int k = 0; k < NGR; k++) {
                const int sh = k < 4 ? 3 * k : 3 * k - 9;
                ga[k] = gb + (((k < 4 ? best : best >> 9) ^ wm) & 1 << sh) * (NGR * NBK * 4 >> sh);
            }
            asm volatile("bar.sync %0, %1;" ::"r"(6 + (ga[0] & ga[1] & ga[2] & ga[3] & ga[4] & ga[5] & lz)), "n"(NT) : "memory");
            TLA(1, 0);
            if (fast) {
                uint32_t v[NGR][2], mx = 0;
#pragma unroll
                for (int k = 0; k < NGR; k++) {
                    const uint2 u = lds_v2(ga[k] + k * (NBK * 4));
                    v[k][0] = u.x, v[k][1] = u.y;
                }
                const uint32_t sq = sb + SM_SEQ + w * SEQCAP * 2;
                const int all = __dp4a(nb.x, 0x01010101u, __dp4a(nb.y, 0x01010101u, __dp4a(nb.z, 0x01010101u, 0u))), d = best >> (NJ + 1);
                const int nst = (all + ((swp >> NJ) & 1 ? -d : d)) >> 1;
                const int npr = __shfl_sync(0xffffffffu, (nst + 3) >> 2, 0), k0 = K0(npr);
                const unsigned taug = __float2uint_rz(__fdividef((float)(N * tau16 >> 4), (float)max(npr, 1)));
                const uint32_t lim = tbase + (N * tau16 >> 8) + lane * taug;
                uint32_t a = -(__popc(swp & 0111111) * (NGR * GCAP + GEXT) + NGR * (NGR - 1) / 2 * GCAP + NGR * 4) + 2 * sq;
#pragma unroll
                for (int k = 0; k < NGR; k++) a += v[k][0] & 0xffc;
                a >>= 1;
                const uint32_t a0 = a;
#pragma unroll
                for (int c = 0; c < 2; c++)
#pragma unroll
                    for (int k = 0; k < NGR; k++) {
                        asm volatile(
                            "{\n.reg .pred p, q;\n.reg .b16 h;\n"
                            "setp.ge.u32 p, %1, 0x10000;\nsetp.ge.u32 q, %1, 0x40000;\n"
                            "cvt.u16.u32 h, %1;\n@p st.shared.u16 [%0], h;\n"
                            "add.u16 h, h, 4;\n@q st.shared.u16 [%0+2], h;\n}" ::"r"(a), "r"(v[k][c])
                            : "memory");
                        a += v[k][c] >> 16;
                        mx = max(mx, v[k][c]);
                    }
                if (mx >= 0x60000) {
                    a = a0;
#pragma unroll
                    for (int c = 0; c < 2; c++)
#pragma unroll
                        for (int k = 0; k < NGR; k++) {
#pragma unroll 1
                            for (uint32_t n = 4; n < v[k][c] >> 16; n += 2) sts_u16(a + n, v[k][c] + 2 * n);
                            a += v[k][c] >> 16;
                        }
                }
                if (!j) {
                    sts_u16(sq + (nst + lane) * 2, (LNUL + 4) | (lane < (-nst & 3) ? GCODE(0) : 0x7c01));
                    if (lane < k0) {
                        mbar_arrive_cnt(sb + SM_BAR + (w * NP + lane) * 16, 3);
                        mbar_arrive_cnt(sb + SM_BAR + (w * NP + lane) * 16 + 8, 4);
                        if (XR) mbar_arrive_cnt(sb + SM_BAR + (w * NP + lane) * 16 + 264, 4);
                    }
                    if (lane == 0) {
                        sts_v2(sb + SM_MISC + MI_INT + 8 + w * 8, npr, k0);
                        sts_u32(sb + SM_MISC + MI_INT + 48 + w * 4, swp);
                    }
                }
                TLA(10, 0);
                asm volatile("cp.async.bulk.wait_group.read 0;" ::: "memory");
                asm volatile("bar.arrive 3, %0;" ::"n"(NT) : "memory");
                PREW(2);
                TLS(5);
                FENCE_ASYNC();
                asm volatile("setmaxnreg.dec.sync.aligned.u32 %0;" ::"n"(PREG));
                produce(pt, pz, pm, bar0, sq + j * 2 + lane * 8, npr, sb + SM_SRC - 8, tbase, lim, taug * 32, tau16, k0 + lane, k0 + 32, tau2, brk
                );
        if (elect()) {
            const uint32_t d = ring + (NP - 2) * 8192 + j * (SM_ODD - 4096);
            const uint32_t fb = bar0 + (NP - 2) * 16, par = ~((lds_u32(sb + SM_MISC + MI_INT + 8 + w * 8) + 1) / NP) & 1;
            mbar_wait(fb + 24, par);
            mbar_arrive_cnt(fb + j * 16, j ? 1 : 3);
            mbar_expect_tx(fb + 16, 8192);
            tma_2d(d, &tmw, fb + 16, 0, j * 64);
            if (j) mbar_arrive(bar0 + DUMB);
            mbar_expect_tx(bar0 + DUMB, 8192);
            tma_2d(d + 8192, &tmw, bar0 + DUMB, 64, j * 64);
        }
        TLMAX(12);
        swp = lds_u32(sb + SM_MISC + MI_INT + 48 + w * 4);
        const int row = 2 * lane < hpb ? (node0 + ((swp >> lane) & 1) * hpb) * 4 + lane * 8 : N * 4;
        const CUtensorMap* po = &tmo;
        asm volatile("" : "+l"(po));
#pragma unroll
        for (int st = 0; st < 5; st++) {
            int rw[5];
#pragma unroll
            for (int k = 0; k < 5; k++)
                if (2 * k < out_n(st)) rw[k] = __shfl_sync(0xffffffffu, row, out_j(st) + 2 * k + (2 * k + 1 < out_n(st) ? j : j * (31 - out_j(st) - 2 * k)));
            asm volatile("bar.sync %0, 192;" ::"r"(6 + 2 * st + w) : "memory");
            if (!(EF >> st & 1)) FENCE_ASYNC();
            if (elect()) {
#pragma unroll
                for (int k = 0; k < 5; k++)
                    if (2 * k < out_n(st)) tma_store(po, ring - j * 3072 + out_at(st) + k * 2048, st < 3 ? 0 : 64, rw[k]);
                asm volatile("cp.async.bulk.commit_group;" ::: "memory");
            }
        }
        asm volatile("cp.async.bulk.wait_group.read 0;" ::: "memory");
        TLMAX(4);
        TLEND();
        return;
            }
        } else {
        asm volatile("bar.arrive 8, %0;" ::"n"(NT) : "memory");
        uint32_t en[5][4], es[5][4], rank[5][4], ca[5][4];
        if (warp >= 8 && (g >> 2) == (t >> 1)) {
            const uint2* cp = (const uint2*)cg + (g & 3) * 4 + (t & 1) * 2;
            asm volatile("ld.global.nc.v2.u32 {%0,%1}, [%2];" : "=r"(c0.x), "=r"(c0.y) : "l"(cp));
            asm volatile("ld.global.nc.v2.u32 {%0,%1}, [%2];" : "=r"(c1.x), "=r"(c1.y) : "l"(cp + 1));
        }
        const int sg[5] = {tid >> 3, (tid >> 3) + NB / 8, (tid >> 3) + NB / 4, (tid >> 3) + (lane & 4) * (NB / 32), (tid >> 3) + NB / 4};
        const uint4* gp[5];
        gp[0] = gbin + bin * nbins * 8 + tid;
        gp[1] = gp[0] + NB;
        gp[2] = gp[0] + 2 * NB;
        gp[3] = gbin + GEX + (bin * nbins + sg[3]) * 4 + (lane & 3);
        gp[4] = gbin + GEX + (bin * nbins + sg[4]) * 4 + (lane & 3);
        unsigned pend = (sg[0] < nbins) | (sg[1] < nbins) << 1 | (sg[2] < nbins) << 2;
#pragma unroll
        for (int k = 0; k < 5; k++) en[k][0] = en[k][1] = en[k][2] = en[k][3] = NULW + lane * (80 << 15);
        auto fetch = [&](int k) {
            asm volatile("{\n.reg .pred p;\nsetp.ne.u32 p, %5, 0;\n@p ld.relaxed.gpu.global.v4.u32 {%0,%1,%2,%3}, [%4];\n}"
                         : "+r"(en[k][0]), "+r"(en[k][1]), "+r"(en[k][2]), "+r"(en[k][3])
                         : "l"(gp[k]), "r"(pend & (1u << k))
                         : "memory");
        };
        int spin = 0;
        auto poll = [&](int k0, int k1) {
            for (;;) {
#pragma unroll
                for (int k = k0; k < k1; k++)
                    if (min(min(en[k][0], en[k][1]), min(en[k][2], en[k][3]))) pend &= ~(1u << k);
                if (!__any_sync(0xffffffffu, PV ? pend & ((1u << k1) - 1) : pend)) break;
#pragma unroll
                for (int k = k0; k < k1; k++) fetch(k);
                if (++spin > 10000000) __trap();
            }
        };
        auto count = [&](int k) {
#pragma unroll
            for (int c = 0; c < 4; c++) {
                const uint32_t v = en[k][c];
                ca[k][c] = (__umulhi(v, 6554) & 0x1ffc) | cnt0;
                rank[k][c] = atoms_add(ca[k][c], 1);
                asm volatile("{\n.reg .b32 a, b;\nprmt.b32 a, %1, %2, 0x6540;\nand.b32 b, %1, 0x7f00;\nmad.lo.u32 %0, b, %3, a;\n}"
                             : "=r"(es[k][c])
                             : "r"(v), "r"(sg[k] - nbins), "r"(nbins));
            }
        };
        while ((int)(clock() - c6) < delay) {}
        TLS(7);
        fetch(0);
        fetch(1);
        fetch(2);
        poll(0, 3);
        TLS(2);
        const bool more = __any_sync(0xffffffffu, (lane & 7) == 7 && min(min(en[0][3], en[1][3]), en[2][3]) < NULW);
        const bool rest = NB / 4 + warp * 4 < nbins;
        if (more) {
            const uint32_t l0 = __shfl_sync(0xffffffffu, en[0][3], lane | 7), l1 = __shfl_sync(0xffffffffu, en[1][3], lane | 7);
            const uint32_t l2 = __shfl_sync(0xffffffffu, en[2][3], lane | 7);
            pend = ((lane & 4 ? l1 : l0) < NULW) << 3 | (!(lane & 4) && l2 < NULW) << 4;
            fetch(3);
            fetch(4);
        }
        if (tid == 7 && en[0][3 - MS] >= NULW) sts_u32(sb + SM_MISC + MI_INT + 4, en[0][3 - MS]);
        count(0);
        count(1);
        if (rest) count(2);
        if (more) {
            const unsigned ext = pend;
            poll(3, 5);
#pragma unroll
            for (int k = 3; k < 5; k++) {
                if ((ext >> k) & 1) {
                    __stcg((uint4*)gp[k], make_uint4(0, 0, 0, 0));
                    if ((lane & 3) == 3 && en[k][3] < NULW) sts_u32(sb + SM_MISC + MI_INT + 44, 1);
                }
            }
            count(3);
            count(4);
        }
        TLS(9);
        SYNC();
        {
            const int w0 = warp >= NGR, gr = warp - w0 * NGR;
            const uint32_t cp = cnt0 + (warp * NBK + lane * (NBK / 32)) * 4;
            uint32_t r[5];
            const uint4 cv = lds_v4(cp);
            r[0] = 0, r[1] = cv.x, r[2] = cv.x + cv.y, r[3] = r[2] + cv.z, r[4] = r[3] + cv.w;
            const uint32_t tot = __reduce_add_sync(0xffffffffu, r[NBK / 32]);
            const uint32_t base = warp * GCAP + w0 * GEXT;
            const bool full = tot > GCAP + (gr == NGR - 1 ? GEXT : 0);
            asm volatile("st.shared.u8 [%0], %1;" ::"r"(sb + SM_MISC + MI_INT + 32 + (full ? 12 : (gr < 4 ? w0 * 4 : 4 + w0 * 2) + gr)), "r"(full ? 1 : (tot + 3) >> 2) : "memory");
            asm volatile("bar.arrive 5, %0;" ::"n"(NT) : "memory");
            const uint32_t off = warp_incl_scan(r[NBK / 32], lane, lds_u32(sb + SM_MISC + MI_INT)) - r[NBK / 32] + base + 7 - CE + GCODE(gr);
            if (lane == 31) r[NBK / 32] += CE;
#pragma unroll
            for (int c = 0; c <= NBK / 32; c++) r[c] += off;
#pragma unroll
            for (int c = 0; c < NBK / 32; c++) r[c] += ((r[c + 1] & ~3) - (r[c] & ~3)) << 15;
            sts_v4(cp, make_uint4(r[0], r[1], r[2], r[3]));
            asm volatile("{\n.reg .pred p;\n.reg .b16 h;\nsetp.lt.u32 p, %0, %1;\ncvt.u16.u32 h, %3;\n@p st.shared.u16 [%2], h;\n@p st.shared.u32 [%4], 0x80000000;\n}" ::"r"(lane),
                         "r"(full ? 0 : -tot & 3), "r"(sb + SM_SRC + (base + tot + lane) * 2), "r"(N + warp * KEYW), "r"(sb + SM_EID + (base + tot + lane) * 4)
                         : "memory");
        }
        TLS(10);
        asm volatile("bar.arrive 6, %0;" ::"n"(NT) : "memory");
#pragma unroll
        for (int h = 0; h < 2; h++)
            asm volatile("ldmatrix.sync.aligned.m8n8.x4.trans.shared.b16 {%0,%1,%2,%3}, [%4];"
                         : "=r"(wa[h * 4]), "=r"(wa[h * 4 + 1]), "=r"(wa[h * 4 + 2]), "=r"(wa[h * 4 + 3])
                         : "r"(sb + SC_WR + (h * 8 + (warp & 3) * 2 + ((lane >> 3) & 1)) * 272 + (lane >> 4) * 128 + (lane & 7) * 16));
        asm volatile("bar.sync 7, %0;" ::"n"(NB) : "memory");
        auto place0 = [&](int k, int nc = 4) {
#pragma unroll
            for (int c = 0; c < nc; c++)
                asm volatile("{\n.reg .pred p;\nsetp.lt.u32 p, %1, " STR(NULW) ";\n@p ld.shared.u16 %0, [%0];\n}" : "+r"(ca[k][c]) : "r"(en[k][c]));
#pragma unroll
            for (int c = 0; c < nc; c++) ca[k][c] = (ca[k][c] & 0xfff) + rank[k][c];
        };
        auto place1 = [&](int k, int nc = 4) {
#pragma unroll
            for (int c = 0; c < nc; c++)
                asm volatile(
                    "{\n.reg .pred p;\n.reg .b32 t;\n.reg .b16 h;\n"
                    "setp.lt.u32 p, %0, " STR(NULW) ";\n"
                    "shr.u32 t, %0, 15;\ncvt.u16.u32 h, t;\n"
                    "@p st.shared.u16 [%1], h;\n}" ::"r"(en[k][c]),
                    "r"(sb + SM_SRC - (7 - CE) * 2 + ca[k][c] * 2)
                    : "memory");
        };
        auto place2 = [&](int k, int nc = 4) {
#pragma unroll
            for (int c = 0; c < nc; c++)
                asm volatile("{\n.reg .pred p;\nsetp.lt.u32 p, %0, " STR(NULW) ";\n@p st.shared.u32 [%1], %2;\n}" ::"r"(en[k][c]),
                             "r"(sb + SM_EID - (7 - CE) * 4 + ca[k][c] * 4), "r"(es[k][c])
                             : "memory");
        };
        auto all = [&](auto f) {
            f(0);
            f(1);
            if (rest) f(2);
            if (more) f(3), f(4);
        };
        fast = lds_u32(sb + SM_MISC + MI_INT + 44) == 0;
        if (fast) {
            all([&](int k) { place0(k), place1(k); });
            TLS(14);
            TLA(14, 0);
            LISTS();
            all([&](int k) { place2(k); });
            if (warp < 8) asm volatile("bar.arrive 3, %0;" ::"n"(NT) : "memory");
        }
        }
    }

    if (fast && (warp >> 2) == 2) {
        asm volatile("setmaxnreg.dec.sync.aligned.u32 %0;" ::"n"(HREG));
        const int w = warp & 1, j = (warp >> 1) & 1;
        const uint32_t bar0 = sb + SM_BAR + w * NP * 16;
        const int blk = (lane >> 4) * 2 + (t >> 1);
        uint32_t fseq = sb + SM_SEQ + w * SEQCAP * 2 + j * 8 + blk * 2;
        const uint32_t feid = sb + SM_EID - 16 + (g & 3) * 4;
        uint32_t pea = sb + SM_EA + w * 4096 + j * 512 + (lane ^ ((lane >> 3) & 1)) * 16;
        const uint32_t psd = sb + SM_SIDE + (warp - 8) * 512 + (lane >> 1) * 16 + (lane & 1) * 4;
        const uint32_t pt = sb + SM_BT + w * (TS * 256) + j * 512 + blk * BT_B + ((lane ^ (lane >> 3)) & 1) * BT_K + (g & 3) * 4;
        const char* gea = (const char*)ea + (lane & 1) * 16;
        uint32_t es, va[2], ta[2], old[2] = {pt, pt}, dea = 2048;
        auto ids = [&]() {
            es = lds_u32(feid + (lds_u16(fseq) & 0xffc) * 4);
            fseq += 16;
        };
        uint32_t wf[4];
        wf[0] = __byte_perm(c0.x, c1.x, 0x5410), wf[1] = __byte_perm(c0.x, c1.x, 0x7632);
        wf[2] = __byte_perm(c0.y, c1.y, 0x5410), wf[3] = __byte_perm(c0.y, c1.y, 0x7632);
        int pfl = lane < PL ? PFN * nbins * 128 + (bin * 4 + warp - 8) * PL + lane - N * 8 : 0;
        int pfs = nbins * (4 * PL);
        const char* pfb = (const char*)(x + (size_t)N * 512);
        auto run = [&](auto odd) {
            auto fetch = [&](int i) {
                asm volatile(
                    "{\n.reg .pred p, q;\n.reg .b32 e;\n.reg .b64 a;\n"
                    "setp.lt.s32 p, %0, 0;\n"
                    "and.b32 e, %0, 0x7ffffff8;\n"
                    "mad.wide.u32 a, e, 4, %1;\n"
                    "cp.async.cg.shared.global [%2], [a], 16, p;\n"
                    "}" ::"r"(es), "l"(gea), "r"(pea + i * 1024) : "memory");
                va[i] = psd + (es & 8);
                ta[i] = pt + (es & 7) * 64;
                if (odd.value) {
                    cp_async4(va[i] + i * 256, (const char*)sh + (es & 0x7ffffff8) + (lane & 1) * 4, (int)es >= 0 ? 4 : 0);
                } else {
                    asm volatile(
                        "{\n.reg .pred p;\n.reg .b32 e;\n.reg .b64 a;\n"
                        "setp.lt.s32 p, %0, 0;\n"
                        "and.b32 e, %0, 0x7ffffff0;\n"
                        "mad.wide.u32 a, e, 1, %1;\n"
                        "cp.async.cg.shared.global [%2], [a], 16, p;\n"
                        "}" ::"r"(es), "l"(sh), "r"((psd & ~15) + i * 256) : "memory");
                }
                asm volatile("cp.async.commit_group;" ::: "memory");
                if (i) pea += dea, dea = -dea;
            };
            asm volatile("bar.sync 3, %0;" ::"n"(NT) : "memory");
            TLA(7, 0);
            const uint2 nk = lds_v2(sb + SM_MISC + MI_INT + 8 + w * 8);
            ids();
            fetch(0);
            ids();
            fetch(1);
            const int npr = __shfl_sync(0xffffffffu, nk.x, 0), kj = __shfl_sync(0xffffffffu, nk.y, 0) + j;
        uint32_t vf = bar0 + (kj < NP ? kj : 0) * 16;
        uint32_t pe = kj < NP;
#pragma unroll 1
            for (int m = (npr + 1 - j) >> 1; m > 0;) {
#pragma unroll
                for (int i = 0; i < 2; i++) {
                    asm volatile("cp.async.wait_group 1;" ::: "memory");
                    __syncwarp();
                    const uint32_t v = lds_u32(va[i] + i * 256);
                    ids();
                    float d0[4], d1[4];
                    mma_diag(d0, v, wf[0], wf[1]);
                    mma_diag(d1, v, wf[2], wf[3]);
                    uint32_t vn = vf + 32;
                    if (vn >= bar0 + NP * 16) vn -= NP * 16, pe ^= 1;
                    TWAIT(vn + 8, pe);
#pragma unroll
                    for (int k = 0; k < 4; k++) sts_u32(old[i] + i * 1024 + k * 16, 0);
                    old[i] = ta[i];
                    sts_u32(old[i] + i * 1024, pack_bf16(d0[0], d0[1]));
                    sts_u32(old[i] + i * 1024 + 16, pack_bf16(d0[2], d0[3]));
                    sts_u32(old[i] + i * 1024 + 32, pack_bf16(d1[0], d1[1]));
                    sts_u32(old[i] + i * 1024 + 48, pack_bf16(d1[2], d1[3]));
                    FENCE_ASYNC();
                    fetch(i);
                    __syncwarp();
                    if (lane == 0) mbar_arrive(vf);
                    asm volatile("{\n.reg .pred p;\n.reg .b64 a;\nsetp.lt.s32 p, %0, 0;\nmad.wide.s32 a, %0, 128, %1;\n@p prefetch.global.L2 [a];\n}" ::"r"(pfl),
                                 "l"(pfb));
                    pfl += pfs;
                    vf = vn;
                    if (--m <= 0) break;
                }
            }
        };
        if (E & 1) run(std::true_type()); else run(std::false_type());
        asm volatile("cp.async.wait_group 0;" ::: "memory");
        TLMAX(13);
    } else if (fast) {
        const int w = warp >> 2, wq = warp & 3;
        asm volatile("setmaxnreg.inc.sync.aligned.u32 %0;" ::"n"(CREG));
        const int k0 = __shfl_sync(0xffffffffu, lds_u32(sb + SM_MISC + MI_INT + 12 + w * 8), 0);
        const uint32_t ring = sb + w * RING_BYTES, bar0 = sb + SM_BAR + w * NP * 16;
        float acc[2][NJ][4];
        uint32_t a0[8][4], a1[8][4];
        {
            const int e = (lane >> 1) & 3, m = lane >> 3;
            const int line = 2 * ((lane & 1) + 2 * ((m >> 1) ^ (e >> 1))), ch = 2 * wq + (m & 1);
            const uint32_t xb = ring + (e & 1 ? SM_ODD : SM_EVEN) + (e >> 1) * 1024 + line * 128;
            consume(acc, a0, ring, xb + ((ch ^ ((line + (e & 1)) & 7)) * 16), xb + 128 + ((ch ^ ((line + 1 + (e & 1)) & 7)) * 16),
                    k0 * 8192, bar0, (((sb + SM_EA + w * 4096) & 0x3ffff) >> 4) | (1 << 16),
                    (((sb + SM_BT + w * (TS * 256)) & 0x3ffff) >> 4) | (BT_K / 16 << 16), sb + SM_SEQ + w * SEQCAP * 2, lane & (E >> 31),
                    wa);
        }
        const uint32_t tb = ring + wq * (NJ * 256) + lane * 16, db = (ring >> 4) + (8 << 16);
        const uint32_t cr = ring + (lane & 7) * 128 + (lane >> 4) * 1024, cc = 2 * wq + ((lane >> 3) & 1);
        const uint32_t ce = cr + (cc ^ (lane & 7)) * 16, co = cr + (cc ^ ((lane + 1) & 7)) * 16;
        float o0[CH0][4], o1[CH1][4], o2[CH2][4], o3[CH3][4], o4[CH4][4];
        TLMAX(11);
#pragma unroll
        for (int u = 0; u <= CH0; u++) put_agg<0, CH0>(acc, tb, u);
        TLE(1);
        FENCE_ASYNC();
        WG_SYNC(w);
        TLE(6);
        mul_out<0>(o0, a0, db, [&](int u) { put_agg<CH0, CH1>(acc, tb, u); });
        const bool ok1 = mbar_test(bar0 + DUMB, 0);
        FENCE_ASYNC();
        WG_SYNC(w);
        TLE(7);
        mul_out<KA>(o1, a0, db + CH0 * 16, [&](int u) {
            if (u == 0) {
                TLE(2);
#pragma unroll
                for (int k = 0; 2 * k < CH0; k++) put_out<0>(o0, ce, k, w);
                TLMAX(3);
            } else if (EO < 0 || u <= EO) {
                put_agg<CH0 + CH1, CH2>(acc, tb, 2 * u - 2);
                put_agg<CH0 + CH1, CH2>(acc, tb, 2 * u - 1);
            }
        });
        FENCE_ASYNC();
        if (!ok1) mbar_wait(bar0 + DUMB, 0);
        WG_SYNC(w);
        TLE(9);
        mul_out<KA>(o2, a0, db + (CH0 + CH1) * 16, [&](int u) {
            put_out<1>(o1, co, 2 * u, w);
            put_out<1>(o1, co, 2 * u + 1, w);
            if (u == 1) TLE(5);
            get_w(a1, ce + (NP - 1) * 8192, co + (NP - 1) * 8192, 2 * u - 4);
            get_w(a1, ce + (NP - 1) * 8192, co + (NP - 1) * 8192, 2 * u - 3);
        });
        mul_out<KA>(o3, a1, db, [&](int u) {
            if (u == 0) TLE(10);
            put_out<2>(o2, ce, u, w);
            if (u == 8 - KA) WG_SYNC(w);
        });
        mul_out<KA>(o4, a1, db + CH3 * 16, [&](int u) { put_out<3>(o3, co, u, w); });
        TLE(14);
        WG_WAIT(0);
#pragma unroll
        for (int u = 0; 2 * u < CH4; u++) put_out<4>(o4, ce, u, w);
        TLMAX(15);
    } else {
        float* accs = (float*)smem;
        constexpr int NACC = SM_EID / 2048;
        const int nnodes = max(0, min(npb, N - node0));
#pragma unroll 1
        for (int nb = 0; nb < nnodes; nb += NACC) {
            __syncthreads();
            for (int i = tid; i < NACC * 512; i += NT) accs[i] = 0.f;
            __syncthreads();
#pragma unroll 1
            for (int base = warp * 32; base < E; base += NT) {
                const int e = base + lane;
                int dl = e < E ? dst[e] - node0 - nb : -1;
                if (dl + nb >= nnodes) dl = -1;
                unsigned mask = __ballot_sync(0xffffffffu, dl >= 0 && dl < NACC);
#pragma unroll 1
                while (mask) {
                    const int l = __ffs(mask) - 1;
                    mask &= mask - 1;
                    const int ee = __shfl_sync(0xffffffffu, e, l);
                    const int dd = __shfl_sync(0xffffffffu, dl, l);
                    slow_edge(ee, src[ee], accs + dd * 512, x, sh, ea, cg, wr, lane);
                }
            }
            __syncthreads();
#pragma unroll 1
            for (int nl = warp; nl < NACC && nb + nl < nnodes; nl += NW)
                slow_out(accs + nl * 512, wout, out + (size_t)(node0 + nb + nl) * 512, lane);
        }
        __syncthreads();
    }

    TLMAX(4);
    TLEND();
}

typedef CUresult (*EncodeTiledFn)(CUtensorMap*, CUtensorMapDataType, cuuint32_t, void*, const cuuint64_t*,
                                  const cuuint64_t*, const cuuint32_t*, const cuuint32_t*, CUtensorMapInterleave,
                                  CUtensorMapSwizzle, CUtensorMapL2promotion, CUtensorMapFloatOOBfill);

extern "C" void kernel_launch(void* const* d_in, const int* in_sizes, int n_in, void* d_out, int out_size) {
    const __nv_bfloat16* x = (const __nv_bfloat16*)d_in[0];
    const int* src = (const int*)d_in[1];
    const int* dst = (const int*)d_in[2];
    const __nv_bfloat16* sh = (const __nv_bfloat16*)d_in[3];
    const __nv_bfloat16* ea = (const __nv_bfloat16*)d_in[4];
    const __nv_bfloat16* cg = (const __nv_bfloat16*)d_in[5];
    const __nv_bfloat16* wr = (const __nv_bfloat16*)d_in[6];
    const __nv_bfloat16* wout = (const __nv_bfloat16*)d_in[7];
    __nv_bfloat16* out = (__nv_bfloat16*)d_out;
    const int N = in_sizes[0] / 512;
    const int E = in_sizes[1];

    static int num_sms = 0;
    static EncodeTiledFn encode = nullptr;
    static uint4* gbin = nullptr;
    if (num_sms == 0) {
        int dev = 0;
        cudaGetDevice(&dev);
        cudaDeviceGetAttribute(&num_sms, cudaDevAttrMultiProcessorCount, dev);
        cudaFuncSetAttribute(main_kernel, cudaFuncAttributeMaxDynamicSharedMemorySize, SM_TOTAL + TLX);
        cudaGetSymbolAddress((void**)&gbin, g_bin);
        void* fn = nullptr;
        cudaDriverEntryPointQueryResult qr;
        cudaGetDriverEntryPoint("cuTensorMapEncodeTiled", &fn, cudaEnableDefault, &qr);
        encode = (EncodeTiledFn)fn;
    }
    const int nbins = num_sms < NB * 3 / 8 ? num_sms : NB * 3 / 8;
    int npb = ((N + nbins - 1) / nbins + 3) & ~3;
    if (npb < 32) npb = 32;
    const int fast_ok = E > 0 && npb <= 2 * HPB && N <= (NBK - 1) * 80 - 8 && E <= EPS * NT * nbins;
    auto map2d = [&](CUtensorMap* tm, const void* p, int d0, int d1, int b1) {
        const cuuint64_t gd[2] = {(cuuint64_t)d0, (cuuint64_t)d1};
        const cuuint64_t gs[1] = {(cuuint64_t)d0 * 2};
        const cuuint32_t bx[2] = {64, (cuuint32_t)b1};
        const cuuint32_t es[2] = {1, 1};
        encode(tm, CU_TENSOR_MAP_DATA_TYPE_BFLOAT16, 2, (void*)p, gd, gs, bx, es, CU_TENSOR_MAP_INTERLEAVE_NONE,
               CU_TENSOR_MAP_SWIZZLE_128B, CU_TENSOR_MAP_L2_PROMOTION_NONE, CU_TENSOR_MAP_FLOAT_OOB_FILL_NONE);
    };
    CUtensorMap tme, tmx, tmw, tmo;
    {
        const cuuint64_t gd[2] = {(cuuint64_t)nbins * 32, (cuuint64_t)nbins};
        const cuuint64_t gs[1] = {(cuuint64_t)nbins * 128};
        const cuuint32_t bx[2] = {32, (cuuint32_t)nbins};
        const cuuint32_t es[2] = {1, 1};
        encode(&tme, CU_TENSOR_MAP_DATA_TYPE_UINT32, 2, (void*)gbin, gd, gs, bx, es, CU_TENSOR_MAP_INTERLEAVE_NONE,
               SW ? CU_TENSOR_MAP_SWIZZLE_128B : CU_TENSOR_MAP_SWIZZLE_NONE, CU_TENSOR_MAP_L2_PROMOTION_NONE, CU_TENSOR_MAP_FLOAT_OOB_FILL_NONE);
    }
    {
        const cuuint64_t gd[2] = {(cuuint64_t)N * 256 - 224, 8};
        const cuuint64_t gs[1] = {128};
        const cuuint32_t bx[2] = {32, 8};
        const cuuint32_t es[2] = {1, 1};
        encode(&tmx, CU_TENSOR_MAP_DATA_TYPE_UINT32, 2, (void*)x, gd, gs, bx, es, CU_TENSOR_MAP_INTERLEAVE_NONE,
               CU_TENSOR_MAP_SWIZZLE_128B, CU_TENSOR_MAP_L2_PROMOTION_NONE, CU_TENSOR_MAP_FLOAT_OOB_FILL_NONE);
    }
    map2d(&tmw, wout, 128, 128, 64);
    map2d(&tmo, out, 128, N * 4, 8);
    const unsigned npb_magic = (unsigned)((0x100000000ull + npb - 1) / npb);
    const int chunk = (E + nbins - 1) / nbins;
    int tau16 = (int)fmin((double)PACE * 16.0 * chunk / N, 100000.0), toff = TOFF, delay = DELAY;
    int tau2 = tau16 * PACE2 / 100, brk = BRK;
    brk = (tau16 - tau2) * (N * brk / 50);
    main_kernel<<<nbins, NT, SM_TOTAL + TLX, cudaStreamPerThread>>>(dst, src, gbin, E, nbins, fast_ok, npb, npb_magic, N, tme, tmx, tmw,
                                                              tmo, x, sh, ea, cg, wr, wout, out, tau16, toff, delay, tau2, brk);
}
```

```cpp
#include <cuda_runtime.h>
#include <cuda.h>
#include <cuda_bf16.h>
#include <stdint.h>
#include <stdlib.h>
#include <type_traits>

#define MAXBINS 160
#define NW 16
#define NT (NW * 32)
#define HPB 38
#define GCAP 280
#define GEXT 72
#define NGR 6
#define LNUL (2 * (NGR * GCAP + GEXT))
#define NBK 128
#define KEYW 10240
#define CE 2
#define GSZ 6
#define NS 10
#define RING_BYTES 40960
static_assert(RING_BYTES == NS * 4096, "ring");
#define NP (NS / 2)
#define CREG 224
#define PREG 24
#define HREG 40
#define TS 8
#define SM_EVEN 0
#define SM_MISC (2 * RING_BYTES)
#define SM_ODD (SM_MISC + 128)
#define SM_EA (SM_BT + TS * 4096 + 128)
#define SM_BT (SM_ODD + 2 * RING_BYTES)
#define BT_B (TS * 512 + 16)
#define BT_K (4 * BT_B)
#define SM_SIDE (SM_EA + 8192)
#define SM_EID (SM_SIDE + 2048)
#define SM_SRC (SM_EID + (LNUL + 4) * 4)
#define SEQCAP ((LNUL / 8 + 32 + 7) / 8 * 8)
#define SM_SEQ (SM_SRC + (LNUL + 8) * 2)
#define SM_BAR ((SM_SEQ + 2 * SEQCAP * 2 + 63) / 64 * 64)
#define XR 0
#define SM_TOTAL (SM_BAR + NW * 16)
#define DUMB (2 * NP * 16)
#define MI_INT 0
#define EPS 5
#define SC_ENT 0
#define SC_EXT (SC_ENT + MAXBINS * 128)
#define SC_TAB (SC_EXT + MAXBINS * 64)
#define SC_HIST (SC_TAB + 320)
#define SC_END (SC_HIST + MAXBINS * 4 + 128)
#define SC_WR SC_END
#define SC_CNT (SC_WR + 4352)
static_assert(SC_END % 16 == 0 && SC_HIST % 16 == 0 && SC_END - SC_HIST <= NT * 16 && SC_CNT + 16384 <= SM_MISC && SC_TAB <= 4 * NT * 16 && 2 * HPB <= 80 && MAXBINS >= 24 * NGR, "scratch");
static_assert(LNUL >= 3072 && LNUL + 8 <= 4096 && GCAP % 4 == 0 && GEXT % 4 == 0, "lists");
static_assert(SM_TOTAL <= 232448 && SM_BAR % 16 == 0 && SM_SEQ % 16 == 0 && SM_SRC % 16 == 0 && SM_EA % 256 == 0, "smem");
#define PACE 18.6
#define PACE2 96
#define BRK 85
#define TOFF 7650
#define PSLEEP 20

#define GEX (MAXBINS * MAXBINS * 8)
__device__ __align__(128) uint4 g_bin[GEX + GEX / 2];
#define STR2(x) #x
#define STR(x) STR2(x)
#define TLINIT()
#define TLEND()
#define TLX 0
#define TLSTAMP(i)
#define TLMAX(i)

#define TLA(i, d)
#define TLS(i) TLMAX(i)
#define TLE(i)
__device__ __forceinline__ uint32_t pack_bf16(float lo, float hi) {
    uint32_t r;
    asm("cvt.rn.bf16x2.f32 %0, %1, %2;" : "=r"(r) : "f"(hi), "f"(lo));
    return r;
}
__device__ __forceinline__ void mma1688_z(float (&d)[4], uint32_t a0, uint32_t a1, uint32_t b0) {
    asm("mma.sync.aligned.m16n8k8.row.col.f32.bf16.bf16.f32 {%0,%1,%2,%3}, {%4,%5}, {%6}, {%7,%7,%7,%7};"
        : "=f"(d[0]), "=f"(d[1]), "=f"(d[2]), "=f"(d[3])
        : "r"(a0), "r"(a1), "r"(b0), "f"(0.f));
}
__device__ __forceinline__ void mma_diag(float (&d)[4], uint32_t a, uint32_t b0, uint32_t b1) {
    asm("mma.sync.aligned.m16n8k16.row.col.f32.bf16.bf16.f32 {%0,%1,%2,%3}, {%4,%8,%8,%4}, {%5,%6}, {%7,%7,%7,%7};"
        : "=f"(d[0]), "=f"(d[1]), "=f"(d[2]), "=f"(d[3])
        : "r"(a), "r"(b0), "r"(b1), "f"(0.f), "r"(0));
}
__device__ __forceinline__ uint32_t s2u(const void* p) { return (uint32_t)__cvta_generic_to_shared(p); }
__device__ __forceinline__ void mbar_init(uint32_t a, int c) {
    asm volatile("mbarrier.init.shared.b64 [%0], %1;" ::"r"(a), "r"(c));
}
__device__ __forceinline__ void mbar_expect_tx(uint32_t a, int bytes) {
    asm volatile("mbarrier.arrive.expect_tx.shared.b64 _, [%0], %1;" ::"r"(a), "r"(bytes) : "memory");
}
__device__ __forceinline__ void mbar_arrive(uint32_t a) {
    asm volatile("mbarrier.arrive.shared.b64 _, [%0];" ::"r"(a) : "memory");
}
__device__ __forceinline__ void mbar_arrive_cnt(uint32_t a, int c) {
    asm volatile("mbarrier.arrive.shared.b64 _, [%0], %1;" ::"r"(a), "r"(c) : "memory");
}
__device__ __forceinline__ void mbar_wait(uint32_t a, int parity) {
    asm volatile(
        "{\n.reg .pred p;\n.reg .u32 c;\n"
        "mov.u32 c, 0;\n"
        "LAB_WAIT:\n"
        "mbarrier.try_wait.parity.shared.b64 p, [%0], %1, 2000;\n"
        "@p bra DONE;\n"
        "add.u32 c, c, 1;\n"
        "setp.lt.u32 p, c, 2000000;\n"
        "@p bra LAB_WAIT;\n"
        "trap;\n"
        "DONE:\n}" ::"r"(a),
        "r"(parity)
        : "memory");
}
__device__ __forceinline__ void mbar_wait_u(uint32_t a, int parity) {
    asm volatile(
        "{\n.reg .pred p;\n.reg .u32 c;\n"
        "mov.u32 c, 0;\n"
        "LAB_WAIT:\n"
        "mbarrier.try_wait.parity.shared.b64 p, [%0], %1, 2000;\n"
        "@p bra.uni DONE;\n"
        "add.u32 c, c, 1;\n"
        "setp.lt.u32 p, c, 2000000;\n"
        "@p bra.uni LAB_WAIT;\n"
        "trap;\n"
        "DONE:\n}" ::"r"(a),
        "r"(parity)
        : "memory");
}
__device__ __forceinline__ void mbar_spin_u(uint32_t a, int parity) {
    asm volatile(
        "{\n.reg .pred p;\n.reg .u32 c;\n"
        "mov.u32 c, 0;\n"
        "LAB_WAIT:\n"
        "mbarrier.test_wait.parity.shared.b64 p, [%0], %1;\n"
        "@p bra.uni DONE;\n"
        "add.u32 c, c, 1;\n"
        "setp.lt.u32 p, c, 20000000;\n"
        "@p bra.uni LAB_WAIT;\n"
        "trap;\n"
        "DONE:\n}" ::"r"(a),
        "r"(parity)
        : "memory");
}
__device__ __forceinline__ void mbar_lean(uint32_t a, int parity) {
    asm volatile(
        "{\n.reg .pred p;\n.reg .u32 c;\n"
        "mov.u32 c, 0;\n"
        "LAB_WAIT:\n"
        "mbarrier.try_wait.parity.shared.b64 p, [%0], %1;\n"
        "@p bra DONE;\n"
        "add.u32 c, c, 1;\n"
        "setp.lt.u32 p, c, 4000000;\n"
        "@p bra LAB_WAIT;\n"
        "trap;\n"
        "DONE:\n}" ::"r"(a),
        "r"(parity)
        : "memory");
}
__device__ __forceinline__ void mbar_lean_u(uint32_t a, int parity) {
    asm volatile(
        "{\n.reg .pred p;\n.reg .u32 c;\n"
        "mov.u32 c, 0;\n"
        "LAB_WAIT:\n"
        "mbarrier.try_wait.parity.shared.b64 p, [%0], %1;\n"
        "@p bra.uni DONE;\n"
        "add.u32 c, c, 1;\n"
        "setp.lt.u32 p, c, 4000000;\n"
        "@p bra.uni LAB_WAIT;\n"
        "trap;\n"
        "DONE:\n}" ::"r"(a),
        "r"(parity)
        : "memory");
}
__device__ __forceinline__ bool mbar_test(uint32_t a, int parity) {
    uint32_t p;
    asm volatile("{\n.reg .pred P;\nmbarrier.test_wait.parity.shared.b64 P, [%1], %2;\nselp.u32 %0, 1, 0, P;\n}"
                 : "=r"(p)
                 : "r"(a), "r"(parity)
                 : "memory");
    return p;
}
__device__ __forceinline__ bool elect() {
    uint32_t p;
    asm volatile("{\n.reg .pred P;\nelect.sync _|P, 0xffffffff;\nselp.u32 %0, 1, 0, P;\n}" : "=r"(p));
    return p;
}
__device__ __forceinline__ void tma_2d(uint32_t dst, const CUtensorMap* tm, uint32_t bar, int c0, int c1) {
    asm volatile(
        "cp.async.bulk.tensor.2d.shared::cluster.global.mbarrier::complete_tx::bytes [%0], [%1, {%3, %4}], [%2];" ::"r"(dst),
        "l"(tm), "r"(bar), "r"(c0), "r"(c1)
        : "memory");
}
__device__ __forceinline__ void tma_row(uint32_t dst, const CUtensorMap* tm, uint32_t bar, int row8) {
    tma_2d(dst, tm, bar, 0, row8);
}
__device__ __forceinline__ void tma_store(const CUtensorMap* tm, uint32_t src, int c0, int c1) {
    asm volatile("cp.async.bulk.tensor.2d.global.shared::cta.bulk_group [%0, {%2, %3}], [%1];" ::"l"(tm), "r"(src),
                 "r"(c0), "r"(c1)
                 : "memory");
}
__device__ __forceinline__ uint2 lds_v2(uint32_t a) {
    uint2 v;
    asm volatile("ld.shared.v2.u32 {%0,%1}, [%2];" : "=r"(v.x), "=r"(v.y) : "r"(a));
    return v;
}
__device__ __forceinline__ uint4 lds_v4(uint32_t a) {
    uint4 v;
    asm volatile("ld.shared.v4.u32 {%0,%1,%2,%3}, [%4];" : "=r"(v.x), "=r"(v.y), "=r"(v.z), "=r"(v.w) : "r"(a));
    return v;
}
__device__ __forceinline__ uint32_t lds_u32(uint32_t a) {
    uint32_t v;
    asm volatile("ld.shared.u32 %0, [%1];" : "=r"(v) : "r"(a));
    return v;
}
__device__ __forceinline__ uint32_t lds_u16(uint32_t a) {
    uint32_t v;
    asm volatile("ld.shared.u16 %0, [%1];" : "=r"(v) : "r"(a));
    return v;
}
__device__ __forceinline__ void sts_v2(uint32_t a, uint32_t x, uint32_t y) {
    asm volatile("st.shared.v2.u32 [%0], {%1,%2};" ::"r"(a), "r"(x), "r"(y) : "memory");
}
__device__ __forceinline__ void sts_v4(uint32_t a, uint4 v) {
    asm volatile("st.shared.v4.u32 [%0], {%1,%2,%3,%4};" ::"r"(a), "r"(v.x), "r"(v.y), "r"(v.z), "r"(v.w) : "memory");
}
__device__ __forceinline__ void stsm4(uint32_t a, uint32_t r0, uint32_t r1, uint32_t r2, uint32_t r3) {
    asm volatile("stmatrix.sync.aligned.m8n8.x4.shared.b16 [%0], {%1,%2,%3,%4};" ::"r"(a), "r"(r0), "r"(r1), "r"(r2), "r"(r3)
                 : "memory");
}
__device__ __forceinline__ void stsm2(uint32_t a, uint32_t r0, uint32_t r1) {
    asm volatile("stmatrix.sync.aligned.m8n8.x2.shared.b16 [%0], {%1,%2};" ::"r"(a), "r"(r0), "r"(r1) : "memory");
}
__device__ __forceinline__ void stsm4t(uint32_t a, uint32_t r0, uint32_t r1, uint32_t r2, uint32_t r3) {
    asm volatile("stmatrix.sync.aligned.m8n8.x4.trans.shared.b16 [%0], {%1,%2,%3,%4};" ::"r"(a), "r"(r0), "r"(r1), "r"(r2),
                 "r"(r3)
                 : "memory");
}
__device__ __forceinline__ void stsm2t(uint32_t a, uint32_t r0, uint32_t r1) {
    asm volatile("stmatrix.sync.aligned.m8n8.x2.trans.shared.b16 [%0], {%1,%2};" ::"r"(a), "r"(r0), "r"(r1) : "memory");
}
__device__ __forceinline__ void cp_async16(uint32_t d, const void* s, int n) {
    asm volatile("cp.async.cg.shared.global [%0], [%1], 16, %2;" ::"r"(d), "l"(s), "r"(n) : "memory");
}
__device__ __forceinline__ void cp_async4(uint32_t d, const void* s, int n) {
    asm volatile("cp.async.ca.shared.global [%0], [%1], 4, %2;" ::"r"(d), "l"(s), "r"(n) : "memory");
}
__device__ __forceinline__ void sts_u32(uint32_t a, uint32_t x) {
    asm volatile("st.shared.u32 [%0], %1;" ::"r"(a), "r"(x) : "memory");
}
#define FENCE_ASYNC() asm volatile("fence.proxy.async.shared::cta;" ::: "memory")
#define ZS 4
__device__ __forceinline__ int warp_incl_scan(int v, int lane, int z) {
#pragma unroll
    for (int o = 1; o < 32; o <<= 1) {
        const int y = __shfl_up_sync(0xffffffffu, v, o);
        if (lane >= o) v += y;
        if (o == ZS) v += z;
    }
    return v;
}

__device__ __forceinline__ uint32_t atoms_add(uint32_t a, uint32_t v) {
    uint32_t r;
    asm volatile("atom.shared.add.u32 %0, [%1], %2;" : "=r"(r) : "r"(a), "r"(v) : "memory");
    return r;
}
__device__ __forceinline__ void sts_u16(uint32_t a, uint32_t x) {
    asm volatile("{\n.reg .b16 h;\ncvt.u16.u32 h, %1;\nst.shared.u16 [%0], h;\n}" ::"r"(a), "r"(x) : "memory");
}
#define NJ 19
__device__ __forceinline__ void consume(float (&acc)[2][NJ][4], uint32_t (&wo)[8][4], uint32_t ring, uint32_t xa0, uint32_t xa1, uint32_t so0, uint32_t bar0,
                                        uint32_t ea0, uint32_t d0, uint32_t pl0, int lz, const uint32_t (&wa)[8]) {
    asm volatile(
        "{\n"
        ".reg .pred p, pf, plead, pok, t0, t1, t2, u0, u1, u2;\n"
        ".reg .b32 ca, cb, cz, rbar;\n"
        "mov.b32 cz, 0;\n"
        "mov.b32 ca, 0x20002000;\n"
        "mov.b32 cb, 0x30003000;\n"
        ".reg .b32 cnt, so, q, qe, bar, nbar, pl, ctl, ctm, ix, iy, dl, v0, v1, v2, v3, pp;\n"
        ".reg .b16 sl, sh;\n"
        ".reg .b32 hXa0, hXa1, hXa2, hXa3, hXa4, hXa5, hXa6, hXa7, hXb0, hXb1, hXb2, hXb3, hXb4, hXb5, hXb6, hXb7, hYa0, hYa1, hYa2, hYa3, hYa4, hYa5, hYa6, hYa7, hYb0, hYb1, hYb2, hYb3, hYb4, hYb5, hYb6, hYb7, hLa0, hLa1, hLa2, hLa3, hLa4, hLa5, hLa6, hLa7, hLb0, hLb1, hLb2, hLb3, hLb4, hLb5, hLb6, hLb7;\n"
        ".reg .b32 pX0, pX1, pX2, pX3, pY0, pY1, pY2, pY3;\n"
        ".reg .f32 r0, r1, r2, r3, r4, r5, r6, r7, r8, r9, r10, r11, r12, r13, r14, r15;\n"
        ".reg .b64 daX, dbX, daY, dbY, de0, de1;\n"
        ".reg .b32 dh<6>, eb0, par, npar, wa<8>, uz, bend;\n"
        "add.u32 wa0, %192, %191;\n"
        "add.u32 wa1, %193, %191;\n"
        "add.u32 wa2, %194, %191;\n"
        "add.u32 wa3, %195, %191;\n"
        "add.u32 wa4, %196, %191;\n"
        "add.u32 wa5, %197, %191;\n"
        "add.u32 wa6, %198, %191;\n"
        "add.u32 wa7, %199, %191;\n"
        "mov.f32 %0, 0f00000000;\n"
        "mov.f32 %1, 0f00000000;\n"
        "mov.f32 %2, 0f00000000;\n"
        "mov.f32 %3, 0f00000000;\n"
        "mov.f32 %4, 0f00000000;\n"
        "mov.f32 %5, 0f00000000;\n"
        "mov.f32 %6, 0f00000000;\n"
        "mov.f32 %7, 0f00000000;\n"
        "mov.f32 %8, 0f00000000;\n"
        "mov.f32 %9, 0f00000000;\n"
        "mov.f32 %10, 0f00000000;\n"
        "mov.f32 %11, 0f00000000;\n"
        "mov.f32 %12, 0f00000000;\n"
        "mov.f32 %13, 0f00000000;\n"
        "mov.f32 %14, 0f00000000;\n"
        "mov.f32 %15, 0f00000000;\n"
        "mov.f32 %16, 0f00000000;\n"
        "mov.f32 %17, 0f00000000;\n"
        "mov.f32 %18, 0f00000000;\n"
        "mov.f32 %19, 0f00000000;\n"
        "mov.f32 %20, 0f00000000;\n"
        "mov.f32 %21, 0f00000000;\n"
        "mov.f32 %22, 0f00000000;\n"
        "mov.f32 %23, 0f00000000;\n"
        "mov.f32 %24, 0f00000000;\n"
        "mov.f32 %25, 0f00000000;\n"
        "mov.f32 %26, 0f00000000;\n"
        "mov.f32 %27, 0f00000000;\n"
        "mov.f32 %28, 0f00000000;\n"
        "mov.f32 %29, 0f00000000;\n"
        "mov.f32 %30, 0f00000000;\n"
        "mov.f32 %31, 0f00000000;\n"
        "mov.f32 %32, 0f00000000;\n"
        "mov.f32 %33, 0f00000000;\n"
        "mov.f32 %34, 0f00000000;\n"
        "mov.f32 %35, 0f00000000;\n"
        "mov.f32 %36, 0f00000000;\n"
        "mov.f32 %37, 0f00000000;\n"
        "mov.f32 %38, 0f00000000;\n"
        "mov.f32 %39, 0f00000000;\n"
        "mov.f32 %40, 0f00000000;\n"
        "mov.f32 %41, 0f00000000;\n"
        "mov.f32 %42, 0f00000000;\n"
        "mov.f32 %43, 0f00000000;\n"
        "mov.f32 %44, 0f00000000;\n"
        "mov.f32 %45, 0f00000000;\n"
        "mov.f32 %46, 0f00000000;\n"
        "mov.f32 %47, 0f00000000;\n"
        "mov.f32 %48, 0f00000000;\n"
        "mov.f32 %49, 0f00000000;\n"
        "mov.f32 %50, 0f00000000;\n"
        "mov.f32 %51, 0f00000000;\n"
        "mov.f32 %52, 0f00000000;\n"
        "mov.f32 %53, 0f00000000;\n"
        "mov.f32 %54, 0f00000000;\n"
        "mov.f32 %55, 0f00000000;\n"
        "mov.f32 %56, 0f00000000;\n"
        "mov.f32 %57, 0f00000000;\n"
        "mov.f32 %58, 0f00000000;\n"
        "mov.f32 %59, 0f00000000;\n"
        "mov.f32 %60, 0f00000000;\n"
        "mov.f32 %61, 0f00000000;\n"
        "mov.f32 %62, 0f00000000;\n"
        "mov.f32 %63, 0f00000000;\n"
        "mov.f32 %64, 0f00000000;\n"
        "mov.f32 %65, 0f00000000;\n"
        "mov.f32 %66, 0f00000000;\n"
        "mov.f32 %67, 0f00000000;\n"
        "mov.f32 %68, 0f00000000;\n"
        "mov.f32 %69, 0f00000000;\n"
        "mov.f32 %70, 0f00000000;\n"
        "mov.f32 %71, 0f00000000;\n"
        "mov.f32 %72, 0f00000000;\n"
        "mov.f32 %73, 0f00000000;\n"
        "mov.f32 %74, 0f00000000;\n"
        "mov.f32 %75, 0f00000000;\n"
        "mov.f32 %76, 0f00000000;\n"
        "mov.f32 %77, 0f00000000;\n"
        "mov.f32 %78, 0f00000000;\n"
        "mov.f32 %79, 0f00000000;\n"
        "mov.f32 %80, 0f00000000;\n"
        "mov.f32 %81, 0f00000000;\n"
        "mov.f32 %82, 0f00000000;\n"
        "mov.f32 %83, 0f00000000;\n"
        "mov.f32 %84, 0f00000000;\n"
        "mov.f32 %85, 0f00000000;\n"
        "mov.f32 %86, 0f00000000;\n"
        "mov.f32 %87, 0f00000000;\n"
        "mov.f32 %88, 0f00000000;\n"
        "mov.f32 %89, 0f00000000;\n"
        "mov.f32 %90, 0f00000000;\n"
        "mov.f32 %91, 0f00000000;\n"
        "mov.f32 %92, 0f00000000;\n"
        "mov.f32 %93, 0f00000000;\n"
        "mov.f32 %94, 0f00000000;\n"
        "mov.f32 %95, 0f00000000;\n"
        "mov.f32 %96, 0f00000000;\n"
        "mov.f32 %97, 0f00000000;\n"
        "mov.f32 %98, 0f00000000;\n"
        "mov.f32 %99, 0f00000000;\n"
        "mov.f32 %100, 0f00000000;\n"
        "mov.f32 %101, 0f00000000;\n"
        "mov.f32 %102, 0f00000000;\n"
        "mov.f32 %103, 0f00000000;\n"
        "mov.f32 %104, 0f00000000;\n"
        "mov.f32 %105, 0f00000000;\n"
        "mov.f32 %106, 0f00000000;\n"
        "mov.f32 %107, 0f00000000;\n"
        "mov.f32 %108, 0f00000000;\n"
        "mov.f32 %109, 0f00000000;\n"
        "mov.f32 %110, 0f00000000;\n"
        "mov.f32 %111, 0f00000000;\n"
        "mov.f32 %112, 0f00000000;\n"
        "mov.f32 %113, 0f00000000;\n"
        "mov.f32 %114, 0f00000000;\n"
        "mov.f32 %115, 0f00000000;\n"
        "mov.f32 %116, 0f00000000;\n"
        "mov.f32 %117, 0f00000000;\n"
        "mov.f32 %118, 0f00000000;\n"
        "mov.f32 %119, 0f00000000;\n"
        "mov.f32 %120, 0f00000000;\n"
        "mov.f32 %121, 0f00000000;\n"
        "mov.f32 %122, 0f00000000;\n"
        "mov.f32 %123, 0f00000000;\n"
        "mov.f32 %124, 0f00000000;\n"
        "mov.f32 %125, 0f00000000;\n"
        "mov.f32 %126, 0f00000000;\n"
        "mov.f32 %127, 0f00000000;\n"
        "mov.f32 %128, 0f00000000;\n"
        "mov.f32 %129, 0f00000000;\n"
        "mov.f32 %130, 0f00000000;\n"
        "mov.f32 %131, 0f00000000;\n"
        "mov.f32 %132, 0f00000000;\n"
        "mov.f32 %133, 0f00000000;\n"
        "mov.f32 %134, 0f00000000;\n"
        "mov.f32 %135, 0f00000000;\n"
        "mov.f32 %136, 0f00000000;\n"
        "mov.f32 %137, 0f00000000;\n"
        "mov.f32 %138, 0f00000000;\n"
        "mov.f32 %139, 0f00000000;\n"
        "mov.f32 %140, 0f00000000;\n"
        "mov.f32 %141, 0f00000000;\n"
        "mov.f32 %142, 0f00000000;\n"
        "mov.f32 %143, 0f00000000;\n"
        "mov.f32 %144, 0f00000000;\n"
        "mov.f32 %145, 0f00000000;\n"
        "mov.f32 %146, 0f00000000;\n"
        "mov.f32 %147, 0f00000000;\n"
        "mov.f32 %148, 0f00000000;\n"
        "mov.f32 %149, 0f00000000;\n"
        "mov.f32 %150, 0f00000000;\n"
        "mov.f32 %151, 0f00000000;\n"
        "setp.ne.u32 pf, 0, 0;\n"
        "add.u32 v0, %186, %191;\n"
        "shfl.sync.idx.b32 so, v0, 0, 31, 0xffffffff;\n"
        "mov.u32 npar, 0;\n"
        "shfl.sync.idx.b32 uz, %191, 7, 31, 0xffffffff;\n"
        "add.u32 bend, %187, " STR(NP * 16) ";\n"
        "add.u32 v0, %191, 8;\n"
        "shfl.sync.idx.b32 dh0, v0, 0, 31, 0xffffffff;\n"
        "shfl.sync.idx.b32 dh1, v0, 1, 31, 0xffffffff;\n"
        "shfl.sync.idx.b32 dh2, v0, 2, 31, 0xffffffff;\n"
        "shfl.sync.idx.b32 dh3, v0, 3, 31, 0xffffffff;\n"
        "add.u32 v0, %191, 0xc0000010;\n"
        "shfl.sync.idx.b32 dh4, v0, 4, 31, 0xffffffff;\n"
        "shfl.sync.idx.b32 dh5, v0, 5, 31, 0xffffffff;\n"
        "add.u32 v0, %191, %188;\n"
        "shfl.sync.idx.b32 eb0, v0, 0, 31, 0xffffffff;\n"
        "mov.u32 q, 0;\n"
        "mov.u32 pl, %190;\n"
        "shr.u32 nbar, so, 9;\n"
        "add.u32 nbar, nbar, %187;\n"
        "elect.sync _|plead, 0xffffffff;\n"
        "mov.b64 de0, {%188, dh4};\n"
        "mov.b64 de1, {eb0, dh5};\n"
        "mov.b32 hYa0, 0;\n"
        "mov.b32 hYa1, 0;\n"
        "mov.b32 hYa2, 0;\n"
        "mov.b32 hYa3, 0;\n"
        "mov.b32 hYa4, 0;\n"
        "mov.b32 hYa5, 0;\n"
        "mov.b32 hYa6, 0;\n"
        "mov.b32 hYa7, 0;\n"
        "mov.b32 hYb0, 0;\n"
        "mov.b32 hYb1, 0;\n"
        "mov.b32 hYb2, 0;\n"
        "mov.b32 hYb3, 0;\n"
        "mov.b32 hYb4, 0;\n"
        "mov.b32 hYb5, 0;\n"
        "mov.b32 hYb6, 0;\n"
        "mov.b32 hYb7, 0;\n"
        "mov.u32 ctm, 0x10001000;\n"
        "setp.lt.f16x2 t0|u0, ctm, cz;\n"
        "abs.f16x2 v3, ctm;\n"
        "setp.ge.f16x2 t1|u1, v3, ca;\n"
        "setp.geu.f16x2 t2|u2, v3, cb;\n"
        "ld.shared.v2.u32 {ctl, ctm}, [pl];\n"
        "add.u32 pl, pl, 8;\n"
        "add.u32 rbar, %187, " STR(DUMB) ";\n"
        "mov.b64 daX, {%189, dh0};\n"
        "mov.b64 dbX, {%189, dh1};\n"
        "mov.b64 daY, {%189, dh2};\n"
        "mov.b64 dbY, {%189, dh3};\n"
        "mov.u32 bar, nbar;\n"
        "mov.u32 par, npar;\n"
        "sub.u32 so, bar, %187;\n"
        "shl.b32 so, so, 9;\n"
        "add.u32 v0, %184, so;\n"
        "add.u32 v1, %185, so;\n"
        "add.u32 nbar, nbar, 16;\n"
        "setp.eq.u32 p, nbar, bend;\n"
        "selp.b32 nbar, %187, nbar, p;\n"
        "@p xor.b32 npar, npar, 1;\n"
        "SLOW:\n"
        "mov.u32 cnt, 0;\n"
        "W1:\n"
        "mbarrier.try_wait.parity.shared.b64 p, [bar], par;\n"
        "@p bra.uni RES;\n"
        "add.u32 cnt, cnt, 1;\n"
        "setp.lt.u32 p, cnt, 4000000;\n"
        "@p bra.uni W1;\n"
        "trap;\n"
        "CX:\n"
        "mbarrier.test_wait.parity.shared.b64 pok, [nbar], npar;\n"
        "and.b32 dl, q, 0x60;\n"
        "add.u32 dl, dl, %189;\n"
        "add.u32 v3, dl, 0;\n"
        "mov.b64 {v2, dh0}, daX;\n"
        "mov.b64 daX, {v3, dh0};\n"
        "add.u32 v3, dl, 257;\n"
        "mov.b64 {v2, dh1}, dbX;\n"
        "mov.b64 dbX, {v3, dh1};\n"
        "add.u32 v3, dl, 514;\n"
        "mov.b64 {v2, dh2}, daY;\n"
        "mov.b64 daY, {v3, dh2};\n"
        "add.u32 v3, dl, 771;\n"
        "mov.b64 {v2, dh3}, dbY;\n"
        "mov.b64 dbY, {v3, dh3};\n"
        "add.u32 q, q, 32;\n"
        "and.b32 qe, q, 0xe0;\n"
        "add.u32 v3, qe, %188;\n"
        "mov.b64 {v2, dh4}, de0;\n"
        "mov.b64 de0, {v3, dh4};\n"
        "mov.b64 {v2, dh5}, de1;\n"
        "mov.b64 de1, {v3, dh5};\n"
        "setp.lt.f16x2 t0|u0, ctl, cz;\n"
        "abs.f16x2 v3, ctl;\n"
        "setp.ge.f16x2 t1|u1, v3, ca;\n"
        "setp.geu.f16x2 t2|u2, v3, cb;\n"
        "wgmma.wait_group.sync.aligned 2;\n"
        "cvt.rn.bf16x2.f32 pX0, r1, r0;\n"
        "cvt.rn.bf16x2.f32 pX1, r3, r2;\n"
        "cvt.rn.bf16x2.f32 pX2, r9, r8;\n"
        "cvt.rn.bf16x2.f32 pX3, r11, r10;\n"
        "cvt.rn.bf16x2.f32 pY0, r5, r4;\n"
        "cvt.rn.bf16x2.f32 pY1, r7, r6;\n"
        "cvt.rn.bf16x2.f32 pY2, r13, r12;\n"
        "cvt.rn.bf16x2.f32 pY3, r15, r14;\n"
        "mov.b32 {sl, sh}, pX0;\n"
        "mov.b32 pp, {sl, sl};\n"
        "mul.rn.bf16x2 hXa0, hLa0, pp;\n"
        "mul.rn.bf16x2 hXa2, hLa2, pp;\n"
        "mov.b32 {sl, sh}, pX1;\n"
        "mov.b32 pp, {sl, sl};\n"
        "mul.rn.bf16x2 hXa1, hLa1, pp;\n"
        "mul.rn.bf16x2 hXa3, hLa3, pp;\n"
        "mov.b32 {sl, sh}, pX2;\n"
        "mov.b32 pp, {sl, sl};\n"
        "mul.rn.bf16x2 hXa4, hLa4, pp;\n"
        "mul.rn.bf16x2 hXa6, hLa6, pp;\n"
        "mov.b32 {sl, sh}, pX3;\n"
        "mov.b32 pp, {sl, sl};\n"
        "mul.rn.bf16x2 hXa5, hLa5, pp;\n"
        "mul.rn.bf16x2 hXa7, hLa7, pp;\n"
        "mov.b32 {sl, sh}, pX0;\n"
        "mov.b32 pp, {sh, sh};\n"
        "mul.rn.bf16x2 hXb0, hLb0, pp;\n"
        "mul.rn.bf16x2 hXb2, hLb2, pp;\n"
        "mov.b32 {sl, sh}, pX1;\n"
        "mov.b32 pp, {sh, sh};\n"
        "mul.rn.bf16x2 hXb1, hLb1, pp;\n"
        "mul.rn.bf16x2 hXb3, hLb3, pp;\n"
        "mov.b32 {sl, sh}, pX2;\n"
        "mov.b32 pp, {sh, sh};\n"
        "mul.rn.bf16x2 hXb4, hLb4, pp;\n"
        "mul.rn.bf16x2 hXb6, hLb6, pp;\n"
        "mov.b32 {sl, sh}, pX3;\n"
        "mov.b32 pp, {sh, sh};\n"
        "mul.rn.bf16x2 hXb5, hLb5, pp;\n"
        "mul.rn.bf16x2 hXb7, hLb7, pp;\n"
        "ldmatrix.sync.aligned.m8n8.x4.trans.shared.b16 {hLa0,hLa1,hLa2,hLa3}, [v0+4096];\n"
        "ldmatrix.sync.aligned.m8n8.x4.trans.shared.b16 {hLa4,hLa5,hLa6,hLa7}, [v1+4096];\n"
        "ldmatrix.sync.aligned.m8n8.x4.trans.shared.b16 {hLb0,hLb1,hLb2,hLb3}, [v0+6144];\n"
        "ldmatrix.sync.aligned.m8n8.x4.trans.shared.b16 {hLb4,hLb5,hLb6,hLb7}, [v1+6144];\n"
        "@t2 bra.uni T4X;\n"
        "@t1 bra.uni T2X;\n"
        "@t0 bra.uni L1X;\n"
        "L0X:\n"
        "wgmma.fence.sync.aligned;\n"
        "wgmma.mma_async.sync.aligned.m64n24k16.f32.bf16.bf16 {%0,%1,%2,%3,%4,%5,%6,%7,%8,%9,%10,%11}, {hXa0,hXa1,hXa2,hXa3}, daX, 1, 1, 1, 0;\n"
        "wgmma.mma_async.sync.aligned.m64n24k16.f32.bf16.bf16 {%76,%77,%78,%79,%80,%81,%82,%83,%84,%85,%86,%87}, {hXa4,hXa5,hXa6,hXa7}, daX, 1, 1, 1, 0;\n"
        "wgmma.commit_group.sync.aligned;\n"
        "@u2 bra.uni T4Xb;\n"
        "@u1 bra.uni T2Xb;\n"
        "@u0 bra.uni L1Xb;\n"
        "bra.uni L0Xb;\n"
        "L1X:\n"
        "wgmma.fence.sync.aligned;\n"
        "wgmma.mma_async.sync.aligned.m64n24k16.f32.bf16.bf16 {%12,%13,%14,%15,%16,%17,%18,%19,%20,%21,%22,%23}, {hXa0,hXa1,hXa2,hXa3}, daX, 1, 1, 1, 0;\n"
        "wgmma.mma_async.sync.aligned.m64n24k16.f32.bf16.bf16 {%88,%89,%90,%91,%92,%93,%94,%95,%96,%97,%98,%99}, {hXa4,hXa5,hXa6,hXa7}, daX, 1, 1, 1, 0;\n"
        "wgmma.commit_group.sync.aligned;\n"
        "@u2 bra.uni T4Xb;\n"
        "@u1 bra.uni T2Xb;\n"
        "@u0 bra.uni L1Xb;\n"
        "bra.uni L0Xb;\n"
        "T2X:\n"
        "@t0 bra.uni L3X;\n"
        "L2X:\n"
        "wgmma.fence.sync.aligned;\n"
        "wgmma.mma_async.sync.aligned.m64n24k16.f32.bf16.bf16 {%24,%25,%26,%27,%28,%29,%30,%31,%32,%33,%34,%35}, {hXa0,hXa1,hXa2,hXa3}, daX, 1, 1, 1, 0;\n"
        "wgmma.mma_async.sync.aligned.m64n24k16.f32.bf16.bf16 {%100,%101,%102,%103,%104,%105,%106,%107,%108,%109,%110,%111}, {hXa4,hXa5,hXa6,hXa7}, daX, 1, 1, 1, 0;\n"
        "wgmma.commit_group.sync.aligned;\n"
        "@u2 bra.uni T4Xb;\n"
        "@u1 bra.uni T2Xb;\n"
        "@u0 bra.uni L1Xb;\n"
        "bra.uni L0Xb;\n"
        "L3X:\n"
        "wgmma.fence.sync.aligned;\n"
        "wgmma.mma_async.sync.aligned.m64n24k16.f32.bf16.bf16 {%36,%37,%38,%39,%40,%41,%42,%43,%44,%45,%46,%47}, {hXa0,hXa1,hXa2,hXa3}, daX, 1, 1, 1, 0;\n"
        "wgmma.mma_async.sync.aligned.m64n24k16.f32.bf16.bf16 {%112,%113,%114,%115,%116,%117,%118,%119,%120,%121,%122,%123}, {hXa4,hXa5,hXa6,hXa7}, daX, 1, 1, 1, 0;\n"
        "wgmma.commit_group.sync.aligned;\n"
        "@u2 bra.uni T4Xb;\n"
        "@u1 bra.uni T2Xb;\n"
        "@u0 bra.uni L1Xb;\n"
        "bra.uni L0Xb;\n"
        "T4X:\n"
        "@!t1 bra.uni LEXIT;\n"
        "@t0 bra.uni L5X;\n"
        "L4X:\n"
        "wgmma.fence.sync.aligned;\n"
        "wgmma.mma_async.sync.aligned.m64n24k16.f32.bf16.bf16 {%48,%49,%50,%51,%52,%53,%54,%55,%56,%57,%58,%59}, {hXa0,hXa1,hXa2,hXa3}, daX, 1, 1, 1, 0;\n"
        "wgmma.mma_async.sync.aligned.m64n24k16.f32.bf16.bf16 {%124,%125,%126,%127,%128,%129,%130,%131,%132,%133,%134,%135}, {hXa4,hXa5,hXa6,hXa7}, daX, 1, 1, 1, 0;\n"
        "wgmma.commit_group.sync.aligned;\n"
        "@u2 bra.uni T4Xb;\n"
        "@u1 bra.uni T2Xb;\n"
        "@u0 bra.uni L1Xb;\n"
        "bra.uni L0Xb;\n"
        "L5X:\n"
        "wgmma.fence.sync.aligned;\n"
        "wgmma.mma_async.sync.aligned.m64n32k16.f32.bf16.bf16 {%60,%61,%62,%63,%64,%65,%66,%67,%68,%69,%70,%71,%72,%73,%74,%75}, {hXa0,hXa1,hXa2,hXa3}, daX, 1, 1, 1, 0;\n"
        "wgmma.mma_async.sync.aligned.m64n32k16.f32.bf16.bf16 {%136,%137,%138,%139,%140,%141,%142,%143,%144,%145,%146,%147,%148,%149,%150,%151}, {hXa4,hXa5,hXa6,hXa7}, daX, 1, 1, 1, 0;\n"
        "wgmma.commit_group.sync.aligned;\n"
        "@u2 bra.uni T4Xb;\n"
        "@u1 bra.uni T2Xb;\n"
        "@u0 bra.uni L1Xb;\n"
        "L0Xb:\n"
        "wgmma.fence.sync.aligned;\n"
        "wgmma.mma_async.sync.aligned.m64n24k16.f32.bf16.bf16 {%0,%1,%2,%3,%4,%5,%6,%7,%8,%9,%10,%11}, {hXb0,hXb1,hXb2,hXb3}, dbX, 1, 1, 1, 0;\n"
        "wgmma.mma_async.sync.aligned.m64n24k16.f32.bf16.bf16 {%76,%77,%78,%79,%80,%81,%82,%83,%84,%85,%86,%87}, {hXb4,hXb5,hXb6,hXb7}, dbX, 1, 1, 1, 0;\n"
        "wgmma.commit_group.sync.aligned;\n"
        "bra.uni CY;\n"
        "L1Xb:\n"
        "wgmma.fence.sync.aligned;\n"
        "wgmma.mma_async.sync.aligned.m64n24k16.f32.bf16.bf16 {%12,%13,%14,%15,%16,%17,%18,%19,%20,%21,%22,%23}, {hXb0,hXb1,hXb2,hXb3}, dbX, 1, 1, 1, 0;\n"
        "wgmma.mma_async.sync.aligned.m64n24k16.f32.bf16.bf16 {%88,%89,%90,%91,%92,%93,%94,%95,%96,%97,%98,%99}, {hXb4,hXb5,hXb6,hXb7}, dbX, 1, 1, 1, 0;\n"
        "wgmma.commit_group.sync.aligned;\n"
        "bra.uni CY;\n"
        "T2Xb:\n"
        "@u0 bra.uni L3Xb;\n"
        "L2Xb:\n"
        "wgmma.fence.sync.aligned;\n"
        "wgmma.mma_async.sync.aligned.m64n24k16.f32.bf16.bf16 {%24,%25,%26,%27,%28,%29,%30,%31,%32,%33,%34,%35}, {hXb0,hXb1,hXb2,hXb3}, dbX, 1, 1, 1, 0;\n"
        "wgmma.mma_async.sync.aligned.m64n24k16.f32.bf16.bf16 {%100,%101,%102,%103,%104,%105,%106,%107,%108,%109,%110,%111}, {hXb4,hXb5,hXb6,hXb7}, dbX, 1, 1, 1, 0;\n"
        "wgmma.commit_group.sync.aligned;\n"
        "bra.uni CY;\n"
        "L3Xb:\n"
        "wgmma.fence.sync.aligned;\n"
        "wgmma.mma_async.sync.aligned.m64n24k16.f32.bf16.bf16 {%36,%37,%38,%39,%40,%41,%42,%43,%44,%45,%46,%47}, {hXb0,hXb1,hXb2,hXb3}, dbX, 1, 1, 1, 0;\n"
        "wgmma.mma_async.sync.aligned.m64n24k16.f32.bf16.bf16 {%112,%113,%114,%115,%116,%117,%118,%119,%120,%121,%122,%123}, {hXb4,hXb5,hXb6,hXb7}, dbX, 1, 1, 1, 0;\n"
        "wgmma.commit_group.sync.aligned;\n"
        "bra.uni CY;\n"
        "T4Xb:\n"
        "@u0 bra.uni L5Xb;\n"
        "L4Xb:\n"
        "wgmma.fence.sync.aligned;\n"
        "wgmma.mma_async.sync.aligned.m64n24k16.f32.bf16.bf16 {%48,%49,%50,%51,%52,%53,%54,%55,%56,%57,%58,%59}, {hXb0,hXb1,hXb2,hXb3}, dbX, 1, 1, 1, 0;\n"
        "wgmma.mma_async.sync.aligned.m64n24k16.f32.bf16.bf16 {%124,%125,%126,%127,%128,%129,%130,%131,%132,%133,%134,%135}, {hXb4,hXb5,hXb6,hXb7}, dbX, 1, 1, 1, 0;\n"
        "wgmma.commit_group.sync.aligned;\n"
        "bra.uni CY;\n"
        "L5Xb:\n"
        "wgmma.fence.sync.aligned;\n"
        "wgmma.mma_async.sync.aligned.m64n32k16.f32.bf16.bf16 {%60,%61,%62,%63,%64,%65,%66,%67,%68,%69,%70,%71,%72,%73,%74,%75}, {hXb0,hXb1,hXb2,hXb3}, dbX, 1, 1, 1, 0;\n"
        "wgmma.mma_async.sync.aligned.m64n32k16.f32.bf16.bf16 {%136,%137,%138,%139,%140,%141,%142,%143,%144,%145,%146,%147,%148,%149,%150,%151}, {hXb4,hXb5,hXb6,hXb7}, dbX, 1, 1, 1, 0;\n"
        "wgmma.commit_group.sync.aligned;\n"
        "bra.uni CY;\n"
        "CY:\n"
        "mov.u32 rbar, bar;\n"
        "mov.u32 bar, nbar;\n"
        "mov.u32 par, npar;\n"
        "sub.u32 so, bar, %187;\n"
        "shl.b32 so, so, 9;\n"
        "add.u32 v0, %184, so;\n"
        "add.u32 v1, %185, so;\n"
        "add.u32 nbar, nbar, 16;\n"
        "setp.eq.u32 p, nbar, bend;\n"
        "selp.b32 nbar, %187, nbar, p;\n"
        "@p xor.b32 npar, npar, 1;\n"
        "wgmma.wait_group.sync.aligned 2;\n"
        "lop3.b32 v2, hLa3, hLa7, hLb3, 0x80;\n"
        "lop3.b32 v2, v2, hLb7, uz, 0x80;\n"
        "add.u32 v2, v2, rbar;\n"
        "@plead mbarrier.arrive.shared.b64 _, [v2+8];\n"
        "setp.lt.f16x2 t0|u0, ctm, cz;\n"
        "abs.f16x2 v3, ctm;\n"
        "setp.ge.f16x2 t1|u1, v3, ca;\n"
        "setp.geu.f16x2 t2|u2, v3, cb;\n"
        "ld.shared.v2.u32 {ctl, ctm}, [pl];\n"
        "add.u32 pl, pl, 8;\n"
        "mov.b32 {sl, sh}, pY0;\n"
        "mov.b32 pp, {sl, sl};\n"
        "mul.rn.bf16x2 hYa0, hLa0, pp;\n"
        "mul.rn.bf16x2 hYa2, hLa2, pp;\n"
        "mov.b32 {sl, sh}, pY1;\n"
        "mov.b32 pp, {sl, sl};\n"
        "mul.rn.bf16x2 hYa1, hLa1, pp;\n"
        "mul.rn.bf16x2 hYa3, hLa3, pp;\n"
        "mov.b32 {sl, sh}, pY2;\n"
        "mov.b32 pp, {sl, sl};\n"
        "mul.rn.bf16x2 hYa4, hLa4, pp;\n"
        "mul.rn.bf16x2 hYa6, hLa6, pp;\n"
        "mov.b32 {sl, sh}, pY3;\n"
        "mov.b32 pp, {sl, sl};\n"
        "mul.rn.bf16x2 hYa5, hLa5, pp;\n"
        "mul.rn.bf16x2 hYa7, hLa7, pp;\n"
        "mov.b32 {sl, sh}, pY0;\n"
        "mov.b32 pp, {sh, sh};\n"
        "mul.rn.bf16x2 hYb0, hLb0, pp;\n"
        "mul.rn.bf16x2 hYb2, hLb2, pp;\n"
        "mov.b32 {sl, sh}, pY1;\n"
        "mov.b32 pp, {sh, sh};\n"
        "mul.rn.bf16x2 hYb1, hLb1, pp;\n"
        "mul.rn.bf16x2 hYb3, hLb3, pp;\n"
        "mov.b32 {sl, sh}, pY2;\n"
        "mov.b32 pp, {sh, sh};\n"
        "mul.rn.bf16x2 hYb4, hLb4, pp;\n"
        "mul.rn.bf16x2 hYb6, hLb6, pp;\n"
        "mov.b32 {sl, sh}, pY3;\n"
        "mov.b32 pp, {sh, sh};\n"
        "mul.rn.bf16x2 hYb5, hLb5, pp;\n"
        "mul.rn.bf16x2 hYb7, hLb7, pp;\n"
        "@!pok bra.uni SLOW;\n"
        "RES:\n"
        "ldmatrix.sync.aligned.m8n8.x4.trans.shared.b16 {hLa0,hLa1,hLa2,hLa3}, [v0+0];\n"
        "ldmatrix.sync.aligned.m8n8.x4.trans.shared.b16 {hLa4,hLa5,hLa6,hLa7}, [v1+0];\n"
        "ldmatrix.sync.aligned.m8n8.x4.trans.shared.b16 {hLb0,hLb1,hLb2,hLb3}, [v0+2048];\n"
        "ldmatrix.sync.aligned.m8n8.x4.trans.shared.b16 {hLb4,hLb5,hLb6,hLb7}, [v1+2048];\n"
        "wgmma.wait_group.sync.aligned 0;\n"
        "@t2 bra.uni T4Y;\n"
        "@t1 bra.uni T2Y;\n"
        "@t0 bra.uni L1Y;\n"
        "L0Y:\n"
        "wgmma.fence.sync.aligned;\n"
        "wgmma.mma_async.sync.aligned.m64n16k16.f32.bf16.bf16 {r0,r1,r2,r3,r4,r5,r6,r7}, {wa0,wa1,wa2,wa3}, de0, pf, 1, 1, 0;\n"
        "wgmma.mma_async.sync.aligned.m64n16k16.f32.bf16.bf16 {r8,r9,r10,r11,r12,r13,r14,r15}, {wa4,wa5,wa6,wa7}, de1, pf, 1, 1, 0;\n"
        "wgmma.commit_group.sync.aligned;\n"
        "wgmma.mma_async.sync.aligned.m64n24k16.f32.bf16.bf16 {%0,%1,%2,%3,%4,%5,%6,%7,%8,%9,%10,%11}, {hYa0,hYa1,hYa2,hYa3}, daY, 1, 1, 1, 0;\n"
        "wgmma.mma_async.sync.aligned.m64n24k16.f32.bf16.bf16 {%76,%77,%78,%79,%80,%81,%82,%83,%84,%85,%86,%87}, {hYa4,hYa5,hYa6,hYa7}, daY, 1, 1, 1, 0;\n"
        "wgmma.commit_group.sync.aligned;\n"
        "@u2 bra.uni T4Yb;\n"
        "@u1 bra.uni T2Yb;\n"
        "@u0 bra.uni L1Yb;\n"
        "bra.uni L0Yb;\n"
        "L1Y:\n"
        "wgmma.fence.sync.aligned;\n"
        "wgmma.mma_async.sync.aligned.m64n16k16.f32.bf16.bf16 {r0,r1,r2,r3,r4,r5,r6,r7}, {wa0,wa1,wa2,wa3}, de0, pf, 1, 1, 0;\n"
        "wgmma.mma_async.sync.aligned.m64n16k16.f32.bf16.bf16 {r8,r9,r10,r11,r12,r13,r14,r15}, {wa4,wa5,wa6,wa7}, de1, pf, 1, 1, 0;\n"
        "wgmma.commit_group.sync.aligned;\n"
        "wgmma.mma_async.sync.aligned.m64n24k16.f32.bf16.bf16 {%12,%13,%14,%15,%16,%17,%18,%19,%20,%21,%22,%23}, {hYa0,hYa1,hYa2,hYa3}, daY, 1, 1, 1, 0;\n"
        "wgmma.mma_async.sync.aligned.m64n24k16.f32.bf16.bf16 {%88,%89,%90,%91,%92,%93,%94,%95,%96,%97,%98,%99}, {hYa4,hYa5,hYa6,hYa7}, daY, 1, 1, 1, 0;\n"
        "wgmma.commit_group.sync.aligned;\n"
        "@u2 bra.uni T4Yb;\n"
        "@u1 bra.uni T2Yb;\n"
        "@u0 bra.uni L1Yb;\n"
        "bra.uni L0Yb;\n"
        "T2Y:\n"
        "@t0 bra.uni L3Y;\n"
        "L2Y:\n"
        "wgmma.fence.sync.aligned;\n"
        "wgmma.mma_async.sync.aligned.m64n16k16.f32.bf16.bf16 {r0,r1,r2,r3,r4,r5,r6,r7}, {wa0,wa1,wa2,wa3}, de0, pf, 1, 1, 0;\n"
        "wgmma.mma_async.sync.aligned.m64n16k16.f32.bf16.bf16 {r8,r9,r10,r11,r12,r13,r14,r15}, {wa4,wa5,wa6,wa7}, de1, pf, 1, 1, 0;\n"
        "wgmma.commit_group.sync.aligned;\n"
        "wgmma.mma_async.sync.aligned.m64n24k16.f32.bf16.bf16 {%24,%25,%26,%27,%28,%29,%30,%31,%32,%33,%34,%35}, {hYa0,hYa1,hYa2,hYa3}, daY, 1, 1, 1, 0;\n"
        "wgmma.mma_async.sync.aligned.m64n24k16.f32.bf16.bf16 {%100,%101,%102,%103,%104,%105,%106,%107,%108,%109,%110,%111}, {hYa4,hYa5,hYa6,hYa7}, daY, 1, 1, 1, 0;\n"
        "wgmma.commit_group.sync.aligned;\n"
        "@u2 bra.uni T4Yb;\n"
        "@u1 bra.uni T2Yb;\n"
        "@u0 bra.uni L1Yb;\n"
        "bra.uni L0Yb;\n"
        "L3Y:\n"
        "wgmma.fence.sync.aligned;\n"
        "wgmma.mma_async.sync.aligned.m64n16k16.f32.bf16.bf16 {r0,r1,r2,r3,r4,r5,r6,r7}, {wa0,wa1,wa2,wa3}, de0, pf, 1, 1, 0;\n"
        "wgmma.mma_async.sync.aligned.m64n16k16.f32.bf16.bf16 {r8,r9,r10,r11,r12,r13,r14,r15}, {wa4,wa5,wa6,wa7}, de1, pf, 1, 1, 0;\n"
        "wgmma.commit_group.sync.aligned;\n"
        "wgmma.mma_async.sync.aligned.m64n24k16.f32.bf16.bf16 {%36,%37,%38,%39,%40,%41,%42,%43,%44,%45,%46,%47}, {hYa0,hYa1,hYa2,hYa3}, daY, 1, 1, 1, 0;\n"
        "wgmma.mma_async.sync.aligned.m64n24k16.f32.bf16.bf16 {%112,%113,%114,%115,%116,%117,%118,%119,%120,%121,%122,%123}, {hYa4,hYa5,hYa6,hYa7}, daY, 1, 1, 1, 0;\n"
        "wgmma.commit_group.sync.aligned;\n"
        "@u2 bra.uni T4Yb;\n"
        "@u1 bra.uni T2Yb;\n"
        "@u0 bra.uni L1Yb;\n"
        "bra.uni L0Yb;\n"
        "T4Y:\n"
        "@t0 bra.uni L5Y;\n"
        "L4Y:\n"
        "wgmma.fence.sync.aligned;\n"
        "wgmma.mma_async.sync.aligned.m64n16k16.f32.bf16.bf16 {r0,r1,r2,r3,r4,r5,r6,r7}, {wa0,wa1,wa2,wa3}, de0, pf, 1, 1, 0;\n"
        "wgmma.mma_async.sync.aligned.m64n16k16.f32.bf16.bf16 {r8,r9,r10,r11,r12,r13,r14,r15}, {wa4,wa5,wa6,wa7}, de1, pf, 1, 1, 0;\n"
        "wgmma.commit_group.sync.aligned;\n"
        "wgmma.mma_async.sync.aligned.m64n24k16.f32.bf16.bf16 {%48,%49,%50,%51,%52,%53,%54,%55,%56,%57,%58,%59}, {hYa0,hYa1,hYa2,hYa3}, daY, 1, 1, 1, 0;\n"
        "wgmma.mma_async.sync.aligned.m64n24k16.f32.bf16.bf16 {%124,%125,%126,%127,%128,%129,%130,%131,%132,%133,%134,%135}, {hYa4,hYa5,hYa6,hYa7}, daY, 1, 1, 1, 0;\n"
        "wgmma.commit_group.sync.aligned;\n"
        "@u2 bra.uni T4Yb;\n"
        "@u1 bra.uni T2Yb;\n"
        "@u0 bra.uni L1Yb;\n"
        "bra.uni L0Yb;\n"
        "L5Y:\n"
        "wgmma.fence.sync.aligned;\n"
        "wgmma.mma_async.sync.aligned.m64n16k16.f32.bf16.bf16 {r0,r1,r2,r3,r4,r5,r6,r7}, {wa0,wa1,wa2,wa3}, de0, pf, 1, 1, 0;\n"
        "wgmma.mma_async.sync.aligned.m64n16k16.f32.bf16.bf16 {r8,r9,r10,r11,r12,r13,r14,r15}, {wa4,wa5,wa6,wa7}, de1, pf, 1, 1, 0;\n"
        "wgmma.commit_group.sync.aligned;\n"
        "wgmma.mma_async.sync.aligned.m64n32k16.f32.bf16.bf16 {%60,%61,%62,%63,%64,%65,%66,%67,%68,%69,%70,%71,%72,%73,%74,%75}, {hYa0,hYa1,hYa2,hYa3}, daY, 1, 1, 1, 0;\n"
        "wgmma.mma_async.sync.aligned.m64n32k16.f32.bf16.bf16 {%136,%137,%138,%139,%140,%141,%142,%143,%144,%145,%146,%147,%148,%149,%150,%151}, {hYa4,hYa5,hYa6,hYa7}, daY, 1, 1, 1, 0;\n"
        "wgmma.commit_group.sync.aligned;\n"
        "@u2 bra.uni T4Yb;\n"
        "@u1 bra.uni T2Yb;\n"
        "@u0 bra.uni L1Yb;\n"
        "L0Yb:\n"
        "wgmma.fence.sync.aligned;\n"
        "wgmma.mma_async.sync.aligned.m64n24k16.f32.bf16.bf16 {%0,%1,%2,%3,%4,%5,%6,%7,%8,%9,%10,%11}, {hYb0,hYb1,hYb2,hYb3}, dbY, 1, 1, 1, 0;\n"
        "wgmma.mma_async.sync.aligned.m64n24k16.f32.bf16.bf16 {%76,%77,%78,%79,%80,%81,%82,%83,%84,%85,%86,%87}, {hYb4,hYb5,hYb6,hYb7}, dbY, 1, 1, 1, 0;\n"
        "wgmma.commit_group.sync.aligned;\n"
        "bra.uni CX;\n"
        "L1Yb:\n"
        "wgmma.fence.sync.aligned;\n"
        "wgmma.mma_async.sync.aligned.m64n24k16.f32.bf16.bf16 {%12,%13,%14,%15,%16,%17,%18,%19,%20,%21,%22,%23}, {hYb0,hYb1,hYb2,hYb3}, dbY, 1, 1, 1, 0;\n"
        "wgmma.mma_async.sync.aligned.m64n24k16.f32.bf16.bf16 {%88,%89,%90,%91,%92,%93,%94,%95,%96,%97,%98,%99}, {hYb4,hYb5,hYb6,hYb7}, dbY, 1, 1, 1, 0;\n"
        "wgmma.commit_group.sync.aligned;\n"
        "bra.uni CX;\n"
        "T2Yb:\n"
        "@u0 bra.uni L3Yb;\n"
        "L2Yb:\n"
        "wgmma.fence.sync.aligned;\n"
        "wgmma.mma_async.sync.aligned.m64n24k16.f32.bf16.bf16 {%24,%25,%26,%27,%28,%29,%30,%31,%32,%33,%34,%35}, {hYb0,hYb1,hYb2,hYb3}, dbY, 1, 1, 1, 0;\n"
        "wgmma.mma_async.sync.aligned.m64n24k16.f32.bf16.bf16 {%100,%101,%102,%103,%104,%105,%106,%107,%108,%109,%110,%111}, {hYb4,hYb5,hYb6,hYb7}, dbY, 1, 1, 1, 0;\n"
        "wgmma.commit_group.sync.aligned;\n"
        "bra.uni CX;\n"
        "L3Yb:\n"
        "wgmma.fence.sync.aligned;\n"
        "wgmma.mma_async.sync.aligned.m64n24k16.f32.bf16.bf16 {%36,%37,%38,%39,%40,%41,%42,%43,%44,%45,%46,%47}, {hYb0,hYb1,hYb2,hYb3}, dbY, 1, 1, 1, 0;\n"
        "wgmma.mma_async.sync.aligned.m64n24k16.f32.bf16.bf16 {%112,%113,%114,%115,%116,%117,%118,%119,%120,%121,%122,%123}, {hYb4,hYb5,hYb6,hYb7}, dbY, 1, 1, 1, 0;\n"
        "wgmma.commit_group.sync.aligned;\n"
        "bra.uni CX;\n"
        "T4Yb:\n"
        "@u0 bra.uni L5Yb;\n"
        "L4Yb:\n"
        "wgmma.fence.sync.aligned;\n"
        "wgmma.mma_async.sync.aligned.m64n24k16.f32.bf16.bf16 {%48,%49,%50,%51,%52,%53,%54,%55,%56,%57,%58,%59}, {hYb0,hYb1,hYb2,hYb3}, dbY, 1, 1, 1, 0;\n"
        "wgmma.mma_async.sync.aligned.m64n24k16.f32.bf16.bf16 {%124,%125,%126,%127,%128,%129,%130,%131,%132,%133,%134,%135}, {hYb4,hYb5,hYb6,hYb7}, dbY, 1, 1, 1, 0;\n"
        "wgmma.commit_group.sync.aligned;\n"
        "bra.uni CX;\n"
        "L5Yb:\n"
        "wgmma.fence.sync.aligned;\n"
        "wgmma.mma_async.sync.aligned.m64n32k16.f32.bf16.bf16 {%60,%61,%62,%63,%64,%65,%66,%67,%68,%69,%70,%71,%72,%73,%74,%75}, {hYb0,hYb1,hYb2,hYb3}, dbY, 1, 1, 1, 0;\n"
        "wgmma.mma_async.sync.aligned.m64n32k16.f32.bf16.bf16 {%136,%137,%138,%139,%140,%141,%142,%143,%144,%145,%146,%147,%148,%149,%150,%151}, {hYb4,hYb5,hYb6,hYb7}, dbY, 1, 1, 1, 0;\n"
        "wgmma.commit_group.sync.aligned;\n"
        "bra.uni CX;\n"
        "LEXIT:\n"
        "mov.u32 v2, %%tid.x;\n"
        "shr.u32 v3, v2, 4;\n"
        "and.b32 v0, v3, 1;\n"
        "mad.lo.u32 v0, v0, 1024, %200;\n"
        "and.b32 v1, v2, 7;\n"
        "mad.lo.u32 v0, v1, 128, v0;\n"
        "shr.u32 pp, v2, 3;\n"
        "lop3.b32 v3, v3, pp, 6, 0xe4;\n"
        "add.u32 pp, v2, 1;\n"
        "lop3.b32 pp, v3, pp, 7, 0x28;\n"
        "mad.lo.u32 v1, pp, 16, v0;\n"
        "lop3.b32 pp, v3, v2, 7, 0x28;\n"
        "mad.lo.u32 v0, pp, 16, v0;\n"
        "@pok bra.uni LW;\n"
        "mov.u32 cnt, 0;\n"
        "W2:\n"
        "mbarrier.try_wait.parity.shared.b64 p, [nbar], npar;\n"
        "@p bra.uni LW;\n"
        "add.u32 cnt, cnt, 1;\n"
        "setp.lt.u32 p, cnt, 4000000;\n"
        "@p bra.uni W2;\n"
        "trap;\n"
        "LW:\n"
        "ldmatrix.sync.aligned.m8n8.x4.trans.shared.b16 {hLa0,hLa1,hLa2,hLa3}, [v0+" STR((NP - 2) * 8192 + 0 * SM_ODD + 0) "];\n"
        "ldmatrix.sync.aligned.m8n8.x4.trans.shared.b16 {hLa4,hLa5,hLa6,hLa7}, [v0+" STR((NP - 2) * 8192 + 0 * SM_ODD + 2048) "];\n"
        "wgmma.wait_group.sync.aligned 0;\n"
        "ldmatrix.sync.aligned.m8n8.x4.trans.shared.b16 {hLb0,hLb1,hLb2,hLb3}, [v0+" STR((NP - 2) * 8192 + 0 * SM_ODD + 4096) "];\n"
        "ldmatrix.sync.aligned.m8n8.x4.trans.shared.b16 {hLb4,hLb5,hLb6,hLb7}, [v0+" STR((NP - 2) * 8192 + 0 * SM_ODD + 6144) "];\n"
        "ldmatrix.sync.aligned.m8n8.x4.trans.shared.b16 {hXa0,hXa1,hXa2,hXa3}, [v1+" STR((NP - 2) * 8192 + 1 * SM_ODD + 0) "];\n"
        "ldmatrix.sync.aligned.m8n8.x4.trans.shared.b16 {hXa4,hXa5,hXa6,hXa7}, [v1+" STR((NP - 2) * 8192 + 1 * SM_ODD + 2048) "];\n"
        "ldmatrix.sync.aligned.m8n8.x4.trans.shared.b16 {hXb0,hXb1,hXb2,hXb3}, [v1+" STR((NP - 2) * 8192 + 1 * SM_ODD + 4096) "];\n"
        "ldmatrix.sync.aligned.m8n8.x4.trans.shared.b16 {hXb4,hXb5,hXb6,hXb7}, [v1+" STR((NP - 2) * 8192 + 1 * SM_ODD + 6144) "];\n"
        "mov.b32 %152, hLa0;\n"
        "mov.b32 %153, hLa1;\n"
        "mov.b32 %154, hLa2;\n"
        "mov.b32 %155, hLa3;\n"
        "mov.b32 %156, hLa4;\n"
        "mov.b32 %157, hLa5;\n"
        "mov.b32 %158, hLa6;\n"
        "mov.b32 %159, hLa7;\n"
        "mov.b32 %160, hLb0;\n"
        "mov.b32 %161, hLb1;\n"
        "mov.b32 %162, hLb2;\n"
        "mov.b32 %163, hLb3;\n"
        "mov.b32 %164, hLb4;\n"
        "mov.b32 %165, hLb5;\n"
        "mov.b32 %166, hLb6;\n"
        "mov.b32 %167, hLb7;\n"
        "mov.b32 %168, hXa0;\n"
        "mov.b32 %169, hXa1;\n"
        "mov.b32 %170, hXa2;\n"
        "mov.b32 %171, hXa3;\n"
        "mov.b32 %172, hXa4;\n"
        "mov.b32 %173, hXa5;\n"
        "mov.b32 %174, hXa6;\n"
        "mov.b32 %175, hXa7;\n"
        "mov.b32 %176, hXb0;\n"
        "mov.b32 %177, hXb1;\n"
        "mov.b32 %178, hXb2;\n"
        "mov.b32 %179, hXb3;\n"
        "mov.b32 %180, hXb4;\n"
        "mov.b32 %181, hXb5;\n"
        "mov.b32 %182, hXb6;\n"
        "mov.b32 %183, hXb7;\n"
        "}\n"
        : "=f"(acc[0][0][0]), "=f"(acc[0][0][1]), "=f"(acc[0][0][2]), "=f"(acc[0][0][3]),
          "=f"(acc[0][1][0]), "=f"(acc[0][1][1]), "=f"(acc[0][1][2]), "=f"(acc[0][1][3]),
          "=f"(acc[0][2][0]), "=f"(acc[0][2][1]), "=f"(acc[0][2][2]), "=f"(acc[0][2][3]),
          "=f"(acc[0][3][0]), "=f"(acc[0][3][1]), "=f"(acc[0][3][2]), "=f"(acc[0][3][3]),
          "=f"(acc[0][4][0]), "=f"(acc[0][4][1]), "=f"(acc[0][4][2]), "=f"(acc[0][4][3]),
          "=f"(acc[0][5][0]), "=f"(acc[0][5][1]), "=f"(acc[0][5][2]), "=f"(acc[0][5][3]),
          "=f"(acc[0][6][0]), "=f"(acc[0][6][1]), "=f"(acc[0][6][2]), "=f"(acc[0][6][3]),
          "=f"(acc[0][7][0]), "=f"(acc[0][7][1]), "=f"(acc[0][7][2]), "=f"(acc[0][7][3]),
          "=f"(acc[0][8][0]), "=f"(acc[0][8][1]), "=f"(acc[0][8][2]), "=f"(acc[0][8][3]),
          "=f"(acc[0][9][0]), "=f"(acc[0][9][1]), "=f"(acc[0][9][2]), "=f"(acc[0][9][3]),
          "=f"(acc[0][10][0]), "=f"(acc[0][10][1]), "=f"(acc[0][10][2]), "=f"(acc[0][10][3]),
          "=f"(acc[0][11][0]), "=f"(acc[0][11][1]), "=f"(acc[0][11][2]), "=f"(acc[0][11][3]),
          "=f"(acc[0][12][0]), "=f"(acc[0][12][1]), "=f"(acc[0][12][2]), "=f"(acc[0][12][3]),
          "=f"(acc[0][13][0]), "=f"(acc[0][13][1]), "=f"(acc[0][13][2]), "=f"(acc[0][13][3]),
          "=f"(acc[0][14][0]), "=f"(acc[0][14][1]), "=f"(acc[0][14][2]), "=f"(acc[0][14][3]),
          "=f"(acc[0][15][0]), "=f"(acc[0][15][1]), "=f"(acc[0][15][2]), "=f"(acc[0][15][3]),
          "=f"(acc[0][16][0]), "=f"(acc[0][16][1]), "=f"(acc[0][16][2]), "=f"(acc[0][16][3]),
          "=f"(acc[0][17][0]), "=f"(acc[0][17][1]), "=f"(acc[0][17][2]), "=f"(acc[0][17][3]),
          "=f"(acc[0][18][0]), "=f"(acc[0][18][1]), "=f"(acc[0][18][2]), "=f"(acc[0][18][3]),
          "=f"(acc[1][0][0]), "=f"(acc[1][0][1]), "=f"(acc[1][0][2]), "=f"(acc[1][0][3]),
          "=f"(acc[1][1][0]), "=f"(acc[1][1][1]), "=f"(acc[1][1][2]), "=f"(acc[1][1][3]),
          "=f"(acc[1][2][0]), "=f"(acc[1][2][1]), "=f"(acc[1][2][2]), "=f"(acc[1][2][3]),
          "=f"(acc[1][3][0]), "=f"(acc[1][3][1]), "=f"(acc[1][3][2]), "=f"(acc[1][3][3]),
          "=f"(acc[1][4][0]), "=f"(acc[1][4][1]), "=f"(acc[1][4][2]), "=f"(acc[1][4][3]),
          "=f"(acc[1][5][0]), "=f"(acc[1][5][1]), "=f"(acc[1][5][2]), "=f"(acc[1][5][3]),
          "=f"(acc[1][6][0]), "=f"(acc[1][6][1]), "=f"(acc[1][6][2]), "=f"(acc[1][6][3]),
          "=f"(acc[1][7][0]), "=f"(acc[1][7][1]), "=f"(acc[1][7][2]), "=f"(acc[1][7][3]),
          "=f"(acc[1][8][0]), "=f"(acc[1][8][1]), "=f"(acc[1][8][2]), "=f"(acc[1][8][3]),
          "=f"(acc[1][9][0]), "=f"(acc[1][9][1]), "=f"(acc[1][9][2]), "=f"(acc[1][9][3]),
          "=f"(acc[1][10][0]), "=f"(acc[1][10][1]), "=f"(acc[1][10][2]), "=f"(acc[1][10][3]),
          "=f"(acc[1][11][0]), "=f"(acc[1][11][1]), "=f"(acc[1][11][2]), "=f"(acc[1][11][3]),
          "=f"(acc[1][12][0]), "=f"(acc[1][12][1]), "=f"(acc[1][12][2]), "=f"(acc[1][12][3]),
          "=f"(acc[1][13][0]), "=f"(acc[1][13][1]), "=f"(acc[1][13][2]), "=f"(acc[1][13][3]),
          "=f"(acc[1][14][0]), "=f"(acc[1][14][1]), "=f"(acc[1][14][2]), "=f"(acc[1][14][3]),
          "=f"(acc[1][15][0]), "=f"(acc[1][15][1]), "=f"(acc[1][15][2]), "=f"(acc[1][15][3]),
          "=f"(acc[1][16][0]), "=f"(acc[1][16][1]), "=f"(acc[1][16][2]), "=f"(acc[1][16][3]),
          "=f"(acc[1][17][0]), "=f"(acc[1][17][1]), "=f"(acc[1][17][2]), "=f"(acc[1][17][3]),
          "=f"(acc[1][18][0]), "=f"(acc[1][18][1]), "=f"(acc[1][18][2]), "=f"(acc[1][18][3]),
          "=r"(wo[0][0]), "=r"(wo[0][1]), "=r"(wo[0][2]), "=r"(wo[0][3]),
          "=r"(wo[1][0]), "=r"(wo[1][1]), "=r"(wo[1][2]), "=r"(wo[1][3]),
          "=r"(wo[2][0]), "=r"(wo[2][1]), "=r"(wo[2][2]), "=r"(wo[2][3]),
          "=r"(wo[3][0]), "=r"(wo[3][1]), "=r"(wo[3][2]), "=r"(wo[3][3]),
          "=r"(wo[4][0]), "=r"(wo[4][1]), "=r"(wo[4][2]), "=r"(wo[4][3]),
          "=r"(wo[5][0]), "=r"(wo[5][1]), "=r"(wo[5][2]), "=r"(wo[5][3]),
          "=r"(wo[6][0]), "=r"(wo[6][1]), "=r"(wo[6][2]), "=r"(wo[6][3]),
          "=r"(wo[7][0]), "=r"(wo[7][1]), "=r"(wo[7][2]), "=r"(wo[7][3])
        : "r"(xa0), "r"(xa1), "r"(so0), "r"(bar0), "r"(ea0), "r"(d0), "r"(pl0), "r"(lz), "r"(wa[0]), "r"(wa[1]), "r"(wa[2]),
          "r"(wa[3]), "r"(wa[4]), "r"(wa[5]), "r"(wa[6]), "r"(wa[7]), "r"(ring)
        : "memory");
}
#define CH0 4
#define CH1 7
#define CH2 8
#define CH3 10
#define CH4 9
__device__ __forceinline__ void wgmma_out(float (&o)[4][4], const uint32_t (&a)[4], uint64_t db, bool acc) {
    if (!acc)
        asm volatile(
            "wgmma.mma_async.sync.aligned.m64n32k16.f32.bf16.bf16 {%0,%1,%2,%3,%4,%5,%6,%7,%8,%9,%10,%11,%12,%13,%14,%15}, {%16,%17,%18,%19}, %20, 0, 1, 1, 1;"
            : "=f"(o[0][0]), "=f"(o[0][1]), "=f"(o[0][2]), "=f"(o[0][3]),
              "=f"(o[1][0]), "=f"(o[1][1]), "=f"(o[1][2]), "=f"(o[1][3]),
              "=f"(o[2][0]), "=f"(o[2][1]), "=f"(o[2][2]), "=f"(o[2][3]),
              "=f"(o[3][0]), "=f"(o[3][1]), "=f"(o[3][2]), "=f"(o[3][3])
            : "r"(a[0]), "r"(a[1]), "r"(a[2]), "r"(a[3]), "l"(db)
            : "memory");
    else
        asm volatile(
            "wgmma.mma_async.sync.aligned.m64n32k16.f32.bf16.bf16 {%0,%1,%2,%3,%4,%5,%6,%7,%8,%9,%10,%11,%12,%13,%14,%15}, {%16,%17,%18,%19}, %20, 1, 1, 1, 1;"
            : "+f"(o[0][0]), "+f"(o[0][1]), "+f"(o[0][2]), "+f"(o[0][3]),
              "+f"(o[1][0]), "+f"(o[1][1]), "+f"(o[1][2]), "+f"(o[1][3]),
              "+f"(o[2][0]), "+f"(o[2][1]), "+f"(o[2][2]), "+f"(o[2][3]),
              "+f"(o[3][0]), "+f"(o[3][1]), "+f"(o[3][2]), "+f"(o[3][3])
            : "r"(a[0]), "r"(a[1]), "r"(a[2]), "r"(a[3]), "l"(db)
            : "memory");
}
__device__ __forceinline__ void wgmma_out(float (&o)[7][4], const uint32_t (&a)[4], uint64_t db, bool acc) {
    if (!acc)
        asm volatile(
            "wgmma.mma_async.sync.aligned.m64n56k16.f32.bf16.bf16 {%0,%1,%2,%3,%4,%5,%6,%7,%8,%9,%10,%11,%12,%13,%14,%15,%16,%17,%18,%19,%20,%21,%22,%23,%24,%25,%26,%27}, {%28,%29,%30,%31}, %32, 0, 1, 1, 1;"
            : "=f"(o[0][0]), "=f"(o[0][1]), "=f"(o[0][2]), "=f"(o[0][3]),
              "=f"(o[1][0]), "=f"(o[1][1]), "=f"(o[1][2]), "=f"(o[1][3]),
              "=f"(o[2][0]), "=f"(o[2][1]), "=f"(o[2][2]), "=f"(o[2][3]),
              "=f"(o[3][0]), "=f"(o[3][1]), "=f"(o[3][2]), "=f"(o[3][3]),
              "=f"(o[4][0]), "=f"(o[4][1]), "=f"(o[4][2]), "=f"(o[4][3]),
              "=f"(o[5][0]), "=f"(o[5][1]), "=f"(o[5][2]), "=f"(o[5][3]),
              "=f"(o[6][0]), "=f"(o[6][1]), "=f"(o[6][2]), "=f"(o[6][3])
            : "r"(a[0]), "r"(a[1]), "r"(a[2]), "r"(a[3]), "l"(db)
            : "memory");
    else
        asm volatile(
            "wgmma.mma_async.sync.aligned.m64n56k16.f32.bf16.bf16 {%0,%1,%2,%3,%4,%5,%6,%7,%8,%9,%10,%11,%12,%13,%14,%15,%16,%17,%18,%19,%20,%21,%22,%23,%24,%25,%26,%27}, {%28,%29,%30,%31}, %32, 1, 1, 1, 1;"
            : "+f"(o[0][0]), "+f"(o[0][1]), "+f"(o[0][2]), "+f"(o[0][3]),
              "+f"(o[1][0]), "+f"(o[1][1]), "+f"(o[1][2]), "+f"(o[1][3]),
              "+f"(o[2][0]), "+f"(o[2][1]), "+f"(o[2][2]), "+f"(o[2][3]),
              "+f"(o[3][0]), "+f"(o[3][1]), "+f"(o[3][2]), "+f"(o[3][3]),
              "+f"(o[4][0]), "+f"(o[4][1]), "+f"(o[4][2]), "+f"(o[4][3]),
              "+f"(o[5][0]), "+f"(o[5][1]), "+f"(o[5][2]), "+f"(o[5][3]),
              "+f"(o[6][0]), "+f"(o[6][1]), "+f"(o[6][2]), "+f"(o[6][3])
            : "r"(a[0]), "r"(a[1]), "r"(a[2]), "r"(a[3]), "l"(db)
            : "memory");
}
__device__ __forceinline__ void wgmma_out(float (&o)[8][4], const uint32_t (&a)[4], uint64_t db, bool acc) {
    if (!acc)
        asm volatile(
            "wgmma.mma_async.sync.aligned.m64n64k16.f32.bf16.bf16 {%0,%1,%2,%3,%4,%5,%6,%7,%8,%9,%10,%11,%12,%13,%14,%15,%16,%17,%18,%19,%20,%21,%22,%23,%24,%25,%26,%27,%28,%29,%30,%31}, {%32,%33,%34,%35}, %36, 0, 1, 1, 1;"
            : "=f"(o[0][0]), "=f"(o[0][1]), "=f"(o[0][2]), "=f"(o[0][3]),
              "=f"(o[1][0]), "=f"(o[1][1]), "=f"(o[1][2]), "=f"(o[1][3]),
              "=f"(o[2][0]), "=f"(o[2][1]), "=f"(o[2][2]), "=f"(o[2][3]),
              "=f"(o[3][0]), "=f"(o[3][1]), "=f"(o[3][2]), "=f"(o[3][3]),
              "=f"(o[4][0]), "=f"(o[4][1]), "=f"(o[4][2]), "=f"(o[4][3]),
              "=f"(o[5][0]), "=f"(o[5][1]), "=f"(o[5][2]), "=f"(o[5][3]),
              "=f"(o[6][0]), "=f"(o[6][1]), "=f"(o[6][2]), "=f"(o[6][3]),
              "=f"(o[7][0]), "=f"(o[7][1]), "=f"(o[7][2]), "=f"(o[7][3])
            : "r"(a[0]), "r"(a[1]), "r"(a[2]), "r"(a[3]), "l"(db)
            : "memory");
    else
        asm volatile(
            "wgmma.mma_async.sync.aligned.m64n64k16.f32.bf16.bf16 {%0,%1,%2,%3,%4,%5,%6,%7,%8,%9,%10,%11,%12,%13,%14,%15,%16,%17,%18,%19,%20,%21,%22,%23,%24,%25,%26,%27,%28,%29,%30,%31}, {%32,%33,%34,%35}, %36, 1, 1, 1, 1;"
            : "+f"(o[0][0]), "+f"(o[0][1]), "+f"(o[0][2]), "+f"(o[0][3]),
              "+f"(o[1][0]), "+f"(o[1][1]), "+f"(o[1][2]), "+f"(o[1][3]),
              "+f"(o[2][0]), "+f"(o[2][1]), "+f"(o[2][2]), "+f"(o[2][3]),
              "+f"(o[3][0]), "+f"(o[3][1]), "+f"(o[3][2]), "+f"(o[3][3]),
              "+f"(o[4][0]), "+f"(o[4][1]), "+f"(o[4][2]), "+f"(o[4][3]),
              "+f"(o[5][0]), "+f"(o[5][1]), "+f"(o[5][2]), "+f"(o[5][3]),
              "+f"(o[6][0]), "+f"(o[6][1]), "+f"(o[6][2]), "+f"(o[6][3]),
              "+f"(o[7][0]), "+f"(o[7][1]), "+f"(o[7][2]), "+f"(o[7][3])
            : "r"(a[0]), "r"(a[1]), "r"(a[2]), "r"(a[3]), "l"(db)
            : "memory");
}
__device__ __forceinline__ void wgmma_out(float (&o)[9][4], const uint32_t (&a)[4], uint64_t db, bool acc) {
    if (!acc)
        asm volatile(
            "wgmma.mma_async.sync.aligned.m64n72k16.f32.bf16.bf16 {%0,%1,%2,%3,%4,%5,%6,%7,%8,%9,%10,%11,%12,%13,%14,%15,%16,%17,%18,%19,%20,%21,%22,%23,%24,%25,%26,%27,%28,%29,%30,%31,%32,%33,%34,%35}, {%36,%37,%38,%39}, %40, 0, 1, 1, 1;"
            : "=f"(o[0][0]), "=f"(o[0][1]), "=f"(o[0][2]), "=f"(o[0][3]),
              "=f"(o[1][0]), "=f"(o[1][1]), "=f"(o[1][2]), "=f"(o[1][3]),
              "=f"(o[2][0]), "=f"(o[2][1]), "=f"(o[2][2]), "=f"(o[2][3]),
              "=f"(o[3][0]), "=f"(o[3][1]), "=f"(o[3][2]), "=f"(o[3][3]),
              "=f"(o[4][0]), "=f"(o[4][1]), "=f"(o[4][2]), "=f"(o[4][3]),
              "=f"(o[5][0]), "=f"(o[5][1]), "=f"(o[5][2]), "=f"(o[5][3]),
              "=f"(o[6][0]), "=f"(o[6][1]), "=f"(o[6][2]), "=f"(o[6][3]),
              "=f"(o[7][0]), "=f"(o[7][1]), "=f"(o[7][2]), "=f"(o[7][3]),
              "=f"(o[8][0]), "=f"(o[8][1]), "=f"(o[8][2]), "=f"(o[8][3])
            : "r"(a[0]), "r"(a[1]), "r"(a[2]), "r"(a[3]), "l"(db)
            : "memory");
    else
        asm volatile(
            "wgmma.mma_async.sync.aligned.m64n72k16.f32.bf16.bf16 {%0,%1,%2,%3,%4,%5,%6,%7,%8,%9,%10,%11,%12,%13,%14,%15,%16,%17,%18,%19,%20,%21,%22,%23,%24,%25,%26,%27,%28,%29,%30,%31,%32,%33,%34,%35}, {%36,%37,%38,%39}, %40, 1, 1, 1, 1;"
            : "+f"(o[0][0]), "+f"(o[0][1]), "+f"(o[0][2]), "+f"(o[0][3]),
              "+f"(o[1][0]), "+f"(o[1][1]), "+f"(o[1][2]), "+f"(o[1][3]),
              "+f"(o[2][0]), "+f"(o[2][1]), "+f"(o[2][2]), "+f"(o[2][3]),
              "+f"(o[3][0]), "+f"(o[3][1]), "+f"(o[3][2]), "+f"(o[3][3]),
              "+f"(o[4][0]), "+f"(o[4][1]), "+f"(o[4][2]), "+f"(o[4][3]),
              "+f"(o[5][0]), "+f"(o[5][1]), "+f"(o[5][2]), "+f"(o[5][3]),
              "+f"(o[6][0]), "+f"(o[6][1]), "+f"(o[6][2]), "+f"(o[6][3]),
              "+f"(o[7][0]), "+f"(o[7][1]), "+f"(o[7][2]), "+f"(o[7][3]),
              "+f"(o[8][0]), "+f"(o[8][1]), "+f"(o[8][2]), "+f"(o[8][3])
            : "r"(a[0]), "r"(a[1]), "r"(a[2]), "r"(a[3]), "l"(db)
            : "memory");
}
__device__ __forceinline__ void wgmma_out(float (&o)[10][4], const uint32_t (&a)[4], uint64_t db, bool acc) {
    if (!acc)
        asm volatile(
            "wgmma.mma_async.sync.aligned.m64n80k16.f32.bf16.bf16 {%0,%1,%2,%3,%4,%5,%6,%7,%8,%9,%10,%11,%12,%13,%14,%15,%16,%17,%18,%19,%20,%21,%22,%23,%24,%25,%26,%27,%28,%29,%30,%31,%32,%33,%34,%35,%36,%37,%38,%39}, {%40,%41,%42,%43}, %44, 0, 1, 1, 1;"
            : "=f"(o[0][0]), "=f"(o[0][1]), "=f"(o[0][2]), "=f"(o[0][3]),
              "=f"(o[1][0]), "=f"(o[1][1]), "=f"(o[1][2]), "=f"(o[1][3]),
              "=f"(o[2][0]), "=f"(o[2][1]), "=f"(o[2][2]), "=f"(o[2][3]),
              "=f"(o[3][0]), "=f"(o[3][1]), "=f"(o[3][2]), "=f"(o[3][3]),
              "=f"(o[4][0]), "=f"(o[4][1]), "=f"(o[4][2]), "=f"(o[4][3]),
              "=f"(o[5][0]), "=f"(o[5][1]), "=f"(o[5][2]), "=f"(o[5][3]),
              "=f"(o[6][0]), "=f"(o[6][1]), "=f"(o[6][2]), "=f"(o[6][3]),
              "=f"(o[7][0]), "=f"(o[7][1]), "=f"(o[7][2]), "=f"(o[7][3]),
              "=f"(o[8][0]), "=f"(o[8][1]), "=f"(o[8][2]), "=f"(o[8][3]),
              "=f"(o[9][0]), "=f"(o[9][1]), "=f"(o[9][2]), "=f"(o[9][3])
            : "r"(a[0]), "r"(a[1]), "r"(a[2]), "r"(a[3]), "l"(db)
            : "memory");
    else
        asm volatile(
            "wgmma.mma_async.sync.aligned.m64n80k16.f32.bf16.bf16 {%0,%1,%2,%3,%4,%5,%6,%7,%8,%9,%10,%11,%12,%13,%14,%15,%16,%17,%18,%19,%20,%21,%22,%23,%24,%25,%26,%27,%28,%29,%30,%31,%32,%33,%34,%35,%36,%37,%38,%39}, {%40,%41,%42,%43}, %44, 1, 1, 1, 1;"
            : "+f"(o[0][0]), "+f"(o[0][1]), "+f"(o[0][2]), "+f"(o[0][3]),
              "+f"(o[1][0]), "+f"(o[1][1]), "+f"(o[1][2]), "+f"(o[1][3]),
              "+f"(o[2][0]), "+f"(o[2][1]), "+f"(o[2][2]), "+f"(o[2][3]),
              "+f"(o[3][0]), "+f"(o[3][1]), "+f"(o[3][2]), "+f"(o[3][3]),
              "+f"(o[4][0]), "+f"(o[4][1]), "+f"(o[4][2]), "+f"(o[4][3]),
              "+f"(o[5][0]), "+f"(o[5][1]), "+f"(o[5][2]), "+f"(o[5][3]),
              "+f"(o[6][0]), "+f"(o[6][1]), "+f"(o[6][2]), "+f"(o[6][3]),
              "+f"(o[7][0]), "+f"(o[7][1]), "+f"(o[7][2]), "+f"(o[7][3]),
              "+f"(o[8][0]), "+f"(o[8][1]), "+f"(o[8][2]), "+f"(o[8][3]),
              "+f"(o[9][0]), "+f"(o[9][1]), "+f"(o[9][2]), "+f"(o[9][3])
            : "r"(a[0]), "r"(a[1]), "r"(a[2]), "r"(a[3]), "l"(db)
            : "memory");
}

__device__ __forceinline__ void slow_edge(int ee, int s, float* accn, const __nv_bfloat16* __restrict__ x,
                                          const __nv_bfloat16* __restrict__ sh, const __nv_bfloat16* __restrict__ ea,
                                          const __nv_bfloat16* __restrict__ cg, const __nv_bfloat16* __restrict__ wr,
                                          int lane) {
    float rwv[4] = {0.f, 0.f, 0.f, 0.f};
#pragma unroll 4
    for (int d = 0; d < 16; d++) {
        const float a = __bfloat162float(ea[(size_t)ee * 16 + d]);
        const uint2 wv = *(const uint2*)(wr + d * 128 + lane * 4);
        rwv[0] += a * __uint_as_float(wv.x << 16);
        rwv[1] += a * __uint_as_float(wv.x & 0xffff0000u);
        rwv[2] += a * __uint_as_float(wv.y << 16);
        rwv[3] += a * __uint_as_float(wv.y & 0xffff0000u);
    }
    float A = 0.f;
#pragma unroll
    for (int v = 0; v < 4; v++)
        A += __bfloat162float(cg[((lane >> 2) & 3) * 16 + v * 4 + (lane & 3)]) * __bfloat162float(sh[(size_t)ee * 4 + v]);
    float m[4][4];
#pragma unroll
    for (int w = 0; w < 4; w++)
#pragma unroll
        for (int j = 0; j < 4; j++) m[w][j] = 0.f;
#pragma unroll
    for (int u = 0; u < 4; u++) {
        const uint2 xv = *(const uint2*)(x + (size_t)s * 512 + u * 128 + lane * 4);
        const float x0 = __uint_as_float(xv.x << 16), x1 = __uint_as_float(xv.x & 0xffff0000u);
        const float x2 = __uint_as_float(xv.y << 16), x3 = __uint_as_float(xv.y & 0xffff0000u);
#pragma unroll
        for (int w = 0; w < 4; w++) {
            const float a = __shfl_sync(0xffffffffu, A, u * 4 + w);
            m[w][0] += a * x0;
            m[w][1] += a * x1;
            m[w][2] += a * x2;
            m[w][3] += a * x3;
        }
    }
#pragma unroll
    for (int w = 0; w < 4; w++)
#pragma unroll
        for (int j = 0; j < 4; j++) atomicAdd(accn + w * 128 + lane * 4 + j, m[w][j] * rwv[j]);
}

__device__ __forceinline__ void slow_out(const float* accn, const __nv_bfloat16* __restrict__ wout,
                                         __nv_bfloat16* __restrict__ outn, int lane) {
    float o[4][4];
#pragma unroll
    for (int w = 0; w < 4; w++)
#pragma unroll
        for (int j = 0; j < 4; j++) o[w][j] = 0.f;
#pragma unroll 2
    for (int c = 0; c < 128; c++) {
        const uint2 wv = *(const uint2*)(wout + c * 128 + lane * 4);
        const float w0 = __uint_as_float(wv.x << 16), w1 = __uint_as_float(wv.x & 0xffff0000u);
        const float w2 = __uint_as_float(wv.y << 16), w3 = __uint_as_float(wv.y & 0xffff0000u);
#pragma unroll
        for (int w = 0; w < 4; w++) {
            const float a = __bfloat162float(__float2bfloat16(accn[w * 128 + c]));
            o[w][0] += a * w0;
            o[w][1] += a * w1;
            o[w][2] += a * w2;
            o[w][3] += a * w3;
        }
    }
#pragma unroll
    for (int w = 0; w < 4; w++)
        *(uint2*)(outn + w * 128 + lane * 4) = make_uint2(pack_bf16(o[w][0], o[w][1]), pack_bf16(o[w][2], o[w][3]));
}

static_assert(NW > 2 * NP, "barriers");
#define MS 0
#define BIAS 0
#define STG 0
#define ES 0
#define EB BRK
#define HS 0
#define HALF(w) (HS == 1 ? (w) * 64 : HS == 2 ? (blockIdx.x & 1) * 64 : HS == 3 ? ((blockIdx.x ^ (w)) & 1) * 64 : 0)
#define EO -1
#define EF 22
#define OWN 0
#define PLC 1
#define PFT 45
#define PFC 1
#define PFS 1
#define BULK 0
#define PFX 300
#define PX0 0
#define EZ 1
#define PFA 0
#define SPEC 0
#define SH 0
#define FE 2
#define PO 0
#define CL 0
#define HH 0
#define E0 1
#define SW 1
#define TA 0
#define FA 1
#define NA 0
#define PV 0
#define PB 0
#define FPOS 1
#define PW 0
#define TWAIT mbar_lean_u
#define PWAIT mbar_lean
#define TMA_ROW(k) "@pl cp.async.bulk.tensor.2d.shared::cluster.global.mbarrier::complete_tx::bytes [d" #k "], [tm, {r" #k ", %2" #k "}], [b" #k "];\n"
#define TMA_PREP(k) "mad.lo.u32 d" #k ", dd, 512, %3" #k ";\nadd.u32 b" #k ", dd, %2" #k ";\n"
#define RDCLK(c) "mov.u64 ck, %%clock64;\ncvt.u32.u64 " c ", ck;\n"
#define PMIN "min.u32"
#define BCAST(d, k) "selp.b32 " d ", a" #k ", 0, me;\nredux.sync.or.b32 " d ", " d ", 0xffffffff;\n"
#define PTIME(t, x, y, z) "shr.u32 " t ", " x ", 16;\nand.b32 c, " y ", 0xffff;\nadd.u32 " t ", " t ", c;\nmad.lo.u32 c, " t ", %13, %14;\nmul.lo.u32 " t ", " t ", %9;\n" PMIN " " t ", " t ", c;\nshr.u32 " t ", " t ", 5;\nadd.u32 " t ", " t ", %6;\nmin.u32 " t ", " t ", lim;\nlop3.b32 " t ", " t ", " z ", 7, 0xd8;\n"
#define PROWA(s, t) "and.b32 " t ", " s ", 0xffc;\nsetp.gt.u32 p, " t ", " STR(LNUL / 2) ";\nmad.lo.u32 " t ", " t ", 2, %5;\nshr.u32 t0, " s ", 11;\nand.b32 t0, t0, 6;\nshr.u32 " s ", " s ", 15;\nadd.u32 t0, t0, " s ";\nselp.s32 " s ", " STR(NGR - 2) ", -2, p;\nadd.u32 t0, t0, " s ";\nmul.lo.s32 t0, t0, " STR(-KEYW) ";\nprmt.b32 " s ", t0, 0, 0x1010;\n"
#define PROWB(s, t, x, y) "ld.shared.v2.u32 {" x ", " y "}, [" t "];\nadd.u16x2 " x ", " x ", " s ";\nadd.u16x2 " y ", " y ", " s ";\n"
#define PROWS(s, x, y) "and.b32 t0, " s ", 0xffc;\nsetp.gt.u32 p, t0, " STR(LNUL / 2) ";\nmad.lo.u32 t0, t0, 2, %5;\nld.shared.v2.u32 {" x ", " y "}, [t0];\nshr.u32 t0, " s ", 11;\nand.b32 t0, t0, 6;\nshr.u32 " s ", " s ", 15;\nadd.u32 t0, t0, " s ";\nselp.s32 " s ", " STR(NGR - 2) ", -2, p;\nadd.u32 t0, t0, " s ";\nmul.lo.s32 t0, t0, " STR(-KEYW) ";\nprmt.b32 t0, t0, 0, 0x1010;\nadd.u16x2 " x ", " x ", t0;\nadd.u16x2 " y ", " y ", t0;\n"
__device__ __forceinline__ void produce(const uint32_t (&pt)[2], const uint32_t (&pz)[8], const uint32_t (&pm)[8], uint32_t bar, uint32_t ps,
                                        int nit, uint32_t psrc, uint32_t tbase, uint32_t lim, uint32_t taug64, uint32_t taus, uint32_t n,
                                        int pr0, uint32_t tau2, uint32_t brk
) {
    asm volatile(
        "{\n.reg .pred p, pl, ok, me;\n.reg .b32 a<6>, u<4>, r<8>, d<8>, b<8>, ps, lim, n, it, pr, pe, tgt, tgu, c, dd, dn, par, t0, t1;\n"
        ".reg .b64 st, tm, ck;\n"
        "elect.sync _|pl, 0xffffffff;\n"
        "mov.b64 tm, {%0, %2};\n"
        "mov.u32 ps, %3;\n"
        "mov.u32 it, %4;\n"
        "mov.u32 lim, %7;\n"
        "mov.u32 n, %10;\n"
        "mov.u32 pr, %12;\n"
        "setp.le.s32 p, it, 0;\n"
        "bar.sync 4, " STR(NT) ";\n"
        "@p bra.uni PEND;\n"
        "PBAT:\n"
        "ld.shared.u16 c, [ps];\n"
        "ld.shared.u16 t1, [ps+4];\n"
        "add.u32 ps, ps, 256;\n"
        "mul.lo.u32 par, n, " STR(65536 / NP + 1) ";\n"
        "shr.u32 par, par, 16;\n"
        "mad.lo.s32 dn, par, " STR(-NP) ", n;\n"
        "add.u32 n, n, 32;\n"
        "not.b32 par, par;\n"
        PROWS("c", "a0", "a1") PROWS("t1", "a2", "a3")
        "min.s32 pe, it, 32;\n"
        "sub.s32 it, it, 32;\n"
        "add.u32 pe, pe, pr;\n"
        PTIME("a4", "a0", "a1", "dn") PTIME("a5", "a2", "a3", "par")
        "add.u32 lim, lim, %8;\n"
        "PLOOP:\n"
        "setp.eq.u32 me, n, pr;\n"
        "add.u32 pr, pr, 1;\n"
        BCAST("tgt", 4) BCAST("tgu", 5) BCAST("u0", 0) BCAST("u1", 1) BCAST("u2", 2) BCAST("u3", 3)
        "and.b32 dd, tgt, 7;\n"
        "mad.lo.u32 dd, dd, 16, %1;\n"
        "and.b32 par, tgu, 1;\n"
        "mbarrier.test_wait.parity.shared.b64 ok, [dd+8], par;\n"
        "prmt.b32 r0, u0, 0, 0x4104;\nprmt.b32 r1, u0, 0, 0x4324;\nprmt.b32 r2, u1, 0, 0x4104;\nprmt.b32 r3, u1, 0, 0x4324;\n"
        "prmt.b32 r4, u2, 0, 0x4104;\nprmt.b32 r5, u2, 0, 0x4324;\nprmt.b32 r6, u3, 0, 0x4104;\nprmt.b32 r7, u3, 0, 0x4324;\n"
        TMA_PREP(0) TMA_PREP(1) TMA_PREP(2) TMA_PREP(3) TMA_PREP(4) TMA_PREP(5) TMA_PREP(6) TMA_PREP(7)
        RDCLK("c")
        "sub.s32 c, c, tgt;\n"
        "setp.ge.and.s32 p, c, 0, ok;\n"
        "@!p bra.uni PSLP;\n"
        "PRES:\n"
        "@pl mbarrier.arrive.expect_tx.shared.b64 _, [b0], 8192;\n"
        TMA_ROW(0) TMA_ROW(1) TMA_ROW(2) TMA_ROW(3)
        RDCLK("c")
        "sub.s32 c, c, tgu;\n"
        "setp.lt.s32 p, c, 0;\n"
        "@p bra.uni PSL2;\n"
        "PRE2:\n"
        TMA_ROW(4) TMA_ROW(5) TMA_ROW(6) TMA_ROW(7)
        "setp.lt.u32 p, pr, pe;\n"
        "@p bra.uni PLOOP;\n"
        "setp.gt.s32 p, it, 0;\n"
        "@p bra.uni PBAT;\n"
        "bra.uni PEND;\n"
        "PSL2:\n"
        "nanosleep.u32 " STR(PSLEEP) ";\n"
        RDCLK("c")
        "sub.s32 c, c, tgu;\n"
        "setp.lt.s32 p, c, 0;\n"
        "@p bra.uni PSL2;\n"
        "bra.uni PRE2;\n"
        "PSL1:\n"
        "nanosleep.u32 " STR(PSLEEP) ";\n"
        RDCLK("c")
        "sub.s32 c, c, tgt;\n"
        "PSLP:\n"
        "setp.lt.s32 p, c, 0;\n"
        "@p bra.uni PSL1;\n"
        "@ok bra.uni PRES;\n"
        "mov.u32 c, 0;\n"
        "PW:\n"
        "mbarrier.try_wait.parity.shared.b64 p, [b0+8], par;\n"
        "@p bra.uni PRES;\n"
        "add.u32 c, c, 1;\n"
        "setp.lt.u32 p, c, 4000000;\n"
        "@p bra.uni PW;\n"
        "trap;\n"
        "PEND:\n}"
        :
        : "r"(pt[0]), "r"(bar), "r"(pt[1]), "r"(ps), "r"(nit), "r"(psrc), "r"(tbase), "r"(lim), "r"(taug64), "r"(taus), "r"(n), "n"(0),
          "r"(pr0), "r"(tau2), "r"(brk), "n"(0), "n"(0), "n"(0), "n"(0), "n"(0), "r"(pz[0]), "r"(pz[1]), "r"(pz[2]), "r"(pz[3]), "r"(pz[4]),
          "r"(pz[5]), "r"(pz[6]), "r"(pz[7]), "n"(0), "n"(0), "r"(pm[0]), "r"(pm[1]), "r"(pm[2]), "r"(pm[3]), "r"(pm[4]), "r"(pm[5]),
          "r"(pm[6]), "r"(pm[7])
        : "memory");
}
template <int J0, int JN>
__device__ __forceinline__ void put_agg(const float (&acc)[2][NJ][4], uint32_t tb, int u) {
    const int h = u & 1, j = u & ~1;
    const float(*a)[4] = acc[h] + J0 + (j < JN ? j : 0);
    if (j + 1 < JN)
        stsm4(tb + h * SM_ODD + (J0 + j) * 256, pack_bf16(a[0][0], a[0][1]), pack_bf16(a[0][2], a[0][3]), pack_bf16(a[1][0], a[1][1]),
              pack_bf16(a[1][2], a[1][3]));
    else if (j < JN)
        stsm2(tb + h * SM_ODD + (J0 + j) * 256, pack_bf16(a[0][0], a[0][1]), pack_bf16(a[0][2], a[0][3]));
}
template <int JN>
__device__ __forceinline__ void pin(float (&o)[JN][4]) {
#pragma unroll
    for (int j = 0; j < JN; j++)
#pragma unroll
        for (int k = 0; k < 4; k++) asm volatile("" : "+f"(o[j][k])::"memory");
}
#define WG_WAIT(n) asm volatile("wgmma.wait_group.sync.aligned %0;" ::"n"(n) : "memory")
#define WG_COMMIT() asm volatile("wgmma.commit_group.sync.aligned;" ::: "memory")
#define KA 2
template <int K0, int JN, class F>
__device__ __forceinline__ void mul_out(float (&o)[JN][4], const uint32_t (&a)[8][4], uint32_t db, F f) {
    asm volatile("wgmma.fence.sync.aligned;" ::: "memory");
#pragma unroll
    for (int ks = 0; ks < 8; ks++) {
        wgmma_out(o, a[ks], (uint64_t)(db + (((ks >> 2) * SM_ODD + (ks & 3) * (NJ * 256)) >> 4)) | (16ull << 32), ks);
        if (ks == K0 - 1 || ks == 7) WG_COMMIT();
        if (ks == K0 - 1) WG_WAIT(1);
        if (ks >= K0 - 1) f(K0 ? ks - K0 + 1 : ks);
    }
}
static_assert(CH1 <= 8 && CH2 <= 8 && CH3 <= 10 && CH4 <= 10 && KA <= 3 && NJ == 19 && NP == 5 && SM_EVEN == 0 && SM_ODD % 1024 == 128 && CH0 + CH2 <= 13 && CH1 <= 13 && CH0 + CH2 + CH4 <= 21 && CH1 + CH3 <= 21, "epilogue");
__device__ constexpr int out_n(int st) { return st == 0 ? CH0 : st == 1 ? CH1 : st == 2 ? CH2 : st == 3 ? CH3 : CH4; }
__device__ constexpr int out_j(int st) { return st == 1 ? CH0 : st == 2 ? CH0 + CH1 : st == 4 ? CH3 : 0; }
__device__ constexpr int out_at(int st) { return (NJ + (st == 2 ? CH0 : st == 3 ? CH1 : st == 4 ? CH0 + CH2 : 0)) * 1024 + (st & 1) * SM_ODD; }
#define WG_SYNC(w) asm volatile("bar.sync %0, 128;" ::"r"((w) + 1) : "memory")
#define HAND(st, w) asm volatile("bar.arrive %0, %1;" ::"r"(6 + 2 * (st) + (w)), "n"(OWN ? 160 : 192) : "memory")
template <int R>
__device__ __forceinline__ void store_out(const CUtensorMap* po, uint32_t sb, int w, int j, int node0, int hpb, int lane) {
    const uint32_t swp = lds_u32(sb + SM_MISC + MI_INT + 48 + w * 4), ring = sb + w * RING_BYTES;
    const int row = 2 * lane < hpb ? (node0 + ((swp >> lane) & 1) * hpb) * 4 + lane * 8 : 1 << 30;
    asm volatile("" : "+l"(po));
#pragma unroll
    for (int st = 0; st < 5; st++) {
        if ((OWN >> (3 * st + 1) & 1) == R && (OWN >> 3 * st & 1) == j) {
            int rw[10];
#pragma unroll
            for (int k = 0; k < 10; k++)
                if (k < out_n(st)) rw[k] = __shfl_sync(0xffffffffu, row, out_j(st) + k);
            asm volatile("bar.sync %0, 160;" ::"r"(6 + 2 * st + w) : "memory");
            FENCE_ASYNC();
            if (elect()) {
#pragma unroll
                for (int k = 0; k < 10; k++)
                    if (k < out_n(st)) tma_store(po, ring + out_at(st) + k * 1024, st < 3 ? 0 : 64, rw[k]);
                asm volatile("cp.async.bulk.commit_group;" ::: "memory");
            }
        }
    }
    asm volatile("cp.async.bulk.wait_group.read 0;" ::: "memory");
}
template <int ST, int JN>
__device__ __forceinline__ void put_out(float (&o)[JN][4], uint32_t c, int u, int w) {
    if (u == 0) pin(o);
    const int j = 2 * u < JN ? 2 * u : 0;
    if (2 * u + 1 < JN)
        stsm4t(c + out_at(ST) + j * 1024, pack_bf16(o[j][0], o[j][1]), pack_bf16(o[j][2], o[j][3]), pack_bf16(o[j + 1][0], o[j + 1][1]),
               pack_bf16(o[j + 1][2], o[j + 1][3]));
    else if (2 * u < JN)
        stsm2t(c + out_at(ST) + j * 1024, pack_bf16(o[j][0], o[j][1]), pack_bf16(o[j][2], o[j][3]));
    if (u == (JN - 1) / 2) {
        if (EF >> ST & 1) FENCE_ASYNC();
        HAND(ST, w);
    }
}
__device__ __forceinline__ void get_w(uint32_t (&a)[8][4], uint32_t ce, uint32_t co, int ks) {
    if (ks >= 0 && ks < 8)
        asm volatile("ldmatrix.sync.aligned.m8n8.x4.trans.shared.b16 {%0,%1,%2,%3}, [%4];"
                     : "=r"(a[ks & 7][0]), "=r"(a[ks & 7][1]), "=r"(a[ks & 7][2]), "=r"(a[ks & 7][3])
                     : "r"((ks < 4 ? ce : co + SM_ODD) + (ks & 3) * 2048)
                     : "memory");
}
#define TB 8
#define DELAY 4100
#define NULW 0xf0000000
#define LW 128
#define DREF 1
#define K0(npr) ((2 * NP - 2 - (npr) % NP) % NP)
#define GCODE(g) ((((g) >> 1) + 1) << 12 | ((g) & 1) << 15)
#define SYNC() asm volatile("bar.sync 0;" ::: "memory")
#define LISTS() asm volatile("bar.sync 4, %0;" ::"n"(NT) : "memory")
#define NB (2 * NGR * 32)
#define PREF(p, tot, k0, n)                                                                                       \
    {                                                                                                             \
        _Pragma("unroll") for (int k = (k0); k < (k0) + (n); k++) {                                                \
            const int l = (k * nbins + bin) * 128 + tid - NB;                                                     \
            if (l < (tot)) asm volatile("prefetch.global.L2 [%0];" ::"l"(p + (size_t)l * 64) : "memory");         \
        }                                                                                                         \
    }
#define WX 010
#define WS 0011
#define WE 000
#define PL 8
#define PLE 0
#define DG(v, i) ((v) >> (6 - 3 * (i)) & 7)
#define PREW(i)                                                                                \
    PREF(x, N * 8, (i > 0 ? DG(WX, 0) : 0) + (i > 1 ? DG(WX, 1) : 0), DG(WX, i))                \
    PREF(sh, E / 16, (i > 0 ? DG(WS, 0) : 0) + (i > 1 ? DG(WS, 1) : 0), DG(WS, i))              \
    PREF(ea, E / 4, (i > 0 ? DG(WE, 0) : 0) + (i > 1 ? DG(WE, 1) : 0), DG(WE, i))
#define PFN (DG(WX, 0) + DG(WX, 1) + DG(WX, 2))
#define PFE (DG(WE, 0) + DG(WE, 1) + DG(WE, 2))
__global__ void __launch_bounds__(NT, 1)
main_kernel(const int* __restrict__ dst, const int* __restrict__ src, uint4* __restrict__ gbin, int E, int nbins, int fast_ok,
            int npb, unsigned npb_magic, int N, const __grid_constant__ CUtensorMap tme,
            const __grid_constant__ CUtensorMap tmx, const __grid_constant__ CUtensorMap tmw,
            const __grid_constant__ CUtensorMap tmo, const __nv_bfloat16* __restrict__ x,
            const __nv_bfloat16* __restrict__ sh, const __nv_bfloat16* __restrict__ ea,
            const __nv_bfloat16* __restrict__ cg, const __nv_bfloat16* __restrict__ wr,
            const __nv_bfloat16* __restrict__ wout, __nv_bfloat16* __restrict__ out, int tau16, int toff, int delay,
            int tau2, int brk) {
    extern __shared__ __align__(1024) unsigned char smem[];
    const uint32_t sb = __shfl_sync(0xffffffffu, s2u(smem), 0);
    const int tid = threadIdx.x;
    const int warp = __shfl_sync(0xffffffffu, tid >> 5, 0), lane = tid & 31;
    const int g = lane >> 2, t = lane & 3;

    TLSTAMP(0);
    TLINIT();
    const int bin = blockIdx.x;
    const int node0 = bin * npb, hpb = npb >> 1;
    uint32_t wa[8];
    uint2 c0 = make_uint2(0, 0), c1 = c0;
    bool fast = fast_ok;
    if (fast_ok) {
        int pd[EPS], ps[EPS];
        const int e0 = ((tid >> 5) * nbins + bin) * 32 + lane;
#pragma unroll
        for (int k = 0; k < EPS; k++)
            asm volatile("ld.global.nc.u32 %0, [%1];" : "=r"(pd[k]) : "l"(dst + min(e0 + k * NT * nbins, E - 1)));
#pragma unroll
        for (int k = 0; k < EPS; k++)
            asm volatile("ld.global.nc.u32 %0, [%1];" : "=r"(ps[k]) : "l"(src + min(e0 + k * NT * nbins, E - 1)));
        const unsigned ck0 = clock();
        const uint32_t cnt0 = (sb + SC_CNT + 8191) & ~8191;
        {
            const int ch = (SW ? tid ^ tid >> 3 : tid) & 7;
            const uint32_t nul = NULW + ((bin & 3) * 8 + ch) * (80 << 15);
#pragma unroll
            for (int k = 0; k < 4; k++) {
                const int i = tid + k * NT;
                if (i < SC_EXT / 16 ? ch != 7 : i < SC_TAB / 16) sts_v4(sb + SC_ENT + i * 16, make_uint4(nul, nul, nul, nul));
            }
            if (warp == NW - 1) {
                uint32_t now;
                asm volatile("mov.u32 %0, %%globaltimer_lo;" : "=r"(now));
                now = __shfl_sync(0xffffffffu, (now & 0x7ffff) | nul, SW ? 7 ^ (NW - 1) * 4 % 8 : 7);
#pragma unroll
                for (int k = 0; k < MAXBINS / 32; k++) sts_v4(sb + SC_ENT + (k * 32 + lane) * 128 + (SW ? (~lane & 7) * 16 : 112), make_uint4(now, now, now, MS ? ~0u : now));
                if (lane == 0) {
                    asm volatile("prefetch.tensormap [%0];" ::"l"(&tme) : "memory");
                    asm volatile("prefetch.tensormap [%0];" ::"l"(&tmx) : "memory");
                    asm volatile("prefetch.tensormap [%0];" ::"l"(&tmw) : "memory");
                    asm volatile("prefetch.tensormap [%0];" ::"l"(&tmo) : "memory");
                    sts_v2(sb + SM_MISC + MI_INT, 0, now);
                    sts_u32(sb + SM_MISC + MI_INT + 44, 0);
                    sts_u32(sb + SM_MISC + MI_INT + 24, 0);
                }
            }
            sts_v4(cnt0 + tid * 16, make_uint4(0, 0, 0, 0));
            if (tid < (SC_END - SC_HIST) / 16) {
                const uint32_t v = (tid >> 3) == MAXBINS / 32 ? 0x80000000u : 0;
                sts_v4(sb + SC_HIST + tid * 16, make_uint4(v, v, v, v));
            }
            if (tid < 2 * HPB) {
                const int w = tid >= hpb, loc = tid - (w ? hpb : 0), gr = min(loc * 43 >> 8, NGR - 1);
                sts_u32(sb + SC_TAB + tid * 4, ((w ? NGR : 0) + gr) * (KEYW << 15) + loc - gr * GSZ);
            }
        }
        if (elect()) {
#pragma unroll
            for (int k = 0; k < (NP > 5 || XR ? 4 : 2); k++) mbar_init(sb + SM_BAR + (warp * (NP > 5 || XR ? 4 : 2) + k) * 8, 3 + (k & 1));
        }
#pragma unroll
        for (int k = 0; k < TS / 2; k++) sts_v4(sb + SM_BT + (tid + k * NT) * 16, make_uint4(0, 0, 0, 0));
        if (tid < 8) sts_v4(sb + SM_BT + (tid + TS / 2 * NT) * 16, make_uint4(0, 0, 0, 0));
        if (tid < 4) {
            sts_u16(sb + SM_SRC + (LNUL + tid) * 2, N + NGR * KEYW);
            sts_u32(sb + SM_EID + (LNUL + tid) * 4, 0x80000000u);
        }
        TLS(1);
        __syncthreads();
        {
            const uint32_t z = lds_u32(sb + SM_MISC + MI_INT);
            int pb[EPS], pr[EPS];
            uint32_t v[EPS];
#pragma unroll
            for (int k = 0; k < EPS; k++) {
                pb[k] = (int)__umulhi((unsigned)pd[k], npb_magic + z);
                v[k] = lds_u32(sb + SC_TAB + (pd[k] - pb[k] * npb) * 4);
                pr[k] = atoms_add(sb + SC_HIST + (e0 + k * NT * nbins < E ? pb[k] : MAXBINS + lane) * 4, 4);
            }
            int mx = 0;
#pragma unroll
            for (int k = 0; k < EPS; k++) {
                v[k] += ps[k] * (32768 + z) + (k * NT + tid + 32) * 8;
                asm volatile("{\n.reg .pred p;\nsetp.lt.u32 p, %0, " STR(LW) ";\n@p st.shared.u32 [%1], %2;\n}" ::"r"(pr[k]),
                             "r"(SW ? (sb + SC_ENT + pb[k] * 128 + (pb[k] & 7) * 16) ^ pr[k] : sb + SC_ENT + pb[k] * 128 + pr[k]), "r"(v[k])
                             : "memory");
                mx = max(mx, pr[k]);
            }
            if (mx >= LW) {
#pragma unroll
                for (int k = 0; k < EPS; k++)
                    if (pr[k] >= LW && pr[k] < LW + 64) {
                        sts_u32(sb + SC_EXT + pb[k] * 64 + (MS ? (pr[k] - LW & 28) * 2 + (pr[k] - LW >> 5) * 4 : pr[k] - LW), v[k]);
                    }
            }
        }
        TLS(6);
        __syncthreads();
        const unsigned c6 = DREF ? ck0 : clock();
        if (warp == NW - 1 && elect()) {
            FENCE_ASYNC();
            tma_store(&tme, sb + SC_ENT, bin * 32, 0);
            asm volatile("cp.async.bulk.commit_group;" ::: "memory");
        }
        if (tid < nbins && lds_u32(sb + SC_HIST + tid * 4) >= 128) {
#pragma unroll 1
            for (int k = 0; k < 4; k++) __stcg(gbin + GEX + (tid * nbins + bin) * 4 + k, lds_v4(sb + SC_EXT + tid * 64 + k * 16));
        }
#pragma unroll
        for (int k = 0; k < EPS; k++) {
            if (ps[k] < (N * PFT >> 10)) {
                const uint32_t p = atoms_add(sb + SM_MISC + MI_INT + 24, 4);
                if (p < PFC * 512) sts_u32(sb + SM_EA + p, min(e0 + k * NT * nbins, E - 1));
            }
        }
        if (warp >= 2 * NGR) {
            uint2 wv[4];
#pragma unroll
            for (int k = 0; k < 4; k++)
                asm volatile("ld.global.nc.v2.u32 {%0,%1}, [%2];" : "=r"(wv[k].x), "=r"(wv[k].y) : "l"((const uint2*)wr + (tid - NB) + k * 128));
#pragma unroll
            for (int k = 0; k < 4; k++) sts_v2(sb + SC_WR + (lane >> 1) * 272 + (warp - 2 * NGR + k * 4) * 16 + (lane & 1) * 8, wv[k].x, wv[k].y);
            PREW(0);
            const int w = warp & 1, j = (warp >> 1) & 1;
            const uint32_t bar0 = sb + SM_BAR + w * NP * 16, ring = sb + w * RING_BYTES + j * 4096;
            uint32_t pz[8], pm[8], pt[2];
            const uint32_t lz = lane & (E >> 31);
            {
                const uint32_t d0 = ring - j * 2048 - bar0 * 512 + lz;
#pragma unroll
                for (int k = 0; k < 8; k++) {
                    pz[k] = __shfl_sync(0xffffffffu, lz, k);
                    pm[k] = __shfl_sync(0xffffffffu, d0 + (k & 1) * SM_ODD + (k >> 1 & 1) * 1024 + (k >> 2) * 4096, 0);
                }
                asm("mov.b64 {%0, %1}, %2;" : "=r"(pt[0]), "=r"(pt[1]) : "l"(&tmx));
                pt[0] = __shfl_sync(0xffffffffu, pt[0] + lz, 0);
                pt[1] = __shfl_sync(0xffffffffu, pt[1] + lz, 0);
            }
            uint32_t sg0 = 0x01010101 | ((lane & 1) << 8 | (lane & 2) << 15 | (lane & 4) << 22) * 0xfe;
            uint32_t sg2 = (0x0101 | ((lane >> 3 & 1) | (lane & 16) << 4) * 0xfe) * 0x10001 ^ 0xfefe0000;
            uint32_t cand = ((lane & 1) << 3 | (lane & 2) << 5 | (lane & 4) << 7 | (lane & 8) << 9) * 7 + (lane & 16) * (15 << 11);
            uint32_t sg1 = __shfl_sync(0xffffffffu, sg0 ^ 0xfefefefe, lane), gb = cnt0 + (warp & 2) * NBK + lane * 8;
            sg0 = __shfl_sync(0xffffffffu, sg0, lane), sg2 = __shfl_sync(0xffffffffu, sg2, lane);
            cand = __shfl_sync(0xffffffffu, cand, lane), gb = __shfl_sync(0xffffffffu, gb, lane);
            const uint32_t wm = __shfl_sync(0xffffffffu, lz - w, lane);
            FENCE_ASYNC();
            asm volatile("bar.sync 8, %0;" ::"n"(NT) : "memory");
            while ((int)(clock() - c6) < (PFA ? PFA : delay + PFX)) {}
            {
                const uint32_t n = lds_u32(sb + SM_MISC + MI_INT + 24);
#pragma unroll
                for (int k = 0; k < PFC; k++) {
                    const uint32_t i = (tid - NB + k * 128) * 4, e = lds_u32(sb + SM_EA + i);
                    if (i < n) {
                        asm volatile("prefetch.global.L2 [%0];" ::"l"(ea + (size_t)e * 16) : "memory");
                        asm volatile("prefetch.global.L2 [%0];" ::"l"(sh + (size_t)e * 4) : "memory");
                    }
                }
            }
            SYNC();
            PREW(1);
            if (warp == NW - 1 && elect()) {
                asm volatile("cp.async.bulk.global.shared::cta.bulk_group [%0], [%1], %2;" ::"l"(gbin + bin * nbins * 8), "r"(sb + SM_BT),
                             "r"(nbins * 128)
                             : "memory");
                asm volatile("cp.async.bulk.commit_group;" ::: "memory");
                const uint32_t t0 = lds_u32(sb + SM_MISC + MI_INT + 4);
                uint32_t now, ck;
                asm volatile(
                    "{\n.reg .pred p;\n.reg .b32 a, n;\nmov.u32 a, %%globaltimer_lo;\nmov.u32 n, 0;\n"
                    "TK:\nmov.u32 %0, %%globaltimer_lo;\nmov.u32 %1, %%clock;\nadd.u32 n, n, 1;\n"
                    "setp.lt.u32 p, n, " STR(TB) ";\nsetp.eq.and.u32 p, %0, a, p;\n@p bra TK;\n}"
                    : "=r"(now), "=r"(ck));
                sts_u32(sb + SM_MISC + MI_INT + 4, ck - (min((now - t0) & 0x7ffff, 1u << 16) * 63 >> 5) + toff);
            }
            asm volatile("bar.sync 5, %0;" ::"n"(NT) : "memory");
            const uint4 nb = lds_v4(sb + SM_MISC + MI_INT + 32);
            const unsigned tbase = lds_u32(sb + SM_MISC + MI_INT + 4) - w * STG;
            fast = nb.w == 0;
            int df;
            asm("{\n.reg .s32 a;\ndp4a.u32.s32 a, %1, %4, " STR(-(BIAS)) ";\ndp4a.u32.s32 a, %2, %5, a;\ndp4a.u32.s32 %0, %3, %6, a;\n}"
                : "=r"(df)
                : "r"(nb.x), "r"(nb.y), "r"(nb.z), "r"(sg0), "r"(sg1), "r"(sg2));
            const uint32_t best = __reduce_min_sync(0xffffffffu, abs(df) << (NJ + 1) | (df < 0) << NJ | cand);
            uint32_t swp = best ^ -w;
            uint32_t ga[NGR];
#pragma unroll
            for (int k = 0; k < NGR; k++) {
                const int sh = k < 4 ? 3 * k : 3 * k - 9;
                ga[k] = gb + (((k < 4 ? best : best >> 9) ^ wm) & 1 << sh) * (NGR * NBK * 4 >> sh);
            }
            asm volatile("bar.sync %0, %1;" ::"r"(6 + (ga[0] & ga[1] & ga[2] & ga[3] & ga[4] & ga[5] & lz)), "n"(NT) : "memory");
            TLA(1, 0);
            if (fast) {
                uint32_t v[NGR][2], mx = 0;
#pragma unroll
                for (int k = 0; k < NGR; k++) {
                    const uint2 u = lds_v2(ga[k] + k * (NBK * 4));
                    v[k][0] = u.x, v[k][1] = u.y;
                }
                const uint32_t sq = sb + SM_SEQ + w * SEQCAP * 2;
                const int all = __dp4a(nb.x, 0x01010101u, __dp4a(nb.y, 0x01010101u, __dp4a(nb.z, 0x01010101u, 0u))), d = best >> (NJ + 1);
                const int nst = (all + ((swp >> NJ) & 1 ? -d : d) + (BIAS ? (BIAS ^ -w) + w : 0)) >> 1;
                const int npr = __shfl_sync(0xffffffffu, (nst + 3) >> 2, 0), k0 = K0(npr);
                const unsigned taug = __float2uint_rz(__fdividef((float)(N * tau16 >> 4), (float)max(npr, 1)));
                const uint32_t lim = tbase + (N * tau16 >> 8) + lane * taug;
                uint32_t a = -(__popc(swp & 0111111) * (NGR * GCAP + GEXT) + NGR * (NGR - 1) / 2 * GCAP + NGR * 4) + 2 * sq;
#pragma unroll
                for (int k = 0; k < NGR; k++) a += v[k][0] & 0xffc;
                a >>= 1;
                const uint32_t a0 = a;
#pragma unroll
                for (int c = 0; c < 2; c++)
#pragma unroll
                    for (int k = 0; k < NGR; k++) {
                        asm volatile(
                            "{\n.reg .pred p, q;\n.reg .b16 h;\n"
                            "setp.ge.u32 p, %1, 0x10000;\nsetp.ge.u32 q, %1, 0x40000;\n"
                            "cvt.u16.u32 h, %1;\n@p st.shared.u16 [%0], h;\n"
                            "add.u16 h, h, 4;\n@q st.shared.u16 [%0+2], h;\n}" ::"r"(a), "r"(v[k][c])
                            : "memory");
                        a += v[k][c] >> 16;
                        mx = max(mx, v[k][c]);
                    }
                if (mx >= 0x60000) {
                    a = a0;
#pragma unroll
                    for (int c = 0; c < 2; c++)
#pragma unroll
                        for (int k = 0; k < NGR; k++) {
#pragma unroll 1
                            for (uint32_t n = 4; n < v[k][c] >> 16; n += 2) sts_u16(a + n, v[k][c] + 2 * n);
                            a += v[k][c] >> 16;
                        }
                }
                if (!j) {
                    sts_u16(sq + (nst + lane) * 2, (LNUL + 4) | (lane < (-nst & 3) ? GCODE(0) : 0x7c01));
                    if (lane < k0) {
                        mbar_arrive_cnt(sb + SM_BAR + (w * NP + lane) * 16, 3);
                        mbar_arrive_cnt(sb + SM_BAR + (w * NP + lane) * 16 + 8, 4);
                        if (XR) mbar_arrive_cnt(sb + SM_BAR + (w * NP + lane) * 16 + 264, 4);
                    }
                    if (lane == 0) {
                        sts_v2(sb + SM_MISC + MI_INT + 8 + w * 8, npr, k0);
                        sts_u32(sb + SM_MISC + MI_INT + 48 + w * 4, swp);
                    }
                }
                TLA(10, 0);
                asm volatile("cp.async.bulk.wait_group.read 0;" ::: "memory");
                asm volatile("bar.arrive 3, %0;" ::"n"(NT) : "memory");
                PREW(2);
                TLS(5);
                FENCE_ASYNC();
                asm volatile("setmaxnreg.dec.sync.aligned.u32 %0;" ::"n"(PREG));
                produce(pt, pz, pm, bar0, sq + j * 2 + lane * 8, npr, sb + SM_SRC - 8, tbase, lim, taug * 32, tau16, k0 + lane, k0 + 32, tau2 - w * ES, brk + w * ES * (N * EB / 50)
                );
        if (elect()) {
            const uint32_t d = ring + (NP - 2) * 8192 + j * (SM_ODD - 4096);
            const uint32_t fb = bar0 + (NP - 2) * 16, par = ~((lds_u32(sb + SM_MISC + MI_INT + 8 + w * 8) + 1) / NP) & 1;
            mbar_wait(fb + 24, par);
            mbar_arrive_cnt(fb + j * 16, j ? 1 : 3);
            mbar_expect_tx(fb + 16, 8192);
            tma_2d(d, &tmw, fb + 16, HALF(w), j * 64);
            if (j) mbar_arrive(bar0 + DUMB);
            mbar_expect_tx(bar0 + DUMB, 8192);
            tma_2d(d + 8192, &tmw, bar0 + DUMB, 64 - HALF(w), j * 64);
        }
        TLMAX(12);
        swp = lds_u32(sb + SM_MISC + MI_INT + 48 + w * 4);
        const int row = 2 * lane < hpb ? (node0 + ((swp >> lane) & 1) * hpb) * 4 + lane * 8 : N * 4;
        const CUtensorMap* po = &tmo;
        asm volatile("" : "+l"(po));
#pragma unroll
        for (int st = 0; st < 5; st++) {
            int rw[5];
#pragma unroll
            for (int k = 0; k < 5; k++)
                if (2 * k < out_n(st)) rw[k] = __shfl_sync(0xffffffffu, row, out_j(st) + 2 * k + (2 * k + 1 < out_n(st) ? j : j * (31 - out_j(st) - 2 * k)));
            asm volatile("bar.sync %0, 192;" ::"r"(6 + 2 * st + w) : "memory");
            if (!(EF >> st & 1)) FENCE_ASYNC();
            if (elect()) {
#pragma unroll
                for (int k = 0; k < 5; k++)
                    if (2 * k < out_n(st)) tma_store(po, ring - j * 3072 + out_at(st) + k * 2048, st < 3 ? HALF(w) : 64 - HALF(w), rw[k]);
                asm volatile("cp.async.bulk.commit_group;" ::: "memory");
            }
        }
        asm volatile("cp.async.bulk.wait_group.read 0;" ::: "memory");
        TLMAX(4);
        TLEND();
        return;
            }
        } else {
        asm volatile("bar.arrive 8, %0;" ::"n"(NT) : "memory");
        uint32_t en[5][4], es[5][4], rank[5][4], ca[5][4];
        if (warp >= 8 && (g >> 2) == (t >> 1)) {
            const uint2* cp = (const uint2*)cg + (g & 3) * 4 + (t & 1) * 2;
            asm volatile("ld.global.nc.v2.u32 {%0,%1}, [%2];" : "=r"(c0.x), "=r"(c0.y) : "l"(cp));
            asm volatile("ld.global.nc.v2.u32 {%0,%1}, [%2];" : "=r"(c1.x), "=r"(c1.y) : "l"(cp + 1));
        }
        const int sg[5] = {tid >> 3, (tid >> 3) + NB / 8, (tid >> 3) + NB / 4, (tid >> 3) + (lane & 4) * (NB / 32), (tid >> 3) + NB / 4};
        const uint4* gp[5];
        gp[0] = gbin + bin * nbins * 8 + tid;
        gp[1] = gp[0] + NB;
        gp[2] = gp[0] + 2 * NB;
        gp[3] = gbin + GEX + (bin * nbins + sg[3]) * 4 + (lane & 3);
        gp[4] = gbin + GEX + (bin * nbins + sg[4]) * 4 + (lane & 3);
        unsigned pend = (sg[0] < nbins) | (sg[1] < nbins) << 1 | (sg[2] < nbins) << 2;
#pragma unroll
        for (int k = 0; k < 5; k++) en[k][0] = en[k][1] = en[k][2] = en[k][3] = NULW + lane * (80 << 15);
        auto fetch = [&](int k) {
            asm volatile("{\n.reg .pred p;\nsetp.ne.u32 p, %5, 0;\n@p ld.relaxed.gpu.global.v4.u32 {%0,%1,%2,%3}, [%4];\n}"
                         : "+r"(en[k][0]), "+r"(en[k][1]), "+r"(en[k][2]), "+r"(en[k][3])
                         : "l"(gp[k]), "r"(pend & (1u << k))
                         : "memory");
        };
        int spin = 0;
        auto poll = [&](int k0, int k1) {
            for (;;) {
#pragma unroll
                for (int k = k0; k < k1; k++)
                    if (min(min(en[k][0], en[k][1]), min(en[k][2], en[k][3]))) pend &= ~(1u << k);
                if (!__any_sync(0xffffffffu, PV ? pend & ((1u << k1) - 1) : pend)) break;
#pragma unroll
                for (int k = k0; k < k1; k++) fetch(k);
                if (++spin > 10000000) __trap();
            }
        };
        auto count = [&](int k) {
#pragma unroll
            for (int c = 0; c < 4; c++) {
                const uint32_t v = en[k][c];
                ca[k][c] = (__umulhi(v, 6554) & 0x1ffc) | cnt0;
                rank[k][c] = atoms_add(ca[k][c], 1);
                asm volatile("{\n.reg .b32 a, b;\nprmt.b32 a, %1, %2, 0x6540;\nand.b32 b, %1, 0x7f00;\nmad.lo.u32 %0, b, %3, a;\n}"
                             : "=r"(es[k][c])
                             : "r"(v), "r"(sg[k] - nbins), "r"(nbins));
            }
        };
        while ((int)(clock() - c6) < delay) {}
        TLS(7);
        fetch(0);
        fetch(1);
        fetch(2);
        poll(0, 3);
        TLS(2);
        const bool more = __any_sync(0xffffffffu, (lane & 7) == 7 && min(min(en[0][3], en[1][3]), en[2][3]) < NULW);
        const bool rest = NB / 4 + warp * 4 < nbins;
        if (more) {
            const uint32_t l0 = __shfl_sync(0xffffffffu, en[0][3], lane | 7), l1 = __shfl_sync(0xffffffffu, en[1][3], lane | 7);
            const uint32_t l2 = __shfl_sync(0xffffffffu, en[2][3], lane | 7);
            pend = ((lane & 4 ? l1 : l0) < NULW) << 3 | (!(lane & 4) && l2 < NULW) << 4;
            fetch(3);
            fetch(4);
        }
        if (tid == 7 && en[0][3 - MS] >= NULW) sts_u32(sb + SM_MISC + MI_INT + 4, en[0][3 - MS]);
        count(0);
        count(1);
        if (rest) count(2);
        if (more) {
            const unsigned ext = pend;
            poll(3, 5);
#pragma unroll
            for (int k = 3; k < 5; k++) {
                if ((ext >> k) & 1) {
                    __stcg((uint4*)gp[k], make_uint4(0, 0, 0, 0));
                    if ((lane & 3) == 3 && en[k][3] < NULW) sts_u32(sb + SM_MISC + MI_INT + 44, 1);
                }
            }
            count(3);
            count(4);
        }
        TLS(9);
        SYNC();
        {
            const int w0 = warp >= NGR, gr = warp - w0 * NGR;
            const uint32_t cp = cnt0 + (warp * NBK + lane * (NBK / 32)) * 4;
            uint32_t r[5];
            const uint4 cv = lds_v4(cp);
            r[0] = 0, r[1] = cv.x, r[2] = cv.x + cv.y, r[3] = r[2] + cv.z, r[4] = r[3] + cv.w;
            const uint32_t tot = __reduce_add_sync(0xffffffffu, r[NBK / 32]);
            const uint32_t base = warp * GCAP + w0 * GEXT;
            const bool full = tot > GCAP + (gr == NGR - 1 ? GEXT : 0);
            asm volatile("st.shared.u8 [%0], %1;" ::"r"(sb + SM_MISC + MI_INT + 32 + (full ? 12 : (gr < 4 ? w0 * 4 : 4 + w0 * 2) + gr)), "r"(full ? 1 : (tot + 3) >> 2) : "memory");
            asm volatile("bar.arrive 5, %0;" ::"n"(NT) : "memory");
            const uint32_t off = warp_incl_scan(r[NBK / 32], lane, lds_u32(sb + SM_MISC + MI_INT)) - r[NBK / 32] + base + 7 - CE + GCODE(gr);
            if (lane == 31) r[NBK / 32] += CE;
#pragma unroll
            for (int c = 0; c <= NBK / 32; c++) r[c] += off;
#pragma unroll
            for (int c = 0; c < NBK / 32; c++) r[c] += ((r[c + 1] & ~3) - (r[c] & ~3)) << 15;
            sts_v4(cp, make_uint4(r[0], r[1], r[2], r[3]));
            asm volatile("{\n.reg .pred p;\n.reg .b16 h;\nsetp.lt.u32 p, %0, %1;\ncvt.u16.u32 h, %3;\n@p st.shared.u16 [%2], h;\n@p st.shared.u32 [%4], 0x80000000;\n}" ::"r"(lane),
                         "r"(full ? 0 : -tot & 3), "r"(sb + SM_SRC + (base + tot + lane) * 2), "r"(N + warp * KEYW), "r"(sb + SM_EID + (base + tot + lane) * 4)
                         : "memory");
        }
        TLS(10);
        asm volatile("bar.arrive 6, %0;" ::"n"(NT) : "memory");
#pragma unroll
        for (int h = 0; h < 2; h++)
            asm volatile("ldmatrix.sync.aligned.m8n8.x4.trans.shared.b16 {%0,%1,%2,%3}, [%4];"
                         : "=r"(wa[h * 4]), "=r"(wa[h * 4 + 1]), "=r"(wa[h * 4 + 2]), "=r"(wa[h * 4 + 3])
                         : "r"(sb + SC_WR + (h * 8 + (warp & 3) * 2 + ((lane >> 3) & 1)) * 272 + (lane >> 4) * 128 + (lane & 7) * 16));
        asm volatile("bar.sync 7, %0;" ::"n"(NB) : "memory");
        auto place0 = [&](int k, int nc = 4) {
#pragma unroll
            for (int c = 0; c < nc; c++)
                asm volatile("{\n.reg .pred p;\nsetp.lt.u32 p, %1, " STR(NULW) ";\n@p ld.shared.u16 %0, [%0];\n}" : "+r"(ca[k][c]) : "r"(en[k][c]));
#pragma unroll
            for (int c = 0; c < nc; c++) ca[k][c] = (ca[k][c] & 0xfff) + rank[k][c];
        };
        auto place1 = [&](int k, int nc = 4) {
#pragma unroll
            for (int c = 0; c < nc; c++)
                asm volatile(
                    "{\n.reg .pred p;\n.reg .b32 t;\n.reg .b16 h;\n"
                    "setp.lt.u32 p, %0, " STR(NULW) ";\n"
                    "shr.u32 t, %0, 15;\ncvt.u16.u32 h, t;\n"
                    "@p st.shared.u16 [%1], h;\n}" ::"r"(en[k][c]),
                    "r"(sb + SM_SRC - (7 - CE) * 2 + ca[k][c] * 2)
                    : "memory");
        };
        auto place2 = [&](int k, int nc = 4) {
#pragma unroll
            for (int c = 0; c < nc; c++)
                asm volatile("{\n.reg .pred p;\nsetp.lt.u32 p, %0, " STR(NULW) ";\n@p st.shared.u32 [%1], %2;\n}" ::"r"(en[k][c]),
                             "r"(sb + SM_EID - (7 - CE) * 4 + ca[k][c] * 4), "r"(es[k][c])
                             : "memory");
        };
        auto all = [&](auto f) {
            f(0);
            f(1);
            if (rest) f(2);
            if (more) f(3), f(4);
        };
        fast = lds_u32(sb + SM_MISC + MI_INT + 44) == 0;
        if (fast) {
            all([&](int k) { place0(k), place1(k); });
            TLS(14);
            TLA(14, 0);
            LISTS();
            all([&](int k) { place2(k); });
            if (warp < 8) asm volatile("bar.arrive 3, %0;" ::"n"(NT) : "memory");
        }
        }
    }

    if (fast && (warp >> 2) == 2) {
        asm volatile("setmaxnreg.dec.sync.aligned.u32 %0;" ::"n"(HREG));
        const int w = warp & 1, j = (warp >> 1) & 1;
        const uint32_t bar0 = sb + SM_BAR + w * NP * 16;
        const int blk = (lane >> 4) * 2 + (t >> 1);
        uint32_t fseq = sb + SM_SEQ + w * SEQCAP * 2 + j * 8 + blk * 2;
        const uint32_t feid = sb + SM_EID - 16 + (g & 3) * 4;
        uint32_t pea = sb + SM_EA + w * 4096 + j * 512 + (lane ^ ((lane >> 3) & 1)) * 16;
        const uint32_t psd = sb + SM_SIDE + (warp - 8) * 512 + (lane >> 1) * 16 + (lane & 1) * 4;
        const uint32_t pt = sb + SM_BT + w * (TS * 256) + j * 512 + blk * BT_B + ((lane ^ (lane >> 3)) & 1) * BT_K + (g & 3) * 4;
        const char* gea = (const char*)ea + (lane & 1) * 16;
        uint32_t es, va[2], ta[2], old[2] = {pt, pt}, dea = 2048;
        auto ids = [&]() {
            es = lds_u32(feid + (lds_u16(fseq) & 0xffc) * 4);
            fseq += 16;
        };
        uint32_t wf[4];
        wf[0] = __byte_perm(c0.x, c1.x, 0x5410), wf[1] = __byte_perm(c0.x, c1.x, 0x7632);
        wf[2] = __byte_perm(c0.y, c1.y, 0x5410), wf[3] = __byte_perm(c0.y, c1.y, 0x7632);
        int pfl = lane < PL ? PFN * nbins * 128 + (bin * 4 + warp - 8) * PL + lane - N * 8 : 0;
        int pfs = nbins * (4 * PL);
        const char* pfb = (const char*)(x + (size_t)N * 512);
        auto run = [&](auto odd) {
            auto fetch = [&](int i, int mm = 1000) {
                asm volatile(
                    "{\n.reg .pred p, q;\n.reg .b32 e;\n.reg .b64 a;\n"
                    "setp.lt.s32 p, %0, 0;\n"
                    "and.b32 e, %0, 0x7ffffff8;\n"
                    "mad.wide.u32 a, e, 4, %1;\n"
                    "cp.async.cg.shared.global [%2], [a], 16, p;\n"
                    "}" ::"r"(es), "l"(gea), "r"(pea + i * 1024) : "memory");
                va[i] = psd + (es & 8);
                ta[i] = pt + (es & 7) * 64;
                if (odd.value) {
                    cp_async4(va[i] + i * 256, (const char*)sh + (es & 0x7ffffff8) + (lane & 1) * 4, (int)es >= 0 ? 4 : 0);
                } else {
                    asm volatile(
                        "{\n.reg .pred p;\n.reg .b32 e;\n.reg .b64 a;\n"
                        "setp.lt.s32 p, %0, 0;\n"
                        "and.b32 e, %0, 0x7ffffff0;\n"
                        "mad.wide.u32 a, e, 1, %1;\n"
                        "cp.async.cg.shared.global [%2], [a], 16, p;\n"
                        "}" ::"r"(es), "l"(sh), "r"((psd & ~15) + i * 256), "r"(mm) : "memory");
                }
                asm volatile("cp.async.commit_group;" ::: "memory");
                if (i) pea += dea, dea = -dea;
            };
            asm volatile("bar.sync 3, %0;" ::"n"(NT) : "memory");
            TLA(7, 0);
            const uint2 nk = lds_v2(sb + SM_MISC + MI_INT + 8 + w * 8);
            ids();
            fetch(0);
            ids();
            fetch(1);
            const int npr = __shfl_sync(0xffffffffu, nk.x, 0), kj = __shfl_sync(0xffffffffu, nk.y, 0) + j;
        uint32_t vf = bar0 + (kj < NP ? kj : 0) * 16;
        uint32_t pe = kj < NP;
#pragma unroll 1
            for (int m = (npr + 1 - j) >> 1; m > 0;) {
#pragma unroll
                for (int i = 0; i < 2; i++) {
                    asm volatile("cp.async.wait_group 1;" ::: "memory");
                    __syncwarp();
                    const uint32_t v = lds_u32(va[i] + i * 256);
                    ids();
                    float d0[4], d1[4];
                    mma_diag(d0, v, wf[0], wf[1]);
                    mma_diag(d1, v, wf[2], wf[3]);
                    uint32_t vn = vf + 32;
                    if (vn >= bar0 + NP * 16) vn -= NP * 16, pe ^= 1;
                    TWAIT(vn + 8, pe);
#pragma unroll
                    for (int k = 0; k < 4; k++) sts_u32(old[i] + i * 1024 + k * 16, 0);
                    old[i] = ta[i];
                    sts_u32(old[i] + i * 1024, pack_bf16(d0[0], d0[1]));
                    sts_u32(old[i] + i * 1024 + 16, pack_bf16(d0[2], d0[3]));
                    sts_u32(old[i] + i * 1024 + 32, pack_bf16(d1[0], d1[1]));
                    sts_u32(old[i] + i * 1024 + 48, pack_bf16(d1[2], d1[3]));
                    FENCE_ASYNC();
                    fetch(i, m);
                    __syncwarp();
                    if (lane == 0) mbar_arrive(vf);
                    asm volatile("{\n.reg .pred p;\n.reg .b64 a;\nsetp.lt.s32 p, %0, 0;\nmad.wide.s32 a, %0, 128, %1;\n@p prefetch.global.L2 [a];\n}" ::"r"(pfl),
                                 "l"(pfb));
                    pfl += pfs;
                    vf = vn;
                    if (--m <= 0) break;
                }
            }
        };
        if (E & 1) run(std::true_type()); else run(std::false_type());
        asm volatile("cp.async.wait_group 0;" ::: "memory");
        TLMAX(13);
    } else if (fast) {
        const int w = warp >> 2, wq = warp & 3;
        asm volatile("setmaxnreg.inc.sync.aligned.u32 %0;" ::"n"(CREG));
        const int k0 = __shfl_sync(0xffffffffu, lds_u32(sb + SM_MISC + MI_INT + 12 + w * 8), 0);
        const uint32_t ring = sb + w * RING_BYTES, bar0 = sb + SM_BAR + w * NP * 16;
        float acc[2][NJ][4];
        uint32_t a0[8][4], a1[8][4];
        {
            const int e = (lane >> 1) & 3, m = lane >> 3;
            const int line = 2 * ((lane & 1) + 2 * ((m >> 1) ^ (e >> 1))), ch = 2 * wq + (m & 1);
            const uint32_t xb = ring + (e & 1 ? SM_ODD : SM_EVEN) + (e >> 1) * 1024 + line * 128;
            consume(acc, a0, ring, xb + ((ch ^ ((line + (e & 1)) & 7)) * 16), xb + 128 + ((ch ^ ((line + 1 + (e & 1)) & 7)) * 16),
                    k0 * 8192, bar0, (((sb + SM_EA + w * 4096) & 0x3ffff) >> 4) | (1 << 16),
                    (((sb + SM_BT + w * (TS * 256)) & 0x3ffff) >> 4) | (BT_K / 16 << 16), sb + SM_SEQ + w * SEQCAP * 2, lane & (E >> 31),
                    wa);
        }
        const uint32_t tb = ring + wq * (NJ * 256) + lane * 16, db = (ring >> 4) + (8 << 16);
        const uint32_t cr = ring + (lane & 7) * 128 + (lane >> 4) * 1024, cc = 2 * wq + ((lane >> 3) & 1);
        const uint32_t ce = cr + (cc ^ (lane & 7)) * 16, co = cr + (cc ^ ((lane + 1) & 7)) * 16;
        float o0[CH0][4], o1[CH1][4], o2[CH2][4], o3[CH3][4], o4[CH4][4];
        TLMAX(11);
#pragma unroll
        for (int u = 0; u <= CH0; u++) put_agg<0, CH0>(acc, tb, u);
        TLE(1);
        FENCE_ASYNC();
        WG_SYNC(w);
        TLE(6);
        mul_out<0>(o0, a0, db, [&](int u) { put_agg<CH0, CH1>(acc, tb, u); });
        const bool ok1 = mbar_test(bar0 + DUMB, 0);
        FENCE_ASYNC();
        WG_SYNC(w);
        TLE(7);
        mul_out<KA>(o1, a0, db + CH0 * 16, [&](int u) {
            if (u == 0) {
                TLE(2);
#pragma unroll
                for (int k = 0; 2 * k < CH0; k++) put_out<0>(o0, ce, k, w);
                TLMAX(3);
            } else if (EO < 0 || u <= EO) {
                put_agg<CH0 + CH1, CH2>(acc, tb, 2 * u - 2);
                put_agg<CH0 + CH1, CH2>(acc, tb, 2 * u - 1);
            }
        });
        FENCE_ASYNC();
        if (!ok1) mbar_wait(bar0 + DUMB, 0);
        WG_SYNC(w);
        TLE(9);
        mul_out<KA>(o2, a0, db + (CH0 + CH1) * 16, [&](int u) {
            put_out<1>(o1, co, 2 * u, w);
            put_out<1>(o1, co, 2 * u + 1, w);
            if (u == 1) TLE(5);
            get_w(a1, ce + (NP - 1) * 8192, co + (NP - 1) * 8192, 2 * u - 4);
            get_w(a1, ce + (NP - 1) * 8192, co + (NP - 1) * 8192, 2 * u - 3);
        });
        mul_out<KA>(o3, a1, db, [&](int u) {
            if (u == 0) TLE(10);
            put_out<2>(o2, ce, u, w);
            if (u == 8 - KA) WG_SYNC(w);
        });
        mul_out<KA>(o4, a1, db + CH3 * 16, [&](int u) { put_out<3>(o3, co, u, w); });
        TLE(14);
        WG_WAIT(0);
#pragma unroll
        for (int u = 0; 2 * u < CH4; u++) put_out<4>(o4, ce, u, w);
        TLMAX(15);
    } else {
        float* accs = (float*)smem;
        constexpr int NACC = SM_EID / 2048;
        const int nnodes = max(0, min(npb, N - node0));
#pragma unroll 1
        for (int nb = 0; nb < nnodes; nb += NACC) {
            __syncthreads();
            for (int i = tid; i < NACC * 512; i += NT) accs[i] = 0.f;
            __syncthreads();
#pragma unroll 1
            for (int base = warp * 32; base < E; base += NT) {
                const int e = base + lane;
                int dl = e < E ? dst[e] - node0 - nb : -1;
                if (dl + nb >= nnodes) dl = -1;
                unsigned mask = __ballot_sync(0xffffffffu, dl >= 0 && dl < NACC);
#pragma unroll 1
                while (mask) {
                    const int l = __ffs(mask) - 1;
                    mask &= mask - 1;
                    const int ee = __shfl_sync(0xffffffffu, e, l);
                    const int dd = __shfl_sync(0xffffffffu, dl, l);
                    slow_edge(ee, src[ee], accs + dd * 512, x, sh, ea, cg, wr, lane);
                }
            }
            __syncthreads();
#pragma unroll 1
            for (int nl = warp; nl < NACC && nb + nl < nnodes; nl += NW)
                slow_out(accs + nl * 512, wout, out + (size_t)(node0 + nb + nl) * 512, lane);
        }
        __syncthreads();
    }

    TLMAX(4);
    TLEND();
}

typedef CUresult (*EncodeTiledFn)(CUtensorMap*, CUtensorMapDataType, cuuint32_t, void*, const cuuint64_t*,
                                  const cuuint64_t*, const cuuint32_t*, const cuuint32_t*, CUtensorMapInterleave,
                                  CUtensorMapSwizzle, CUtensorMapL2promotion, CUtensorMapFloatOOBfill);

extern "C" void kernel_launch(void* const* d_in, const int* in_sizes, int n_in, void* d_out, int out_size) {
    const __nv_bfloat16* x = (const __nv_bfloat16*)d_in[0];
    const int* src = (const int*)d_in[1];
    const int* dst = (const int*)d_in[2];
    const __nv_bfloat16* sh = (const __nv_bfloat16*)d_in[3];
    const __nv_bfloat16* ea = (const __nv_bfloat16*)d_in[4];
    const __nv_bfloat16* cg = (const __nv_bfloat16*)d_in[5];
    const __nv_bfloat16* wr = (const __nv_bfloat16*)d_in[6];
    const __nv_bfloat16* wout = (const __nv_bfloat16*)d_in[7];
    __nv_bfloat16* out = (__nv_bfloat16*)d_out;
    const int N = in_sizes[0] / 512;
    const int E = in_sizes[1];

    static int num_sms = 0;
    static EncodeTiledFn encode = nullptr;
    static uint4* gbin = nullptr;
    if (num_sms == 0) {
        int dev = 0;
        cudaGetDevice(&dev);
        cudaDeviceGetAttribute(&num_sms, cudaDevAttrMultiProcessorCount, dev);
        cudaFuncSetAttribute(main_kernel, cudaFuncAttributeMaxDynamicSharedMemorySize, SM_TOTAL + TLX);
        cudaGetSymbolAddress((void**)&gbin, g_bin);
        void* fn = nullptr;
        cudaDriverEntryPointQueryResult qr;
        cudaGetDriverEntryPoint("cuTensorMapEncodeTiled", &fn, cudaEnableDefault, &qr);
        encode = (EncodeTiledFn)fn;
    }
    const int nbins = num_sms < NB * 3 / 8 ? num_sms : NB * 3 / 8;
    int npb = ((N + nbins - 1) / nbins + 3) & ~3;
    if (npb < 32) npb = 32;
    const int fast_ok = E > 0 && npb <= 2 * HPB && N <= (NBK - 1) * 80 - 8 && E <= EPS * NT * nbins;
    auto map2d = [&](CUtensorMap* tm, const void* p, int d0, int d1, int b1) {
        const cuuint64_t gd[2] = {(cuuint64_t)d0, (cuuint64_t)d1};
        const cuuint64_t gs[1] = {(cuuint64_t)d0 * 2};
        const cuuint32_t bx[2] = {64, (cuuint32_t)b1};
        const cuuint32_t es[2] = {1, 1};
        encode(tm, CU_TENSOR_MAP_DATA_TYPE_BFLOAT16, 2, (void*)p, gd, gs, bx, es, CU_TENSOR_MAP_INTERLEAVE_NONE,
               CU_TENSOR_MAP_SWIZZLE_128B, CU_TENSOR_MAP_L2_PROMOTION_NONE, CU_TENSOR_MAP_FLOAT_OOB_FILL_NONE);
    };
    CUtensorMap tme, tmx, tmw, tmo;
    {
        const cuuint64_t gd[2] = {(cuuint64_t)nbins * 32, (cuuint64_t)nbins};
        const cuuint64_t gs[1] = {(cuuint64_t)nbins * 128};
        const cuuint32_t bx[2] = {32, (cuuint32_t)nbins};
        const cuuint32_t es[2] = {1, 1};
        encode(&tme, CU_TENSOR_MAP_DATA_TYPE_UINT32, 2, (void*)gbin, gd, gs, bx, es, CU_TENSOR_MAP_INTERLEAVE_NONE,
               SW ? CU_TENSOR_MAP_SWIZZLE_128B : CU_TENSOR_MAP_SWIZZLE_NONE, CU_TENSOR_MAP_L2_PROMOTION_NONE, CU_TENSOR_MAP_FLOAT_OOB_FILL_NONE);
    }
    {
        const cuuint64_t gd[2] = {(cuuint64_t)N * 256 - 224, 8};
        const cuuint64_t gs[1] = {128};
        const cuuint32_t bx[2] = {32, 8};
        const cuuint32_t es[2] = {1, 1};
        encode(&tmx, CU_TENSOR_MAP_DATA_TYPE_UINT32, 2, (void*)x, gd, gs, bx, es, CU_TENSOR_MAP_INTERLEAVE_NONE,
               CU_TENSOR_MAP_SWIZZLE_128B, CU_TENSOR_MAP_L2_PROMOTION_NONE, CU_TENSOR_MAP_FLOAT_OOB_FILL_NONE);
    }
    map2d(&tmw, wout, 128, 128, 64);
    map2d(&tmo, out, 128, N * 4, 8);
    const unsigned npb_magic = (unsigned)((0x100000000ull + npb - 1) / npb);
    const int chunk = (E + nbins - 1) / nbins;
    int tau16 = (int)fmin((double)PACE * 16.0 * chunk / N, 100000.0), toff = TOFF, delay = DELAY;
    int tau2 = tau16 * PACE2 / 100, brk = BRK;
    brk = (tau16 - tau2) * (N * brk / 50);
    main_kernel<<<nbins, NT, SM_TOTAL + TLX, cudaStreamPerThread>>>(dst, src, gbin, E, nbins, fast_ok, npb, npb_magic, N, tme, tmx, tmw,
                                                              tmo, x, sh, ea, cg, wr, wout, out, tau16, toff, delay, tau2, brk);
}
```
